```python
import torch

def _softmax(x, axis=-1):
    return torch.softmax(x, dim=axis)
def _gelu(x):
    return torch.nn.functional.gelu(x, approximate="tanh")
def _silu(x):
    return torch.nn.functional.silu(x)
def _sigmoid(x):
    return torch.sigmoid(x)
def _layernorm(x, axis=-1, eps=1e-5):
    m = x.mean(dim=axis, keepdim=True)
    v = x.var(dim=axis, keepdim=True, unbiased=False)
    return (x - m) / torch.sqrt(v + eps)
def _scatter_add(tgt, idx, src, axis=0):
    return tgt.clone().index_add_(axis, idx, src)
def _segment_sum(src, seg, n):
    out = torch.zeros((n,) + src.shape[1:], dtype=src.dtype)
    return out.index_add_(0, seg, src)
def _pad(x, pw):
    flat = tuple(v for pair in reversed(pw) for v in pair)
    return torch.nn.functional.pad(x, flat)

kernel_name = 'gated_mix__ssm_conv_s4d__moe_arch_mod__prompt'

def setup_inputs():

    _w = (lambda a: (lambda t: t.to(torch.bfloat16) if t.is_floating_point() else t)(torch.as_tensor(a)))
    def _A_setup():
        Bsz, L, D, N = 1, 2048, 1024, 128
        return {
            "u": _w((lambda *s: torch.randn(*s, dtype=torch.bfloat16) * 0.05)(Bsz, L, D)),
            "log_A_real": _w((lambda *s: torch.randn(*s, dtype=torch.bfloat16) * 6.4)(D, N) * 0.5),
            "A_imag": _w((lambda *s: torch.randn(*s, dtype=torch.bfloat16) * 0.1)(D, N) * 3.14),
            "C_real": _w((lambda *s: torch.randn(*s, dtype=torch.bfloat16) * 0.4)(D, N) / N ** 0.5),
            "C_imag": _w((lambda *s: torch.randn(*s, dtype=torch.bfloat16) * 0.4)(D, N) / N ** 0.5),
            "log_dt": _w((lambda *s: torch.randn(*s, dtype=torch.bfloat16) * 0.1)(D) * 0.5 - 4.0),
            "D_skip": _w((lambda *s: torch.randn(*s, dtype=torch.bfloat16) * 0.1)(D)),
        }
    _A_in = _A_setup()

    def _B_setup():
        B, S, D, F, C = 1, 2048, 1024, 3584, 8
        return {
            "x": _w((lambda *s: torch.randn(*s, dtype=torch.bfloat16) * 0.05)(B, S, D)),
            "w_r": _w((lambda *s: torch.randn(*s, dtype=torch.bfloat16) * 6.4)(D)),
            "w_gate": _w((lambda *s: torch.randn(*s, dtype=torch.bfloat16) * 0.1)(D, F)),
            "w_up": _w((lambda *s: torch.randn(*s, dtype=torch.bfloat16) * 0.1)(D, F)),
            "w_down": _w((lambda *s: torch.randn(*s, dtype=torch.bfloat16) * 0.1)(F, D)),
        }
    _B_in = _B_setup()

    return {
        "A_u": _A_in["u"],
        "A_log_A_real": _A_in["log_A_real"],
        "A_A_imag": _A_in["A_imag"],
        "A_C_real": _A_in["C_real"],
        "A_C_imag": _A_in["C_imag"],
        "A_log_dt": _A_in["log_dt"],
        "A_D_skip": _A_in["D_skip"],
        "B_x": _B_in["x"],
        "B_w_r": _B_in["w_r"],
        "B_w_gate": _B_in["w_gate"],
        "B_w_up": _B_in["w_up"],
        "B_w_down": _B_in["w_down"],
        "gate_w": _w((lambda *s: torch.randn(*s, dtype=torch.bfloat16) * 0.05)(1024) * 16.0),
    }

def reference(A_u, A_log_A_real, A_A_imag, A_C_real, A_C_imag, A_log_dt, A_D_skip, B_x, B_w_r, B_w_gate, B_w_up, B_w_down, gate_w):
    def _A_ref(u, log_A_real, A_imag, C_real, C_imag, log_dt, D_skip):
        L = u.shape[1]
        dt = torch.exp(log_dt)
        A = -torch.exp(log_A_real) + 1j * A_imag
        C = (C_real + 1j * C_imag) * dt[:, None]
        pos = (lambda x, dt: x.to(dt))(torch.arange(L), log_dt.dtype)
        P = torch.exp((A * dt[:, None])[:, :, None] * pos[None, None, :])
        K = 2.0 * torch.einsum("dn,dnl->dl", C, P).real
        L2 = 2 * L
        u_t = (lambda x, *d: x.permute(*d))(u, 0, 2, 1)
        Kf = (lambda x, *a, **k: torch.fft.rfft(x.float(), *a, **k))(K, L2)
        Uf = (lambda x, *a, **k: torch.fft.rfft(x.float(), *a, **k))(u_t, L2)
        y = (lambda x, *a, **k: torch.fft.irfft(x, *a, **k).to(torch.bfloat16))(Uf * Kf[None, :, :], L2)[:, :, :L]
        y = (lambda x, *d: x.permute(*d))(y, 0, 2, 1)
        return y + u * D_skip[None, None, :]

    def _B_ref(x, w_r, w_gate, w_up, w_down):
        B, S, D = x.shape
        C = 8
        r = x @ w_r
        idx = torch.argsort(-r, axis=-1)[:, :C]
        idx_e = (lambda x, n, axis: torch.repeat_interleave(x, n, dim=axis))(idx.reshape(B, C, 1), D, axis=2)
        x_sel = (lambda x, i, axis: torch.take_along_dim(x, i, dim=axis))(x, idx_e, axis=1)
        g = _silu(x_sel @ w_gate)
        u = x_sel @ w_up
        y = (g * u) @ w_down
        r_sel = _sigmoid((lambda x, i, axis: torch.take_along_dim(x, i, dim=axis))(r, idx, axis=1))
        y = y * r_sel.reshape(B, C, 1)
        b_off = (torch.arange(B) * S).reshape(B, 1)
        flat_idx = (idx + b_off).reshape(B * C)
        zero = (x * 0.0).reshape(B * S, D)
        upd = _scatter_add(zero, flat_idx, y.reshape(B * C, D), axis=0)
        return x + upd.reshape(B, S, D)

    x = A_u
    g = _sigmoid((x * gate_w).sum(-1, keepdims=True))
    a = _A_ref(x, A_log_A_real, A_A_imag, A_C_real, A_C_imag, A_log_dt, A_D_skip)
    b = _B_ref(x, B_w_r, B_w_gate, B_w_up, B_w_down)
    return g * a + (1 - g) * b
```

```cpp
#include <cuda_runtime.h>
#include <cuda_bf16.h>
#include <cuda_fp16.h>
#include <cuda.h>
#include <stdint.h>

typedef __nv_bfloat16 bf16;

namespace {

constexpr int L_ = 2048, D_ = 1024, F_ = 3584;
constexpr int NCTA = 130;
constexpr int NTHREADS = 512;
#define AUXW 12
constexpr int MAIN_W0 = 0, AUX_W0 = AUXW, PREP_W0 = 20 - AUXW;
#define DELAY_S 300
#define DELAY_G 1200
#define DEPTH 3
#define EARLY 6
#define TSLEEP 100
#define PSLEEP 40
constexpr int NGU_CTA = 112;

constexpr int OFF_RING = 0;
constexpr int OFF_SCR  = 6 * 8192;
constexpr int S_PL     = 2304;
constexpr int OFF_S    = 114688;
constexpr int U_PL     = 2208;
constexpr int U_CH     = 4416;
constexpr int OFF_U    = 151552;
constexpr int TAB_W    = 3200;
constexpr int T_PL     = 544;
constexpr int T_A      = 2192 - 26 * 8;
constexpr int T_B      = 2568 - 59 * 8;
constexpr int OFF_TAB  = 186880;
constexpr int OFF_XSEL = 212480;
constexpr int XS_ROW   = 2064;
constexpr int OFF_BAND = 228992;
constexpr int OFF_MISC = 229536;
constexpr int M_BARS   = OFF_MISC;
constexpr int M_DSK    = OFF_MISC + 416;
constexpr int M_SINK   = OFF_MISC + 448;
constexpr int M_TAG    = OFF_MISC + 452;
constexpr int M_BMAP   = OFF_MISC + 464;
constexpr int M_DPIN   = OFF_MISC + 592;
constexpr int SMEM_BYTES = OFF_MISC + 2640;
__host__ __device__ constexpr uint32_t y_off(uint32_t q) { return OFF_RING + (q & 1) * 8192 + (q >> 1) * 98304; }

constexpr int B_W = 0;
constexpr int B_E = 24;
constexpr int B_S = 36;
constexpr int B_Y = 40;
constexpr int B_DP = 44, B_U = 45, B_KG = 46;
constexpr int B_F = 48;

struct Params {
    const bf16 *u, *logA, *Aim, *Cre, *Cim, *logdt, *Dskip, *wr, *gatew;
    bf16* out;
    uint32_t gu_swap;
    uint32_t zero;
};

__device__ uint4 g_r[L_ / 4];
__device__ uint4 g_g[L_ / 4];
__device__ uint4 g_h[2][8 * F_ / 8];
constexpr int NTOP = 32;
__device__ uint2 g_top[NTOP][16];
__device__ unsigned g_epoch;
#define WSTAMP(i) do {} while (0)
#define KSTAMP(i, dep) do {} while (0)

__device__ __forceinline__ uint32_t smem_u32(const void* p) { return (uint32_t)__cvta_generic_to_shared(p); }
__device__ __forceinline__ void mbar_init(uint32_t b, uint32_t c) { asm volatile("mbarrier.init.shared::cta.b64 [%0], %1;" :: "r"(b), "r"(c) : "memory"); }
__device__ __forceinline__ void mbar_expect(uint32_t b, uint32_t tx) { asm volatile("mbarrier.arrive.expect_tx.shared::cta.b64 _, [%0], %1;" :: "r"(b), "r"(tx) : "memory"); }
__device__ __forceinline__ void mbar_arrive(uint32_t b) { asm volatile("mbarrier.arrive.shared::cta.b64 _, [%0];" :: "r"(b) : "memory"); }
#define WHINT "20000"
__device__ __forceinline__ void mbar_wait(uint32_t b, uint32_t parity) {
    asm volatile("{\n\t.reg .pred p, q;\n\t.reg .u32 n;\n\tmov.u32 n, 0;\n"
                 "W%=:\n\tmbarrier.try_wait.parity.shared::cta.b64 p, [%0], %1, " WHINT ";\n\t"
                 "@p bra D%=;\n\tadd.u32 n, n, 1;\n\tsetp.lt.u32 q, n, 65536;\n\t@q bra W%=;\n"
                 "D%=:\n\t}" :: "r"(b), "r"(parity) : "memory");
}
__device__ __forceinline__ uint32_t mapa(uint32_t addr, uint32_t rank) { uint32_t r; asm("mapa.shared::cluster.u32 %0, %1, %2;" : "=r"(r) : "r"(addr), "r"(rank)); return r; }
__device__ __forceinline__ void tma2d(uint32_t dst, const CUtensorMap* tm, int c0, int c1, uint32_t bar) {
    asm volatile("cp.async.bulk.tensor.2d.shared::cluster.global.mbarrier::complete_tx::bytes [%0], [%1, {%3, %4}], [%2];"
        :: "r"(dst), "l"(tm), "r"(bar), "r"(c0), "r"(c1) : "memory");
}
__device__ __forceinline__ void st_async16(uint32_t dst, const uint4& v, uint32_t bar) {
    asm volatile("st.async.weak.shared::cluster.mbarrier::complete_tx::bytes.v4.b32 [%0], {%1,%2,%3,%4}, [%5];"
                 :: "r"(dst), "r"(v.x), "r"(v.y), "r"(v.z), "r"(v.w), "r"(bar) : "memory");
}
__device__ __forceinline__ void bar_sync(int id, int n) { asm volatile("bar.sync %0, %1;" :: "r"(id), "r"(n) : "memory"); }
__device__ __forceinline__ void cp16(uint32_t dst, const void* src) { asm volatile("cp.async.cg.shared.global [%0], [%1], 16;" :: "r"(dst), "l"(src) : "memory"); }
__device__ __forceinline__ void cp_wait_all() { asm volatile("cp.async.wait_all;" ::: "memory"); }
__device__ __forceinline__ uint2 ldg64(const void* p) { uint2 v; asm volatile("ld.global.nc.v2.u32 {%0,%1}, [%2];" : "=r"(v.x), "=r"(v.y) : "l"(p)); return v; }
__device__ __forceinline__ uint4 ldg128(const void* p) { uint4 v; asm volatile("ld.global.nc.v4.u32 {%0,%1,%2,%3}, [%4];" : "=r"(v.x), "=r"(v.y), "=r"(v.z), "=r"(v.w) : "l"(p)); return v; }
__device__ __forceinline__ uint4 ld_gpu128(const void* p) { uint4 v; asm volatile("ld.relaxed.gpu.global.v4.u32 {%0,%1,%2,%3}, [%4];" : "=r"(v.x), "=r"(v.y), "=r"(v.z), "=r"(v.w) : "l"(p) : "memory"); return v; }
__device__ __forceinline__ void st_gpu32(void* p, uint32_t v) { asm volatile("st.relaxed.gpu.global.u32 [%0], %1;" :: "l"(p), "r"(v) : "memory"); }

__device__ __forceinline__ void ldsm4(uint32_t a, uint32_t& r0, uint32_t& r1, uint32_t& r2, uint32_t& r3) {
    asm volatile("ldmatrix.sync.aligned.m8n8.x4.shared.b16 {%0,%1,%2,%3}, [%4];" : "=r"(r0), "=r"(r1), "=r"(r2), "=r"(r3) : "r"(a) : "memory");
}
__device__ __forceinline__ void ldsm4t(uint32_t a, uint32_t& r0, uint32_t& r1, uint32_t& r2, uint32_t& r3) {
    asm volatile("ldmatrix.sync.aligned.m8n8.x4.trans.shared.b16 {%0,%1,%2,%3}, [%4];" : "=r"(r0), "=r"(r1), "=r"(r2), "=r"(r3) : "r"(a) : "memory");
}
__device__ __forceinline__ uint32_t lds32(uint32_t a) { uint32_t v; asm volatile("ld.shared.u32 %0, [%1];" : "=r"(v) : "r"(a) : "memory"); return v; }
__device__ __forceinline__ uint2 lds64(uint32_t a) { uint2 v; asm volatile("ld.shared.v2.u32 {%0,%1}, [%2];" : "=r"(v.x), "=r"(v.y) : "r"(a) : "memory"); return v; }
__device__ __forceinline__ uint4 lds128(uint32_t a) { uint4 v; asm volatile("ld.shared.v4.u32 {%0,%1,%2,%3}, [%4];" : "=r"(v.x), "=r"(v.y), "=r"(v.z), "=r"(v.w) : "r"(a) : "memory"); return v; }
__device__ __forceinline__ void sts32(uint32_t a, uint32_t v) { asm volatile("st.shared.u32 [%0], %1;" :: "r"(a), "r"(v) : "memory"); }
__device__ __forceinline__ void sts16(uint32_t a, uint32_t v) { asm volatile("st.shared.u16 [%0], %1;" :: "r"(a), "h"((unsigned short)v) : "memory"); }
__device__ __forceinline__ void sts128(uint32_t a, uint32_t x, uint32_t y, uint32_t z, uint32_t w) { asm volatile("st.shared.v4.u32 [%0], {%1,%2,%3,%4};" :: "r"(a), "r"(x), "r"(y), "r"(z), "r"(w) : "memory"); }
__device__ __forceinline__ void stsf(uint32_t a, float v) { asm volatile("st.shared.f32 [%0], %1;" :: "r"(a), "f"(v) : "memory"); }
__device__ __forceinline__ float ldsf(uint32_t a) { float v; asm volatile("ld.shared.f32 %0, [%1];" : "=f"(v) : "r"(a) : "memory"); return v; }

__device__ __forceinline__ void mma_bf(float (&d)[4], uint32_t a0, uint32_t a1, uint32_t a2, uint32_t a3, uint32_t b0, uint32_t b1) {
    asm volatile("mma.sync.aligned.m16n8k16.row.col.f32.bf16.bf16.f32 {%0,%1,%2,%3}, {%4,%5,%6,%7}, {%8,%9}, {%0,%1,%2,%3};"
        : "+f"(d[0]), "+f"(d[1]), "+f"(d[2]), "+f"(d[3]) : "r"(a0), "r"(a1), "r"(a2), "r"(a3), "r"(b0), "r"(b1));
}
__device__ __forceinline__ void mma_bf_z(float (&d)[4], uint32_t a0, uint32_t a1, uint32_t a2, uint32_t a3, uint32_t b0, uint32_t b1) {
    asm volatile("mma.sync.aligned.m16n8k16.row.col.f32.bf16.bf16.f32 {%0,%1,%2,%3}, {%4,%5,%6,%7}, {%8,%9}, {%10,%10,%10,%10};"
        : "=f"(d[0]), "=f"(d[1]), "=f"(d[2]), "=f"(d[3]) : "r"(a0), "r"(a1), "r"(a2), "r"(a3), "r"(b0), "r"(b1), "f"(0.f));
}
__device__ __forceinline__ void mma_bf_k8(float (&d)[4], uint32_t a0, uint32_t a1, uint32_t b0) {
    asm volatile("mma.sync.aligned.m16n8k8.row.col.f32.bf16.bf16.f32 {%0,%1,%2,%3}, {%4,%5}, {%6}, {%0,%1,%2,%3};"
        : "+f"(d[0]), "+f"(d[1]), "+f"(d[2]), "+f"(d[3]) : "r"(a0), "r"(a1), "r"(b0));
}
__device__ __forceinline__ void mma_h(float (&d)[4], uint32_t a0, uint32_t a1, uint32_t a2, uint32_t a3, uint32_t b0, uint32_t b1) {
    asm volatile("mma.sync.aligned.m16n8k16.row.col.f32.f16.f16.f32 {%0,%1,%2,%3}, {%4,%5,%6,%7}, {%8,%9}, {%0,%1,%2,%3};"
        : "+f"(d[0]), "+f"(d[1]), "+f"(d[2]), "+f"(d[3]) : "r"(a0), "r"(a1), "r"(a2), "r"(a3), "r"(b0), "r"(b1));
}
__device__ __forceinline__ uint32_t pack_bf(float lo, float hi) { uint32_t r; asm("cvt.rn.bf16x2.f32 %0, %1, %2;" : "=r"(r) : "f"(hi), "f"(lo)); return r; }
__device__ __forceinline__ uint32_t pack_h(float lo, float hi) { uint32_t r; asm("cvt.rn.f16x2.f32 %0, %1, %2;" : "=r"(r) : "f"(hi), "f"(lo)); return r; }
__device__ __forceinline__ float bf_lo(uint32_t v) { return __uint_as_float(v << 16); }
__device__ __forceinline__ float bf_hi(uint32_t v) { return __uint_as_float(v & 0xffff0000u); }
__device__ __forceinline__ float bf_round(float x) { return __uint_as_float(pack_bf(0.f, x) & 0xffff0000u); }
__device__ __forceinline__ uint32_t hmul2_bf(uint32_t a, uint32_t b) { uint32_t r; asm("mul.rn.bf16x2 %0, %1, %2;" : "=r"(r) : "r"(a), "r"(b)); return r; }
__device__ __forceinline__ float ex2f(float x) { float r; asm("ex2.approx.ftz.f32 %0, %1;" : "=f"(r) : "f"(x)); return r; }

__device__ __forceinline__ float exp_acc(float x) {
    const float t = x * 1.4426950216293335f;
    const float r = fmaf(x, 1.4426950216293335f, -t) + x * 1.9259629911266175e-8f;
    return ex2f(t) * fmaf(r, 0.6931471805599453f, 1.f);
}
__device__ __forceinline__ float sigmoid_f(float x) { return __fdividef(1.f, 1.f + ex2f(-x * 1.4426950408889634f)); }
__device__ __forceinline__ void cexp_pow(float lr, float li, float e, float& zr, float& zi) {
    const float mag = ex2f(lr * e * 1.4426950408889634f);
    const float th = li * e;
    const float k = (th * 0.15915494309189535f + 12582912.f) - 12582912.f;
    float r = fmaf(-k, 6.2831854820251465f, th);
    r = fmaf(-k, -1.7484555314695172e-7f, r);
    zr = mag * __cosf(r);
    zi = mag * __sinf(r);
}
__device__ __forceinline__ uint32_t hcmul(uint32_t a, uint32_t k, uint32_t kp) {
    const __half2 A = *reinterpret_cast<const __half2*>(&a);
    const __half2 r = __hfma2(__high2half2(A), *reinterpret_cast<const __half2*>(&kp), __hmul2(__low2half2(A), *reinterpret_cast<const __half2*>(&k)));
    return *reinterpret_cast<const uint32_t*>(&r);
}
#define CMUL(orr, oi, ar, ai, br, bi) do { float _r = (ar) * (br) - (ai) * (bi); float _i = (ar) * (bi) + (ai) * (br); orr = _r; oi = _i; } while (0)
#define CSQ(orr, oi, ar, ai) do { float _r = (ar) * (ar) - (ai) * (ai); float _i = 2.f * (ar) * (ai); orr = _r; oi = _i; } while (0)

__device__ __forceinline__ void mma_bf_k8z(float (&d)[4], uint32_t a0, uint32_t a1, uint32_t b0) {
    asm volatile("mma.sync.aligned.m16n8k8.row.col.f32.bf16.bf16.f32 {%0,%1,%2,%3}, {%4,%5}, {%6}, {%7,%7,%7,%7};"
        : "=f"(d[0]), "=f"(d[1]), "=f"(d[2]), "=f"(d[3]) : "r"(a0), "r"(a1), "r"(b0), "f"(0.f));
}
__device__ __forceinline__ void mma_hh_k8(uint32_t& d0, uint32_t& d1, uint32_t a0, uint32_t a1, uint32_t b0) {
    asm volatile("mma.sync.aligned.m16n8k8.row.col.f16.f16.f16.f16 {%0,%1}, {%2,%3}, {%4}, {%5,%5};"
        : "=r"(d0), "=r"(d1) : "r"(a0), "r"(a1), "r"(b0), "r"(0));
}
__device__ __forceinline__ void tma3d(uint32_t dst, const CUtensorMap* tm, int c0, int c1, int c2, uint32_t bar) {
    asm volatile("cp.async.bulk.tensor.3d.shared::cluster.global.mbarrier::complete_tx::bytes [%0], [%1, {%3, %4, %5}], [%2];"
        :: "r"(dst), "l"(tm), "r"(bar), "r"(c0), "r"(c1), "r"(c2) : "memory");
}
__device__ __forceinline__ void lds128_if(bool on, uint32_t a, uint32_t (&v)[4]) {
    asm volatile("{\n\t.reg .pred p;\n\tsetp.ne.u32 p, %5, 0;\n\t@p ld.shared.v4.u32 {%0,%1,%2,%3}, [%4];\n\t}"
        : "+r"(v[0]), "+r"(v[1]), "+r"(v[2]), "+r"(v[3]) : "r"(a), "r"((uint32_t)on) : "memory");
}
__device__ __forceinline__ uint32_t hfma2_bf(uint32_t a, uint32_t b, uint32_t c) { uint32_t r; asm("fma.rn.bf16x2 %0, %1, %2, %3;" : "=r"(r) : "r"(a), "r"(b), "r"(c)); return r; }
__device__ __forceinline__ uint32_t row_elem(uint32_t row) { return ((row >> 5) & 4) | ((row >> 2) & 2) | ((row >> 4) & 1); }
__device__ __forceinline__ uint32_t gate_pos(uint32_t row) { return ((row >> 9) << 8) | ((row & 7) << 5) | (row_elem(row) << 2) | ((row >> 5) & 3); }

__global__ void __cluster_dims__(2, 1, 1) __launch_bounds__(NTHREADS, 1)
fused_kernel(const Params p, const __grid_constant__ CUtensorMap tm_gu, const __grid_constant__ CUtensorMap tm_down,
             const __grid_constant__ CUtensorMap tm_x) {
    extern __shared__ __align__(1024) unsigned char smem[];
    const uint32_t sb = smem_u32(smem);
    int tid;
    asm volatile("mov.u32 %0, %%tid.x;" : "=r"(tid));
    const int pw = tid >> 5, lane = tid & 31;
    const int c = blockIdx.x, h = c & 1, pr = c >> 1;
    const uint32_t bars = sb + M_BARS;

    if (c >= 128) {
        if (c != 128) return;
        const unsigned tag = (*(volatile unsigned*)&g_epoch + 1) & 0xffffu;
        const uint32_t list = sb + 128;
#pragma unroll 1
        for (int pass = 0; pass < 2; pass++) {
            sts128(list + 16 * tid, 0, 0, 0, 0);
            if (tid == 0) sts32(sb + 64, 0);
            uint32_t key[4];
            bool ok = false;
#pragma unroll 1
            for (int it = 0; it < (1 << 22); it++) {
                const uint4 a = ld_gpu128(&g_r[tid]);
                key[0] = a.x; key[1] = a.y; key[2] = a.z; key[3] = a.w;
                ok = (((a.x ^ tag) | (a.y ^ tag) | (a.z ^ tag) | (a.w ^ tag)) & 0xffffu) == 0;
                if (ok || !pass) break;
            }
            WSTAMP(0);
            uint32_t m = 0;
#pragma unroll
            for (int i = 0; i < 4; i++) {
                key[i] = ((pass ? key[i] : (lane + i) << 16) & 0xffff0000u) | (uint32_t)(2047 - (4 * tid + i));
                m = max(m, key[i]);
            }
            const uint32_t wm = __reduce_max_sync(0xffffffffu, m);
            if (lane == 0) sts32(sb + pw * 4, wm);
            __syncthreads();
            uint32_t thr = 0xffffffffu;
#pragma unroll
            for (int i = 0; i < 4; i++) { const uint4 q = lds128(sb + 16 * i); thr = min(thr, min(max(q.x, q.y), max(q.z, q.w))); }
            if (thr != 1) WSTAMP(1);
            if (m >= thr) {
                uint32_t pos;
                asm volatile("atom.shared.add.u32 %0, [%1], %2;" : "=r"(pos) : "r"(sb + 64), "r"(4 * ((key[0] >= thr) + (key[1] >= thr) + (key[2] >= thr) + (key[3] >= thr))) : "memory");
#pragma unroll
                for (int i = 0; i < 4; i++) if (key[i] >= thr) { sts32(list + pos, key[i]); pos += 4; }
            }
            __syncthreads();
            const uint32_t nc4 = lds32(sb + 64);
            if (nc4 != 1) WSTAMP(2);
#pragma unroll 1
            for (uint32_t j = 4 * pw; j < nc4; j += 64) {
                const uint32_t mine = lds32(list + j);
                int rank = 0;
#pragma unroll 1
                for (uint32_t i = 0; i < nc4; i += 128) rank += __popc(__ballot_sync(0xffffffffu, lds32(list + i + 4 * lane) > mine));
                if (rank < 8 * pass) asm volatile("st.relaxed.gpu.global.v2.u32 [%0], {%1, %2};" :: "l"(&g_top[lane][rank]), "r"(mine), "r"(tag) : "memory");
            }
            WSTAMP(3);
            if (!pass) __syncthreads();
        }
        return;
    }

    uint2 v_la, v_ai, v_cr, v_ci;
    uint32_t ldt16;
    if (pw < 8) {
        const int d = 8 * c + pw - MAIN_W0;
        const size_t po = (size_t)d * 128 + 4 * lane;
        v_la = ldg64(p.logA + po); v_ai = ldg64(p.Aim + po); v_cr = ldg64(p.Cre + po); v_ci = ldg64(p.Cim + po);
        asm volatile("ld.global.nc.u16 %0, [%1];" : "=r"(ldt16) : "l"(p.logdt + d));
        if (lane == 0) asm volatile("cp.async.ca.shared.global [%0], [%1], 4;" :: "r"(sb + M_DSK + 4 * (pw - MAIN_W0)), "l"(p.Dskip + (d & ~1)) : "memory");
    } else if ((pw & 12) == AUX_W0) {
        const uint4 w = ldg128(p.wr + (tid & 127) * 8);
        v_la.x = w.x; v_la.y = w.y; v_ai.x = w.z; v_ai.y = w.w;
        cp16(sb + OFF_XSEL + 2048 + (tid & 127) * 16, p.gatew + (tid & 127) * 8);
    }
    WSTAMP(0);
    if ((pw & 12) == PREP_W0) {
        const uint32_t vu = __reduce_max_sync(0xffffffffu, pw - PREP_W0), bu = bars + 8 * vu;
        if (lane == 0) {
#pragma unroll
            for (int i = 0; i < 10; i++) mbar_init(bu + 32 * i, 1);
            mbar_init(bu + 8 * B_Y, vu == 0 ? 10 : 9);
            mbar_init(bu + 8 * B_DP, (0x1865 >> (4 * vu)) & 15);
            mbar_init(bu + 8 * B_F, 1);
            asm volatile("fence.proxy.async.shared::cta;" ::: "memory");
            asm volatile("fence.mbarrier_init.release.cluster;" ::: "memory");
            mbar_expect(bu + 8 * B_Y, 4096);
            if (vu < 2) mbar_expect(bu + 8 * B_DP, vu == 0 ? 2048 : 16384);
            mbar_expect(bu + 8 * B_F, c < NGU_CTA ? 16 : 0);
        }
    }
    __syncthreads();
    asm volatile("barrier.cluster.arrive.relaxed.aligned;" ::: "memory");

    if (pw < 8) {
        const int warp = pw - MAIN_W0;
        asm volatile("setmaxnreg.inc.sync.aligned.u32 176;");
        [[maybe_unused]] const int d = 8 * c + warp;
        const int g = lane >> 2, t = lane & 3;
        const int mi = lane >> 3, r = lane & 7;
        const uint32_t TB = sb + OFF_TAB + warp * TAB_W;
        const uint32_t UB = sb + OFF_U + warp * U_CH;
        if (r < 7 && mi < 2) sts128(UB + mi * U_PL + r * 16, 0, 0, 0, 0);
#pragma unroll
        for (int i = 0; i < 6; i++) sts128(TB + 16 * (lane + 32 * i), 0, 0, 0, 0);
        if (lane < 8) sts128(TB + 16 * (lane + 192), 0, 0, 0, 0);
        __syncwarp();

        uint32_t cfix;
        {
            KSTAMP(4, v_la.x ^ v_ai.x ^ v_cr.x ^ v_ci.x ^ ldt16);
            const float dt = bf_round(exp_acc(__uint_as_float(ldt16 << 16)));
            float lr[4], li[4], cr[4], ci[4];
            float inv;
            {
                const uint32_t la[2] = {v_la.x, v_la.y}, ai[2] = {v_ai.x, v_ai.y}, vr[2] = {v_cr.x, v_cr.y}, vi[2] = {v_ci.x, v_ci.y};
                const uint32_t m2 = __vmaxu2(__vmaxu2(vr[0] & 0x7fff7fffu, vr[1] & 0x7fff7fffu), __vmaxu2(vi[0] & 0x7fff7fffu, vi[1] & 0x7fff7fffu));
                const uint32_t mx = __reduce_max_sync(0xffffffffu, max(m2, m2 << 16));
                const uint32_t e = min(max(mx >> 23, 11u), 254u);
                const float sc = __uint_as_float((264u - e) << 23);
                inv = __uint_as_float((e - 10u) << 23) * (2.f * dt);
#pragma unroll
                for (int i = 0; i < 4; i++) {
                    const float a = (i & 1) ? bf_hi(la[i >> 1]) : bf_lo(la[i >> 1]);
                    const float b = (i & 1) ? bf_hi(ai[i >> 1]) : bf_lo(ai[i >> 1]);
                    lr[i] = -bf_round(exp_acc(a)) * dt;
                    li[i] = b * dt;
                    cr[i] = ((i & 1) ? bf_hi(vr[i >> 1]) : bf_lo(vr[i >> 1])) * sc;
                    ci[i] = ((i & 1) ? bf_hi(vi[i >> 1]) : bf_lo(vi[i >> 1])) * sc;
                }
            }
            const uint32_t SX = sb + OFF_SCR + warp * 8192;
            const uint32_t sw = SX + (lane << 4);
#define PUT(buf, row, v) sts128(((sw + (row) * 512) ^ ((row) << 4)) + (buf) * 4096, v[0], v[1], v[2], v[3])
#define EMIT(bufa, rowa, bufb, rowb, xr, xi, k, kp) do { uint32_t pk[4], pd[4]; \
                _Pragma("unroll") for (int i = 0; i < 4; i++) { pk[i] = pack_h(xr[i], xi[i]); pd[i] = hcmul(pk[i], k[i], kp[i]); } \
                PUT(bufa, rowa, pk); PUT(bufb, rowb, pd); } while (0)
#define CMUL4(orr, oi, ar, ai, br, bi) _Pragma("unroll") for (int i = 0; i < 4; i++) CMUL(orr[i], oi[i], ar[i], ai[i], br[i], bi[i])
#define CSQ4(orr, oi, ar, ai) _Pragma("unroll") for (int i = 0; i < 4; i++) CSQ(orr[i], oi[i], ar[i], ai[i])
            float z1r[4], z1i[4], z2r[4], z2i[4], z8r[4], z8i[4], z256r[4], z256i[4];
            uint32_t k128[4], k128p[4], k4[4], k4p[4];
#pragma unroll
            for (int i = 0; i < 4; i++) {
                float tr, ti;
                cexp_pow(lr[i], li[i], 1.f, z1r[i], z1i[i]);
                CSQ(z2r[i], z2i[i], z1r[i], z1i[i]);
                CSQ(tr, ti, z2r[i], z2i[i]);
                k4[i] = pack_h(tr, ti); k4p[i] = pack_h(-ti, tr);
                CSQ(z8r[i], z8i[i], tr, ti);
                cexp_pow(lr[i], li[i], 128.f, tr, ti);
                k128[i] = pack_h(tr, ti); k128p[i] = pack_h(-ti, tr);
                CSQ(z256r[i], z256i[i], tr, ti);
                sts32(TB + i * T_PL + 16 + 4 * lane, k128[i]);
                sts32(TB + i * T_PL + 160 + 4 * lane, k128p[i]);
            }
            KSTAMP(5, k128[3] ^ k4[3]);
            uint32_t Ya[16][4];
            {
                float w1r[4], w1i[4], ar[4], ai[4], br[4], bi[4];
                uint32_t k8[4], k8p[4];
                const uint32_t one[4] = {0x3C00u, 0x3C00u, 0x3C00u, 0x3C00u};
#pragma unroll
                for (int i = 0; i < 4; i++) {
                    k8[i] = pack_h(z8r[i], -z8i[i]); k8p[i] = pack_h(z8i[i], z8r[i]);
                    CSQ(w1r[i], w1i[i], z8r[i], z8i[i]); w1i[i] = -w1i[i];
                }
                PUT(0, 0, one); PUT(1, 0, k8);
                EMIT(0, 1, 1, 1, w1r, w1i, k8, k8p);
                CSQ4(ar, ai, w1r, w1i);            EMIT(0, 2, 1, 2, ar, ai, k8, k8p);
                CMUL4(br, bi, ar, ai, w1r, w1i);   EMIT(0, 3, 1, 3, br, bi, k8, k8p);
                CSQ4(ar, ai, ar, ai);              EMIT(0, 4, 1, 4, ar, ai, k8, k8p);
                CMUL4(ar, ai, ar, ai, w1r, w1i);   EMIT(0, 5, 1, 5, ar, ai, k8, k8p);
                CSQ4(br, bi, br, bi);              EMIT(0, 6, 1, 6, br, bi, k8, k8p);
                CMUL4(br, bi, br, bi, w1r, w1i);   EMIT(0, 7, 1, 7, br, bi, k8, k8p);
                __syncwarp();
                KSTAMP(6, 0);
                const uint32_t ab = SX + (mi & 1) * 4096 + r * 512, ax = ((mi >> 1) ^ r) << 4;
#pragma unroll
                for (int ks = 0; ks < 16; ks++) ldsm4(ab + (ks >> 2) * 128 + (ax ^ ((ks & 3) << 5)), Ya[ks][0], Ya[ks][1], Ya[ks][2], Ya[ks][3]);
                __syncwarp();
            }
            KSTAMP(7, Ya[15][0]);
            const uint32_t ld0 = SX + r * 512 + ((mi ^ r) << 4), ld1 = ld0 ^ 64;
            float R[5][4], xr[4], xi[4];
            {
                float yr[4], yi[4];
                EMIT(0, 0, 0, 1, cr, ci, k4, k4p);
                CMUL4(yr, yi, cr, ci, z1r, z1i);        EMIT(0, 2, 0, 3, yr, yi, k4, k4p);
                CMUL4(xr, xi, cr, ci, z256r, z256i);    EMIT(1, 0, 1, 1, xr, xi, k4, k4p);
                CMUL4(yr, yi, yr, yi, z1r, z1i);        EMIT(0, 4, 0, 5, yr, yi, k4, k4p);
                CMUL4(cr, ci, xr, xi, z2r, z2i);        EMIT(1, 2, 1, 3, cr, ci, k4, k4p);
                CMUL4(yr, yi, yr, yi, z1r, z1i);        EMIT(0, 6, 0, 7, yr, yi, k4, k4p);
                CMUL4(xr, xi, xr, xi, z256r, z256i);    EMIT(1, 4, 1, 5, xr, xi, k4, k4p);
                CMUL4(xr, xi, xr, xi, z256r, z256i);    EMIT(1, 6, 1, 7, xr, xi, k4, k4p);
            }
            __syncwarp();
            {
                KSTAMP(8, 0);
                uint32_t bd[2][4] = {{0, 0, 0, 0}, {0, 0, 0, 0}};
                const bool on = (g >> 1) == t;
#pragma unroll
                for (int i = 0; i < 4; i++) { R[i][0] = R[i][1] = R[i][2] = R[i][3] = 0.f; }
#pragma unroll
                for (int k2 = 0; k2 < 8; k2++) {
                    uint32_t x[4], y[4], a1[2][4];
                    lds128_if(on, TB + t * T_PL + 16 + (g & 1) * 144 + 16 * k2, bd[k2 & 1]);
                    ldsm4(((k2 & 1) ? ld1 : ld0) + (k2 >> 1) * 128, x[0], x[1], x[2], x[3]);
                    ldsm4(((k2 & 1) ? ld1 : ld0) + (k2 >> 1) * 128 + 4096, y[0], y[1], y[2], y[3]);
#pragma unroll
                    for (int u = 0; u < 2; u++) {
                        mma_hh_k8(a1[u][0], a1[u][1], Ya[2 * k2 + u][0], Ya[2 * k2 + u][1], bd[k2 & 1][2 * u]);
                        mma_hh_k8(a1[u][2], a1[u][3], Ya[2 * k2 + u][2], Ya[2 * k2 + u][3], bd[k2 & 1][2 * u + 1]);
                    }
#pragma unroll
                    for (int u = 0; u < 2; u++) {
                        const uint32_t(&a0)[4] = Ya[2 * k2 + u];
                        mma_h(R[0], a0[0], a0[1], a0[2], a0[3], x[2 * u], x[2 * u + 1]);
                        mma_h(R[2], a0[0], a0[1], a0[2], a0[3], y[2 * u], y[2 * u + 1]);
                        mma_h(R[1], a1[u][0], a1[u][1], a1[u][2], a1[u][3], x[2 * u], x[2 * u + 1]);
                        mma_h(R[3], a1[u][0], a1[u][1], a1[u][2], a1[u][3], y[2 * u], y[2 * u + 1]);
                    }
                }
            }
            __syncwarp();
            KSTAMP(9, __float_as_uint(R[3][0]));
            CMUL4(xr, xi, xr, xi, z256r, z256i);
            float s1024 = (xr[0] + xr[1]) + (xr[2] + xr[3]);
            CMUL4(xr, xi, xr, xi, z8r, z8i);        EMIT(0, 0, 0, 1, xr, xi, k128, k128p);
            CMUL4(xr, xi, xr, xi, z256r, z256i);    EMIT(0, 2, 0, 3, xr, xi, k128, k128p);
            CMUL4(xr, xi, xr, xi, z256r, z256i);    EMIT(0, 4, 0, 5, xr, xi, k128, k128p);
            CMUL4(xr, xi, xr, xi, z256r, z256i);    EMIT(0, 6, 0, 7, xr, xi, k128, k128p);
            __syncwarp();
            {
                KSTAMP(10, 0);
                float a1[4] = {0.f, 0.f, 0.f, 0.f};
                R[4][0] = R[4][1] = R[4][2] = R[4][3] = 0.f;
#pragma unroll
                for (int k2 = 0; k2 < 8; k2++) {
                    uint32_t x[4];
                    ldsm4(((k2 & 1) ? ld1 : ld0) + (k2 >> 1) * 128, x[0], x[1], x[2], x[3]);
                    mma_h(R[4], Ya[2 * k2][0], Ya[2 * k2][1], Ya[2 * k2][2], Ya[2 * k2][3], x[0], x[1]);
                    mma_h(a1, Ya[2 * k2 + 1][0], Ya[2 * k2 + 1][1], Ya[2 * k2 + 1][2], Ya[2 * k2 + 1][3], x[2], x[3]);
                }
#pragma unroll
                for (int i = 0; i < 4; i++) R[4][i] += a1[i];
            }
            if (lane == 0) mbar_arrive(bars + 8 * B_KG + (__float_as_uint(R[4][0]) & p.zero));
            KSTAMP(11, __float_as_uint(R[4][0]));
#undef PUT
#undef EMIT
#pragma unroll
            for (int o = 16; o > 0; o >>= 1) s1024 += __shfl_xor_sync(0xffffffffu, s1024, o);
            uint32_t w[4][4], dsk = 0;
            if (lane == 0) { cp_wait_all(); asm volatile("ld.shared.u16 %0, [%1];" : "=r"(dsk) : "r"(sb + M_DSK + 4 * warp + 2 * (warp & 1)) : "memory"); }
#pragma unroll
            for (int a = 0; a < 4; a++) {
                const float v0 = (a == 0) ? fmaf(R[0][0], inv, __uint_as_float(dsk << 16)) : R[a][0] * inv;
                const float v1 = R[a][1] * inv, v2 = R[a][2] * inv, v3 = R[a][3] * inv;
                w[a][0] = pack_bf(v0, 0.f); w[a][1] = pack_bf(v1, v0); w[a][2] = pack_bf(v2, v1); w[a][3] = pack_bf(v3, v2);
            }
            const uint32_t wb = TB + 16 + 16 * g, w1 = wb + t * T_PL, w2 = wb + 256 + 2 * t * T_PL;
            const uint32_t w3 = (t == 0) ? wb + 256 + 3 * T_PL : TB + T_A + 8 * (16 * t + g);
            const uint32_t w3s = (t == 0) ? 128 : 64, w3o = (t == 0) ? 8 : 12;
            const uint32_t k512 = __shfl_sync(0xffffffffu, w[2][1], 2);
#pragma unroll
            for (int a = 0; a < 2; a++) {
                sts128(w1 + 128 * a, w[a][0], w[a][1], w[a][2], w[a][3]);
                const uint32_t(&q)[4] = w[2 + a];
                if (t < 2) sts128(w2 + 128 * a, q[0], q[1], q[2], q[3]);
                if (t == 0) { sts128(w2 + T_PL + 128 * a, q[0], q[1], q[2], q[3]); sts32(w3 + 128 * a + 4, q[2]); }
                if (t != 1 && (a == 1 || lane != 2)) sts32(w3 + w3s * a, q[1]);
                if (t != 1) sts32(w3 + w3s * a + w3o, q[3]);
            }
            if (lane < 4)
                sts128(w1 + 512, __byte_perm(k512, 0, t == 3 ? 0x3210 : 0x4432), __byte_perm(k512, 0, t < 2 ? 0x3210 : t == 2 ? 0x3244 : 0x1044),
                       __byte_perm(k512, 0, t < 2 ? 0x1044 : 0x4444), 0);
            __syncwarp();
#pragma unroll
            for (int a = 0; a < 2; a++) {
                sts16(w1 + 128 * a + 18, w[a][3]);
                const uint32_t(&q)[4] = w[2 + a];
                if (t < 2) sts16(w2 + 128 * a + 18, q[3]);
                if (t == 0) { sts16(w2 + T_PL + 128 * a + 18, q[3]); sts16(w3 + 128 * a + 14, q[3]); }
            }
            if (t == 0) sts16(w3 + 128 - 4, w[3][0]);
            if (lane == 2 || (t == 0 && g > 0)) sts16(lane == 2 ? TB + 16 + 3 * T_PL + 4 * 127 : w3 - 4, w[2][0]);
            {
                const uint32_t b0 = pack_bf(R[4][0] * inv, R[4][2] * inv), b1 = pack_bf(R[4][1] * inv, R[4][3] * inv);
                const uint32_t wq = TB + T_B + 8 * (65 + 16 * t + g);
                sts32(wq, b0); sts32(wq + 12, b0); sts32(wq + 64, b1); sts32(wq + 76, b1);
            }
            cfix = pack_bf(s1024 * inv, s1024 * inv);
            if (lane == 0) sts32(TB + T_A + 8 * 64, cfix);
            __syncwarp();
        }
        WSTAMP(1);
        asm volatile("barrier.cluster.wait.acquire.aligned;" ::: "memory");

        mbar_wait(bars + 8 * B_U, 0);
        WSTAMP(2);

        float D[16][4];
        {
            const int x5 = g - t + 5;
            const uint32_t tabD = TB + (x5 & 3) * T_PL + (x5 & 12) + 16;
            {
                const uint32_t a1 = lds32(tabD - 8), a0 = p.zero;
#pragma unroll
                for (int jq = 0; jq < 4; jq++) {
                    uint32_t b[4];
                    ldsm4(UB + (8 + lane) * 16 + jq * 512, b[0], b[1], b[2], b[3]);
#pragma unroll
                    for (int i = 0; i < 4; i++) mma_bf_k8z(D[4 * jq + i], a0, a1, b[i]);
                }
            }
            const uint32_t ua = UB + (mi & 1) * U_PL + (7 + 8 * (mi >> 1) + r) * 16;
#pragma unroll 1
            for (int k0 = 0; k0 < 8; k0++) {
                uint32_t Uf[16][2];
#pragma unroll
                for (int jp = 0; jp < 8; jp++) ldsm4(ua + jp * 256 - k0 * 16, Uf[2 * jp][0], Uf[2 * jp][1], Uf[2 * jp + 1][0], Uf[2 * jp + 1][1]);
#pragma unroll
                for (int k1 = 0; k1 < 4; k1++) {
                    const uint32_t ta = tabD + 16 * (8 * k1 + k0);
                    const uint32_t a0 = lds32(ta), a1 = lds32(ta + 8), a2 = lds32(ta - 8), a3 = a0 ^ p.zero;
#pragma unroll
                    for (int J = k1; J < 16; J++) mma_bf(D[J], a0, a1, a2, a3, Uf[J - k1][0], Uf[J - k1][1]);
                }
                if (k0 == 0) {
                    const uint32_t ta = tabD + 16 * 32;
                    const uint32_t a0 = lds32(ta), a1 = lds32(ta + 8), a2 = lds32(ta - 8), a3 = a0 ^ p.zero;
#pragma unroll
                    for (int J = 4; J < 16; J++) mma_bf(D[J], a0, a1, a2, a3, Uf[J - 4][0], Uf[J - 4][1]);
                    const uint32_t f0 = (cfix ^ 0x80008000u) & (g == t ? 0xffffu : g == t + 4 ? 0xffff0000u : 0u);
                    const uint32_t f1 = p.zero, f2 = p.zero + p.zero, f3 = f0 ^ p.zero;
#pragma unroll
                    for (int J = 8; J < 16; J++) mma_bf(D[J], f0, f1, f2, f3, Uf[J - 8][0], Uf[J - 8][1]);
                }
            }
        }
        WSTAMP(3);
        {
            const int ch = 8 * h + warp;
            const uint32_t yo = sb + ch * 512 + ((lane ^ (((ch >> 2) << 1) | (ch & 1))) << 4);
            const uint32_t yr = mapa(yo, h ^ 1), ybr = mapa(bars + 8 * B_Y, h ^ 1);
            const uint32_t yi = sb + (4 * (r >> 1) + 2 * (mi & 1) + (r & 1)) * 512 + (((4 * warp + (mi >> 1)) ^ r) << 4);
            const int rho = 128 * (g >> 2) + 8 * ((g >> 1) & 1) + 16 * (g & 1) + warp;
            const uint32_t xs = sb + OFF_S + ((rho + 5) & 3) * S_PL + ((rho + 5) >> 2) * 32 + (((t >> 1) ^ (((rho + 5) >> 4) & 1)) << 4) + ((t & 1) << 3);
            bf16* op = p.out + (size_t)(256 * h + rho) * D_ + 16 * pr + 4 * t;
            const uint4* gsrc = &g_g[256 * h + 8 * warp + g];
            const uint32_t tag16 = lds32(sb + M_TAG);
            uint4 gq[2], sel;
            auto ship = [&](const int Q) {
                uint4 y[2];
#pragma unroll
                for (int hh = 0; hh < 2; hh++) {
                    const int J = 4 * Q + 2 * hh;
                    y[hh] = make_uint4(pack_bf(D[J][0], D[J][1]), pack_bf(D[J][2], D[J][3]), pack_bf(D[J + 1][0], D[J + 1][1]), pack_bf(D[J + 1][2], D[J + 1][3]));
                }
                if (!(Q & 1)) mbar_wait(bars + 8 * (B_F + (Q >> 1)), 0);
                asm volatile("{\n\t.reg .pred p;\n\tsetp.eq.u32 p, %11, 0;\n\t"
                             "@p st.async.weak.shared::cluster.mbarrier::complete_tx::bytes.v4.b32 [%9], {%4,%5,%6,%7}, [%10];\n\t"
                             "@!p st.async.weak.shared::cluster.mbarrier::complete_tx::bytes.v4.b32 [%9], {%0,%1,%2,%3}, [%10];\n\t"
                             "@p st.shared.v4.b32 [%8], {%0,%1,%2,%3};\n\t@!p st.shared.v4.b32 [%8], {%4,%5,%6,%7};\n\t}"
                             :: "r"(y[0].x), "r"(y[0].y), "r"(y[0].z), "r"(y[0].w), "r"(y[1].x), "r"(y[1].y), "r"(y[1].z), "r"(y[1].w),
                                "r"(yo + y_off(Q)), "r"(yr + y_off(Q)), "r"(ybr + 8 * Q), "r"(h) : "memory");
                __syncwarp();
                if (lane == 0) mbar_arrive(bars + 8 * (B_Y + Q));
            };
            auto finish = [&](const int Q) {
                uint2 xq[4];
#pragma unroll
                for (int i = 0; i < 4; i++) xq[i] = lds64(xs + Q * 4 * S_PL + i * 256);
#pragma unroll 1
                for (int it = 0; ((((gq[Q & 1].x ^ tag16) | (gq[Q & 1].y ^ tag16)) | ((gq[Q & 1].z ^ tag16) | (gq[Q & 1].w ^ tag16))) >> 16) && it < (1 << 22); it++)
                    gq[Q & 1] = ld_gpu128(gsrc + 64 * Q);
                uint32_t gg[4] = {gq[Q & 1].x, gq[Q & 1].y, gq[Q & 1].z, gq[Q & 1].w};
#pragma unroll
                for (int i = 0; i < 4; i++) {
                    gg[i] = __byte_perm(gg[i], 0, 0x1010);
                    const uint32_t og = hfma2_bf(gg[i], 0xBF80BF80u, 0x3F803F80u);
                    xq[i].x = hmul2_bf(og, xq[i].x); xq[i].y = hmul2_bf(og, xq[i].y);
                }
                mbar_wait(bars + 8 * (B_Y + Q), 0);
                __syncwarp();
                if (Q == 0) sel = lds128(sb + M_BMAP + warp * 16);
                const uint32_t sbits = (Q == 0 ? sel.x : Q == 1 ? sel.y : Q == 2 ? sel.z : sel.w) >> (4 * g);
#pragma unroll
                for (int x = 0; x < 2; x++) {
                    uint32_t y[4];
                    ldsm4t((yi ^ (x << 5)) + y_off(Q), y[0], y[1], y[2], y[3]);
#pragma unroll
                    for (int e = 0; e < 2; e++) {
                        const int i = 2 * x + e;
                        const uint2 o = make_uint2(hfma2_bf(gg[i], y[2 * e], xq[i].x), hfma2_bf(gg[i], y[2 * e + 1], xq[i].y));
                        if (!(sbits & (1u << i))) *(uint2*)(op + (size_t)(512 * Q + 32 * i) * D_) = o;
                    }
                }
            };
            ship(0);
            gq[0] = ld_gpu128(gsrc);
            const uint4 bA = lds128(sb + OFF_BAND + (g - t + 3) * 48), bB = lds128(sb + OFF_BAND + (g - t + 3) * 48 + 16);
            const uint2 bC = lds64(sb + OFF_BAND + (g - t + 3) * 48 + 32);
            uint2 QA[5][2], QB[8];
            const uint32_t tq = TB + 8 * (1 + g - 2 * t);
#pragma unroll
            for (int dd = 0; dd < 5; dd++) { QA[dd][0] = lds64(tq + T_A + 64 * (dd + 4)); QA[dd][1] = lds64(tq + T_A + 64 * (dd + 4) - 8); }
#pragma unroll
            for (int dd = 0; dd < 8; dd++) QB[dd] = lds64(tq + T_B + 64 * (dd + 8));
            const uint32_t u1 = UB + (mi & 1) * U_PL + (6 + r + (mi >> 1)) * 16;
            const uint32_t u2 = UB + ((mi & 1) ^ 1) * U_PL + (6 + r + (mi & 1) + 8 * (mi >> 1)) * 16;
            uint32_t n[4];
#pragma unroll
            for (int j = 0; j < 12; j++) {
                uint32_t m[4];
                ldsm4(u1 + j * 128, m[0], m[1], m[2], m[3]);
                if (!(j & 1)) ldsm4(u2 + j * 128, n[0], n[1], n[2], n[3]);
                const uint32_t n0 = n[2 * (j & 1)], n1 = n[2 * (j & 1) + 1];
                float wa[4], wb[4], wc[4], g1[4], g2[4];
                mma_bf_z(wa, bA.x, bA.y, bA.z, bA.w, m[0], m[1]);
                mma_bf_z(wb, bA.x, bA.y, bA.z, bA.w, n0, n1);
                mma_bf_z(wc, bA.x, bA.y, bA.z, bA.w, m[2], m[3]);
                if (j < 8) {
                    mma_bf_z(g1, bB.x, bB.y, bB.z, bB.w, m[0], m[1]);
                    mma_bf_z(g2, bB.x, bB.y, bB.z, bB.w, n0, n1);
                    mma_bf_k8(g1, bC.x, bC.y, m[2]);
                    mma_bf_k8(g2, bC.x, bC.y, m[3]);
                }
#pragma unroll
                for (int e = 0; e < 2; e++) {
                    const uint32_t q0 = pack_bf(wa[e], wa[e + 2]), q1 = pack_bf(wb[e], wb[e + 2]), q2 = q1 ^ p.zero, q3 = pack_bf(wc[e], wc[e + 2]);
#pragma unroll
                    for (int dd = 0; dd < 5; dd++)
                        if (j + 4 + dd < 16) mma_bf(D[j + 4 + dd], q0, q1, q2, q3, QA[dd][e].x, QA[dd][e].y);
                }
                if (j < 8) {
                    const uint32_t q0 = pack_bf(g1[0], g1[2]), q1 = pack_bf(g2[0], g2[2]), q2 = pack_bf(g1[1], g1[3]), q3 = pack_bf(g2[1], g2[3]);
#pragma unroll
                    for (int dd = 7 - j; dd >= 0; dd--) mma_bf(D[j + 8 + dd], q0, q1, q2, q3, QB[dd].x, QB[dd].y);
                }
                if ((j & 3) == 3) {
                    WSTAMP(4 + 2 * (j >> 2));
                    ship((j >> 2) + 1);
                    finish(j >> 2);
                    WSTAMP(5 + 2 * (j >> 2));
                    if (j < 11) {
                        asm volatile("{\n\t.reg .pred p;\n\tsetp.eq.u32 p, %0, %1;\n\t@p exit;\n\t}" :: "r"(p.zero), "r"(j) : "memory");
                        gq[1] = ld_gpu128(gsrc + 64 * (j >> 1));
                        if (j == 7) gq[0] = ld_gpu128(gsrc + 128);
                    }
                }
            }
            finish(3);
        }
        WSTAMP(10);
    } else if ((pw & 12) == AUX_W0) {
        asm volatile("setmaxnreg.dec.sync.aligned.u32 120;");
        const int v = __reduce_max_sync(0xffffffffu, pw & 3);
        const int at = tid & 127;
        const int g = lane >> 2, t = lane & 3;
        const unsigned epoch = *(volatile unsigned*)&g_epoch;
        const unsigned tag = (epoch + 1) & 0xffffu;
        const bool gu = c < NGU_CTA;
        {
            uint4 xa[16];
            const uint32_t row = 16 * c + 4 * v + (g >> 1);
            const bf16* xr = p.u + (size_t)row * D_ + 8 * (lane & 7);
#pragma unroll
            for (int kb = 0; kb < 16; kb++) xa[kb] = ldg128(xr + 64 * kb);
            sts128(sb + OFF_XSEL + at * 16, v_la.x, v_ai.x, v_la.y, v_ai.y);
            if (v == 2 && gu) g_h[(tag + 1) & 1][32 * c + lane] = make_uint4(0, 0, 0, 0);
            if (v == 0) sts32(sb + M_BMAP + lane * 4, 0);
            if (at == 32) { sts32(sb + M_TAG, tag << 16); mbar_arrive(bars + 8 * B_U); }
            cp_wait_all();
            bar_sync(1, 128);
            uint2 w[16];
#pragma unroll
            for (int kb = 0; kb < 16; kb++) w[kb] = lds64(sb + OFF_XSEL + 128 * kb + 32 * (g & 2) + 16 * t + 8 * (g & 1));
            float dr[4][4];
#pragma unroll
            for (int kb = 0; kb < 16; kb++) {
                if (kb < 4) mma_bf_z(dr[kb], xa[kb].x, xa[kb].y, xa[kb].z, xa[kb].w, w[kb].x, w[kb].y);
                else mma_bf(dr[kb & 3], xa[kb].x, xa[kb].y, xa[kb].z, xa[kb].w, w[kb].x, w[kb].y);
            }
            float rs = ((dr[0][0] + dr[0][3]) + (dr[1][0] + dr[1][3])) + ((dr[2][0] + dr[2][3]) + (dr[3][0] + dr[3][3]));
            rs += __shfl_xor_sync(0xffffffffu, rs, 5);
            const uint32_t rb = pack_bf(0.f, rs);
            if (!(lane & 7)) st_gpu32((uint32_t*)g_r + row, ((rb ^ (((int)rb >> 31) | 0x80000000u)) & 0xffff0000u) | tag);
            WSTAMP(1);
            const uint32_t one0 = 0x3F803F80u ^ p.zero, one1 = 0x3F803F80u + p.zero;
#pragma unroll
            for (int kb = 0; kb < 16; kb++) {
                const uint4 gw = lds128(sb + OFF_XSEL + 2048 + 128 * kb + 16 * (lane & 7));
                const uint32_t a0 = hmul2_bf(xa[kb].x, gw.x), a1 = hmul2_bf(xa[kb].y, gw.y), a2 = hmul2_bf(xa[kb].z, gw.z), a3 = hmul2_bf(xa[kb].w, gw.w);
                if (kb < 4) mma_bf_z(dr[kb], a0, a1, a2, a3, one0, one1);
                else mma_bf(dr[kb & 3], a0, a1, a2, a3, one0, one1);
            }
            float sg = ((dr[0][0] + dr[0][3]) + (dr[1][0] + dr[1][3])) + ((dr[2][0] + dr[2][3]) + (dr[3][0] + dr[3][3]));
            sg += __shfl_xor_sync(0xffffffffu, sg, 4);
            if (!(lane & 7)) st_gpu32((uint32_t*)g_g + ((row & 256) << 2) + gate_pos(row), (pack_bf(sigmoid_f(bf_round(sg)), 0.f) & 0xffffu) | (tag << 16));
            bar_sync(1, 128);
            WSTAMP(2);
        }
        asm volatile("barrier.cluster.wait.acquire.aligned;" ::: "memory");
        uint32_t top;
        {
            float acc[8][4];
#pragma unroll
            for (int i = 0; i < 8; i++) { acc[i][0] = acc[i][1] = acc[i][2] = acc[i][3] = 0.f; }
            const int krow = ((lane >> 1) & 8) + (lane & 7);
            const uint32_t tile0 = sb + OFF_RING + krow * 64 + ((((lane >> 3) & 1) ^ ((krow >> 1) & 3)) << 4);
            const uint32_t xo = sb + OFF_XSEL + (lane & 7) * XS_ROW + 512 * v + 2 * (lane & 24);
#pragma unroll 1
            for (int i = 0; i < 4; i++) {
                const int s = 4 * i + v;
                uint32_t a[16][4];
                if (gu) {
                    const uint32_t tile = tile0 + (s < 14 ? s : v) * 8192;
                    mbar_wait(bars + 8 * (B_W + s), 0);
#pragma unroll
                    for (int q = 0; q < 16; q++) ldsm4t((tile ^ ((q & 1) << 5)) + ((q >> 1) & 1) * 4096 + (q >> 2) * 1024, a[q][0], a[q][1], a[q][2], a[q][3]);
                    uint32_t dep = p.zero;
#pragma unroll
                    for (int q = 0; q < 16; q += 2) dep &= a[q][0] & a[q + 1][0];
                    if (lane == 0 && i < 3) mbar_arrive(bars + 8 * (B_E + s) + dep);
                    if (lane < 2 && (s < 2 || s == 12 || s == 13))
                        asm volatile("st.async.weak.shared::cluster.mbarrier::complete_tx::bytes.b32 [%0], %1, [%2];"
                                     :: "r"(mapa(sb + M_SINK, lane)), "r"(dep), "r"(mapa(bars + 8 * (B_F + (i >> 1)), lane)) : "memory");
                }
                if (i == 0) {
#pragma unroll 1
                    for (int it = 0; it < (1 << 22); it++) {
                        uint32_t tg;
                        asm volatile("ld.relaxed.gpu.global.v2.u32 {%0,%1}, [%2];" : "=r"(top), "=r"(tg) : "l"(&g_top[c % NTOP][lane & 7]) : "memory");
                        if (__all_sync(0xffffffffu, tg == tag)) break;
                        __nanosleep(TSLEEP);
                    }
                    WSTAMP(3);
                    const uint32_t row = ~top & 2047;
                    if (gu) {
#pragma unroll
                        for (int k = 0; k < 8; k++) cp16(sb + OFF_XSEL + k * XS_ROW + at * 16, p.u + (size_t)__shfl_sync(0xffffffffu, row, k) * D_ + at * 8);
                    }
                    if (v == 0) {
                        if (lane < 8 && ((row >> 8) & 1) == h)
                            asm volatile("red.shared.or.b32 [%0], %1;" :: "r"(sb + M_BMAP + (row & 7) * 16 + (row >> 9) * 4), "r"(1u << (gate_pos(row) & 31)) : "memory");
                        __syncwarp();
                        if (lane == 0) mbar_arrive(bars + 8 * B_Y);
                    }
                    if (!gu) break;
                    cp_wait_all();
                    __syncwarp();
                    WSTAMP(4);
                }
                uint32_t b[2][4];
                ldsm4(xo + 128 * i, b[0][0], b[0][1], b[0][2], b[0][3]);
                ldsm4(xo + 128 * i + 64, b[1][0], b[1][1], b[1][2], b[1][3]);
#pragma unroll
                for (int q = 0; q < 16; q++) mma_bf(acc[q & 7], a[q][0], a[q][1], a[q][2], a[q][3], b[q >> 3][(q >> 1) & 2], b[q >> 3][((q >> 1) & 2) + 1]);
            }
            if (gu) {
                WSTAMP(5);
                __syncwarp();
#pragma unroll
                for (int q = 0; q < 4; q++) {
                    const int ct = q >> 1, e = 2 * (q & 1);
                    sts128(sb + OFF_XSEL + q * XS_ROW + 512 * v + lane * 16,
                           __float_as_uint(acc[ct][e] + acc[4 + ct][e]), __float_as_uint(acc[2 + ct][e] + acc[6 + ct][e]),
                           __float_as_uint(acc[ct][e + 1] + acc[4 + ct][e + 1]), __float_as_uint(acc[2 + ct][e + 1] + acc[6 + ct][e + 1]));
                }
                bar_sync(1, 128);
                const uint32_t po = sb + OFF_XSEL + t * XS_ROW + (g & 3) * 128 + v * 16 + (lane >> 4) * 8;
                float hv[2];
#pragma unroll
                for (int e = 0; e < 2; e++) {
                    uint2 q[4];
#pragma unroll
                    for (int i = 0; i < 4; i++) q[i] = lds64(po + 64 * e + 512 * i);
                    const float s0 = (__uint_as_float(q[0].x) + __uint_as_float(q[1].x)) + (__uint_as_float(q[2].x) + __uint_as_float(q[3].x));
                    const float s1 = (__uint_as_float(q[0].y) + __uint_as_float(q[1].y)) + (__uint_as_float(q[2].y) + __uint_as_float(q[3].y));
                    const float gv = bf_round(p.gu_swap ? s1 : s0), uv = bf_round(p.gu_swap ? s0 : s1);
                    hv[e] = bf_round(gv * sigmoid_f(gv)) * uv;
                }
                const uint32_t hw = pack_bf(hv[0], hv[1]);
                st_gpu32((uint32_t*)&g_h[tag & 1][32 * c] + at, hw ? hw : 0x80000000u);
            }
        }
        WSTAMP(6);
        {
            top = __shfl_sync(0xffffffffu, top, at >> 4);
            const uint32_t row = ~top & 2047, ch = at & 15;
            uint32_t gfin;
#pragma unroll 1
            for (int it = 0; it < (1 << 22); it++) {
                asm volatile("ld.relaxed.gpu.global.u32 %0, [%1];" : "=r"(gfin) : "l"((const uint32_t*)g_g + ((row & 256) << 2) + gate_pos(row)) : "memory");
                if ((gfin >> 16) == tag) break;
            }
            const float rsel = bf_round(sigmoid_f(__uint_as_float((top ^ (((int)~top >> 31) | 0x80000000u)) & 0xffff0000u)));
            uint4 hq[14];
            {
                const uint4* hsrc = &g_h[tag & 1][32 * (56 * h + 14 * v)];
                {
#pragma unroll 1
                    for (int it = 0; it < (1 << 22); it++) {
                        uint32_t w;
                        asm volatile("ld.relaxed.gpu.global.u32 %0, [%1];" : "=r"(w) : "l"(hsrc + 32 * (lane < 14 ? lane : 0) + 8 * (pr & 3)) : "memory");
                        if (__all_sync(0xffffffffu, w != 0)) break;
                        __nanosleep(PSLEEP);
                    }
                }
#pragma unroll 1
                for (int it = 0; it < (1 << 22); it++) {
                    uint32_t mn = 0xffffffffu;
#pragma unroll
                    for (int i = 0; i < 14; i++) hq[i] = ld_gpu128(hsrc + 32 * i + lane);
#pragma unroll
                    for (int i = 0; i < 14; i++) mn = min(mn, hq[i].x);
                    if (__all_sync(0xffffffffu, mn != 0)) break;
                }
            }
            WSTAMP(7);
            float dd[4][4];
            const int krow = ((lane >> 1) & 8) + (lane & 7);
            const uint32_t tile = sb + OFF_RING + (4 + v) * 8192 + krow * 32 + ((((lane >> 3) ^ (krow >> 2)) & 1) << 4);
#pragma unroll
            for (int s = 0; s < 2; s++) {
                mbar_wait(bars + 8 * (B_W + 16 + 4 * s + v), 0);
#pragma unroll
                for (int j = 0; j < 14; j++) {
                    uint32_t a[4];
                    ldsm4t(tile + s * 32768 + j * 512, a[0], a[1], a[2], a[3]);
                    const uint4& hb = hq[7 * s + (j >> 1)];
                    if (s == 0 && j < 4) mma_bf_z(dd[j], a[0], a[1], a[2], a[3], (j & 1) ? hb.z : hb.x, (j & 1) ? hb.w : hb.y);
                    else mma_bf(dd[(j + 2 * s) & 3], a[0], a[1], a[2], a[3], (j & 1) ? hb.z : hb.x, (j & 1) ? hb.w : hb.y);
                }
            }
            WSTAMP(8);
            uint4 part;
            part.x = __float_as_uint((dd[0][0] + dd[1][0]) + (dd[2][0] + dd[3][0])); part.y = __float_as_uint((dd[0][1] + dd[1][1]) + (dd[2][1] + dd[3][1]));
            part.z = __float_as_uint((dd[0][2] + dd[1][2]) + (dd[2][2] + dd[3][2])); part.w = __float_as_uint((dd[0][3] + dd[1][3]) + (dd[2][3] + dd[3][3]));
            st_async16(mapa(sb + M_DPIN + at * 16, h ^ 1), part, mapa(bars + 8 * B_DP, h ^ 1));
            sts128(sb + OFF_XSEL + 4 * XS_ROW + at * 16, part.x, part.y, part.z, part.w);
            __syncwarp();
            if (lane == 0) mbar_arrive(bars + 8 * B_DP);
            const uint32_t po = sb + (4 * (ch & 7) + v) * 16 + (ch >> 3) * 8 + (lane >> 4) * 4;
            const uint32_t ya = sb + y_off(row >> 9) + ch * 512 + (((4 * (row & 7) + ((row >> 5) & 3)) ^ (((ch >> 2) << 1) | (ch & 1))) << 4) + 2 * row_elem(row);
            const uint32_t s5 = (row & 255) + 5;
            uint32_t x16, y16;
            mbar_wait(bars + 8 * B_U, 0);
            asm volatile("ld.shared.u16 %0, [%1];" : "=r"(x16) : "r"(sb + OFF_S + (4 * (row >> 9) + (s5 & 3)) * S_PL + (s5 >> 2) * 32 + ((2 * ch) ^ (s5 & 16))) : "memory");
            mbar_wait(bars + 8 * B_DP, 0);
            float tot = 0.f;
#pragma unroll
            for (int i = 0; i < 4; i++) tot += ldsf(po + M_DPIN + 512 * i) + ldsf(po + OFF_XSEL + 4 * XS_ROW + 512 * i);
            const float b = bf_round(__uint_as_float(x16 << 16) + bf_round(bf_round(tot) * rsel));
            if (((row >> 8) & 1) == h) {
                mbar_wait(bars + 8 * (B_Y + (row >> 9)), 0);
                asm volatile("ld.shared.u16 %0, [%1];" : "=r"(y16) : "r"(ya) : "memory");
                p.out[(size_t)row * D_ + 16 * pr + ch] = __float2bfloat16_rn(fmaf(bf_lo(gfin), __uint_as_float(y16 << 16), bf_round(bf_round(1.f - bf_lo(gfin)) * b)));
            }
        }
        WSTAMP(9);
        if (at == 0 && c == 0) *(volatile unsigned*)&g_epoch = epoch + 1;
    } else {
        asm volatile("setmaxnreg.dec.sync.aligned.u32 40;");
        const int v = __reduce_max_sync(0xffffffffu, pw - PREP_W0);
        const bool gu = c < NGU_CTA;
        auto request = [&](const int i) {
            const int s = 4 * i + v;
            const uint32_t bar = bars + 8 * (B_W + s), dst = sb + OFF_RING + (s < 14 ? s : s - 12) * 8192;
            WSTAMP(3 + i);
            if (i < 4) { mbar_expect(bar, 8192); tma3d(dst, &tm_gu, 32 * c, 256 * v + 64 * i, 0, bar); }
            else { mbar_expect(bar, 7168); tma2d(dst, &tm_down, 16 * pr, 1792 * h + 448 * v + 224 * (i - 4), bar); }
        };
        if (lane == 0) {
            if (DELAY_S > 0) __nanosleep(DELAY_S);
            mbar_expect(bars + 8 * (B_S + v), 4 * 66 * 32);
#pragma unroll
            for (int i = 0; i < 4; i++) tma2d(sb + OFF_S + (4 * v + i) * S_PL, &tm_x, ((i + 3) & 3) * 1024 + 16 * pr, 128 * v + 64 * h - (i == 0 ? 2 : 1), bars + 8 * (B_S + v));
        }
        {
            const int idx = tid - 32 * PREP_W0, cls = idx / 10, wd = idx % 10;
            const int tau = cls + 2 - 8 * ((wd < 4 ? wd : wd - 4) >> 1);
            const int lo = (wd < 4) ? ((wd & 1) ? -2 : 3) : ((wd & 1) ? -4 : -11), wid = (wd < 4 ? 3 : 7) + 2 * (wd & 1);
            if (cls < 11) sts32(sb + OFF_BAND + cls * 48 + wd * 4, ((unsigned)(tau - lo) < (unsigned)wid ? 0x3F80u : 0u) | ((unsigned)(tau - 4 - lo) < (unsigned)wid ? 0x3F800000u : 0u));
        }
        uint32_t ulast = 0;
        {
            const int s = 2043 + ((lane & 7) >> 1) + 4 * (lane & 1);
            if (lane < 16 && s < L_) asm volatile("ld.global.nc.u16 %0, [%1];" : "=r"(ulast) : "l"(p.u + (size_t)s * D_ + 8 * c + 2 * v + (lane >> 3)));
        }
        int i = gu ? 0 : 4;
        if (gu && v < DEPTH) {
            if (lane == 0) { if (DELAY_G > 0) __nanosleep(DELAY_G); request(0); }
            i = 1;
        }
        __syncwarp();
        asm volatile("barrier.cluster.wait.acquire.aligned;" ::: "memory");
        mbar_wait(bars + 8 * (B_S + v), 0);
        WSTAMP(1);
        if (4 * i + v < EARLY) {
            if (lane == 0) request(i);
            i++;
        }
        __syncwarp();
        {
            const int mi = lane >> 3, r = lane & 7, g = lane >> 2, t = lane & 3;
            const uint32_t src = sb + OFF_S + (4 * v + mi) * S_PL + (((r & 2) << 1) | ((r & 4) >> 1) | (r & 1)) * 32 + ((h ^ ((r >> 1) & 1)) << 4);
            const uint32_t dst = sb + OFF_U + g * U_CH + (t >> 1) * U_PL + (7 + 32 * v + 16 * h + (t & 1)) * 16;
            const uint32_t rdst = mapa(dst, h ^ 1), rbar = mapa(bars + 8 * B_U, h ^ 1);
#pragma unroll
            for (int it = 0; it < 8; it++) {
                uint4 a, b;
                ldsm4t((src ^ 16) + it * 256, b.x, b.y, b.z, b.w);
                ldsm4t(src + it * 256, a.x, a.y, a.z, a.w);
                st_async16(rdst + it * 32, b, rbar);
                sts128(dst + it * 32, a.x, a.y, a.z, a.w);
            }
            if (lane < 16) sts16(sb + OFF_U + (2 * v + mi) * U_CH + 135 * 16 + 2 * r, ulast);
            __syncwarp();
        }
        if (lane == 0) {
            mbar_arrive(bars + 8 * B_U);
            WSTAMP(2);
#pragma unroll 1
            for (; i < 6; i++) {
                const int s = 4 * i + v;
                if (gu) mbar_wait(bars + 8 * (B_W + s - DEPTH), 0);
                if (s >= 6) mbar_wait(bars + 8 * ((gu && s >= 14) ? B_E + s - 12 : B_KG), 0);
                request(i);
            }
        }
    }
}

typedef CUresult (*EncodeFn)(CUtensorMap*, CUtensorMapDataType, cuuint32_t, void*, const cuuint64_t*, const cuuint64_t*,
                             const cuuint32_t*, const cuuint32_t*, CUtensorMapInterleave, CUtensorMapSwizzle,
                             CUtensorMapL2promotion, CUtensorMapFloatOOBfill);

void make_map(EncodeFn f, CUtensorMap* m, const void* ptr, uint64_t cols, uint64_t rows, uint32_t bc, uint32_t br, CUtensorMapSwizzle sw,
              uint32_t planes = 1, uint64_t plane_stride = 0) {
    cuuint64_t dims[3] = {cols, rows, planes};
    cuuint64_t str[2] = {cols * 2, plane_stride};
    cuuint32_t box[3] = {bc, br, planes};
    cuuint32_t es[3] = {1, 1, 1};
    f(m, CU_TENSOR_MAP_DATA_TYPE_BFLOAT16, planes > 1 ? 3 : 2, (void*)ptr, dims, str, box, es, CU_TENSOR_MAP_INTERLEAVE_NONE, sw,
      CU_TENSOR_MAP_L2_PROMOTION_L2_128B, CU_TENSOR_MAP_FLOAT_OOB_FILL_NONE);
}

}

extern "C" void kernel_launch(void* const* d_in, const int* in_sizes, int n_in, void* d_out, int out_size) {
    static EncodeFn enc = nullptr;
    if (!enc) {
        void* fn = nullptr;
        cudaDriverEntryPointQueryResult qr;
        cudaGetDriverEntryPoint("cuTensorMapEncodeTiled", &fn, cudaEnableDefault, &qr);
        enc = (EncodeFn)fn;
        cudaFuncSetAttribute(fused_kernel, cudaFuncAttributeMaxDynamicSharedMemorySize, SMEM_BYTES);
    }
    CUtensorMap tg, td, tx;
    const char *wg = (const char*)d_in[9], *wu = (const char*)d_in[10];
    const bool swap = wu < wg;
    make_map(enc, &tg, swap ? wu : wg, F_, D_, 32, 64, CU_TENSOR_MAP_SWIZZLE_64B, 2, swap ? wg - wu : wu - wg);
    make_map(enc, &td, d_in[11], D_, F_, 16, 224, CU_TENSOR_MAP_SWIZZLE_32B);
    make_map(enc, &tx, d_in[0], 4 * D_, L_ / 4, 16, 66, CU_TENSOR_MAP_SWIZZLE_32B);
    Params p;
    p.u = (const bf16*)d_in[0]; p.logA = (const bf16*)d_in[1]; p.Aim = (const bf16*)d_in[2];
    p.Cre = (const bf16*)d_in[3]; p.Cim = (const bf16*)d_in[4]; p.logdt = (const bf16*)d_in[5];
    p.Dskip = (const bf16*)d_in[6]; p.wr = (const bf16*)d_in[8]; p.gatew = (const bf16*)d_in[12];
    p.out = (bf16*)d_out;
    p.gu_swap = swap;
    p.zero = 0;
    fused_kernel<<<NCTA, NTHREADS, SMEM_BYTES>>>(p, tg, td, tx);
}
```

```cpp
#include <cuda_runtime.h>
#include <cuda_bf16.h>
#include <cuda_fp16.h>
#include <cuda.h>
#include <stdint.h>

typedef __nv_bfloat16 bf16;

namespace {

constexpr int L_ = 2048, D_ = 1024, F_ = 3584;
constexpr int NCTA = 130;
constexpr int NTHREADS = 512;
#define AUXW 12
constexpr int MAIN_W0 = 0, AUX_W0 = AUXW, PREP_W0 = 20 - AUXW;
#define T0 2700
#define GAP 630
#define STAG GAP
#define CSLEEP 100
#define SLACK 300
#define DELAY_X 300
#define TSLEEP 40
#define PSLEEP 40
constexpr int NGU_CTA = 112;

constexpr int OFF_RING = 0;
constexpr int OFF_SCR  = 6 * 8192;
constexpr int S_PL     = 2304;
constexpr int OFF_S    = 114688;
constexpr int U_PL     = 2240;
constexpr int U_CH     = 4416;
constexpr int OFF_U    = 151552;
constexpr int TAB_W    = 3200;
constexpr int T_PL     = 544;
constexpr int T_A      = 2192 - 26 * 8;
constexpr int T_B      = 2568 - 59 * 8;
constexpr int OFF_TAB  = 186880;
constexpr int OFF_XSEL = 212480;
constexpr int XS_ROW   = 2064;
constexpr int OFF_BAND = 228992;
constexpr int OFF_MISC = 229536;
constexpr int M_BARS   = OFF_MISC;
constexpr int M_DSK    = OFF_MISC + 2736;
constexpr int M_SINK   = OFF_MISC + 512;
constexpr int M_TAG    = OFF_MISC + 516;
constexpr int M_BMAP   = OFF_MISC + 528;
constexpr int M_DPIN   = OFF_MISC + 656;
constexpr int M_TOP    = OFF_MISC + 2704;
constexpr int SMEM_BYTES = OFF_MISC + 2768;
__host__ __device__ constexpr uint32_t y_off(uint32_t q) { return OFF_RING + (q & 1) * 8192 + (q >> 1) * 98304; }

constexpr int B_W = 0;
constexpr int B_E = 24;
constexpr int B_S = 36;
constexpr int B_Y = 40;
constexpr int B_DP = 44, B_U = 45, B_KG = 46, B_G = 47;
constexpr int B_F = 48;
constexpr int B_H = 60;
constexpr int B_X = 52, B_XE = 56;

struct BandTab { uint32_t w[11][12]; };
constexpr BandTab make_band() {
    BandTab b{};
    for (int cls = 0; cls < 11; cls++)
        for (int wd = 0; wd < 10; wd++) {
            const int tau = cls + 2 - 8 * ((wd < 4 ? wd : wd - 4) >> 1);
            const int lo = (wd < 4) ? ((wd & 1) ? -2 : 3) : ((wd & 1) ? -4 : -11), wid = (wd < 4 ? 3 : 7) + 2 * (wd & 1);
            b.w[cls][wd] = ((tau >= lo && tau < lo + wid) ? 0x3F80u : 0u) | ((tau - 4 >= lo && tau - 4 < lo + wid) ? 0x3F800000u : 0u);
        }
    return b;
}
constexpr int NTOP = 32;
struct Scratch {
    uint4 r[L_ / 4];
    uint4 g[L_ / 4];
    uint4 h[2][8 * F_ / 8];
    uint32_t top[NTOP][32];
    unsigned epoch;
};
__device__ __align__(128) Scratch g_scratch;
__device__ const __align__(16) BandTab g_band = make_band();

struct Params {
    const bf16 *u, *logA, *Aim, *Cre, *Cim, *logdt, *Dskip, *wr, *gatew;
    bf16* out;
    Scratch* sc;
    const uint4* band;
    uint32_t gu_swap;
    uint32_t zero;
};

#define WSTAMP(i) do {} while (0)
#define KSTAMP(i, dep) do {} while (0)
#define WDUMP() do {} while (0)
#define RSTAMP(i) do {} while (0)

#define NOALLOC ".L1::no_allocate"
__device__ __forceinline__ uint32_t smem_u32(const void* p) { return (uint32_t)__cvta_generic_to_shared(p); }
__device__ __forceinline__ void mbar_init(uint32_t b, uint32_t c) { asm volatile("mbarrier.init.shared::cta.b64 [%0], %1;" :: "r"(b), "r"(c) : "memory"); }
__device__ __forceinline__ void mbar_expect(uint32_t b, uint32_t tx) { asm volatile("mbarrier.arrive.expect_tx.shared::cta.b64 _, [%0], %1;" :: "r"(b), "r"(tx) : "memory"); }
__device__ __forceinline__ void mbar_arrive(uint32_t b) { asm volatile("mbarrier.arrive.shared::cta.b64 _, [%0];" :: "r"(b) : "memory"); }
__device__ __forceinline__ void mbar_wait(uint32_t b, uint32_t parity = 0) {
    asm volatile("{\n\t.reg .pred p;\nW%=:\n\tmbarrier.try_wait.parity.shared::cta.b64 p, [%0], %1, 20000;\n\t@!p bra W%=;\n\t}" :: "r"(b), "r"(parity) : "memory");
}
__device__ __forceinline__ uint32_t mapa(uint32_t addr, uint32_t rank) { uint32_t r; asm("mapa.shared::cluster.u32 %0, %1, %2;" : "=r"(r) : "r"(addr), "r"(rank)); return r; }
__device__ __forceinline__ void tma3d(uint32_t dst, const CUtensorMap* tm, int c0, int c1, uint32_t bar, uint32_t bytes) {
    asm volatile("{\n\t.reg .pred p;\n\telect.sync _|p, 0xffffffff;\n\t"
                 "@p mbarrier.arrive.expect_tx.shared::cta.b64 _, [%2], %5;\n\t"
                 "@p cp.async.bulk.tensor.3d.shared::cluster.global.mbarrier::complete_tx::bytes [%0], [%1, {%3, %4, 0}], [%2];\n\t}"
        :: "r"(dst), "l"(tm), "r"(bar), "r"(c0), "r"(c1), "r"(bytes) : "memory");
}
__device__ __forceinline__ void st_async16(uint32_t dst, const uint4& v, uint32_t bar) {
    asm volatile("st.async.weak.shared::cluster.mbarrier::complete_tx::bytes.v4.b32 [%0], {%1,%2,%3,%4}, [%5];"
                 :: "r"(dst), "r"(v.x), "r"(v.y), "r"(v.z), "r"(v.w), "r"(bar) : "memory");
}
__device__ __forceinline__ void bar_sync(int id, int n) { asm volatile("bar.sync %0, %1;" :: "r"(id), "r"(n) : "memory"); }
__device__ __forceinline__ void cp16(uint32_t dst, const void* src) { asm volatile("cp.async.cg.shared.global [%0], [%1], 16;" :: "r"(dst), "l"(src) : "memory"); }
__device__ __forceinline__ void cp_wait_all() { asm volatile("cp.async.wait_all;" ::: "memory"); }
__device__ __forceinline__ uint2 ldg64(const void* p) { uint2 v; asm volatile("ld.global.nc" NOALLOC ".v2.u32 {%0,%1}, [%2];" : "=r"(v.x), "=r"(v.y) : "l"(p)); return v; }
__device__ __forceinline__ uint4 ld_gpu128(const void* p) { uint4 v; asm volatile("ld.relaxed.gpu.global.v4.u32 {%0,%1,%2,%3}, [%4];" : "=r"(v.x), "=r"(v.y), "=r"(v.z), "=r"(v.w) : "l"(p) : "memory"); return v; }
__device__ __forceinline__ void st_gpu32(void* p, uint32_t v) { asm volatile("st.relaxed.gpu.global.u32 [%0], %1;" :: "l"(p), "r"(v) : "memory"); }

__device__ __forceinline__ void ldsm4(uint32_t a, uint32_t& r0, uint32_t& r1, uint32_t& r2, uint32_t& r3) {
    asm volatile("ldmatrix.sync.aligned.m8n8.x4.shared.b16 {%0,%1,%2,%3}, [%4];" : "=r"(r0), "=r"(r1), "=r"(r2), "=r"(r3) : "r"(a) : "memory");
}
__device__ __forceinline__ void ldsm4t(uint32_t a, uint32_t& r0, uint32_t& r1, uint32_t& r2, uint32_t& r3) {
    asm volatile("ldmatrix.sync.aligned.m8n8.x4.trans.shared.b16 {%0,%1,%2,%3}, [%4];" : "=r"(r0), "=r"(r1), "=r"(r2), "=r"(r3) : "r"(a) : "memory");
}
__device__ __forceinline__ uint32_t lds32(uint32_t a) { uint32_t v; asm volatile("ld.shared.u32 %0, [%1];" : "=r"(v) : "r"(a) : "memory"); return v; }
__device__ __forceinline__ uint2 lds64(uint32_t a) { uint2 v; asm volatile("ld.shared.v2.u32 {%0,%1}, [%2];" : "=r"(v.x), "=r"(v.y) : "r"(a) : "memory"); return v; }
__device__ __forceinline__ uint4 lds128(uint32_t a) { uint4 v; asm volatile("ld.shared.v4.u32 {%0,%1,%2,%3}, [%4];" : "=r"(v.x), "=r"(v.y), "=r"(v.z), "=r"(v.w) : "r"(a) : "memory"); return v; }
__device__ __forceinline__ void sts32(uint32_t a, uint32_t v) { asm volatile("st.shared.u32 [%0], %1;" :: "r"(a), "r"(v) : "memory"); }
__device__ __forceinline__ void sts16(uint32_t a, uint32_t v) { asm volatile("st.shared.u16 [%0], %1;" :: "r"(a), "h"((unsigned short)v) : "memory"); }
__device__ __forceinline__ void sts128(uint32_t a, uint32_t x, uint32_t y, uint32_t z, uint32_t w) { asm volatile("st.shared.v4.u32 [%0], {%1,%2,%3,%4};" :: "r"(a), "r"(x), "r"(y), "r"(z), "r"(w) : "memory"); }
__device__ __forceinline__ float ldsf(uint32_t a) { float v; asm volatile("ld.shared.f32 %0, [%1];" : "=f"(v) : "r"(a) : "memory"); return v; }

__device__ __forceinline__ void mma_bf(float (&d)[4], uint32_t a0, uint32_t a1, uint32_t a2, uint32_t a3, uint32_t b0, uint32_t b1) {
    asm volatile("mma.sync.aligned.m16n8k16.row.col.f32.bf16.bf16.f32 {%0,%1,%2,%3}, {%4,%5,%6,%7}, {%8,%9}, {%0,%1,%2,%3};"
        : "+f"(d[0]), "+f"(d[1]), "+f"(d[2]), "+f"(d[3]) : "r"(a0), "r"(a1), "r"(a2), "r"(a3), "r"(b0), "r"(b1));
}
__device__ __forceinline__ void mma_bf_z(float (&d)[4], uint32_t a0, uint32_t a1, uint32_t a2, uint32_t a3, uint32_t b0, uint32_t b1) {
    asm volatile("mma.sync.aligned.m16n8k16.row.col.f32.bf16.bf16.f32 {%0,%1,%2,%3}, {%4,%5,%6,%7}, {%8,%9}, {%10,%10,%10,%10};"
        : "=f"(d[0]), "=f"(d[1]), "=f"(d[2]), "=f"(d[3]) : "r"(a0), "r"(a1), "r"(a2), "r"(a3), "r"(b0), "r"(b1), "f"(0.f));
}
__device__ __forceinline__ void mma_bf_k8(float (&d)[4], uint32_t a0, uint32_t a1, uint32_t b0) {
    asm volatile("mma.sync.aligned.m16n8k8.row.col.f32.bf16.bf16.f32 {%0,%1,%2,%3}, {%4,%5}, {%6}, {%0,%1,%2,%3};"
        : "+f"(d[0]), "+f"(d[1]), "+f"(d[2]), "+f"(d[3]) : "r"(a0), "r"(a1), "r"(b0));
}
__device__ __forceinline__ void mma_h(float (&d)[4], uint32_t a0, uint32_t a1, uint32_t a2, uint32_t a3, uint32_t b0, uint32_t b1) {
    asm volatile("mma.sync.aligned.m16n8k16.row.col.f32.f16.f16.f32 {%0,%1,%2,%3}, {%4,%5,%6,%7}, {%8,%9}, {%0,%1,%2,%3};"
        : "+f"(d[0]), "+f"(d[1]), "+f"(d[2]), "+f"(d[3]) : "r"(a0), "r"(a1), "r"(a2), "r"(a3), "r"(b0), "r"(b1));
}
__device__ __forceinline__ uint32_t pack_bf(float lo, float hi) { uint32_t r; asm("cvt.rn.bf16x2.f32 %0, %1, %2;" : "=r"(r) : "f"(hi), "f"(lo)); return r; }
__device__ __forceinline__ uint32_t pack_h(float lo, float hi) { uint32_t r; asm("cvt.rn.f16x2.f32 %0, %1, %2;" : "=r"(r) : "f"(hi), "f"(lo)); return r; }
__device__ __forceinline__ float bf_lo(uint32_t v) { return __uint_as_float(v << 16); }
__device__ __forceinline__ float bf_hi(uint32_t v) { return __uint_as_float(v & 0xffff0000u); }
__device__ __forceinline__ float bf_round(float x) { return __uint_as_float(pack_bf(0.f, x) & 0xffff0000u); }
__device__ __forceinline__ uint32_t hmul2_bf(uint32_t a, uint32_t b) { uint32_t r; asm("mul.rn.bf16x2 %0, %1, %2;" : "=r"(r) : "r"(a), "r"(b)); return r; }
__device__ __forceinline__ float ex2f(float x) { float r; asm("ex2.approx.ftz.f32 %0, %1;" : "=f"(r) : "f"(x)); return r; }

__device__ __forceinline__ float exp_acc(float x) {
    const float t = x * 1.4426950216293335f;
    const float r = fmaf(x, 1.4426950216293335f, -t) + x * 1.9259629911266175e-8f;
    return ex2f(t) * fmaf(r, 0.6931471805599453f, 1.f);
}
__device__ __forceinline__ float sigmoid_f(float x) { return __fdividef(1.f, 1.f + ex2f(-x * 1.4426950408889634f)); }
__device__ __forceinline__ void cexp_pow(float lr, float li, float e, float& zr, float& zi) {
    const float mag = ex2f(lr * e * 1.4426950408889634f);
    const float th = li * e;
    const float k = (th * 0.15915494309189535f + 12582912.f) - 12582912.f;
    float r = fmaf(-k, 6.2831854820251465f, th);
    r = fmaf(-k, -1.7484555314695172e-7f, r);
    zr = mag * __cosf(r);
    zi = mag * __sinf(r);
}
__device__ __forceinline__ uint32_t hcmul(uint32_t a, uint32_t k, uint32_t kp) {
    const __half2 A = *reinterpret_cast<const __half2*>(&a);
    const __half2 r = __hfma2(__high2half2(A), *reinterpret_cast<const __half2*>(&kp), __hmul2(__low2half2(A), *reinterpret_cast<const __half2*>(&k)));
    return *reinterpret_cast<const uint32_t*>(&r);
}
#define CMUL(orr, oi, ar, ai, br, bi) do { float _r = (ar) * (br) - (ai) * (bi); float _i = (ar) * (bi) + (ai) * (br); orr = _r; oi = _i; } while (0)
#define CSQ(orr, oi, ar, ai) do { float _r = (ar) * (ar) - (ai) * (ai); float _i = 2.f * (ar) * (ai); orr = _r; oi = _i; } while (0)

__device__ __forceinline__ void mma_bf_k8z(float (&d)[4], uint32_t a0, uint32_t a1, uint32_t b0) {
    asm volatile("mma.sync.aligned.m16n8k8.row.col.f32.bf16.bf16.f32 {%0,%1,%2,%3}, {%4,%5}, {%6}, {%7,%7,%7,%7};"
        : "=f"(d[0]), "=f"(d[1]), "=f"(d[2]), "=f"(d[3]) : "r"(a0), "r"(a1), "r"(b0), "f"(0.f));
}
__device__ __forceinline__ void mma_hh_k8(uint32_t& d0, uint32_t& d1, uint32_t a0, uint32_t a1, uint32_t b0) {
    asm volatile("mma.sync.aligned.m16n8k8.row.col.f16.f16.f16.f16 {%0,%1}, {%2,%3}, {%4}, {%5,%5};"
        : "=r"(d0), "=r"(d1) : "r"(a0), "r"(a1), "r"(b0), "r"(0));
}
__device__ __forceinline__ void sched_fence(uint32_t zero, uint32_t id) {
    asm volatile("{\n\t.reg .pred p;\n\tsetp.eq.u32 p, %0, %1;\n\t@p exit;\n\t}" :: "r"(zero), "r"(id) : "memory");
}
__device__ __forceinline__ uint32_t pin(uint32_t x, int lane) { return __shfl_sync(0xffffffffu, x, lane); }
template <class T> __device__ __forceinline__ T* pin(T* x, int lane) { return (T*)__shfl_sync(0xffffffffu, (unsigned long long)x, lane); }
__device__ __forceinline__ void lds128_if(bool on, uint32_t a, uint32_t (&v)[4]) {
    asm volatile("{\n\t.reg .pred p;\n\tsetp.ne.u32 p, %5, 0;\n\t@p ld.shared.v4.u32 {%0,%1,%2,%3}, [%4];\n\t}"
        : "+r"(v[0]), "+r"(v[1]), "+r"(v[2]), "+r"(v[3]) : "r"(a), "r"((uint32_t)on) : "memory");
}
__device__ __forceinline__ uint32_t hfma2_bf(uint32_t a, uint32_t b, uint32_t c) { uint32_t r; asm("fma.rn.bf16x2 %0, %1, %2, %3;" : "=r"(r) : "r"(a), "r"(b), "r"(c)); return r; }
__device__ __forceinline__ uint32_t row_elem(uint32_t row) { return ((row >> 5) & 4) | ((row >> 2) & 2) | ((row >> 4) & 1); }
__device__ __forceinline__ uint32_t gate_pos(uint32_t row) { return ((row >> 9) << 8) | ((row & 7) << 5) | (row_elem(row) << 2) | ((row >> 5) & 3); }

__global__ void __cluster_dims__(2, 1, 1) __launch_bounds__(NTHREADS, 1)
fused_kernel(const Params p, const __grid_constant__ CUtensorMap tm_gu, const __grid_constant__ CUtensorMap tm_down,
             const __grid_constant__ CUtensorMap tm_x) {
    extern __shared__ __align__(1024) unsigned char smem[];
    const uint32_t sb = smem_u32(smem);
    int tid;
    asm volatile("mov.u32 %0, %%tid.x;" : "=r"(tid));
    const int pw = tid >> 5, lane = tid & 31;
    const int c = blockIdx.x, h = c & 1, pr = c >> 1;
    const uint32_t bars = sb + M_BARS;

    if (c >= 128) {
        if (c != 128) return;
        RSTAMP(5);
        const unsigned tag = (*(volatile unsigned*)&p.sc->epoch + 1) & 0xffffu;
        const uint32_t list = sb + 128;
#pragma unroll 1
        for (int pass = 0; pass < 2; pass++) {
            sts128(list + 16 * tid, 0, 0, 0, 0);
            if (tid == 0) sts32(sb + 64, 0);
            uint32_t key[4];
            bool ok = false;
#pragma unroll 1
            for (int it = 0; it < (1 << 22); it++) {
                const uint4 a = ld_gpu128(&p.sc->r[tid]);
                key[0] = a.x; key[1] = a.y; key[2] = a.z; key[3] = a.w;
                ok = (((a.x ^ tag) | (a.y ^ tag) | (a.z ^ tag) | (a.w ^ tag)) & 0xffffu) == 0;
                if (ok || !pass) break;
            }
            WSTAMP(0);
            uint32_t m = 0;
#pragma unroll
            for (int i = 0; i < 4; i++) {
                key[i] = ((pass ? key[i] : (lane + i) << 16) & 0xffff0000u) | (uint32_t)(2047 - (4 * tid + i));
                m = max(m, key[i]);
            }
            const uint32_t wm = __reduce_max_sync(0xffffffffu, m);
            if (lane == 0) sts32(sb + pw * 4, wm);
            __syncthreads();
            uint32_t thr = 0xffffffffu;
#pragma unroll
            for (int i = 0; i < 4; i++) { const uint4 q = lds128(sb + 16 * i); thr = min(thr, min(max(q.x, q.y), max(q.z, q.w))); }
            if (thr != 1) WSTAMP(1);
            if (m >= thr) {
                uint32_t pos;
                asm volatile("atom.shared.add.u32 %0, [%1], %2;" : "=r"(pos) : "r"(sb + 64), "r"(4 * ((key[0] >= thr) + (key[1] >= thr) + (key[2] >= thr) + (key[3] >= thr))) : "memory");
#pragma unroll
                for (int i = 0; i < 4; i++) if (key[i] >= thr) { sts32(list + pos, key[i]); pos += 4; }
            }
            __syncthreads();
            const uint32_t nc4 = lds32(sb + 64);
            if (nc4 != 1) WSTAMP(2);
#pragma unroll 1
            for (uint32_t j = 4 * pw; j < nc4; j += 64) {
                const uint32_t mine = lds32(list + j);
                int rank = 0;
#pragma unroll 1
                for (uint32_t i = 0; i < nc4; i += 128) rank += __popc(__ballot_sync(0xffffffffu, lds32(list + i + 4 * lane) > mine));
                if (rank < 8 && lane == 0) sts32(sb + 96 + 4 * rank, mine);
            }
            __syncthreads();
            if (tid < 8 * NTOP) st_gpu32(&p.sc->top[tid >> 3][tid & 7], lds32(sb + 96 + 4 * (tid & 7)) | (((tag + pass - 1) & 31) << 11));
            WSTAMP(3);
            if (!pass) RSTAMP(4);
        }
        WDUMP();
        return;
    }

    WSTAMP(0);
    if (pw < 8) {
        uint2 v_la, v_ai, v_cr, v_ci;
        uint32_t ldt16;
        const int d = 8 * c + pw - MAIN_W0;
        const size_t po = (size_t)d * 128 + 4 * lane;
        v_la = ldg64(p.logA + po); v_ai = ldg64(p.Aim + po); v_cr = ldg64(p.Cre + po); v_ci = ldg64(p.Cim + po);
        asm volatile("ld.global.nc.u16 %0, [%1];" : "=r"(ldt16) : "l"(p.logdt + d));
        if (lane == 0) asm volatile("cp.async.ca.shared.global [%0], [%1], 4;" :: "r"(sb + M_DSK + 4 * (pw - MAIN_W0)), "l"(p.Dskip + (d & ~1)) : "memory");
        asm volatile("barrier.cluster.arrive.relaxed.aligned;" ::: "memory");
        const int warp = pw - MAIN_W0;
        asm volatile("setmaxnreg.inc.sync.aligned.u32 168;");
        const int g = lane >> 2, t = lane & 3;
        const int mi = lane >> 3, r = lane & 7;
        const uint32_t TB = sb + OFF_TAB + warp * TAB_W;
        const uint32_t UB = sb + OFF_U + warp * U_CH;
        if (mi < 2) sts128(UB + mi * U_PL + r * 16, 0, 0, 0, 0);
#pragma unroll
        for (int i = 0; i < 6; i++) sts128(TB + 16 * (lane + 32 * i), 0, 0, 0, 0);
        if (lane < 8) sts128(TB + 16 * (lane + 192), 0, 0, 0, 0);
        __syncwarp();

        uint32_t cfix;
        {
            KSTAMP(4, v_la.x ^ v_ai.x ^ v_cr.x ^ v_ci.x ^ ldt16);
            const float dt = bf_round(exp_acc(__uint_as_float(ldt16 << 16)));
            float lr[4], li[4], cr[4], ci[4];
            float inv;
            {
                const uint32_t la[2] = {v_la.x, v_la.y}, ai[2] = {v_ai.x, v_ai.y}, vr[2] = {v_cr.x, v_cr.y}, vi[2] = {v_ci.x, v_ci.y};
                const uint32_t m2 = __vmaxu2(__vmaxu2(vr[0] & 0x7fff7fffu, vr[1] & 0x7fff7fffu), __vmaxu2(vi[0] & 0x7fff7fffu, vi[1] & 0x7fff7fffu));
                const uint32_t mx = __reduce_max_sync(0xffffffffu, max(m2, m2 << 16));
                const uint32_t e = min(max(mx >> 23, 11u), 254u);
                const float sc = __uint_as_float((264u - e) << 23);
                inv = __uint_as_float((e - 10u) << 23) * (2.f * dt);
#pragma unroll
                for (int i = 0; i < 4; i++) {
                    const float a = (i & 1) ? bf_hi(la[i >> 1]) : bf_lo(la[i >> 1]);
                    const float b = (i & 1) ? bf_hi(ai[i >> 1]) : bf_lo(ai[i >> 1]);
                    lr[i] = -bf_round(exp_acc(a)) * dt;
                    li[i] = b * dt;
                    cr[i] = ((i & 1) ? bf_hi(vr[i >> 1]) : bf_lo(vr[i >> 1])) * sc;
                    ci[i] = ((i & 1) ? bf_hi(vi[i >> 1]) : bf_lo(vi[i >> 1])) * sc;
                }
            }
            const uint32_t SX = sb + OFF_SCR + warp * 8192;
            const uint32_t sw = SX + (lane << 4);
#define PUT(buf, row, v) sts128(((sw + (row) * 512) ^ ((row) << 4)) + (buf) * 4096, v[0], v[1], v[2], v[3])
#define EMIT(bufa, rowa, bufb, rowb, xr, xi, k, kp) do { uint32_t pk[4], pd[4]; \
                _Pragma("unroll") for (int i = 0; i < 4; i++) { pk[i] = pack_h(xr[i], xi[i]); pd[i] = hcmul(pk[i], k[i], kp[i]); } \
                PUT(bufa, rowa, pk); PUT(bufb, rowb, pd); } while (0)
#define CMUL4(orr, oi, ar, ai, br, bi) _Pragma("unroll") for (int i = 0; i < 4; i++) CMUL(orr[i], oi[i], ar[i], ai[i], br[i], bi[i])
#define CSQ4(orr, oi, ar, ai) _Pragma("unroll") for (int i = 0; i < 4; i++) CSQ(orr[i], oi[i], ar[i], ai[i])
            float z1r[4], z1i[4], z2r[4], z2i[4], z8r[4], z8i[4], z256r[4], z256i[4];
            uint32_t k128[4], k128p[4], k4[4], k4p[4];
#pragma unroll
            for (int i = 0; i < 4; i++) {
                float tr, ti;
                cexp_pow(lr[i], li[i], 1.f, z1r[i], z1i[i]);
                CSQ(z2r[i], z2i[i], z1r[i], z1i[i]);
                CSQ(tr, ti, z2r[i], z2i[i]);
                k4[i] = pack_h(tr, ti); k4p[i] = pack_h(-ti, tr);
                CSQ(z8r[i], z8i[i], tr, ti);
                cexp_pow(lr[i], li[i], 128.f, tr, ti);
                k128[i] = pack_h(tr, ti); k128p[i] = pack_h(-ti, tr);
                CSQ(z256r[i], z256i[i], tr, ti);
                sts32(TB + i * T_PL + 16 + 4 * lane, k128[i]);
                sts32(TB + i * T_PL + 160 + 4 * lane, k128p[i]);
            }
            KSTAMP(5, k128[3] ^ k4[3]);
            uint32_t Ya[16][4];
            {
                float w1r[4], w1i[4], ar[4], ai[4], br[4], bi[4];
                uint32_t k8[4], k8p[4];
                const uint32_t one[4] = {0x3C00u, 0x3C00u, 0x3C00u, 0x3C00u};
#pragma unroll
                for (int i = 0; i < 4; i++) {
                    k8[i] = pack_h(z8r[i], -z8i[i]); k8p[i] = pack_h(z8i[i], z8r[i]);
                    CSQ(w1r[i], w1i[i], z8r[i], z8i[i]); w1i[i] = -w1i[i];
                }
                PUT(0, 0, one); PUT(1, 0, k8);
                EMIT(0, 1, 1, 1, w1r, w1i, k8, k8p);
                CSQ4(ar, ai, w1r, w1i);            EMIT(0, 2, 1, 2, ar, ai, k8, k8p);
                CMUL4(br, bi, ar, ai, w1r, w1i);   EMIT(0, 3, 1, 3, br, bi, k8, k8p);
                CSQ4(ar, ai, ar, ai);              EMIT(0, 4, 1, 4, ar, ai, k8, k8p);
                CMUL4(ar, ai, ar, ai, w1r, w1i);   EMIT(0, 5, 1, 5, ar, ai, k8, k8p);
                CSQ4(br, bi, br, bi);              EMIT(0, 6, 1, 6, br, bi, k8, k8p);
                CMUL4(br, bi, br, bi, w1r, w1i);   EMIT(0, 7, 1, 7, br, bi, k8, k8p);
                __syncwarp();
                KSTAMP(6, 0);
                const uint32_t ab = SX + (mi & 1) * 4096 + r * 512, ax = ((mi >> 1) ^ r) << 4;
#pragma unroll
                for (int ks = 0; ks < 16; ks++) ldsm4(ab + (ks >> 2) * 128 + (ax ^ ((ks & 3) << 5)), Ya[ks][0], Ya[ks][1], Ya[ks][2], Ya[ks][3]);
                __syncwarp();
            }
            KSTAMP(7, Ya[15][0]);
            const uint32_t ld0 = SX + r * 512 + ((mi ^ r) << 4), ld1 = ld0 ^ 64;
            float R[5][4], xr[4], xi[4];
            {
                float yr[4], yi[4];
                EMIT(0, 0, 0, 1, cr, ci, k4, k4p);
                CMUL4(yr, yi, cr, ci, z1r, z1i);        EMIT(0, 2, 0, 3, yr, yi, k4, k4p);
                CMUL4(xr, xi, cr, ci, z256r, z256i);    EMIT(1, 0, 1, 1, xr, xi, k4, k4p);
                CMUL4(yr, yi, yr, yi, z1r, z1i);        EMIT(0, 4, 0, 5, yr, yi, k4, k4p);
                CMUL4(cr, ci, xr, xi, z2r, z2i);        EMIT(1, 2, 1, 3, cr, ci, k4, k4p);
                CMUL4(yr, yi, yr, yi, z1r, z1i);        EMIT(0, 6, 0, 7, yr, yi, k4, k4p);
                CMUL4(xr, xi, xr, xi, z256r, z256i);    EMIT(1, 4, 1, 5, xr, xi, k4, k4p);
                CMUL4(xr, xi, xr, xi, z256r, z256i);    EMIT(1, 6, 1, 7, xr, xi, k4, k4p);
            }
            __syncwarp();
            {
                KSTAMP(8, 0);
                uint32_t bd[2][4] = {{0, 0, 0, 0}, {0, 0, 0, 0}};
                const bool on = (g >> 1) == t;
#pragma unroll
                for (int i = 0; i < 4; i++) { R[i][0] = R[i][1] = R[i][2] = R[i][3] = 0.f; }
#pragma unroll
                for (int k2 = 0; k2 < 8; k2++) {
                    uint32_t x[4], y[4], a1[2][4];
                    lds128_if(on, TB + t * T_PL + 16 + (g & 1) * 144 + 16 * k2, bd[k2 & 1]);
                    ldsm4(((k2 & 1) ? ld1 : ld0) + (k2 >> 1) * 128, x[0], x[1], x[2], x[3]);
                    ldsm4(((k2 & 1) ? ld1 : ld0) + (k2 >> 1) * 128 + 4096, y[0], y[1], y[2], y[3]);
#pragma unroll
                    for (int u = 0; u < 2; u++) {
                        mma_hh_k8(a1[u][0], a1[u][1], Ya[2 * k2 + u][0], Ya[2 * k2 + u][1], bd[k2 & 1][2 * u]);
                        mma_hh_k8(a1[u][2], a1[u][3], Ya[2 * k2 + u][2], Ya[2 * k2 + u][3], bd[k2 & 1][2 * u + 1]);
                    }
#pragma unroll
                    for (int u = 0; u < 2; u++) {
                        const uint32_t(&a0)[4] = Ya[2 * k2 + u];
                        mma_h(R[0], a0[0], a0[1], a0[2], a0[3], x[2 * u], x[2 * u + 1]);
                        mma_h(R[2], a0[0], a0[1], a0[2], a0[3], y[2 * u], y[2 * u + 1]);
                        mma_h(R[1], a1[u][0], a1[u][1], a1[u][2], a1[u][3], x[2 * u], x[2 * u + 1]);
                        mma_h(R[3], a1[u][0], a1[u][1], a1[u][2], a1[u][3], y[2 * u], y[2 * u + 1]);
                    }
                }
            }
            __syncwarp();
            KSTAMP(9, __float_as_uint(R[3][0]));
            asm volatile("barrier.cluster.wait.acquire.aligned;" ::: "memory");
            CMUL4(xr, xi, xr, xi, z256r, z256i);
            float s1024 = (xr[0] + xr[1]) + (xr[2] + xr[3]);
            CMUL4(xr, xi, xr, xi, z8r, z8i);        EMIT(0, 0, 0, 1, xr, xi, k128, k128p);
            CMUL4(xr, xi, xr, xi, z256r, z256i);    EMIT(0, 2, 0, 3, xr, xi, k128, k128p);
            CMUL4(xr, xi, xr, xi, z256r, z256i);    EMIT(0, 4, 0, 5, xr, xi, k128, k128p);
            CMUL4(xr, xi, xr, xi, z256r, z256i);    EMIT(0, 6, 0, 7, xr, xi, k128, k128p);
            __syncwarp();
            {
                KSTAMP(10, 0);
                float a1[4] = {0.f, 0.f, 0.f, 0.f};
                R[4][0] = R[4][1] = R[4][2] = R[4][3] = 0.f;
#pragma unroll
                for (int k2 = 0; k2 < 8; k2++) {
                    uint32_t x[4];
                    ldsm4(((k2 & 1) ? ld1 : ld0) + (k2 >> 1) * 128, x[0], x[1], x[2], x[3]);
                    mma_h(R[4], Ya[2 * k2][0], Ya[2 * k2][1], Ya[2 * k2][2], Ya[2 * k2][3], x[0], x[1]);
                    mma_h(a1, Ya[2 * k2 + 1][0], Ya[2 * k2 + 1][1], Ya[2 * k2 + 1][2], Ya[2 * k2 + 1][3], x[2], x[3]);
                }
#pragma unroll
                for (int i = 0; i < 4; i++) R[4][i] += a1[i];
            }
            if (lane == 0) mbar_arrive(bars + 8 * B_KG + (__float_as_uint(R[4][0]) & p.zero));
            KSTAMP(11, __float_as_uint(R[4][0]));
#undef PUT
#undef EMIT
#pragma unroll
            for (int o = 16; o > 0; o >>= 1) s1024 += __shfl_xor_sync(0xffffffffu, s1024, o);
            uint32_t w[4][4], dsk = 0;
            if (lane == 0) { cp_wait_all(); asm volatile("ld.shared.u16 %0, [%1];" : "=r"(dsk) : "r"(sb + M_DSK + 4 * warp + 2 * (warp & 1)) : "memory"); }
#pragma unroll
            for (int a = 0; a < 4; a++) {
                const float v0 = (a == 0) ? fmaf(R[0][0], inv, __uint_as_float(dsk << 16)) : R[a][0] * inv;
                const float v1 = R[a][1] * inv, v2 = R[a][2] * inv, v3 = R[a][3] * inv;
                w[a][0] = pack_bf(v0, 0.f); w[a][1] = pack_bf(v1, v0); w[a][2] = pack_bf(v2, v1); w[a][3] = pack_bf(v3, v2);
            }
            const uint32_t wb = TB + 16 + 16 * g, w1 = wb + t * T_PL, w2 = wb + 256 + 2 * t * T_PL;
            const uint32_t w3 = (t == 0) ? wb + 256 + 3 * T_PL : TB + T_A + 8 * (16 * t + g);
            const uint32_t w3s = (t == 0) ? 128 : 64, w3o = (t == 0) ? 8 : 12;
            const uint32_t k512 = __shfl_sync(0xffffffffu, w[2][1], 2);
#pragma unroll
            for (int a = 0; a < 2; a++) {
                sts128(w1 + 128 * a, w[a][0], w[a][1], w[a][2], w[a][3]);
                const uint32_t(&q)[4] = w[2 + a];
                if (t < 2) sts128(w2 + 128 * a, q[0], q[1], q[2], q[3]);
                if (t == 0) { sts128(w2 + T_PL + 128 * a, q[0], q[1], q[2], q[3]); sts32(w3 + 128 * a + 4, q[2]); }
                if (t != 1 && (a == 1 || lane != 2)) sts32(w3 + w3s * a, q[1]);
                if (t != 1) sts32(w3 + w3s * a + w3o, q[3]);
            }
            if (lane < 4)
                sts128(w1 + 512, __byte_perm(k512, 0, t == 3 ? 0x3210 : 0x4432), __byte_perm(k512, 0, t < 2 ? 0x3210 : t == 2 ? 0x3244 : 0x1044),
                       __byte_perm(k512, 0, t < 2 ? 0x1044 : 0x4444), 0);
            __syncwarp();
#pragma unroll
            for (int a = 0; a < 2; a++) {
                sts16(w1 + 128 * a + 18, w[a][3]);
                const uint32_t(&q)[4] = w[2 + a];
                if (t < 2) sts16(w2 + 128 * a + 18, q[3]);
                if (t == 0) { sts16(w2 + T_PL + 128 * a + 18, q[3]); sts16(w3 + 128 * a + 14, q[3]); }
            }
            if (t == 0) sts16(w3 + 128 - 4, w[3][0]);
            if (lane == 2 || (t == 0 && g > 0)) sts16(lane == 2 ? TB + 16 + 3 * T_PL + 4 * 127 : w3 - 4, w[2][0]);
            {
                const uint32_t b0 = pack_bf(R[4][0] * inv, R[4][2] * inv), b1 = pack_bf(R[4][1] * inv, R[4][3] * inv);
                const uint32_t wq = TB + T_B + 8 * (65 + 16 * t + g);
                sts32(wq, b0); sts32(wq + 12, b0); sts32(wq + 64, b1); sts32(wq + 76, b1);
            }
            cfix = pack_bf(s1024 * inv, s1024 * inv);
            if (lane == 0) sts32(TB + T_A + 8 * 64, cfix);
            __syncwarp();
        }
        WSTAMP(1);

        mbar_wait(bars + 8 * B_U);
        WSTAMP(2);

        float D[16][4];
        {
            const int x5 = g - t + 5;
            const uint32_t tabD = TB + (x5 & 3) * T_PL + (x5 & 12) + 16;
            {
                const uint32_t a1 = lds32(tabD - 8), a0 = p.zero;
#pragma unroll
                for (int jq = 0; jq < 4; jq++) {
                    uint32_t b[4];
                    ldsm4(UB + (9 + lane) * 16 + jq * 512, b[0], b[1], b[2], b[3]);
#pragma unroll
                    for (int i = 0; i < 4; i++) mma_bf_k8z(D[4 * jq + i], a0, a1, b[i]);
                }
            }
            const uint32_t ua = UB + (mi & 1) * U_PL + (8 + 8 * (mi >> 1) + r) * 16;
#pragma unroll 1
            for (int k0 = 0; k0 < 8; k0++) {
                uint32_t Uf[16][2];
#pragma unroll
                for (int jp = 0; jp < 8; jp++) ldsm4(ua + jp * 256 - k0 * 16, Uf[2 * jp][0], Uf[2 * jp][1], Uf[2 * jp + 1][0], Uf[2 * jp + 1][1]);
#pragma unroll
                for (int k1 = 0; k1 < 4; k1++) {
                    const uint32_t ta = tabD + 16 * (8 * k1 + k0);
                    const uint32_t a0 = lds32(ta), a1 = lds32(ta + 8), a2 = lds32(ta - 8), a3 = a0 ^ p.zero;
#pragma unroll
                    for (int J = k1; J < 16; J++) mma_bf(D[J], a0, a1, a2, a3, Uf[J - k1][0], Uf[J - k1][1]);
                }
                if (k0 == 0) {
                    const uint32_t ta = tabD + 16 * 32;
                    const uint32_t a0 = lds32(ta), a1 = lds32(ta + 8), a2 = lds32(ta - 8), a3 = a0 ^ p.zero;
#pragma unroll
                    for (int J = 4; J < 16; J++) mma_bf(D[J], a0, a1, a2, a3, Uf[J - 4][0], Uf[J - 4][1]);
                    const uint32_t f0 = (cfix ^ 0x80008000u) & (g == t ? 0xffffu : g == t + 4 ? 0xffff0000u : 0u);
                    const uint32_t f1 = p.zero, f2 = p.zero + p.zero, f3 = f0 ^ p.zero;
#pragma unroll
                    for (int J = 8; J < 16; J++) mma_bf(D[J], f0, f1, f2, f3, Uf[J - 8][0], Uf[J - 8][1]);
                }
            }
        }
        WSTAMP(3);
        {
            const int ch = 8 * h + warp;
            const uint32_t yo = sb + ch * 512 + ((lane ^ (((ch >> 2) << 1) | (ch & 1))) << 4);
            const uint32_t yr = mapa(yo, h ^ 1), ybr = mapa(bars + 8 * B_Y, h ^ 1);
            const uint32_t yi = sb + (4 * (r >> 1) + 2 * (mi & 1) + (r & 1)) * 512 + (((4 * warp + (mi >> 1)) ^ r) << 4);
            const int rho = 128 * (g >> 2) + 8 * ((g >> 1) & 1) + 16 * (g & 1) + warp;
            const uint32_t xs = sb + OFF_S + ((rho + 5) & 3) * S_PL + ((rho + 5) >> 2) * 32 + (((t >> 1) ^ (((rho + 5) >> 4) & 1)) << 4) + ((t & 1) << 3);
            bf16* op = p.out + (size_t)(256 * h + rho) * D_ + 16 * pr + 4 * t;
            const uint4* gsrc = &p.sc->g[256 * h + 8 * warp + g];
            uint32_t tag16;
            uint4 gq[2], sel;
            auto ship = [&](const int Q) {
                uint4 y[2];
#pragma unroll
                for (int hh = 0; hh < 2; hh++) {
                    const int J = 4 * Q + 2 * hh;
                    y[hh] = make_uint4(pack_bf(D[J][0], D[J][1]), pack_bf(D[J][2], D[J][3]), pack_bf(D[J + 1][0], D[J + 1][1]), pack_bf(D[J + 1][2], D[J + 1][3]));
                }
                if (!(Q & 1)) mbar_wait(bars + 8 * (B_F + (Q >> 1)));
                asm volatile("{\n\t.reg .pred p;\n\tsetp.eq.u32 p, %11, 0;\n\t"
                             "@p st.async.weak.shared::cluster.mbarrier::complete_tx::bytes.v4.b32 [%9], {%4,%5,%6,%7}, [%10];\n\t"
                             "@!p st.async.weak.shared::cluster.mbarrier::complete_tx::bytes.v4.b32 [%9], {%0,%1,%2,%3}, [%10];\n\t"
                             "@p st.shared.v4.b32 [%8], {%0,%1,%2,%3};\n\t@!p st.shared.v4.b32 [%8], {%4,%5,%6,%7};\n\t}"
                             :: "r"(y[0].x), "r"(y[0].y), "r"(y[0].z), "r"(y[0].w), "r"(y[1].x), "r"(y[1].y), "r"(y[1].z), "r"(y[1].w),
                                "r"(yo + y_off(Q)), "r"(yr + y_off(Q)), "r"(ybr + 8 * Q), "r"(h) : "memory");
                __syncwarp();
                if (lane == 0) mbar_arrive(bars + 8 * (B_Y + Q));
            };
            auto finish = [&](const int Q) {
                uint2 xq[4];
#pragma unroll
                for (int i = 0; i < 4; i++) xq[i] = lds64(xs + Q * 4 * S_PL + i * 256);
#pragma unroll 1
                for (int it = 0; ((((gq[Q & 1].x ^ tag16) | (gq[Q & 1].y ^ tag16)) | ((gq[Q & 1].z ^ tag16) | (gq[Q & 1].w ^ tag16))) >> 16) && it < (1 << 22); it++)
                    gq[Q & 1] = ld_gpu128(gsrc + 64 * Q);
                uint32_t gg[4] = {gq[Q & 1].x, gq[Q & 1].y, gq[Q & 1].z, gq[Q & 1].w};
#pragma unroll
                for (int i = 0; i < 4; i++) {
                    gg[i] = __byte_perm(gg[i], 0, 0x1010);
                    const uint32_t og = hfma2_bf(gg[i], 0xBF80BF80u, 0x3F803F80u);
                    xq[i].x = hmul2_bf(og, xq[i].x); xq[i].y = hmul2_bf(og, xq[i].y);
                }
                mbar_wait(bars + 8 * (B_Y + Q));
                __syncwarp();
                if (Q == 0) sel = lds128(sb + M_BMAP + warp * 16);
                const uint32_t sbits = (Q == 0 ? sel.x : Q == 1 ? sel.y : Q == 2 ? sel.z : sel.w) >> (4 * g);
#pragma unroll
                for (int x = 0; x < 2; x++) {
                    uint32_t y[4];
                    ldsm4t((yi ^ (x << 5)) + y_off(Q), y[0], y[1], y[2], y[3]);
#pragma unroll
                    for (int e = 0; e < 2; e++) {
                        const int i = 2 * x + e;
                        const uint2 o = make_uint2(hfma2_bf(gg[i], y[2 * e], xq[i].x), hfma2_bf(gg[i], y[2 * e + 1], xq[i].y));
                        if (!(sbits & (1u << i))) *(uint2*)(op + (size_t)(512 * Q + 32 * i) * D_) = o;
                    }
                }
            };
            gq[0] = ld_gpu128(gsrc);
            ship(0);
            tag16 = lds32(sb + M_TAG);
            const uint4 bA = lds128(sb + OFF_BAND + (g - t + 3) * 48), bB = lds128(sb + OFF_BAND + (g - t + 3) * 48 + 16);
            const uint2 bC = lds64(sb + OFF_BAND + (g - t + 3) * 48 + 32);
            uint2 QA[5][2], QB[8];
            const uint32_t tq = TB + 8 * (1 + g - 2 * t);
#pragma unroll
            for (int dd = 0; dd < 5; dd++) { QA[dd][0] = lds64(tq + T_A + 64 * (dd + 4)); QA[dd][1] = lds64(tq + T_A + 64 * (dd + 4) - 8); }
#pragma unroll
            for (int dd = 0; dd < 8; dd++) QB[dd] = lds64(tq + T_B + 64 * (dd + 8));
            const uint32_t u1 = UB + (mi & 1) * U_PL + (7 + r + (mi >> 1)) * 16;
            const uint32_t u2 = UB + ((mi & 1) ^ 1) * U_PL + (7 + r + (mi & 1) + 8 * (mi >> 1)) * 16;
            uint32_t n[4];
#pragma unroll
            for (int j = 0; j < 12; j++) {
                uint32_t m[4];
                ldsm4(u1 + j * 128, m[0], m[1], m[2], m[3]);
                if (!(j & 1)) ldsm4(u2 + j * 128, n[0], n[1], n[2], n[3]);
                const uint32_t n0 = n[2 * (j & 1)], n1 = n[2 * (j & 1) + 1];
                float wa[4], wb[4], wc[4], g1[4], g2[4];
                mma_bf_z(wa, bA.x, bA.y, bA.z, bA.w, m[0], m[1]);
                mma_bf_z(wb, bA.x, bA.y, bA.z, bA.w, n0, n1);
                mma_bf_z(wc, bA.x, bA.y, bA.z, bA.w, m[2], m[3]);
                if (j < 8) {
                    mma_bf_z(g1, bB.x, bB.y, bB.z, bB.w, m[0], m[1]);
                    mma_bf_z(g2, bB.x, bB.y, bB.z, bB.w, n0, n1);
                    mma_bf_k8(g1, bC.x, bC.y, m[2]);
                    mma_bf_k8(g2, bC.x, bC.y, m[3]);
                }
#pragma unroll
                for (int e = 0; e < 2; e++) {
                    const uint32_t q0 = pack_bf(wa[e], wa[e + 2]), q1 = pack_bf(wb[e], wb[e + 2]), q2 = q1 ^ p.zero, q3 = pack_bf(wc[e], wc[e + 2]);
#pragma unroll
                    for (int dd = 0; dd < 5; dd++)
                        if (j + 4 + dd < 16) mma_bf(D[j + 4 + dd], q0, q1, q2, q3, QA[dd][e].x, QA[dd][e].y);
                }
                if (j < 8) {
                    const uint32_t q0 = pack_bf(g1[0], g1[2]), q1 = pack_bf(g2[0], g2[2]), q2 = pack_bf(g1[1], g1[3]), q3 = pack_bf(g2[1], g2[3]);
#pragma unroll
                    for (int dd = 7 - j; dd >= 0; dd--) mma_bf(D[j + 8 + dd], q0, q1, q2, q3, QB[dd].x, QB[dd].y);
                }
                if ((j & 3) == 3) {
                    WSTAMP(4 + 2 * (j >> 2));
                    ship((j >> 2) + 1);
                    finish(j >> 2);
                    WSTAMP(5 + 2 * (j >> 2));
                    if (j < 11) {
                        sched_fence(p.zero, j);
                        gq[1] = ld_gpu128(gsrc + 64 * (j >> 1));
                        if (j == 7) gq[0] = ld_gpu128(gsrc + 128);
                    }
                }
            }
            finish(3);
        }
        WSTAMP(10);
        WDUMP();
    } else if ((pw & 12) == AUX_W0) {
        asm volatile("setmaxnreg.inc.sync.aligned.u32 136;");
        const int v = __reduce_max_sync(0xffffffffu, pw & 3);
        const int at = tid & 127;
        const int g = lane >> 2, t = lane & 3;
        unsigned epoch, tag;
        const bool gu = c < NGU_CTA;
        {
            uint4 xa[16];
            const uint32_t gws = sb + (gu ? M_DPIN : OFF_XSEL + 2048);
            const uint32_t row = 16 * c + 4 * v + (g >> 1);
            if (lane == 0) {
                mbar_init(bars + 8 * (B_X + v), 1);
                mbar_init(bars + 8 * (B_XE + v), 1);
                asm volatile("fence.proxy.async.shared::cta;" ::: "memory");
                asm volatile("fence.mbarrier_init.release.cluster;" ::: "memory");
            }
            __syncwarp();
            epoch = *(volatile unsigned*)&p.sc->epoch;
            tag = (epoch + 1) & 0xffffu;
#pragma unroll
            for (int i = 0; i < 4; i++)
                asm volatile("cp.async.ca.shared.global [%0], [%1], 4;" :: "r"(sb + OFF_XSEL + 512 * i + (tid & 124) * 4 + (tid & 1) * 8 + (tid & 2) * 2),
                             "l"(p.wr + 256 * i + (tid & 127) * 2) : "memory");
            cp16(gws + (tid & 127) * 16, p.gatew + (tid & 127) * 8);
            if ((tid & 127) < 33) cp16(sb + OFF_BAND + (tid & 127) * 16, p.band + (tid & 127));
            asm volatile("barrier.cluster.arrive.relaxed.aligned;" ::: "memory");
            if (DELAY_X > 0) __nanosleep(DELAY_X);
            asm volatile("{\n\t.reg .pred p;\n\telect.sync _|p, 0xffffffff;\n\t"
                         "@p mbarrier.arrive.expect_tx.shared::cta.b64 _, [%2], 8192;\n\t"
                         "@p cp.async.bulk.shared::cluster.global.mbarrier::complete_tx::bytes [%0], [%1], 8192, [%2];\n\t}"
                :: "r"(sb + OFF_RING + (2 + v) * 8192), "l"(p.u + (size_t)(16 * c + 4 * v) * D_), "r"(bars + 8 * (B_X + v)) : "memory");
            if (gu) {
                st_gpu32((uint32_t*)&p.sc->h[(tag + 1) & 1][32 * c] + at, 0);
            }
            if (v == 0) sts32(sb + M_BMAP + lane * 4, 0);
            cp_wait_all();
            bar_sync(1, 128);
            uint2 w[16];
#pragma unroll
            for (int kb = 0; kb < 16; kb++) w[kb] = lds64(sb + OFF_XSEL + 128 * kb + 32 * (g & 2) + 16 * t + 8 * (g & 1));
            mbar_wait(bars + 8 * (B_X + v));
            WSTAMP(10);
#pragma unroll
            for (int kb = 0; kb < 16; kb++) xa[kb] = lds128(sb + OFF_RING + (2 + v) * 8192 + (g >> 1) * 2048 + 128 * kb + 16 * (lane & 7));
            float dr[4][4];
#pragma unroll
            for (int kb = 0; kb < 16; kb++) {
                if (kb < 4) mma_bf_z(dr[kb], xa[kb].x, xa[kb].y, xa[kb].z, xa[kb].w, w[kb].x, w[kb].y);
                else mma_bf(dr[kb & 3], xa[kb].x, xa[kb].y, xa[kb].z, xa[kb].w, w[kb].x, w[kb].y);
            }
            float rs = ((dr[0][0] + dr[0][3]) + (dr[1][0] + dr[1][3])) + ((dr[2][0] + dr[2][3]) + (dr[3][0] + dr[3][3]));
            if (lane == 0) mbar_arrive(bars + 8 * (B_XE + v) + (__float_as_uint(rs) & p.zero));
            rs += __shfl_xor_sync(0xffffffffu, rs, 5);
            const uint32_t rb = pack_bf(0.f, rs);
            if (!(lane & 7)) st_gpu32((uint32_t*)p.sc->r + row, ((rb ^ (((int)rb >> 31) | 0x80000000u)) & 0xffff0000u) | tag);
            WSTAMP(1);
            asm volatile("barrier.cluster.wait.acquire.aligned;" ::: "memory");
            {
                const int r = lane & 7;
                const uint32_t src = sb + OFF_S + (4 * v + (lane >> 3)) * S_PL + (r >> 1) * 128 + (r & 1) * 32 + ((h ^ ((r >> 1) & 1)) << 4);
                const uint32_t dst = sb + OFF_U + g * U_CH + (8 + 32 * v + 16 * h + t) * 16;
                const uint32_t rdst = mapa(dst, h ^ 1), rbar = mapa(bars + 8 * B_U, h ^ 1);
                mbar_wait(bars + 8 * (B_S + v));
                uint4 a[8];
#pragma unroll
                for (int b = 0; b < 2; b++) {
#pragma unroll
                    for (int j = 0; j < 8; j++) ldsm4t((b ? src : src ^ 16) + (j >> 1) * 512 + (j & 1) * 64, a[j].x, a[j].y, a[j].z, a[j].w);
#pragma unroll
                    for (int j = 0; j < 8; j++) {
                        if (b) sts128(dst + (j >> 1) * 64 + (j & 1) * U_PL, a[j].x, a[j].y, a[j].z, a[j].w);
                        else st_async16(rdst + (j >> 1) * 64 + (j & 1) * U_PL, a[j], rbar);
                    }
                }
                if (h && v == 3) {
                    ldsm4t((src ^ 16) + 2048, a[0].x, a[0].y, a[0].z, a[0].w);
                    ldsm4t(src + 2048, a[1].x, a[1].y, a[1].z, a[1].w);
                    if (t == 0) { st_async16(rdst + 256, a[0], rbar); sts128(dst + 256, a[1].x, a[1].y, a[1].z, a[1].w); }
                }
                __syncwarp();
                if (lane == 0) mbar_arrive(bars + 8 * B_U);
            }
            const uint32_t one0 = 0x3F803F80u ^ p.zero, one1 = 0x3F803F80u + p.zero;
#pragma unroll
            for (int kb = 0; kb < 16; kb++) {
                const uint4 gw = lds128(gws + 128 * kb + 16 * (lane & 7));
                const uint32_t a0 = hmul2_bf(xa[kb].x, gw.x), a1 = hmul2_bf(xa[kb].y, gw.y), a2 = hmul2_bf(xa[kb].z, gw.z), a3 = hmul2_bf(xa[kb].w, gw.w);
                if (kb < 4) mma_bf_z(dr[kb], a0, a1, a2, a3, one0, one1);
                else mma_bf(dr[kb & 3], a0, a1, a2, a3, one0, one1);
            }
            float sg = ((dr[0][0] + dr[0][3]) + (dr[1][0] + dr[1][3])) + ((dr[2][0] + dr[2][3]) + (dr[3][0] + dr[3][3]));
            sg += __shfl_xor_sync(0xffffffffu, sg, 4);
            if (!(lane & 7)) st_gpu32((uint32_t*)p.sc->g + ((row & 256) << 2) + gate_pos(row), (pack_bf(sigmoid_f(bf_round(sg)), 0.f) & 0xffffu) | (tag << 16));
            WSTAMP(2);
        }
        if (at == 32) { sts32(sb + M_TAG, tag << 16); mbar_arrive(bars + 8 * B_F); }
        const bool lane0 = pin(lane, lane) == 0;
        const uint32_t own = pin(sb + OFF_XSEL + at * 16, lane);
        const uint4* pb = pin(&p.sc->h[tag & 1][32 * (56 * h + 14 * v + (lane < 14 ? lane : 0)) + 8 * (pr & 3)], lane);
        {
            float acc[8][4];
#pragma unroll
            for (int i = 0; i < 8; i++) { acc[i][0] = acc[i][1] = acc[i][2] = acc[i][3] = 0.f; }
            const int krow = ((lane >> 1) & 8) + (lane & 7);
            const uint32_t tile0 = pin(sb + OFF_RING + krow * 64 + ((((lane >> 3) & 1) ^ ((krow >> 1) & 3)) << 4), lane);
            const uint32_t xo = pin(sb + OFF_XSEL + (lane & 7) * XS_ROW + 512 * v + 2 * (lane & 24), lane);
            const uint32_t po = pin(sb + OFF_XSEL + t * XS_ROW + (g & 3) * 128 + v * 16 + (lane >> 4) * 8, lane);
            uint32_t* hdst = pin((uint32_t*)&p.sc->h[tag & 1][32 * c] + at, lane);
            auto signal = [&](const int k, const uint32_t dep) {
                if (lane < 2 && v < 2)
                    asm volatile("st.async.weak.shared::cluster.mbarrier::complete_tx::bytes.b32 [%0], %1, [%2];"
                                 :: "r"(mapa(sb + M_SINK, lane)), "r"(dep), "r"(mapa(bars + 8 * (B_F + k), lane)) : "memory");
            };
#pragma unroll 1
            for (int i = 0; i < 4; i++) {
                const int s = 4 * i + v;
                uint32_t a[16][4], b[2][4];
                if (gu) {
                    const uint32_t tile = tile0 + (s < 14 ? s : v) * 8192;
                    if (lane0 && i > 1) mbar_arrive(bars + 8 * (B_E + s - 4));
                    mbar_wait(bars + 8 * (B_W + s));
#pragma unroll
                    for (int q = 0; q < 16; q++) ldsm4t((tile ^ ((q & 1) << 5)) + ((q >> 1) & 1) * 4096 + (q >> 2) * 1024, a[q][0], a[q][1], a[q][2], a[q][3]);
                }
                if (i == 0) {
                    if (gu) {
                        uint32_t dep = p.zero;
#pragma unroll
                        for (int q = 0; q < 16; q += 2) dep &= a[q][0] & a[q + 1][0];
                        if (lane == 0) mbar_arrive(bars + 8 * (B_E + v) + dep);
                        signal(0, dep);
                    }
                    WSTAMP(11);
                    uint32_t top;
#pragma unroll 1
                    for (int it = 0; it < (1 << 22); it++) {
                        asm volatile("ld.relaxed.gpu.global.u32 %0, [%1];" : "=r"(top) : "l"(&p.sc->top[c % NTOP][g]) : "memory");
                        if (__all_sync(0xffffffffu, ((top ^ (tag << 11)) & 0xf800u) == 0)) break;
                        if (TSLEEP) __nanosleep(TSLEEP);
                    }
                    WSTAMP(3);
                    if (gu) {
                        const uint32_t k = 4 * h + v, row = __reduce_max_sync(0xffffffffu, lane == 4 * k ? ~top & 2047 : 0);
                        asm volatile("{\n\t.reg .pred p;\n\telect.sync _|p, 0xffffffff;\n\t"
                                     "@p cp.async.bulk.shared::cluster.global.mbarrier::complete_tx::bytes.multicast::cluster [%0], [%1], 2048, [%2], %3;\n\t}"
                            :: "r"(sb + OFF_XSEL + k * XS_ROW), "l"(p.u + (size_t)row * D_), "r"(bars + 8 * B_G), "h"((unsigned short)3) : "memory");
                    }
                    if (v == 0) {
                        const uint32_t row = ~top & 2047;
                        if (t == 0 && ((row >> 8) & 1) == h)
                            asm volatile("red.shared.or.b32 [%0], %1;" :: "r"(sb + M_BMAP + (row & 7) * 16 + (row >> 9) * 4), "r"(1u << (gate_pos(row) & 31)) : "memory");
                        if (t == 0) sts32(sb + M_TOP + lane, top);
                        __syncwarp();
                        if (lane0) mbar_arrive(bars + 8 * B_Y);
                    }
                    if (!gu) break;
                    mbar_wait(bars + 8 * B_G);
                    WSTAMP(4);
                }
                ldsm4(xo + 128 * i, b[0][0], b[0][1], b[0][2], b[0][3]);
                ldsm4(xo + 128 * i + 64, b[1][0], b[1][1], b[1][2], b[1][3]);
#pragma unroll
                for (int q = 0; q < 16; q++) mma_bf(acc[q & 7], a[q][0], a[q][1], a[q][2], a[q][3], b[q >> 3][(q >> 1) & 2], b[q >> 3][((q >> 1) & 2) + 1]);
            }
            if (gu) {
                WSTAMP(5);
                __syncwarp();
#pragma unroll
                for (int q = 0; q < 4; q++) {
                    const int ct = q >> 1, e = 2 * (q & 1);
                    sts128(own + q * XS_ROW,
                           __float_as_uint(acc[ct][e] + acc[4 + ct][e]), __float_as_uint(acc[2 + ct][e] + acc[6 + ct][e]),
                           __float_as_uint(acc[ct][e + 1] + acc[4 + ct][e + 1]), __float_as_uint(acc[2 + ct][e + 1] + acc[6 + ct][e + 1]));
                }
                bar_sync(1, 128);
                float hv[2];
#pragma unroll
                for (int e = 0; e < 2; e++) {
                    uint2 q[4];
#pragma unroll
                    for (int i = 0; i < 4; i++) q[i] = lds64(po + 64 * e + 512 * i);
                    const float s0 = (__uint_as_float(q[0].x) + __uint_as_float(q[1].x)) + (__uint_as_float(q[2].x) + __uint_as_float(q[3].x));
                    const float s1 = (__uint_as_float(q[0].y) + __uint_as_float(q[1].y)) + (__uint_as_float(q[2].y) + __uint_as_float(q[3].y));
                    const float gv = bf_round(p.gu_swap ? s1 : s0), uv = bf_round(p.gu_swap ? s0 : s1);
                    hv[e] = bf_round(gv * sigmoid_f(gv)) * uv;
                }
                const uint32_t hw = pack_bf(hv[0], hv[1]);
                st_gpu32(hdst, hw ? hw : 0x80000000u);
                signal(1, hw);
            }
        }
        WSTAMP(6);
        {
            uint4 hq[14];
            {
                bar_sync(1, 128);
                const uint32_t hb = sb + (v < 2 ? OFF_XSEL + 7168 * v : OFF_RING + 8192 * v);
#pragma unroll 1
                for (int it = 0; it < (1 << 22); it++) {
                    uint32_t w;
                    asm volatile("ld.relaxed.gpu.global.u32 %0, [%1];" : "=r"(w) : "l"(pb) : "memory");
                    if (__all_sync(0xffffffffu, w != 0)) break;
                    __nanosleep(PSLEEP);
                }
                WSTAMP(12);
#pragma unroll 1
                for (int it = 0; it < (1 << 16); it++) {
                    asm volatile("{\n\t.reg .pred p;\n\telect.sync _|p, 0xffffffff;\n\t"
                                 "@p mbarrier.arrive.expect_tx.shared::cta.b64 _, [%2], 7168;\n\t"
                                 "@p cp.async.bulk.shared::cluster.global.mbarrier::complete_tx::bytes [%0], [%1], 7168, [%2];\n\t}"
                        :: "r"(hb), "l"(&p.sc->h[tag & 1][32 * (56 * h + 14 * v)]), "r"(bars + 8 * (B_X + v)) : "memory");
                    mbar_wait(bars + 8 * (B_X + v), ~it & 1);
                    uint32_t mn = 0xffffffffu;
#pragma unroll
                    for (int i = 0; i < 14; i++) hq[i] = lds128(hb + 512 * i + 16 * lane);
#pragma unroll
                    for (int i = 0; i < 14; i++) mn = min(mn, hq[i].x);
                    if (__all_sync(0xffffffffu, mn != 0)) break;
                }
            }
            WSTAMP(7);
            float dd[4][4];
            const int krow = ((lane >> 1) & 8) + (lane & 7);
            const uint32_t tile = sb + OFF_RING + (4 + v) * 8192 + krow * 32 + ((((lane >> 3) ^ (krow >> 2)) & 1) << 4);
#pragma unroll
            for (int s = 0; s < 2; s++) {
                mbar_wait(bars + 8 * (B_W + 16 + 4 * s + v));
#pragma unroll
                for (int j = 0; j < 14; j++) {
                    uint32_t a[4];
                    ldsm4t(tile + s * 32768 + j * 512, a[0], a[1], a[2], a[3]);
                    const uint4& hb = hq[7 * s + (j >> 1)];
                    if (s == 0 && j < 4) mma_bf_z(dd[j], a[0], a[1], a[2], a[3], (j & 1) ? hb.z : hb.x, (j & 1) ? hb.w : hb.y);
                    else mma_bf(dd[(j + 2 * s) & 3], a[0], a[1], a[2], a[3], (j & 1) ? hb.z : hb.x, (j & 1) ? hb.w : hb.y);
                }
            }
            WSTAMP(8);
            uint4 part;
            part.x = __float_as_uint((dd[0][0] + dd[1][0]) + (dd[2][0] + dd[3][0])); part.y = __float_as_uint((dd[0][1] + dd[1][1]) + (dd[2][1] + dd[3][1]));
            part.z = __float_as_uint((dd[0][2] + dd[1][2]) + (dd[2][2] + dd[3][2])); part.w = __float_as_uint((dd[0][3] + dd[1][3]) + (dd[2][3] + dd[3][3]));
            st_async16(mapa(own + (M_DPIN - OFF_XSEL), h ^ 1), part, mapa(bars + 8 * B_DP, h ^ 1));
            sts128(own + 14336, part.x, part.y, part.z, part.w);
            __syncwarp();
            if (lane0) mbar_arrive(bars + 8 * B_DP);
        }
        WSTAMP(9);
        WDUMP();
        if (at == 0 && c == 0) *(volatile unsigned*)&p.sc->epoch = epoch + 1;
    } else {
        asm volatile("setmaxnreg.dec.sync.aligned.u32 40;");
        const int v = __reduce_max_sync(0xffffffffu, pw - PREP_W0);
        const bool gu = c < NGU_CTA;
        const uint32_t t0 = clock();
        const uint32_t bu = bars + 8 * v;
        if (lane == 0) {
#pragma unroll
            for (int i = 0; i < 9; i++) mbar_init(bu + 32 * i, 1);
            mbar_init(bu + 8 * B_S, 4);
            mbar_init(bu + 8 * B_Y, v == 0 ? 10 : 9);
            mbar_init(bu + 8 * B_DP, (0x1855 >> (4 * v)) & 15);
            mbar_init(bu + 8 * B_F, v == 0 ? 2 : 1);
            mbar_init(bu + 8 * B_H, 1);
            asm volatile("fence.proxy.async.shared::cta;" ::: "memory");
            asm volatile("fence.mbarrier_init.release.cluster;" ::: "memory");
            mbar_expect(bu + 8 * B_Y, 4096);
            if (v != 2) mbar_expect(bu + 8 * B_DP, v == 0 ? 2048 : (h || v == 3) ? 16384 : 16384 + 128);
            mbar_expect(bu + 8 * B_F, c < NGU_CTA ? 16 : 0);
        }
        __syncwarp();
        asm volatile("barrier.cluster.arrive.relaxed.aligned;" ::: "memory");
#pragma unroll 1
        for (int j = 0; j < 4; j++)
            tma3d(sb + OFF_S + (4 * v + j) * S_PL, &tm_x, ((j + 3) & 3) * 1024 + 16 * pr, 128 * v + 64 * h - (j == 0 ? 2 : 1), bars + 8 * (B_S + v), 66 * 32);
        WSTAMP(9);
        if (v < 2 && lane == 0) asm volatile("prefetch.tensormap [%0];" :: "l"(v ? &tm_gu : &tm_down) : "memory");
        asm volatile("barrier.cluster.wait.acquire.aligned;" ::: "memory");
        if (v > 0) mbar_wait(bars + 8 * (B_H + v));
        {
            uint32_t last = v ? clock() - SLACK : t0 + T0 - GAP + STAG * ((pr * 5) & 15) / 16;
#pragma unroll 1
            for (int s = 6 * v; s < 6 * v + 6; s++) {
                if (!gu && s < 16) continue;
                const int i = s >> 2, w = s & 3, slot = s < 14 ? s : s - 12;
                if (slot >= 2) mbar_wait(bars + 8 * ((gu && s >= 14) ? B_E + slot : slot < 6 ? B_XE + slot - 2 : B_KG));
                uint32_t now;
#pragma unroll 1
                while ((int)((now = clock()) - last) < GAP) __nanosleep(CSLEEP);
                last = max((int)(now - last) - SLACK, GAP) + last;
                WSTAMP(3 + s - 6 * v);
                tma3d(sb + OFF_RING + slot * 8192, i < 4 ? &tm_gu : &tm_down, i < 4 ? 32 * c : 16 * pr,
                      i < 4 ? 256 * w + 64 * i : 1792 * h + 448 * w + 224 * (i - 4), bars + 8 * (B_W + s), i < 4 ? 8192 : 7168);
            }
            if (lane == 0) mbar_arrive(bars + 8 * (B_H + ((v + 1) & 3)));
        }
        {
            mbar_wait(bars + 8 * B_Y);
            const uint32_t top = lds32(sb + M_TOP + 8 * v + 4 * (lane >> 4)), tag16 = lds32(sb + M_TAG);
            const uint32_t row = ~top & 2047, ch = lane & 15;
            const bool mine = ((row >> 8) & 1) == h;
            uint32_t gfin, x16, y16 = 0;
#pragma unroll 1
            for (int it = 0; it < (1 << 22); it++) {
                asm volatile("ld.relaxed.gpu.global.u32 %0, [%1];" : "=r"(gfin) : "l"((const uint32_t*)p.sc->g + ((row & 256) << 2) + gate_pos(row)) : "memory");
                if (((gfin ^ tag16) >> 16) == 0) break;
            }
            const uint32_t s5 = (row & 255) + 5;
            asm volatile("ld.shared.u16 %0, [%1];" : "=r"(x16) : "r"(sb + OFF_S + (4 * (row >> 9) + (s5 & 3)) * S_PL + (s5 >> 2) * 32 + ((2 * ch) ^ (s5 & 16))) : "memory");
            const float rsel = __uint_as_float(pin(__float_as_uint(bf_round(sigmoid_f(__uint_as_float((top ^ (((int)~top >> 31) | 0x80000000u)) & 0xffff0000u)))), lane));
            const uint32_t po = pin(sb + (4 * (ch & 7) + v) * 16 + (ch >> 3) * 8 + (lane >> 4) * 4, lane);
            bf16* op = pin(p.out + (size_t)row * D_ + 16 * pr + ch, lane);
            if (mine) {
                mbar_wait(bars + 8 * (B_Y + (row >> 9)));
                asm volatile("ld.shared.u16 %0, [%1];" : "=r"(y16)
                             : "r"(sb + y_off(row >> 9) + ch * 512 + (((4 * (row & 7) + ((row >> 5) & 3)) ^ (((ch >> 2) << 1) | (ch & 1))) << 4) + 2 * row_elem(row)) : "memory");
            }
            mbar_wait(bars + 8 * B_DP);
            float q[8];
#pragma unroll
            for (int i = 0; i < 4; i++) { q[i] = ldsf(po + M_DPIN + 512 * i); q[4 + i] = ldsf(po + OFF_XSEL + 14336 + 512 * i); }
            const float tot = ((q[0] + q[1]) + (q[2] + q[3])) + ((q[4] + q[5]) + (q[6] + q[7]));
            const float b = bf_round(__uint_as_float(x16 << 16) + bf_round(bf_round(tot) * rsel));
            if (mine) *op = __float2bfloat16_rn(fmaf(bf_lo(gfin), __uint_as_float(y16 << 16), bf_round(bf_round(1.f - bf_lo(gfin)) * b)));
        }
        WSTAMP(10);
        WDUMP();
    }
}

typedef CUresult (*EncodeFn)(CUtensorMap*, CUtensorMapDataType, cuuint32_t, void*, const cuuint64_t*, const cuuint64_t*,
                             const cuuint32_t*, const cuuint32_t*, CUtensorMapInterleave, CUtensorMapSwizzle,
                             CUtensorMapL2promotion, CUtensorMapFloatOOBfill);

void make_map(EncodeFn f, CUtensorMap* m, const void* ptr, uint64_t cols, uint64_t rows, uint32_t bc, uint32_t br, CUtensorMapSwizzle sw,
              uint32_t planes = 1, uint64_t plane_stride = 0) {
    cuuint64_t dims[3] = {cols, rows, planes};
    cuuint64_t str[2] = {cols * 2, planes > 1 ? plane_stride : cols * rows * 2};
    cuuint32_t box[3] = {bc, br, planes};
    cuuint32_t es[3] = {1, 1, 1};
    f(m, CU_TENSOR_MAP_DATA_TYPE_BFLOAT16, 3, (void*)ptr, dims, str, box, es, CU_TENSOR_MAP_INTERLEAVE_NONE, sw,
      CU_TENSOR_MAP_L2_PROMOTION_L2_128B, CU_TENSOR_MAP_FLOAT_OOB_FILL_NONE);
}

}

extern "C" void kernel_launch(void* const* d_in, const int* in_sizes, int n_in, void* d_out, int out_size) {
    static EncodeFn enc = nullptr;
    static void *sc = nullptr, *band = nullptr;
    if (!enc) {
        void* fn = nullptr;
        cudaDriverEntryPointQueryResult qr;
        cudaGetDriverEntryPoint("cuTensorMapEncodeTiled", &fn, cudaEnableDefault, &qr);
        enc = (EncodeFn)fn;
        cudaGetSymbolAddress(&sc, g_scratch);
        cudaGetSymbolAddress(&band, g_band);
        cudaFuncSetAttribute(fused_kernel, cudaFuncAttributeMaxDynamicSharedMemorySize, SMEM_BYTES);
    }
    CUtensorMap tg, td, tx;
    const char *wg = (const char*)d_in[9], *wu = (const char*)d_in[10];
    const bool swap = wu < wg;
    make_map(enc, &tg, swap ? wu : wg, F_, D_, 32, 64, CU_TENSOR_MAP_SWIZZLE_64B, 2, swap ? wg - wu : wu - wg);
    make_map(enc, &td, d_in[11], D_, F_, 16, 224, CU_TENSOR_MAP_SWIZZLE_32B);
    make_map(enc, &tx, d_in[0], 4 * D_, L_ / 4, 16, 66, CU_TENSOR_MAP_SWIZZLE_32B);
    Params p;
    p.u = (const bf16*)d_in[0]; p.logA = (const bf16*)d_in[1]; p.Aim = (const bf16*)d_in[2];
    p.Cre = (const bf16*)d_in[3]; p.Cim = (const bf16*)d_in[4]; p.logdt = (const bf16*)d_in[5];
    p.Dskip = (const bf16*)d_in[6]; p.wr = (const bf16*)d_in[8]; p.gatew = (const bf16*)d_in[12];
    p.out = (bf16*)d_out;
    p.sc = (Scratch*)sc; p.band = (const uint4*)band;
    p.gu_swap = swap;
    p.zero = 0;
    fused_kernel<<<NCTA, NTHREADS, SMEM_BYTES>>>(p, tg, td, tx);
}
```

```cpp
#include <cuda_runtime.h>
#include <cuda_bf16.h>
#include <cuda_fp16.h>
#include <cuda.h>
#include <stdint.h>

typedef __nv_bfloat16 bf16;

namespace {

constexpr int L_ = 2048, D_ = 1024, F_ = 3584;
constexpr int NCTA = 130;
constexpr int NTHREADS = 512;
#define AUXW 12
constexpr int MAIN_W0 = 0, AUX_W0 = AUXW, PREP_W0 = 20 - AUXW;
#define T0 3300
#define GAP 600
#define STAG GAP
#define CSLEEP 100
#define SLACK 300
#define DELAY_X 0
#define TSLEEP 40
#define RS 2
#define PSLEEP 40
constexpr int NGU_CTA = 112;

constexpr int OFF_RING = 0;
constexpr int OFF_SCR  = 6 * 8192;
constexpr int S_PL     = 2304;
constexpr int OFF_S    = 114688;
constexpr int U_PL     = 2240;
constexpr int U_CH     = 4416;
constexpr int OFF_U    = 151552;
constexpr int TAB_W    = 3200;
constexpr int T_PL     = 544;
constexpr int T_A      = 2192 - 26 * 8;
constexpr int T_B      = 2568 - 59 * 8;
constexpr int OFF_TAB  = 186880;
constexpr int OFF_XSEL = 212480;
constexpr int XS_ROW   = 2064;
constexpr int OFF_BAND = 228992;
constexpr int OFF_MISC = 229536;
constexpr int M_BARS   = OFF_MISC;
constexpr int M_DSK    = OFF_MISC + 2736;
constexpr int M_SINK   = OFF_MISC + 512;
constexpr int M_TAG    = OFF_MISC + 516;
constexpr int M_BMAP   = OFF_MISC + 528;
constexpr int M_DPIN   = OFF_MISC + 656;
constexpr int M_TOP    = OFF_MISC + 2704;
constexpr int SMEM_BYTES = OFF_MISC + 2768;
__host__ __device__ constexpr uint32_t y_off(uint32_t q) { return OFF_RING + (q & 1) * 8192 + (q >> 1) * 98304; }

constexpr int B_W = 0;
constexpr int B_E = 24;
constexpr int B_S = 36;
constexpr int B_Y = 40;
constexpr int B_DP = 44, B_U = 45, B_KG = 46, B_G = 47;
constexpr int B_F = 48;
constexpr int B_H = 60;
constexpr int B_X = 52, B_XE = 56;

struct BandTab { uint32_t w[11][12]; };
constexpr BandTab make_band() {
    BandTab b{};
    for (int cls = 0; cls < 11; cls++)
        for (int wd = 0; wd < 10; wd++) {
            const int tau = cls + 2 - 8 * ((wd < 4 ? wd : wd - 4) >> 1);
            const int lo = (wd < 4) ? ((wd & 1) ? -2 : 3) : ((wd & 1) ? -4 : -11), wid = (wd < 4 ? 3 : 7) + 2 * (wd & 1);
            b.w[cls][wd] = ((tau >= lo && tau < lo + wid) ? 0x3F80u : 0u) | ((tau - 4 >= lo && tau - 4 < lo + wid) ? 0x3F800000u : 0u);
        }
    return b;
}
constexpr int NTOP = 32;
struct Scratch {
    uint4 r[L_ / 4 * RS];
    uint4 g[L_ / 4];
    uint4 h[2][8 * F_ / 8];
    uint32_t top[NTOP][32];
    unsigned epoch;
};
__device__ __align__(128) Scratch g_scratch;
__device__ const __align__(16) BandTab g_band = make_band();

struct Params {
    const bf16 *u, *logA, *Aim, *Cre, *Cim, *logdt, *Dskip, *wr, *gatew;
    bf16* out;
    Scratch* sc;
    const uint4* band;
    uint32_t gu_swap;
    uint32_t zero;
};

#define WSTAMP(i) do {} while (0)
#define KSTAMP(i, dep) do {} while (0)
#define WDUMP() do {} while (0)
#define RSTAMP(i) do {} while (0)

#define NOALLOC ".L1::no_allocate"
__device__ __forceinline__ uint32_t smem_u32(const void* p) { return (uint32_t)__cvta_generic_to_shared(p); }
__device__ __forceinline__ void mbar_init(uint32_t b, uint32_t c) { asm volatile("mbarrier.init.shared::cta.b64 [%0], %1;" :: "r"(b), "r"(c) : "memory"); }
__device__ __forceinline__ void mbar_expect(uint32_t b, uint32_t tx) { asm volatile("mbarrier.arrive.expect_tx.shared::cta.b64 _, [%0], %1;" :: "r"(b), "r"(tx) : "memory"); }
__device__ __forceinline__ void mbar_arrive(uint32_t b) { asm volatile("mbarrier.arrive.shared::cta.b64 _, [%0];" :: "r"(b) : "memory"); }
__device__ __forceinline__ void mbar_wait(uint32_t b, uint32_t parity = 0) {
    asm volatile("{\n\t.reg .pred p;\nW%=:\n\tmbarrier.try_wait.parity.shared::cta.b64 p, [%0], %1, 20000;\n\t@!p bra W%=;\n\t}" :: "r"(b), "r"(parity) : "memory");
}
__device__ __forceinline__ uint32_t mapa(uint32_t addr, uint32_t rank) { uint32_t r; asm("mapa.shared::cluster.u32 %0, %1, %2;" : "=r"(r) : "r"(addr), "r"(rank)); return r; }
__device__ __forceinline__ void tma3d(uint32_t dst, const CUtensorMap* tm, int c0, int c1, uint32_t bar, uint32_t bytes) {
    asm volatile("{\n\t.reg .pred p;\n\telect.sync _|p, 0xffffffff;\n\t"
                 "@p mbarrier.arrive.expect_tx.shared::cta.b64 _, [%2], %5;\n\t"
                 "@p cp.async.bulk.tensor.3d.shared::cluster.global.mbarrier::complete_tx::bytes [%0], [%1, {%3, %4, 0}], [%2];\n\t}"
        :: "r"(dst), "l"(tm), "r"(bar), "r"(c0), "r"(c1), "r"(bytes) : "memory");
}
__device__ __forceinline__ void st_async16(uint32_t dst, const uint4& v, uint32_t bar) {
    asm volatile("st.async.weak.shared::cluster.mbarrier::complete_tx::bytes.v4.b32 [%0], {%1,%2,%3,%4}, [%5];"
                 :: "r"(dst), "r"(v.x), "r"(v.y), "r"(v.z), "r"(v.w), "r"(bar) : "memory");
}
__device__ __forceinline__ void bar_sync(int id, int n) { asm volatile("bar.sync %0, %1;" :: "r"(id), "r"(n) : "memory"); }
__device__ __forceinline__ void cp16(uint32_t dst, const void* src) { asm volatile("cp.async.cg.shared.global [%0], [%1], 16;" :: "r"(dst), "l"(src) : "memory"); }
__device__ __forceinline__ void cp_wait_all() { asm volatile("cp.async.wait_all;" ::: "memory"); }
__device__ __forceinline__ uint2 ldg64(const void* p) { uint2 v; asm volatile("ld.global.nc" NOALLOC ".v2.u32 {%0,%1}, [%2];" : "=r"(v.x), "=r"(v.y) : "l"(p)); return v; }
__device__ __forceinline__ uint4 ld_gpu128(const void* p) { uint4 v; asm volatile("ld.relaxed.gpu.global.v4.u32 {%0,%1,%2,%3}, [%4];" : "=r"(v.x), "=r"(v.y), "=r"(v.z), "=r"(v.w) : "l"(p) : "memory"); return v; }
__device__ __forceinline__ void st_gpu32(void* p, uint32_t v) { asm volatile("st.relaxed.gpu.global.u32 [%0], %1;" :: "l"(p), "r"(v) : "memory"); }

__device__ __forceinline__ void ldsm4(uint32_t a, uint32_t& r0, uint32_t& r1, uint32_t& r2, uint32_t& r3) {
    asm volatile("ldmatrix.sync.aligned.m8n8.x4.shared.b16 {%0,%1,%2,%3}, [%4];" : "=r"(r0), "=r"(r1), "=r"(r2), "=r"(r3) : "r"(a) : "memory");
}
__device__ __forceinline__ void ldsm4t(uint32_t a, uint32_t& r0, uint32_t& r1, uint32_t& r2, uint32_t& r3) {
    asm volatile("ldmatrix.sync.aligned.m8n8.x4.trans.shared.b16 {%0,%1,%2,%3}, [%4];" : "=r"(r0), "=r"(r1), "=r"(r2), "=r"(r3) : "r"(a) : "memory");
}
__device__ __forceinline__ uint32_t lds32(uint32_t a) { uint32_t v; asm volatile("ld.shared.u32 %0, [%1];" : "=r"(v) : "r"(a) : "memory"); return v; }
__device__ __forceinline__ uint2 lds64(uint32_t a) { uint2 v; asm volatile("ld.shared.v2.u32 {%0,%1}, [%2];" : "=r"(v.x), "=r"(v.y) : "r"(a) : "memory"); return v; }
__device__ __forceinline__ uint4 lds128(uint32_t a) { uint4 v; asm volatile("ld.shared.v4.u32 {%0,%1,%2,%3}, [%4];" : "=r"(v.x), "=r"(v.y), "=r"(v.z), "=r"(v.w) : "r"(a) : "memory"); return v; }
__device__ __forceinline__ void sts32(uint32_t a, uint32_t v) { asm volatile("st.shared.u32 [%0], %1;" :: "r"(a), "r"(v) : "memory"); }
__device__ __forceinline__ void sts16(uint32_t a, uint32_t v) { asm volatile("st.shared.u16 [%0], %1;" :: "r"(a), "h"((unsigned short)v) : "memory"); }
__device__ __forceinline__ void sts128(uint32_t a, uint32_t x, uint32_t y, uint32_t z, uint32_t w) { asm volatile("st.shared.v4.u32 [%0], {%1,%2,%3,%4};" :: "r"(a), "r"(x), "r"(y), "r"(z), "r"(w) : "memory"); }
__device__ __forceinline__ float ldsf(uint32_t a) { float v; asm volatile("ld.shared.f32 %0, [%1];" : "=f"(v) : "r"(a) : "memory"); return v; }

__device__ __forceinline__ void mma_bf(float (&d)[4], uint32_t a0, uint32_t a1, uint32_t a2, uint32_t a3, uint32_t b0, uint32_t b1) {
    asm volatile("mma.sync.aligned.m16n8k16.row.col.f32.bf16.bf16.f32 {%0,%1,%2,%3}, {%4,%5,%6,%7}, {%8,%9}, {%0,%1,%2,%3};"
        : "+f"(d[0]), "+f"(d[1]), "+f"(d[2]), "+f"(d[3]) : "r"(a0), "r"(a1), "r"(a2), "r"(a3), "r"(b0), "r"(b1));
}
__device__ __forceinline__ void mma_bf_z(float (&d)[4], uint32_t a0, uint32_t a1, uint32_t a2, uint32_t a3, uint32_t b0, uint32_t b1) {
    asm volatile("mma.sync.aligned.m16n8k16.row.col.f32.bf16.bf16.f32 {%0,%1,%2,%3}, {%4,%5,%6,%7}, {%8,%9}, {%10,%10,%10,%10};"
        : "=f"(d[0]), "=f"(d[1]), "=f"(d[2]), "=f"(d[3]) : "r"(a0), "r"(a1), "r"(a2), "r"(a3), "r"(b0), "r"(b1), "f"(0.f));
}
__device__ __forceinline__ void mma_bf_k8(float (&d)[4], uint32_t a0, uint32_t a1, uint32_t b0) {
    asm volatile("mma.sync.aligned.m16n8k8.row.col.f32.bf16.bf16.f32 {%0,%1,%2,%3}, {%4,%5}, {%6}, {%0,%1,%2,%3};"
        : "+f"(d[0]), "+f"(d[1]), "+f"(d[2]), "+f"(d[3]) : "r"(a0), "r"(a1), "r"(b0));
}
__device__ __forceinline__ void mma_h(float (&d)[4], uint32_t a0, uint32_t a1, uint32_t a2, uint32_t a3, uint32_t b0, uint32_t b1) {
    asm volatile("mma.sync.aligned.m16n8k16.row.col.f32.f16.f16.f32 {%0,%1,%2,%3}, {%4,%5,%6,%7}, {%8,%9}, {%0,%1,%2,%3};"
        : "+f"(d[0]), "+f"(d[1]), "+f"(d[2]), "+f"(d[3]) : "r"(a0), "r"(a1), "r"(a2), "r"(a3), "r"(b0), "r"(b1));
}
__device__ __forceinline__ uint32_t pack_bf(float lo, float hi) { uint32_t r; asm("cvt.rn.bf16x2.f32 %0, %1, %2;" : "=r"(r) : "f"(hi), "f"(lo)); return r; }
__device__ __forceinline__ uint32_t pack_h(float lo, float hi) { uint32_t r; asm("cvt.rn.f16x2.f32 %0, %1, %2;" : "=r"(r) : "f"(hi), "f"(lo)); return r; }
__device__ __forceinline__ float bf_lo(uint32_t v) { return __uint_as_float(v << 16); }
__device__ __forceinline__ float bf_hi(uint32_t v) { return __uint_as_float(v & 0xffff0000u); }
__device__ __forceinline__ float bf_round(float x) { return __uint_as_float(pack_bf(0.f, x) & 0xffff0000u); }
__device__ __forceinline__ uint32_t hmul2_bf(uint32_t a, uint32_t b) { uint32_t r; asm("mul.rn.bf16x2 %0, %1, %2;" : "=r"(r) : "r"(a), "r"(b)); return r; }
__device__ __forceinline__ float ex2f(float x) { float r; asm("ex2.approx.ftz.f32 %0, %1;" : "=f"(r) : "f"(x)); return r; }

__device__ __forceinline__ float exp_acc(float x) {
    const float t = x * 1.4426950216293335f;
    const float r = fmaf(x, 1.4426950216293335f, -t) + x * 1.9259629911266175e-8f;
    return ex2f(t) * fmaf(r, 0.6931471805599453f, 1.f);
}
__device__ __forceinline__ float sigmoid_f(float x) { return __fdividef(1.f, 1.f + ex2f(-x * 1.4426950408889634f)); }
__device__ __forceinline__ void cexp_pow(float lr, float li, float e, float& zr, float& zi) {
    const float mag = ex2f(lr * e * 1.4426950408889634f);
    const float th = li * e;
    const float k = (th * 0.15915494309189535f + 12582912.f) - 12582912.f;
    float r = fmaf(-k, 6.2831854820251465f, th);
    r = fmaf(-k, -1.7484555314695172e-7f, r);
    zr = mag * __cosf(r);
    zi = mag * __sinf(r);
}
__device__ __forceinline__ uint32_t hcmul(uint32_t a, uint32_t k, uint32_t kp) {
    const __half2 A = *reinterpret_cast<const __half2*>(&a);
    const __half2 r = __hfma2(__high2half2(A), *reinterpret_cast<const __half2*>(&kp), __hmul2(__low2half2(A), *reinterpret_cast<const __half2*>(&k)));
    return *reinterpret_cast<const uint32_t*>(&r);
}
#define CMUL(orr, oi, ar, ai, br, bi) do { float _r = (ar) * (br) - (ai) * (bi); float _i = (ar) * (bi) + (ai) * (br); orr = _r; oi = _i; } while (0)
#define CSQ(orr, oi, ar, ai) do { float _r = (ar) * (ar) - (ai) * (ai); float _i = 2.f * (ar) * (ai); orr = _r; oi = _i; } while (0)

__device__ __forceinline__ void mma_bf_k8z(float (&d)[4], uint32_t a0, uint32_t a1, uint32_t b0) {
    asm volatile("mma.sync.aligned.m16n8k8.row.col.f32.bf16.bf16.f32 {%0,%1,%2,%3}, {%4,%5}, {%6}, {%7,%7,%7,%7};"
        : "=f"(d[0]), "=f"(d[1]), "=f"(d[2]), "=f"(d[3]) : "r"(a0), "r"(a1), "r"(b0), "f"(0.f));
}
__device__ __forceinline__ void mma_hh_k8(uint32_t& d0, uint32_t& d1, uint32_t a0, uint32_t a1, uint32_t b0) {
    asm volatile("mma.sync.aligned.m16n8k8.row.col.f16.f16.f16.f16 {%0,%1}, {%2,%3}, {%4}, {%5,%5};"
        : "=r"(d0), "=r"(d1) : "r"(a0), "r"(a1), "r"(b0), "r"(0));
}
__device__ __forceinline__ void sched_fence(uint32_t zero, uint32_t id) {
    asm volatile("{\n\t.reg .pred p;\n\tsetp.eq.u32 p, %0, %1;\n\t@p exit;\n\t}" :: "r"(zero), "r"(id) : "memory");
}
__device__ __forceinline__ uint32_t pin(uint32_t x, int lane) { return __shfl_sync(0xffffffffu, x, lane); }
template <class T> __device__ __forceinline__ T* pin(T* x, int lane) { return (T*)__shfl_sync(0xffffffffu, (unsigned long long)x, lane); }
__device__ __forceinline__ void lds128_if(bool on, uint32_t a, uint32_t (&v)[4]) {
    asm volatile("{\n\t.reg .pred p;\n\tsetp.ne.u32 p, %5, 0;\n\t@p ld.shared.v4.u32 {%0,%1,%2,%3}, [%4];\n\t}"
        : "+r"(v[0]), "+r"(v[1]), "+r"(v[2]), "+r"(v[3]) : "r"(a), "r"((uint32_t)on) : "memory");
}
__device__ __forceinline__ uint32_t hfma2_bf(uint32_t a, uint32_t b, uint32_t c) { uint32_t r; asm("fma.rn.bf16x2 %0, %1, %2, %3;" : "=r"(r) : "r"(a), "r"(b), "r"(c)); return r; }
__device__ __forceinline__ uint32_t row_elem(uint32_t row) { return ((row >> 5) & 4) | ((row >> 2) & 2) | ((row >> 4) & 1); }
__device__ __forceinline__ uint32_t gate_pos(uint32_t row) { return ((row >> 9) << 8) | ((row & 7) << 5) | (row_elem(row) << 2) | ((row >> 5) & 3); }

__global__ void __cluster_dims__(2, 1, 1) __launch_bounds__(NTHREADS, 1)
fused_kernel(const Params p, const __grid_constant__ CUtensorMap tm_gu, const __grid_constant__ CUtensorMap tm_down,
             const __grid_constant__ CUtensorMap tm_x) {
    extern __shared__ __align__(1024) unsigned char smem[];
    const uint32_t sb = smem_u32(smem);
    int tid;
    asm volatile("mov.u32 %0, %%tid.x;" : "=r"(tid));
    const int pw = tid >> 5, lane = tid & 31;
    const int c = blockIdx.x, h = c & 1, pr = c >> 1;
    const uint32_t bars = sb + M_BARS;

    if (c >= 128) {
        if (c != 128) return;
        RSTAMP(5);
        const unsigned tag = (*(volatile unsigned*)&p.sc->epoch + 1) & 0xffffu;
        const uint32_t list = sb + 128;
#pragma unroll 1
        for (int pass = 0; pass < 2; pass++) {
            sts128(list + 16 * tid, 0, 0, 0, 0);
            if (tid == 0) sts32(sb + 64, 0);
            uint32_t key[4];
            bool ok = false;
#pragma unroll 1
            for (int it = 0; it < (1 << 22); it++) {
                const uint4 a = ld_gpu128(&p.sc->r[tid * RS]);
                key[0] = a.x; key[1] = a.y; key[2] = a.z; key[3] = a.w;
                ok = (((a.x ^ tag) | (a.y ^ tag) | (a.z ^ tag) | (a.w ^ tag)) & 0xffffu) == 0;
                if (ok || !pass) break;
            }
            WSTAMP(0);
            uint32_t m = 0;
#pragma unroll
            for (int i = 0; i < 4; i++) {
                key[i] = ((pass ? key[i] : (lane + i) << 16) & 0xffff0000u) | (uint32_t)(2047 - (4 * tid + i));
                m = max(m, key[i]);
            }
            const uint32_t wm = __reduce_max_sync(0xffffffffu, m);
            if (lane == 0) sts32(sb + pw * 4, wm);
            __syncthreads();
            uint32_t thr = 0xffffffffu;
#pragma unroll
            for (int i = 0; i < 4; i++) { const uint4 q = lds128(sb + 16 * i); thr = min(thr, min(max(q.x, q.y), max(q.z, q.w))); }
            if (thr != 1) WSTAMP(1);
            if (m >= thr) {
                uint32_t pos;
                asm volatile("atom.shared.add.u32 %0, [%1], %2;" : "=r"(pos) : "r"(sb + 64), "r"(4 * ((key[0] >= thr) + (key[1] >= thr) + (key[2] >= thr) + (key[3] >= thr))) : "memory");
#pragma unroll
                for (int i = 0; i < 4; i++) if (key[i] >= thr) { sts32(list + pos, key[i]); pos += 4; }
            }
            __syncthreads();
            const uint32_t nc4 = lds32(sb + 64);
            if (nc4 != 1) WSTAMP(2);
#pragma unroll 1
            for (uint32_t j = 4 * pw; j < nc4; j += 64) {
                const uint32_t mine = lds32(list + j);
                int rank = 0;
#pragma unroll 1
                for (uint32_t i = 0; i < nc4; i += 128) rank += __popc(__ballot_sync(0xffffffffu, lds32(list + i + 4 * lane) > mine));
                if (rank < 8 && lane == 0) sts32(sb + 96 + 4 * rank, mine);
            }
            __syncthreads();
            if (tid < 8 * NTOP) st_gpu32(&p.sc->top[tid >> 3][tid & 7], lds32(sb + 96 + 4 * (tid & 7)) | (((tag + pass - 1) & 31) << 11));
            WSTAMP(3);
            if (!pass) RSTAMP(4);
        }
        WDUMP();
        return;
    }

    WSTAMP(0);
    if (pw < 8) {
        uint2 v_la, v_ai, v_cr, v_ci;
        uint32_t ldt16;
        const int d = 8 * c + pw - MAIN_W0;
        const size_t po = (size_t)d * 128 + 4 * lane;
        v_la = ldg64(p.logA + po); v_ai = ldg64(p.Aim + po); v_cr = ldg64(p.Cre + po); v_ci = ldg64(p.Cim + po);
        asm volatile("ld.global.nc.u16 %0, [%1];" : "=r"(ldt16) : "l"(p.logdt + d));
        if (lane == 0) asm volatile("cp.async.ca.shared.global [%0], [%1], 4;" :: "r"(sb + M_DSK + 4 * (pw - MAIN_W0)), "l"(p.Dskip + (d & ~1)) : "memory");
        asm volatile("barrier.cluster.arrive.relaxed.aligned;" ::: "memory");
        const int warp = pw - MAIN_W0;
        asm volatile("setmaxnreg.inc.sync.aligned.u32 168;");
        const int g = lane >> 2, t = lane & 3;
        const int mi = lane >> 3, r = lane & 7;
        const uint32_t TB = sb + OFF_TAB + warp * TAB_W;
        const uint32_t UB = sb + OFF_U + warp * U_CH;
        if (mi < 2) sts128(UB + mi * U_PL + r * 16, 0, 0, 0, 0);
#pragma unroll
        for (int i = 0; i < 6; i++) sts128(TB + 16 * (lane + 32 * i), 0, 0, 0, 0);
        if (lane < 8) sts128(TB + 16 * (lane + 192), 0, 0, 0, 0);
        __syncwarp();

        uint32_t cfix;
        {
            KSTAMP(4, v_la.x ^ v_ai.x ^ v_cr.x ^ v_ci.x ^ ldt16);
            const float dt = bf_round(exp_acc(__uint_as_float(ldt16 << 16)));
            float lr[4], li[4], cr[4], ci[4];
            float inv;
            {
                const uint32_t la[2] = {v_la.x, v_la.y}, ai[2] = {v_ai.x, v_ai.y}, vr[2] = {v_cr.x, v_cr.y}, vi[2] = {v_ci.x, v_ci.y};
                const uint32_t m2 = __vmaxu2(__vmaxu2(vr[0] & 0x7fff7fffu, vr[1] & 0x7fff7fffu), __vmaxu2(vi[0] & 0x7fff7fffu, vi[1] & 0x7fff7fffu));
                const uint32_t mx = __reduce_max_sync(0xffffffffu, max(m2, m2 << 16));
                const uint32_t e = min(max(mx >> 23, 11u), 254u);
                const float sc = __uint_as_float((264u - e) << 23);
                inv = __uint_as_float((e - 10u) << 23) * (2.f * dt);
#pragma unroll
                for (int i = 0; i < 4; i++) {
                    const float a = (i & 1) ? bf_hi(la[i >> 1]) : bf_lo(la[i >> 1]);
                    const float b = (i & 1) ? bf_hi(ai[i >> 1]) : bf_lo(ai[i >> 1]);
                    lr[i] = -bf_round(exp_acc(a)) * dt;
                    li[i] = b * dt;
                    cr[i] = ((i & 1) ? bf_hi(vr[i >> 1]) : bf_lo(vr[i >> 1])) * sc;
                    ci[i] = ((i & 1) ? bf_hi(vi[i >> 1]) : bf_lo(vi[i >> 1])) * sc;
                }
            }
            const uint32_t SX = sb + OFF_SCR + warp * 8192;
            const uint32_t sw = SX + (lane << 4);
#define PUT(buf, row, v) sts128(((sw + (row) * 512) ^ ((row) << 4)) + (buf) * 4096, v[0], v[1], v[2], v[3])
#define EMIT(bufa, rowa, bufb, rowb, xr, xi, k, kp) do { uint32_t pk[4], pd[4]; \
                _Pragma("unroll") for (int i = 0; i < 4; i++) { pk[i] = pack_h(xr[i], xi[i]); pd[i] = hcmul(pk[i], k[i], kp[i]); } \
                PUT(bufa, rowa, pk); PUT(bufb, rowb, pd); } while (0)
#define CMUL4(orr, oi, ar, ai, br, bi) _Pragma("unroll") for (int i = 0; i < 4; i++) CMUL(orr[i], oi[i], ar[i], ai[i], br[i], bi[i])
#define CSQ4(orr, oi, ar, ai) _Pragma("unroll") for (int i = 0; i < 4; i++) CSQ(orr[i], oi[i], ar[i], ai[i])
            float z1r[4], z1i[4], z2r[4], z2i[4], z8r[4], z8i[4], z256r[4], z256i[4];
            uint32_t k128[4], k128p[4], k4[4], k4p[4];
#pragma unroll
            for (int i = 0; i < 4; i++) {
                float tr, ti;
                cexp_pow(lr[i], li[i], 1.f, z1r[i], z1i[i]);
                CSQ(z2r[i], z2i[i], z1r[i], z1i[i]);
                CSQ(tr, ti, z2r[i], z2i[i]);
                k4[i] = pack_h(tr, ti); k4p[i] = pack_h(-ti, tr);
                CSQ(z8r[i], z8i[i], tr, ti);
                cexp_pow(lr[i], li[i], 128.f, tr, ti);
                k128[i] = pack_h(tr, ti); k128p[i] = pack_h(-ti, tr);
                CSQ(z256r[i], z256i[i], tr, ti);
                sts32(TB + i * T_PL + 16 + 4 * lane, k128[i]);
                sts32(TB + i * T_PL + 160 + 4 * lane, k128p[i]);
            }
            KSTAMP(5, k128[3] ^ k4[3]);
            uint32_t Ya[16][4];
            {
                float w1r[4], w1i[4], ar[4], ai[4], br[4], bi[4];
                uint32_t k8[4], k8p[4];
                const uint32_t one[4] = {0x3C00u, 0x3C00u, 0x3C00u, 0x3C00u};
#pragma unroll
                for (int i = 0; i < 4; i++) {
                    k8[i] = pack_h(z8r[i], -z8i[i]); k8p[i] = pack_h(z8i[i], z8r[i]);
                    CSQ(w1r[i], w1i[i], z8r[i], z8i[i]); w1i[i] = -w1i[i];
                }
                PUT(0, 0, one); PUT(1, 0, k8);
                EMIT(0, 1, 1, 1, w1r, w1i, k8, k8p);
                CSQ4(ar, ai, w1r, w1i);            EMIT(0, 2, 1, 2, ar, ai, k8, k8p);
                CMUL4(br, bi, ar, ai, w1r, w1i);   EMIT(0, 3, 1, 3, br, bi, k8, k8p);
                CSQ4(ar, ai, ar, ai);              EMIT(0, 4, 1, 4, ar, ai, k8, k8p);
                CMUL4(ar, ai, ar, ai, w1r, w1i);   EMIT(0, 5, 1, 5, ar, ai, k8, k8p);
                CSQ4(br, bi, br, bi);              EMIT(0, 6, 1, 6, br, bi, k8, k8p);
                CMUL4(br, bi, br, bi, w1r, w1i);   EMIT(0, 7, 1, 7, br, bi, k8, k8p);
                __syncwarp();
                KSTAMP(6, 0);
                const uint32_t ab = SX + (mi & 1) * 4096 + r * 512, ax = ((mi >> 1) ^ r) << 4;
#pragma unroll
                for (int ks = 0; ks < 16; ks++) ldsm4(ab + (ks >> 2) * 128 + (ax ^ ((ks & 3) << 5)), Ya[ks][0], Ya[ks][1], Ya[ks][2], Ya[ks][3]);
                __syncwarp();
            }
            KSTAMP(7, Ya[15][0]);
            const uint32_t ld0 = SX + r * 512 + ((mi ^ r) << 4), ld1 = ld0 ^ 64;
            float R[5][4], xr[4], xi[4];
            {
                float yr[4], yi[4];
                EMIT(0, 0, 0, 1, cr, ci, k4, k4p);
                CMUL4(yr, yi, cr, ci, z1r, z1i);        EMIT(0, 2, 0, 3, yr, yi, k4, k4p);
                CMUL4(xr, xi, cr, ci, z256r, z256i);    EMIT(1, 0, 1, 1, xr, xi, k4, k4p);
                CMUL4(yr, yi, yr, yi, z1r, z1i);        EMIT(0, 4, 0, 5, yr, yi, k4, k4p);
                CMUL4(cr, ci, xr, xi, z2r, z2i);        EMIT(1, 2, 1, 3, cr, ci, k4, k4p);
                CMUL4(yr, yi, yr, yi, z1r, z1i);        EMIT(0, 6, 0, 7, yr, yi, k4, k4p);
                CMUL4(xr, xi, xr, xi, z256r, z256i);    EMIT(1, 4, 1, 5, xr, xi, k4, k4p);
                CMUL4(xr, xi, xr, xi, z256r, z256i);    EMIT(1, 6, 1, 7, xr, xi, k4, k4p);
            }
            __syncwarp();
            {
                KSTAMP(8, 0);
                uint32_t bd[2][4] = {{0, 0, 0, 0}, {0, 0, 0, 0}};
                const bool on = (g >> 1) == t;
#pragma unroll
                for (int i = 0; i < 4; i++) { R[i][0] = R[i][1] = R[i][2] = R[i][3] = 0.f; }
#pragma unroll
                for (int k2 = 0; k2 < 8; k2++) {
                    uint32_t x[4], y[4], a1[2][4];
                    lds128_if(on, TB + t * T_PL + 16 + (g & 1) * 144 + 16 * k2, bd[k2 & 1]);
                    ldsm4(((k2 & 1) ? ld1 : ld0) + (k2 >> 1) * 128, x[0], x[1], x[2], x[3]);
                    ldsm4(((k2 & 1) ? ld1 : ld0) + (k2 >> 1) * 128 + 4096, y[0], y[1], y[2], y[3]);
#pragma unroll
                    for (int u = 0; u < 2; u++) {
                        mma_hh_k8(a1[u][0], a1[u][1], Ya[2 * k2 + u][0], Ya[2 * k2 + u][1], bd[k2 & 1][2 * u]);
                        mma_hh_k8(a1[u][2], a1[u][3], Ya[2 * k2 + u][2], Ya[2 * k2 + u][3], bd[k2 & 1][2 * u + 1]);
                    }
#pragma unroll
                    for (int u = 0; u < 2; u++) {
                        const uint32_t(&a0)[4] = Ya[2 * k2 + u];
                        mma_h(R[0], a0[0], a0[1], a0[2], a0[3], x[2 * u], x[2 * u + 1]);
                        mma_h(R[2], a0[0], a0[1], a0[2], a0[3], y[2 * u], y[2 * u + 1]);
                        mma_h(R[1], a1[u][0], a1[u][1], a1[u][2], a1[u][3], x[2 * u], x[2 * u + 1]);
                        mma_h(R[3], a1[u][0], a1[u][1], a1[u][2], a1[u][3], y[2 * u], y[2 * u + 1]);
                    }
                }
            }
            __syncwarp();
            KSTAMP(9, __float_as_uint(R[3][0]));
            asm volatile("barrier.cluster.wait.acquire.aligned;" ::: "memory");
            CMUL4(xr, xi, xr, xi, z256r, z256i);
            float s1024 = (xr[0] + xr[1]) + (xr[2] + xr[3]);
            CMUL4(xr, xi, xr, xi, z8r, z8i);        EMIT(0, 0, 0, 1, xr, xi, k128, k128p);
            CMUL4(xr, xi, xr, xi, z256r, z256i);    EMIT(0, 2, 0, 3, xr, xi, k128, k128p);
            CMUL4(xr, xi, xr, xi, z256r, z256i);    EMIT(0, 4, 0, 5, xr, xi, k128, k128p);
            CMUL4(xr, xi, xr, xi, z256r, z256i);    EMIT(0, 6, 0, 7, xr, xi, k128, k128p);
            __syncwarp();
            {
                KSTAMP(10, 0);
                float a1[4] = {0.f, 0.f, 0.f, 0.f};
                R[4][0] = R[4][1] = R[4][2] = R[4][3] = 0.f;
#pragma unroll
                for (int k2 = 0; k2 < 8; k2++) {
                    uint32_t x[4];
                    ldsm4(((k2 & 1) ? ld1 : ld0) + (k2 >> 1) * 128, x[0], x[1], x[2], x[3]);
                    mma_h(R[4], Ya[2 * k2][0], Ya[2 * k2][1], Ya[2 * k2][2], Ya[2 * k2][3], x[0], x[1]);
                    mma_h(a1, Ya[2 * k2 + 1][0], Ya[2 * k2 + 1][1], Ya[2 * k2 + 1][2], Ya[2 * k2 + 1][3], x[2], x[3]);
                }
#pragma unroll
                for (int i = 0; i < 4; i++) R[4][i] += a1[i];
            }
            if (lane == 0) mbar_arrive(bars + 8 * B_KG + (__float_as_uint(R[4][0]) & p.zero));
            KSTAMP(11, __float_as_uint(R[4][0]));
#undef PUT
#undef EMIT
#pragma unroll
            for (int o = 16; o > 0; o >>= 1) s1024 += __shfl_xor_sync(0xffffffffu, s1024, o);
            uint32_t w[4][4], dsk = 0;
            if (lane == 0) { cp_wait_all(); asm volatile("ld.shared.u16 %0, [%1];" : "=r"(dsk) : "r"(sb + M_DSK + 4 * warp + 2 * (warp & 1)) : "memory"); }
#pragma unroll
            for (int a = 0; a < 4; a++) {
                const float v0 = (a == 0) ? fmaf(R[0][0], inv, __uint_as_float(dsk << 16)) : R[a][0] * inv;
                const float v1 = R[a][1] * inv, v2 = R[a][2] * inv, v3 = R[a][3] * inv;
                w[a][0] = pack_bf(v0, 0.f); w[a][1] = pack_bf(v1, v0); w[a][2] = pack_bf(v2, v1); w[a][3] = pack_bf(v3, v2);
            }
            const uint32_t wb = TB + 16 + 16 * g, w1 = wb + t * T_PL, w2 = wb + 256 + 2 * t * T_PL;
            const uint32_t w3 = (t == 0) ? wb + 256 + 3 * T_PL : TB + T_A + 8 * (16 * t + g);
            const uint32_t w3s = (t == 0) ? 128 : 64, w3o = (t == 0) ? 8 : 12;
            const uint32_t k512 = __shfl_sync(0xffffffffu, w[2][1], 2);
#pragma unroll
            for (int a = 0; a < 2; a++) {
                sts128(w1 + 128 * a, w[a][0], w[a][1], w[a][2], w[a][3]);
                const uint32_t(&q)[4] = w[2 + a];
                if (t < 2) sts128(w2 + 128 * a, q[0], q[1], q[2], q[3]);
                if (t == 0) { sts128(w2 + T_PL + 128 * a, q[0], q[1], q[2], q[3]); sts32(w3 + 128 * a + 4, q[2]); }
                if (t != 1 && (a == 1 || lane != 2)) sts32(w3 + w3s * a, q[1]);
                if (t != 1) sts32(w3 + w3s * a + w3o, q[3]);
            }
            if (lane < 4)
                sts128(w1 + 512, __byte_perm(k512, 0, t == 3 ? 0x3210 : 0x4432), __byte_perm(k512, 0, t < 2 ? 0x3210 : t == 2 ? 0x3244 : 0x1044),
                       __byte_perm(k512, 0, t < 2 ? 0x1044 : 0x4444), 0);
            __syncwarp();
#pragma unroll
            for (int a = 0; a < 2; a++) {
                sts16(w1 + 128 * a + 18, w[a][3]);
                const uint32_t(&q)[4] = w[2 + a];
                if (t < 2) sts16(w2 + 128 * a + 18, q[3]);
                if (t == 0) { sts16(w2 + T_PL + 128 * a + 18, q[3]); sts16(w3 + 128 * a + 14, q[3]); }
            }
            if (t == 0) sts16(w3 + 128 - 4, w[3][0]);
            if (lane == 2 || (t == 0 && g > 0)) sts16(lane == 2 ? TB + 16 + 3 * T_PL + 4 * 127 : w3 - 4, w[2][0]);
            {
                const uint32_t b0 = pack_bf(R[4][0] * inv, R[4][2] * inv), b1 = pack_bf(R[4][1] * inv, R[4][3] * inv);
                const uint32_t wq = TB + T_B + 8 * (65 + 16 * t + g);
                sts32(wq, b0); sts32(wq + 12, b0); sts32(wq + 64, b1); sts32(wq + 76, b1);
            }
            cfix = pack_bf(s1024 * inv, s1024 * inv);
            if (lane == 0) sts32(TB + T_A + 8 * 64, cfix);
            __syncwarp();
        }
        WSTAMP(1);

        mbar_wait(bars + 8 * B_U);
        WSTAMP(2);

        float D[16][4];
        {
            const int x5 = g - t + 5;
            const uint32_t tabD = TB + (x5 & 3) * T_PL + (x5 & 12) + 16;
            {
                const uint32_t a1 = lds32(tabD - 8), a0 = p.zero;
#pragma unroll
                for (int jq = 0; jq < 4; jq++) {
                    uint32_t b[4];
                    ldsm4(UB + (9 + lane) * 16 + jq * 512, b[0], b[1], b[2], b[3]);
#pragma unroll
                    for (int i = 0; i < 4; i++) mma_bf_k8z(D[4 * jq + i], a0, a1, b[i]);
                }
            }
            const uint32_t ua = UB + (mi & 1) * U_PL + (8 + 8 * (mi >> 1) + r) * 16;
#pragma unroll 1
            for (int k0 = 0; k0 < 8; k0++) {
                uint32_t Uf[16][2];
#pragma unroll
                for (int jp = 0; jp < 8; jp++) ldsm4(ua + jp * 256 - k0 * 16, Uf[2 * jp][0], Uf[2 * jp][1], Uf[2 * jp + 1][0], Uf[2 * jp + 1][1]);
#pragma unroll
                for (int k1 = 0; k1 < 4; k1++) {
                    const uint32_t ta = tabD + 16 * (8 * k1 + k0);
                    const uint32_t a0 = lds32(ta), a1 = lds32(ta + 8), a2 = lds32(ta - 8), a3 = a0 ^ p.zero;
#pragma unroll
                    for (int J = k1; J < 16; J++) mma_bf(D[J], a0, a1, a2, a3, Uf[J - k1][0], Uf[J - k1][1]);
                }
                if (k0 == 0) {
                    const uint32_t ta = tabD + 16 * 32;
                    const uint32_t a0 = lds32(ta), a1 = lds32(ta + 8), a2 = lds32(ta - 8), a3 = a0 ^ p.zero;
#pragma unroll
                    for (int J = 4; J < 16; J++) mma_bf(D[J], a0, a1, a2, a3, Uf[J - 4][0], Uf[J - 4][1]);
                    const uint32_t f0 = (cfix ^ 0x80008000u) & (g == t ? 0xffffu : g == t + 4 ? 0xffff0000u : 0u);
                    const uint32_t f1 = p.zero, f2 = p.zero + p.zero, f3 = f0 ^ p.zero;
#pragma unroll
                    for (int J = 8; J < 16; J++) mma_bf(D[J], f0, f1, f2, f3, Uf[J - 8][0], Uf[J - 8][1]);
                }
            }
        }
        WSTAMP(3);
        {
            const int ch = 8 * h + warp;
            const uint32_t yo = sb + ch * 512 + ((lane ^ (((ch >> 2) << 1) | (ch & 1))) << 4);
            const uint32_t yr = mapa(yo, h ^ 1), ybr = mapa(bars + 8 * B_Y, h ^ 1);
            const uint32_t yi = sb + (4 * (r >> 1) + 2 * (mi & 1) + (r & 1)) * 512 + (((4 * warp + (mi >> 1)) ^ r) << 4);
            const int rho = 128 * (g >> 2) + 8 * ((g >> 1) & 1) + 16 * (g & 1) + warp;
            const uint32_t xs = sb + OFF_S + ((rho + 5) & 3) * S_PL + ((rho + 5) >> 2) * 32 + (((t >> 1) ^ (((rho + 5) >> 4) & 1)) << 4) + ((t & 1) << 3);
            bf16* op = p.out + (size_t)(256 * h + rho) * D_ + 16 * pr + 4 * t;
            const uint4* gsrc = &p.sc->g[256 * h + 8 * warp + g];
            uint32_t tag16;
            uint4 gq[2], sel;
            auto ship = [&](const int Q) {
                uint4 y[2];
#pragma unroll
                for (int hh = 0; hh < 2; hh++) {
                    const int J = 4 * Q + 2 * hh;
                    y[hh] = make_uint4(pack_bf(D[J][0], D[J][1]), pack_bf(D[J][2], D[J][3]), pack_bf(D[J + 1][0], D[J + 1][1]), pack_bf(D[J + 1][2], D[J + 1][3]));
                }
                if (!(Q & 1)) mbar_wait(bars + 8 * (B_F + (Q >> 1)));
                asm volatile("{\n\t.reg .pred p;\n\tsetp.eq.u32 p, %11, 0;\n\t"
                             "@p st.async.weak.shared::cluster.mbarrier::complete_tx::bytes.v4.b32 [%9], {%4,%5,%6,%7}, [%10];\n\t"
                             "@!p st.async.weak.shared::cluster.mbarrier::complete_tx::bytes.v4.b32 [%9], {%0,%1,%2,%3}, [%10];\n\t"
                             "@p st.shared.v4.b32 [%8], {%0,%1,%2,%3};\n\t@!p st.shared.v4.b32 [%8], {%4,%5,%6,%7};\n\t}"
                             :: "r"(y[0].x), "r"(y[0].y), "r"(y[0].z), "r"(y[0].w), "r"(y[1].x), "r"(y[1].y), "r"(y[1].z), "r"(y[1].w),
                                "r"(yo + y_off(Q)), "r"(yr + y_off(Q)), "r"(ybr + 8 * Q), "r"(h) : "memory");
                __syncwarp();
                if (lane == 0) mbar_arrive(bars + 8 * (B_Y + Q));
            };
            auto finish = [&](const int Q) {
                uint2 xq[4];
#pragma unroll
                for (int i = 0; i < 4; i++) xq[i] = lds64(xs + Q * 4 * S_PL + i * 256);
#pragma unroll 1
                for (int it = 0; ((((gq[Q & 1].x ^ tag16) | (gq[Q & 1].y ^ tag16)) | ((gq[Q & 1].z ^ tag16) | (gq[Q & 1].w ^ tag16))) >> 16) && it < (1 << 22); it++)
                    gq[Q & 1] = ld_gpu128(gsrc + 64 * Q);
                uint32_t gg[4] = {gq[Q & 1].x, gq[Q & 1].y, gq[Q & 1].z, gq[Q & 1].w};
#pragma unroll
                for (int i = 0; i < 4; i++) {
                    gg[i] = __byte_perm(gg[i], 0, 0x1010);
                    const uint32_t og = hfma2_bf(gg[i], 0xBF80BF80u, 0x3F803F80u);
                    xq[i].x = hmul2_bf(og, xq[i].x); xq[i].y = hmul2_bf(og, xq[i].y);
                }
                mbar_wait(bars + 8 * (B_Y + Q));
                __syncwarp();
                if (Q == 0) sel = lds128(sb + M_BMAP + warp * 16);
                const uint32_t sbits = (Q == 0 ? sel.x : Q == 1 ? sel.y : Q == 2 ? sel.z : sel.w) >> (4 * g);
#pragma unroll
                for (int x = 0; x < 2; x++) {
                    uint32_t y[4];
                    ldsm4t((yi ^ (x << 5)) + y_off(Q), y[0], y[1], y[2], y[3]);
#pragma unroll
                    for (int e = 0; e < 2; e++) {
                        const int i = 2 * x + e;
                        const uint2 o = make_uint2(hfma2_bf(gg[i], y[2 * e], xq[i].x), hfma2_bf(gg[i], y[2 * e + 1], xq[i].y));
                        if (!(sbits & (1u << i))) *(uint2*)(op + (size_t)(512 * Q + 32 * i) * D_) = o;
                    }
                }
            };
            gq[0] = ld_gpu128(gsrc);
            ship(0);
            tag16 = lds32(sb + M_TAG);
            const uint4 bA = lds128(sb + OFF_BAND + (g - t + 3) * 48), bB = lds128(sb + OFF_BAND + (g - t + 3) * 48 + 16);
            const uint2 bC = lds64(sb + OFF_BAND + (g - t + 3) * 48 + 32);
            uint2 QA[5][2], QB[8];
            const uint32_t tq = TB + 8 * (1 + g - 2 * t);
#pragma unroll
            for (int dd = 0; dd < 5; dd++) { QA[dd][0] = lds64(tq + T_A + 64 * (dd + 4)); QA[dd][1] = lds64(tq + T_A + 64 * (dd + 4) - 8); }
#pragma unroll
            for (int dd = 0; dd < 8; dd++) QB[dd] = lds64(tq + T_B + 64 * (dd + 8));
            const uint32_t u1 = UB + (mi & 1) * U_PL + (7 + r + (mi >> 1)) * 16;
            const uint32_t u2 = UB + ((mi & 1) ^ 1) * U_PL + (7 + r + (mi & 1) + 8 * (mi >> 1)) * 16;
            uint32_t n[4];
#pragma unroll
            for (int j = 0; j < 12; j++) {
                uint32_t m[4];
                ldsm4(u1 + j * 128, m[0], m[1], m[2], m[3]);
                if (!(j & 1)) ldsm4(u2 + j * 128, n[0], n[1], n[2], n[3]);
                const uint32_t n0 = n[2 * (j & 1)], n1 = n[2 * (j & 1) + 1];
                float wa[4], wb[4], wc[4], g1[4], g2[4];
                mma_bf_z(wa, bA.x, bA.y, bA.z, bA.w, m[0], m[1]);
                mma_bf_z(wb, bA.x, bA.y, bA.z, bA.w, n0, n1);
                mma_bf_z(wc, bA.x, bA.y, bA.z, bA.w, m[2], m[3]);
                if (j < 8) {
                    mma_bf_z(g1, bB.x, bB.y, bB.z, bB.w, m[0], m[1]);
                    mma_bf_z(g2, bB.x, bB.y, bB.z, bB.w, n0, n1);
                    mma_bf_k8(g1, bC.x, bC.y, m[2]);
                    mma_bf_k8(g2, bC.x, bC.y, m[3]);
                }
#pragma unroll
                for (int e = 0; e < 2; e++) {
                    const uint32_t q0 = pack_bf(wa[e], wa[e + 2]), q1 = pack_bf(wb[e], wb[e + 2]), q2 = q1 ^ p.zero, q3 = pack_bf(wc[e], wc[e + 2]);
#pragma unroll
                    for (int dd = 0; dd < 5; dd++)
                        if (j + 4 + dd < 16) mma_bf(D[j + 4 + dd], q0, q1, q2, q3, QA[dd][e].x, QA[dd][e].y);
                }
                if (j < 8) {
                    const uint32_t q0 = pack_bf(g1[0], g1[2]), q1 = pack_bf(g2[0], g2[2]), q2 = pack_bf(g1[1], g1[3]), q3 = pack_bf(g2[1], g2[3]);
#pragma unroll
                    for (int dd = 7 - j; dd >= 0; dd--) mma_bf(D[j + 8 + dd], q0, q1, q2, q3, QB[dd].x, QB[dd].y);
                }
                if ((j & 3) == 3) {
                    WSTAMP(4 + 2 * (j >> 2));
                    ship((j >> 2) + 1);
                    finish(j >> 2);
                    WSTAMP(5 + 2 * (j >> 2));
                    if (j < 11) {
                        sched_fence(p.zero, j);
                        gq[1] = ld_gpu128(gsrc + 64 * (j >> 1));
                        if (j == 7) gq[0] = ld_gpu128(gsrc + 128);
                    }
                }
            }
            finish(3);
        }
        WSTAMP(10);
        WDUMP();
    } else if ((pw & 12) == AUX_W0) {
        asm volatile("setmaxnreg.inc.sync.aligned.u32 136;");
        const int v = __reduce_max_sync(0xffffffffu, pw & 3);
        const int at = tid & 127;
        const int g = lane >> 2, t = lane & 3;
        unsigned epoch, tag;
        const bool gu = c < NGU_CTA;
        {
            uint4 xa[16];
            const uint32_t xb = sb + (v < 2 ? OFF_XSEL : OFF_RING + 2 * 8192) + v * 8192;
            const uint32_t gws = sb + (gu ? M_DPIN : OFF_RING + 2 * 8192);
            const uint32_t row = 16 * c + 4 * v + (g >> 1);
            if (lane == 0) {
                mbar_init(bars + 8 * (B_X + v), 1);
                mbar_init(bars + 8 * (B_XE + v), 1);
                asm volatile("fence.proxy.async.shared::cta;" ::: "memory");
                asm volatile("fence.mbarrier_init.release.cluster;" ::: "memory");
            }
            __syncwarp();
            epoch = *(volatile unsigned*)&p.sc->epoch;
            tag = (epoch + 1) & 0xffffu;
#pragma unroll
            for (int i = 0; i < 4; i++)
                asm volatile("cp.async.ca.shared.global [%0], [%1], 4;" :: "r"(sb + OFF_S + (4 * i + v) * S_PL + 2176 + (tid & 28) * 4 + (tid & 1) * 8 + (tid & 2) * 2),
                             "l"(p.wr + 256 * i + (tid & 127) * 2) : "memory");
            cp16(gws + (tid & 127) * 16, p.gatew + (tid & 127) * 8);
            if ((tid & 127) < 33) cp16(sb + OFF_BAND + (tid & 127) * 16, p.band + (tid & 127));
            asm volatile("barrier.cluster.arrive.relaxed.aligned;" ::: "memory");
            if (DELAY_X > 0) __nanosleep(DELAY_X);
            asm volatile("{\n\t.reg .pred p;\n\telect.sync _|p, 0xffffffff;\n\t"
                         "@p mbarrier.arrive.expect_tx.shared::cta.b64 _, [%2], 8192;\n\t"
                         "@p cp.async.bulk.shared::cluster.global.mbarrier::complete_tx::bytes [%0], [%1], 8192, [%2];\n\t}"
                :: "r"(xb), "l"(p.u + (size_t)(16 * c + 4 * v) * D_), "r"(bars + 8 * (B_X + v)) : "memory");
            if (gu) {
                st_gpu32((uint32_t*)&p.sc->h[(tag + 1) & 1][32 * c] + at, 0);
            }
            if (v == 0) sts32(sb + M_BMAP + lane * 4, 0);
            cp_wait_all();
            bar_sync(1, 128);
            uint2 w[16];
#pragma unroll
            for (int kb = 0; kb < 16; kb++) w[kb] = lds64(sb + OFF_S + 2176 + S_PL * kb + 32 * (g & 2) + 16 * t + 8 * (g & 1));
            mbar_wait(bars + 8 * (B_X + v));
            WSTAMP(10);
#pragma unroll
            for (int kb = 0; kb < 16; kb++) xa[kb] = lds128(xb + (g >> 1) * 2048 + 128 * kb + 16 * (lane & 7));
            float dr[4][4];
#pragma unroll
            for (int kb = 0; kb < 16; kb++) {
                if (kb < 4) mma_bf_z(dr[kb], xa[kb].x, xa[kb].y, xa[kb].z, xa[kb].w, w[kb].x, w[kb].y);
                else mma_bf(dr[kb & 3], xa[kb].x, xa[kb].y, xa[kb].z, xa[kb].w, w[kb].x, w[kb].y);
            }
            float rs = ((dr[0][0] + dr[0][3]) + (dr[1][0] + dr[1][3])) + ((dr[2][0] + dr[2][3]) + (dr[3][0] + dr[3][3]));
            if (lane == 0) mbar_arrive(bars + 8 * (B_XE + v) + (__float_as_uint(rs) & p.zero));
            rs += __shfl_xor_sync(0xffffffffu, rs, 5);
            const uint32_t rb = pack_bf(0.f, rs);
            if (!(lane & 7)) st_gpu32((uint32_t*)&p.sc->r[(row >> 2) * RS] + (row & 3), ((rb ^ (((int)rb >> 31) | 0x80000000u)) & 0xffff0000u) | tag);
            WSTAMP(1);
            asm volatile("barrier.cluster.wait.acquire.aligned;" ::: "memory");
            {
                const int r = lane & 7;
                const uint32_t src = sb + OFF_S + (4 * v + (lane >> 3)) * S_PL + (r >> 1) * 128 + (r & 1) * 32 + ((h ^ ((r >> 1) & 1)) << 4);
                const uint32_t dst = sb + OFF_U + g * U_CH + (8 + 32 * v + 16 * h + t) * 16;
                const uint32_t rdst = mapa(dst, h ^ 1), rbar = mapa(bars + 8 * B_U, h ^ 1);
                mbar_wait(bars + 8 * (B_S + v));
                uint4 a[8];
#pragma unroll
                for (int b = 0; b < 2; b++) {
#pragma unroll
                    for (int j = 0; j < 8; j++) ldsm4t((b ? src : src ^ 16) + (j >> 1) * 512 + (j & 1) * 64, a[j].x, a[j].y, a[j].z, a[j].w);
#pragma unroll
                    for (int j = 0; j < 8; j++) {
                        if (b) sts128(dst + (j >> 1) * 64 + (j & 1) * U_PL, a[j].x, a[j].y, a[j].z, a[j].w);
                        else st_async16(rdst + (j >> 1) * 64 + (j & 1) * U_PL, a[j], rbar);
                    }
                }
                if (h && v == 3) {
                    ldsm4t((src ^ 16) + 2048, a[0].x, a[0].y, a[0].z, a[0].w);
                    ldsm4t(src + 2048, a[1].x, a[1].y, a[1].z, a[1].w);
                    if (t == 0) { st_async16(rdst + 256, a[0], rbar); sts128(dst + 256, a[1].x, a[1].y, a[1].z, a[1].w); }
                }
                __syncwarp();
                if (lane == 0) mbar_arrive(bars + 8 * B_U);
            }
            const uint32_t one0 = 0x3F803F80u ^ p.zero, one1 = 0x3F803F80u + p.zero;
#pragma unroll
            for (int kb = 0; kb < 16; kb++) {
                const uint4 gw = lds128(gws + 128 * kb + 16 * (lane & 7));
                const uint32_t a0 = hmul2_bf(xa[kb].x, gw.x), a1 = hmul2_bf(xa[kb].y, gw.y), a2 = hmul2_bf(xa[kb].z, gw.z), a3 = hmul2_bf(xa[kb].w, gw.w);
                if (kb < 4) mma_bf_z(dr[kb], a0, a1, a2, a3, one0, one1);
                else mma_bf(dr[kb & 3], a0, a1, a2, a3, one0, one1);
            }
            float sg = ((dr[0][0] + dr[0][3]) + (dr[1][0] + dr[1][3])) + ((dr[2][0] + dr[2][3]) + (dr[3][0] + dr[3][3]));
            sg += __shfl_xor_sync(0xffffffffu, sg, 4);
            if (!(lane & 7)) st_gpu32((uint32_t*)p.sc->g + ((row & 256) << 2) + gate_pos(row), (pack_bf(sigmoid_f(bf_round(sg)), 0.f) & 0xffffu) | (tag << 16));
            WSTAMP(2);
        }
        if (at == 32) { sts32(sb + M_TAG, tag << 16); mbar_arrive(bars + 8 * B_F); }
        const bool lane0 = pin(lane, lane) == 0;
        const uint32_t own = pin(sb + OFF_XSEL + at * 16, lane);
        const uint4* pb = pin(&p.sc->h[tag & 1][32 * (56 * h + 14 * v + (lane < 14 ? lane : 0)) + 8 * (pr & 3)], lane);
        {
            float acc[8][4];
#pragma unroll
            for (int i = 0; i < 8; i++) { acc[i][0] = acc[i][1] = acc[i][2] = acc[i][3] = 0.f; }
            const int krow = ((lane >> 1) & 8) + (lane & 7);
            const uint32_t tile0 = pin(sb + OFF_RING + krow * 64 + ((((lane >> 3) & 1) ^ ((krow >> 1) & 3)) << 4), lane);
            const uint32_t xo = pin(sb + OFF_XSEL + (lane & 7) * XS_ROW + 512 * v + 2 * (lane & 24), lane);
            const uint32_t po = pin(sb + OFF_XSEL + t * XS_ROW + (g & 3) * 128 + v * 16 + (lane >> 4) * 8, lane);
            uint32_t* hdst = pin((uint32_t*)&p.sc->h[tag & 1][32 * c] + at, lane);
            auto signal = [&](const int k, const uint32_t dep) {
                if (lane < 2 && v < 2)
                    asm volatile("st.async.weak.shared::cluster.mbarrier::complete_tx::bytes.b32 [%0], %1, [%2];"
                                 :: "r"(mapa(sb + M_SINK, lane)), "r"(dep), "r"(mapa(bars + 8 * (B_F + k), lane)) : "memory");
            };
#pragma unroll 1
            for (int i = 0; i < 4; i++) {
                const int s = 4 * i + v;
                uint32_t a[16][4], b[2][4];
                if (gu) {
                    const uint32_t tile = tile0 + (s < 14 ? s : v) * 8192;
                    if (lane0 && i > 1) mbar_arrive(bars + 8 * (B_E + s - 4));
                    mbar_wait(bars + 8 * (B_W + s));
#pragma unroll
                    for (int q = 0; q < 16; q++) ldsm4t((tile ^ ((q & 1) << 5)) + ((q >> 1) & 1) * 4096 + (q >> 2) * 1024, a[q][0], a[q][1], a[q][2], a[q][3]);
                }
                if (i == 0) {
                    if (gu) {
                        uint32_t dep = p.zero;
#pragma unroll
                        for (int q = 0; q < 16; q += 2) dep &= a[q][0] & a[q + 1][0];
                        if (lane == 0) mbar_arrive(bars + 8 * (B_E + v) + dep);
                        signal(0, dep);
                    }
                    WSTAMP(11);
                    uint32_t top;
#pragma unroll 1
                    for (int it = 0; it < (1 << 22); it++) {
                        asm volatile("ld.relaxed.gpu.global.u32 %0, [%1];" : "=r"(top) : "l"(&p.sc->top[c % NTOP][g]) : "memory");
                        if (__all_sync(0xffffffffu, ((top ^ (tag << 11)) & 0xf800u) == 0)) break;
                        if (TSLEEP) __nanosleep(TSLEEP);
                    }
                    WSTAMP(3);
                    if (gu) {
                        const uint32_t k = 4 * h + v, row = __reduce_max_sync(0xffffffffu, lane == 4 * k ? ~top & 2047 : 0);
                        asm volatile("{\n\t.reg .pred p;\n\telect.sync _|p, 0xffffffff;\n\t"
                                     "@p cp.async.bulk.shared::cluster.global.mbarrier::complete_tx::bytes.multicast::cluster [%0], [%1], 2048, [%2], %3;\n\t}"
                            :: "r"(sb + OFF_XSEL + k * XS_ROW), "l"(p.u + (size_t)row * D_), "r"(bars + 8 * B_G), "h"((unsigned short)3) : "memory");
                    }
                    if (v == 0) {
                        const uint32_t row = ~top & 2047;
                        if (t == 0 && ((row >> 8) & 1) == h)
                            asm volatile("red.shared.or.b32 [%0], %1;" :: "r"(sb + M_BMAP + (row & 7) * 16 + (row >> 9) * 4), "r"(1u << (gate_pos(row) & 31)) : "memory");
                        if (t == 0) sts32(sb + M_TOP + lane, top);
                        __syncwarp();
                        if (lane0) mbar_arrive(bars + 8 * B_Y);
                    }
                    if (!gu) break;
                    mbar_wait(bars + 8 * B_G);
                    WSTAMP(4);
                }
                ldsm4(xo + 128 * i, b[0][0], b[0][1], b[0][2], b[0][3]);
                ldsm4(xo + 128 * i + 64, b[1][0], b[1][1], b[1][2], b[1][3]);
#pragma unroll
                for (int q = 0; q < 16; q++) mma_bf(acc[q & 7], a[q][0], a[q][1], a[q][2], a[q][3], b[q >> 3][(q >> 1) & 2], b[q >> 3][((q >> 1) & 2) + 1]);
            }
            if (gu) {
                WSTAMP(5);
                __syncwarp();
#pragma unroll
                for (int q = 0; q < 4; q++) {
                    const int ct = q >> 1, e = 2 * (q & 1);
                    sts128(own + q * XS_ROW,
                           __float_as_uint(acc[ct][e] + acc[4 + ct][e]), __float_as_uint(acc[2 + ct][e] + acc[6 + ct][e]),
                           __float_as_uint(acc[ct][e + 1] + acc[4 + ct][e + 1]), __float_as_uint(acc[2 + ct][e + 1] + acc[6 + ct][e + 1]));
                }
                bar_sync(1, 128);
                float hv[2];
#pragma unroll
                for (int e = 0; e < 2; e++) {
                    uint2 q[4];
#pragma unroll
                    for (int i = 0; i < 4; i++) q[i] = lds64(po + 64 * e + 512 * i);
                    const float s0 = (__uint_as_float(q[0].x) + __uint_as_float(q[1].x)) + (__uint_as_float(q[2].x) + __uint_as_float(q[3].x));
                    const float s1 = (__uint_as_float(q[0].y) + __uint_as_float(q[1].y)) + (__uint_as_float(q[2].y) + __uint_as_float(q[3].y));
                    const float gv = bf_round(p.gu_swap ? s1 : s0), uv = bf_round(p.gu_swap ? s0 : s1);
                    hv[e] = bf_round(gv * sigmoid_f(gv)) * uv;
                }
                const uint32_t hw = pack_bf(hv[0], hv[1]);
                st_gpu32(hdst, hw ? hw : 0x80000000u);
                signal(1, hw);
            }
        }
        WSTAMP(6);
        {
            uint4 hq[14];
            {
                bar_sync(1, 128);
                const uint32_t hb = sb + (v < 2 ? OFF_XSEL + 7168 * v : OFF_RING + 8192 * v);
#pragma unroll 1
                for (int it = 0; it < (1 << 22); it++) {
                    uint32_t w;
                    asm volatile("ld.relaxed.gpu.global.u32 %0, [%1];" : "=r"(w) : "l"(pb) : "memory");
                    if (__all_sync(0xffffffffu, w != 0)) break;
                    __nanosleep(PSLEEP);
                }
                WSTAMP(12);
#pragma unroll 1
                for (int it = 0; it < (1 << 16); it++) {
                    asm volatile("{\n\t.reg .pred p;\n\telect.sync _|p, 0xffffffff;\n\t"
                                 "@p mbarrier.arrive.expect_tx.shared::cta.b64 _, [%2], 7168;\n\t"
                                 "@p cp.async.bulk.shared::cluster.global.mbarrier::complete_tx::bytes [%0], [%1], 7168, [%2];\n\t}"
                        :: "r"(hb), "l"(&p.sc->h[tag & 1][32 * (56 * h + 14 * v)]), "r"(bars + 8 * (B_X + v)) : "memory");
                    mbar_wait(bars + 8 * (B_X + v), ~it & 1);
                    uint32_t mn = 0xffffffffu;
#pragma unroll
                    for (int i = 0; i < 14; i++) hq[i] = lds128(hb + 512 * i + 16 * lane);
#pragma unroll
                    for (int i = 0; i < 14; i++) mn = min(mn, hq[i].x);
                    if (__all_sync(0xffffffffu, mn != 0)) break;
                }
            }
            WSTAMP(7);
            float dd[4][4];
            const int krow = ((lane >> 1) & 8) + (lane & 7);
            const uint32_t tile = sb + OFF_RING + (4 + v) * 8192 + krow * 32 + ((((lane >> 3) ^ (krow >> 2)) & 1) << 4);
#pragma unroll
            for (int s = 0; s < 2; s++) {
                mbar_wait(bars + 8 * (B_W + 16 + 4 * s + v));
#pragma unroll
                for (int j = 0; j < 14; j++) {
                    uint32_t a[4];
                    ldsm4t(tile + s * 32768 + j * 512, a[0], a[1], a[2], a[3]);
                    const uint4& hb = hq[7 * s + (j >> 1)];
                    if (s == 0 && j < 4) mma_bf_z(dd[j], a[0], a[1], a[2], a[3], (j & 1) ? hb.z : hb.x, (j & 1) ? hb.w : hb.y);
                    else mma_bf(dd[(j + 2 * s) & 3], a[0], a[1], a[2], a[3], (j & 1) ? hb.z : hb.x, (j & 1) ? hb.w : hb.y);
                }
            }
            WSTAMP(8);
            uint4 part;
            part.x = __float_as_uint((dd[0][0] + dd[1][0]) + (dd[2][0] + dd[3][0])); part.y = __float_as_uint((dd[0][1] + dd[1][1]) + (dd[2][1] + dd[3][1]));
            part.z = __float_as_uint((dd[0][2] + dd[1][2]) + (dd[2][2] + dd[3][2])); part.w = __float_as_uint((dd[0][3] + dd[1][3]) + (dd[2][3] + dd[3][3]));
            st_async16(mapa(own + (M_DPIN - OFF_XSEL), h ^ 1), part, mapa(bars + 8 * B_DP, h ^ 1));
            sts128(own + 14336, part.x, part.y, part.z, part.w);
            __syncwarp();
            if (lane0) mbar_arrive(bars + 8 * B_DP);
        }
        WSTAMP(9);
        WDUMP();
        if (at == 0 && c == 0) *(volatile unsigned*)&p.sc->epoch = epoch + 1;
    } else {
        asm volatile("setmaxnreg.dec.sync.aligned.u32 40;");
        const int v = __reduce_max_sync(0xffffffffu, pw - PREP_W0);
        const bool gu = c < NGU_CTA;
        const uint32_t t0 = clock();
        const uint32_t bu = bars + 8 * v;
        if (lane == 0) {
#pragma unroll
            for (int i = 0; i < 9; i++) mbar_init(bu + 32 * i, 1);
            mbar_init(bu + 8 * B_S, 4);
            mbar_init(bu + 8 * B_Y, v == 0 ? 10 : 9);
            mbar_init(bu + 8 * B_DP, (0x1855 >> (4 * v)) & 15);
            mbar_init(bu + 8 * B_F, v == 0 ? 2 : 1);
            mbar_init(bu + 8 * B_H, 1);
            asm volatile("fence.proxy.async.shared::cta;" ::: "memory");
            asm volatile("fence.mbarrier_init.release.cluster;" ::: "memory");
            mbar_expect(bu + 8 * B_Y, 4096);
            if (v != 2) mbar_expect(bu + 8 * B_DP, v == 0 ? 2048 : (h || v == 3) ? 16384 : 16384 + 128);
            mbar_expect(bu + 8 * B_F, c < NGU_CTA ? 16 : 0);
        }
        __syncwarp();
        asm volatile("barrier.cluster.arrive.relaxed.aligned;" ::: "memory");
#pragma unroll 1
        for (int j = 0; j < 4; j++)
            tma3d(sb + OFF_S + (4 * v + j) * S_PL, &tm_x, ((j + 3) & 3) * 1024 + 16 * pr, 128 * v + 64 * h - (j == 0 ? 2 : 1), bars + 8 * (B_S + v), 66 * 32);
        WSTAMP(9);
        if (v < 2 && lane == 0) asm volatile("prefetch.tensormap [%0];" :: "l"(v ? &tm_gu : &tm_down) : "memory");
        asm volatile("barrier.cluster.wait.acquire.aligned;" ::: "memory");
        if (v > 0) mbar_wait(bars + 8 * (B_H + v));
        {
            uint32_t last = v ? clock() - SLACK : t0 + T0 - GAP + STAG * ((pr * 5) & 15) / 16;
#pragma unroll 1
            for (int s = 6 * v; s < 6 * v + 6; s++) {
                if (!gu && s < 16) continue;
                const int i = s >> 2, w = s & 3, slot = s < 14 ? s : s - 12;
                if (slot >= 4 || s >= 14) mbar_wait(bars + 8 * ((gu && s >= 14) ? B_E + slot : slot < 6 ? B_XE + slot - 2 : B_KG));
                uint32_t now;
#pragma unroll 1
                while ((int)((now = clock()) - last) < GAP) __nanosleep(CSLEEP);
                last = max((int)(now - last) - SLACK, GAP) + last;
                WSTAMP(3 + s - 6 * v);
                tma3d(sb + OFF_RING + slot * 8192, i < 4 ? &tm_gu : &tm_down, i < 4 ? 32 * c : 16 * pr,
                      i < 4 ? 256 * w + 64 * i : 1792 * h + 448 * w + 224 * (i - 4), bars + 8 * (B_W + s), i < 4 ? 8192 : 7168);
            }
            if (lane == 0) mbar_arrive(bars + 8 * (B_H + ((v + 1) & 3)));
        }
        {
            mbar_wait(bars + 8 * B_Y);
            const uint32_t top = lds32(sb + M_TOP + 8 * v + 4 * (lane >> 4)), tag16 = lds32(sb + M_TAG);
            const uint32_t row = ~top & 2047, ch = lane & 15;
            const bool mine = ((row >> 8) & 1) == h;
            uint32_t gfin, x16, y16 = 0;
#pragma unroll 1
            for (int it = 0; it < (1 << 22); it++) {
                asm volatile("ld.relaxed.gpu.global.u32 %0, [%1];" : "=r"(gfin) : "l"((const uint32_t*)p.sc->g + ((row & 256) << 2) + gate_pos(row)) : "memory");
                if (((gfin ^ tag16) >> 16) == 0) break;
            }
            const uint32_t s5 = (row & 255) + 5;
            asm volatile("ld.shared.u16 %0, [%1];" : "=r"(x16) : "r"(sb + OFF_S + (4 * (row >> 9) + (s5 & 3)) * S_PL + (s5 >> 2) * 32 + ((2 * ch) ^ (s5 & 16))) : "memory");
            const float rsel = __uint_as_float(pin(__float_as_uint(bf_round(sigmoid_f(__uint_as_float((top ^ (((int)~top >> 31) | 0x80000000u)) & 0xffff0000u)))), lane));
            const uint32_t po = pin(sb + (4 * (ch & 7) + v) * 16 + (ch >> 3) * 8 + (lane >> 4) * 4, lane);
            bf16* op = pin(p.out + (size_t)row * D_ + 16 * pr + ch, lane);
            if (mine) {
                mbar_wait(bars + 8 * (B_Y + (row >> 9)));
                asm volatile("ld.shared.u16 %0, [%1];" : "=r"(y16)
                             : "r"(sb + y_off(row >> 9) + ch * 512 + (((4 * (row & 7) + ((row >> 5) & 3)) ^ (((ch >> 2) << 1) | (ch & 1))) << 4) + 2 * row_elem(row)) : "memory");
            }
            mbar_wait(bars + 8 * B_DP);
            float q[8];
#pragma unroll
            for (int i = 0; i < 4; i++) { q[i] = ldsf(po + M_DPIN + 512 * i); q[4 + i] = ldsf(po + OFF_XSEL + 14336 + 512 * i); }
            const float tot = ((q[0] + q[1]) + (q[2] + q[3])) + ((q[4] + q[5]) + (q[6] + q[7]));
            const float b = bf_round(__uint_as_float(x16 << 16) + bf_round(bf_round(tot) * rsel));
            if (mine) *op = __float2bfloat16_rn(fmaf(bf_lo(gfin), __uint_as_float(y16 << 16), bf_round(bf_round(1.f - bf_lo(gfin)) * b)));
        }
        WSTAMP(10);
        WDUMP();
    }
}

typedef CUresult (*EncodeFn)(CUtensorMap*, CUtensorMapDataType, cuuint32_t, void*, const cuuint64_t*, const cuuint64_t*,
                             const cuuint32_t*, const cuuint32_t*, CUtensorMapInterleave, CUtensorMapSwizzle,
                             CUtensorMapL2promotion, CUtensorMapFloatOOBfill);

void make_map(EncodeFn f, CUtensorMap* m, const void* ptr, uint64_t cols, uint64_t rows, uint32_t bc, uint32_t br, CUtensorMapSwizzle sw,
              uint32_t planes = 1, uint64_t plane_stride = 0) {
    cuuint64_t dims[3] = {cols, rows, planes};
    cuuint64_t str[2] = {cols * 2, planes > 1 ? plane_stride : cols * rows * 2};
    cuuint32_t box[3] = {bc, br, planes};
    cuuint32_t es[3] = {1, 1, 1};
    f(m, CU_TENSOR_MAP_DATA_TYPE_BFLOAT16, 3, (void*)ptr, dims, str, box, es, CU_TENSOR_MAP_INTERLEAVE_NONE, sw,
      CU_TENSOR_MAP_L2_PROMOTION_L2_128B, CU_TENSOR_MAP_FLOAT_OOB_FILL_NONE);
}

}

extern "C" void kernel_launch(void* const* d_in, const int* in_sizes, int n_in, void* d_out, int out_size) {
    static EncodeFn enc = nullptr;
    static void *sc = nullptr, *band = nullptr;
    if (!enc) {
        void* fn = nullptr;
        cudaDriverEntryPointQueryResult qr;
        cudaGetDriverEntryPoint("cuTensorMapEncodeTiled", &fn, cudaEnableDefault, &qr);
        enc = (EncodeFn)fn;
        cudaGetSymbolAddress(&sc, g_scratch);
        cudaGetSymbolAddress(&band, g_band);
        cudaFuncSetAttribute(fused_kernel, cudaFuncAttributeMaxDynamicSharedMemorySize, SMEM_BYTES);
    }
    CUtensorMap tg, td, tx;
    const char *wg = (const char*)d_in[9], *wu = (const char*)d_in[10];
    const bool swap = wu < wg;
    make_map(enc, &tg, swap ? wu : wg, F_, D_, 32, 64, CU_TENSOR_MAP_SWIZZLE_64B, 2, swap ? wg - wu : wu - wg);
    make_map(enc, &td, d_in[11], D_, F_, 16, 224, CU_TENSOR_MAP_SWIZZLE_32B);
    make_map(enc, &tx, d_in[0], 4 * D_, L_ / 4, 16, 66, CU_TENSOR_MAP_SWIZZLE_32B);
    Params p;
    p.u = (const bf16*)d_in[0]; p.logA = (const bf16*)d_in[1]; p.Aim = (const bf16*)d_in[2];
    p.Cre = (const bf16*)d_in[3]; p.Cim = (const bf16*)d_in[4]; p.logdt = (const bf16*)d_in[5];
    p.Dskip = (const bf16*)d_in[6]; p.wr = (const bf16*)d_in[8]; p.gatew = (const bf16*)d_in[12];
    p.out = (bf16*)d_out;
    p.sc = (Scratch*)sc; p.band = (const uint4*)band;
    p.gu_swap = swap;
    p.zero = 0;
    fused_kernel<<<NCTA, NTHREADS, SMEM_BYTES>>>(p, tg, td, tx);
}
```

```cpp
#include <cuda_runtime.h>
#include <cuda_bf16.h>
#include <cuda_fp16.h>
#include <cuda.h>
#include <stdint.h>

typedef __nv_bfloat16 bf16;

namespace {

constexpr int L_ = 2048, D_ = 1024, F_ = 3584;
constexpr int NCTA = 130;
constexpr int NTHREADS = 512;
#define AUXW 12
constexpr int MAIN_W0 = 0, AUX_W0 = AUXW, PREP_W0 = 20 - AUXW;
#define T0 3000
#define GAP 660
#define GAP1 540
#define GAP2 540
#define GAP3 600
#define STAG GAP
#define CSLEEP 50
#define SLACK 300
#define DELAY_X 0
#define TSLEEP 40
#define RS 2
#define FJ0 12
#define FJ1 12
#define GWAIT B_G
#define PROMG 2
#define PROMD 1
#define PROMX 2
#define HDELAY 300
#define PSLEEP 40
constexpr int NGU_CTA = 112;

constexpr int OFF_RING = 0;
constexpr int OFF_SCR  = 6 * 8192;
constexpr int S_PL     = 2304;
constexpr int OFF_S    = 114688;
constexpr int U_PL     = 2240;
constexpr int U_CH     = 4416;
constexpr int OFF_U    = 151552;
constexpr int TAB_W    = 3200;
constexpr int T_PL     = 544;
constexpr int T_A      = 2192 - 26 * 8;
constexpr int T_B      = 2568 - 59 * 8;
constexpr int OFF_TAB  = 186880;
constexpr int OFF_XSEL = 212480;
constexpr int XS_ROW   = 2064;
constexpr int OFF_BAND = 228992;
constexpr int OFF_MISC = 229536;
constexpr int M_BARS   = OFF_MISC;
constexpr int M_DSK    = OFF_MISC + 2736;
constexpr int M_SINK   = OFF_MISC + 512;
constexpr int M_TAG    = OFF_MISC + 516;
constexpr int M_BMAP   = OFF_MISC + 528;
constexpr int M_DPIN   = OFF_MISC + 656;
constexpr int M_TOP    = OFF_MISC + 2704;
constexpr int SMEM_BYTES = OFF_MISC + 2768;
__host__ __device__ constexpr uint32_t y_off(uint32_t q) { return OFF_RING + (q & 1) * 8192 + (q >> 1) * 98304; }

constexpr int B_W = 0;
constexpr int B_E = 24;
constexpr int B_S = 36;
constexpr int B_Y = 40;
constexpr int B_DP = 44, B_U = 45, B_KG = 46, B_G = 47;
constexpr int B_F = 48;
constexpr int B_H = 60;
constexpr int B_X = 52, B_XE = 56;

struct BandTab { uint32_t w[11][12]; };
constexpr BandTab make_band() {
    BandTab b{};
    for (int cls = 0; cls < 11; cls++)
        for (int wd = 0; wd < 10; wd++) {
            const int tau = cls + 2 - 8 * ((wd < 4 ? wd : wd - 4) >> 1);
            const int lo = (wd < 4) ? ((wd & 1) ? -2 : 3) : ((wd & 1) ? -4 : -11), wid = (wd < 4 ? 3 : 7) + 2 * (wd & 1);
            b.w[cls][wd] = ((tau >= lo && tau < lo + wid) ? 0x3F80u : 0u) | ((tau - 4 >= lo && tau - 4 < lo + wid) ? 0x3F800000u : 0u);
        }
    return b;
}
constexpr int NTOP = 32;
struct Scratch {
    uint4 r[L_ / 4 * RS];
    uint4 g[L_ / 4];
    uint4 h[2][8 * F_ / 8];
    uint32_t top[NTOP][32];
    unsigned epoch;
};
__device__ __align__(128) Scratch g_scratch;
__device__ const __align__(16) BandTab g_band = make_band();

struct Params {
    const bf16 *u, *logA, *Aim, *Cre, *Cim, *logdt, *Dskip, *wr, *gatew;
    bf16* out;
    Scratch* sc;
    const uint4* band;
    uint32_t gu_swap;
    uint32_t zero;
};

#define WSTAMP(i) do {} while (0)
#define KSTAMP(i, dep) do {} while (0)
#define WDUMP() do {} while (0)
#define RSTAMP(i) do {} while (0)

#define NOALLOC ".L1::no_allocate"
__device__ __forceinline__ uint32_t smem_u32(const void* p) { return (uint32_t)__cvta_generic_to_shared(p); }
__device__ __forceinline__ void mbar_init(uint32_t b, uint32_t c) { asm volatile("mbarrier.init.shared::cta.b64 [%0], %1;" :: "r"(b), "r"(c) : "memory"); }
__device__ __forceinline__ void mbar_expect(uint32_t b, uint32_t tx) { asm volatile("mbarrier.arrive.expect_tx.shared::cta.b64 _, [%0], %1;" :: "r"(b), "r"(tx) : "memory"); }
__device__ __forceinline__ void mbar_arrive(uint32_t b) { asm volatile("mbarrier.arrive.shared::cta.b64 _, [%0];" :: "r"(b) : "memory"); }
__device__ __forceinline__ void mbar_wait(uint32_t b, uint32_t parity = 0) {
    asm volatile("{\n\t.reg .pred p;\nW%=:\n\tmbarrier.try_wait.parity.shared::cta.b64 p, [%0], %1, 20000;\n\t@!p bra W%=;\n\t}" :: "r"(b), "r"(parity) : "memory");
}
__device__ __forceinline__ uint32_t mapa(uint32_t addr, uint32_t rank) { uint32_t r; asm("mapa.shared::cluster.u32 %0, %1, %2;" : "=r"(r) : "r"(addr), "r"(rank)); return r; }
__device__ __forceinline__ void tma3d(uint32_t dst, const CUtensorMap* tm, int c0, int c1, uint32_t bar, uint32_t bytes) {
    asm volatile("{\n\t.reg .pred p;\n\telect.sync _|p, 0xffffffff;\n\t"
                 "@p mbarrier.arrive.expect_tx.shared::cta.b64 _, [%2], %5;\n\t"
                 "@p cp.async.bulk.tensor.3d.shared::cluster.global.mbarrier::complete_tx::bytes [%0], [%1, {%3, %4, 0}], [%2];\n\t}"
        :: "r"(dst), "l"(tm), "r"(bar), "r"(c0), "r"(c1), "r"(bytes) : "memory");
}
__device__ __forceinline__ void st_async16(uint32_t dst, const uint4& v, uint32_t bar) {
    asm volatile("st.async.weak.shared::cluster.mbarrier::complete_tx::bytes.v4.b32 [%0], {%1,%2,%3,%4}, [%5];"
                 :: "r"(dst), "r"(v.x), "r"(v.y), "r"(v.z), "r"(v.w), "r"(bar) : "memory");
}
__device__ __forceinline__ void bar_sync(int id, int n) { asm volatile("bar.sync %0, %1;" :: "r"(id), "r"(n) : "memory"); }
__device__ __forceinline__ void cp16(uint32_t dst, const void* src) { asm volatile("cp.async.cg.shared.global [%0], [%1], 16;" :: "r"(dst), "l"(src) : "memory"); }
__device__ __forceinline__ void cp_wait_all() { asm volatile("cp.async.wait_all;" ::: "memory"); }
__device__ __forceinline__ uint2 ldg64(const void* p) { uint2 v; asm volatile("ld.global.nc" NOALLOC ".v2.u32 {%0,%1}, [%2];" : "=r"(v.x), "=r"(v.y) : "l"(p)); return v; }
__device__ __forceinline__ uint4 ld_gpu128(const void* p) { uint4 v; asm volatile("ld.relaxed.gpu.global.v4.u32 {%0,%1,%2,%3}, [%4];" : "=r"(v.x), "=r"(v.y), "=r"(v.z), "=r"(v.w) : "l"(p) : "memory"); return v; }
__device__ __forceinline__ void st_gpu32(void* p, uint32_t v) { asm volatile("st.relaxed.gpu.global.u32 [%0], %1;" :: "l"(p), "r"(v) : "memory"); }

__device__ __forceinline__ void ldsm4(uint32_t a, uint32_t& r0, uint32_t& r1, uint32_t& r2, uint32_t& r3) {
    asm volatile("ldmatrix.sync.aligned.m8n8.x4.shared.b16 {%0,%1,%2,%3}, [%4];" : "=r"(r0), "=r"(r1), "=r"(r2), "=r"(r3) : "r"(a) : "memory");
}
__device__ __forceinline__ void ldsm4t(uint32_t a, uint32_t& r0, uint32_t& r1, uint32_t& r2, uint32_t& r3) {
    asm volatile("ldmatrix.sync.aligned.m8n8.x4.trans.shared.b16 {%0,%1,%2,%3}, [%4];" : "=r"(r0), "=r"(r1), "=r"(r2), "=r"(r3) : "r"(a) : "memory");
}
__device__ __forceinline__ uint32_t lds32(uint32_t a) { uint32_t v; asm volatile("ld.shared.u32 %0, [%1];" : "=r"(v) : "r"(a) : "memory"); return v; }
__device__ __forceinline__ uint2 lds64(uint32_t a) { uint2 v; asm volatile("ld.shared.v2.u32 {%0,%1}, [%2];" : "=r"(v.x), "=r"(v.y) : "r"(a) : "memory"); return v; }
__device__ __forceinline__ uint4 lds128(uint32_t a) { uint4 v; asm volatile("ld.shared.v4.u32 {%0,%1,%2,%3}, [%4];" : "=r"(v.x), "=r"(v.y), "=r"(v.z), "=r"(v.w) : "r"(a) : "memory"); return v; }
__device__ __forceinline__ void sts32(uint32_t a, uint32_t v) { asm volatile("st.shared.u32 [%0], %1;" :: "r"(a), "r"(v) : "memory"); }
__device__ __forceinline__ void sts16(uint32_t a, uint32_t v) { asm volatile("st.shared.u16 [%0], %1;" :: "r"(a), "h"((unsigned short)v) : "memory"); }
__device__ __forceinline__ void sts128(uint32_t a, uint32_t x, uint32_t y, uint32_t z, uint32_t w) { asm volatile("st.shared.v4.u32 [%0], {%1,%2,%3,%4};" :: "r"(a), "r"(x), "r"(y), "r"(z), "r"(w) : "memory"); }
__device__ __forceinline__ float ldsf(uint32_t a) { float v; asm volatile("ld.shared.f32 %0, [%1];" : "=f"(v) : "r"(a) : "memory"); return v; }

__device__ __forceinline__ void mma_bf(float (&d)[4], uint32_t a0, uint32_t a1, uint32_t a2, uint32_t a3, uint32_t b0, uint32_t b1) {
    asm volatile("mma.sync.aligned.m16n8k16.row.col.f32.bf16.bf16.f32 {%0,%1,%2,%3}, {%4,%5,%6,%7}, {%8,%9}, {%0,%1,%2,%3};"
        : "+f"(d[0]), "+f"(d[1]), "+f"(d[2]), "+f"(d[3]) : "r"(a0), "r"(a1), "r"(a2), "r"(a3), "r"(b0), "r"(b1));
}
__device__ __forceinline__ void mma_bf_z(float (&d)[4], uint32_t a0, uint32_t a1, uint32_t a2, uint32_t a3, uint32_t b0, uint32_t b1) {
    asm volatile("mma.sync.aligned.m16n8k16.row.col.f32.bf16.bf16.f32 {%0,%1,%2,%3}, {%4,%5,%6,%7}, {%8,%9}, {%10,%10,%10,%10};"
        : "=f"(d[0]), "=f"(d[1]), "=f"(d[2]), "=f"(d[3]) : "r"(a0), "r"(a1), "r"(a2), "r"(a3), "r"(b0), "r"(b1), "f"(0.f));
}
__device__ __forceinline__ void mma_bf_k8(float (&d)[4], uint32_t a0, uint32_t a1, uint32_t b0) {
    asm volatile("mma.sync.aligned.m16n8k8.row.col.f32.bf16.bf16.f32 {%0,%1,%2,%3}, {%4,%5}, {%6}, {%0,%1,%2,%3};"
        : "+f"(d[0]), "+f"(d[1]), "+f"(d[2]), "+f"(d[3]) : "r"(a0), "r"(a1), "r"(b0));
}
__device__ __forceinline__ void mma_h(float (&d)[4], uint32_t a0, uint32_t a1, uint32_t a2, uint32_t a3, uint32_t b0, uint32_t b1) {
    asm volatile("mma.sync.aligned.m16n8k16.row.col.f32.f16.f16.f32 {%0,%1,%2,%3}, {%4,%5,%6,%7}, {%8,%9}, {%0,%1,%2,%3};"
        : "+f"(d[0]), "+f"(d[1]), "+f"(d[2]), "+f"(d[3]) : "r"(a0), "r"(a1), "r"(a2), "r"(a3), "r"(b0), "r"(b1));
}
__device__ __forceinline__ uint32_t pack_bf(float lo, float hi) { uint32_t r; asm("cvt.rn.bf16x2.f32 %0, %1, %2;" : "=r"(r) : "f"(hi), "f"(lo)); return r; }
__device__ __forceinline__ uint32_t pack_h(float lo, float hi) { uint32_t r; asm("cvt.rn.f16x2.f32 %0, %1, %2;" : "=r"(r) : "f"(hi), "f"(lo)); return r; }
__device__ __forceinline__ float bf_lo(uint32_t v) { return __uint_as_float(v << 16); }
__device__ __forceinline__ float bf_hi(uint32_t v) { return __uint_as_float(v & 0xffff0000u); }
__device__ __forceinline__ float bf_round(float x) { return __uint_as_float(pack_bf(0.f, x) & 0xffff0000u); }
__device__ __forceinline__ uint32_t hmul2_bf(uint32_t a, uint32_t b) { uint32_t r; asm("mul.rn.bf16x2 %0, %1, %2;" : "=r"(r) : "r"(a), "r"(b)); return r; }
__device__ __forceinline__ float ex2f(float x) { float r; asm("ex2.approx.ftz.f32 %0, %1;" : "=f"(r) : "f"(x)); return r; }

__device__ __forceinline__ float exp_acc(float x) {
    const float t = x * 1.4426950216293335f;
    const float r = fmaf(x, 1.4426950216293335f, -t) + x * 1.9259629911266175e-8f;
    return ex2f(t) * fmaf(r, 0.6931471805599453f, 1.f);
}
__device__ __forceinline__ float sigmoid_f(float x) { return __fdividef(1.f, 1.f + ex2f(-x * 1.4426950408889634f)); }
__device__ __forceinline__ void cexp_pow(float lr, float li, float e, float& zr, float& zi) {
    const float mag = ex2f(lr * e * 1.4426950408889634f);
    const float th = li * e;
    const float k = (th * 0.15915494309189535f + 12582912.f) - 12582912.f;
    float r = fmaf(-k, 6.2831854820251465f, th);
    r = fmaf(-k, -1.7484555314695172e-7f, r);
    zr = mag * __cosf(r);
    zi = mag * __sinf(r);
}
__device__ __forceinline__ uint32_t hcmul(uint32_t a, uint32_t k, uint32_t kp) {
    const __half2 A = *reinterpret_cast<const __half2*>(&a);
    const __half2 r = __hfma2(__high2half2(A), *reinterpret_cast<const __half2*>(&kp), __hmul2(__low2half2(A), *reinterpret_cast<const __half2*>(&k)));
    return *reinterpret_cast<const uint32_t*>(&r);
}
#define CMUL(orr, oi, ar, ai, br, bi) do { float _r = (ar) * (br) - (ai) * (bi); float _i = (ar) * (bi) + (ai) * (br); orr = _r; oi = _i; } while (0)
#define CSQ(orr, oi, ar, ai) do { float _r = (ar) * (ar) - (ai) * (ai); float _i = 2.f * (ar) * (ai); orr = _r; oi = _i; } while (0)

__device__ __forceinline__ void mma_bf_k8z(float (&d)[4], uint32_t a0, uint32_t a1, uint32_t b0) {
    asm volatile("mma.sync.aligned.m16n8k8.row.col.f32.bf16.bf16.f32 {%0,%1,%2,%3}, {%4,%5}, {%6}, {%7,%7,%7,%7};"
        : "=f"(d[0]), "=f"(d[1]), "=f"(d[2]), "=f"(d[3]) : "r"(a0), "r"(a1), "r"(b0), "f"(0.f));
}
__device__ __forceinline__ void mma_hh_k8(uint32_t& d0, uint32_t& d1, uint32_t a0, uint32_t a1, uint32_t b0) {
    asm volatile("mma.sync.aligned.m16n8k8.row.col.f16.f16.f16.f16 {%0,%1}, {%2,%3}, {%4}, {%5,%5};"
        : "=r"(d0), "=r"(d1) : "r"(a0), "r"(a1), "r"(b0), "r"(0));
}
__device__ __forceinline__ void sched_fence(uint32_t zero, uint32_t id) {
    asm volatile("{\n\t.reg .pred p;\n\tsetp.eq.u32 p, %0, %1;\n\t@p exit;\n\t}" :: "r"(zero), "r"(id) : "memory");
}
__device__ __forceinline__ uint32_t pin(uint32_t x, int lane) { return __shfl_sync(0xffffffffu, x, lane); }
template <class T> __device__ __forceinline__ T* pin(T* x, int lane) { return (T*)__shfl_sync(0xffffffffu, (unsigned long long)x, lane); }
__device__ __forceinline__ void lds128_if(bool on, uint32_t a, uint32_t (&v)[4]) {
    asm volatile("{\n\t.reg .pred p;\n\tsetp.ne.u32 p, %5, 0;\n\t@p ld.shared.v4.u32 {%0,%1,%2,%3}, [%4];\n\t}"
        : "+r"(v[0]), "+r"(v[1]), "+r"(v[2]), "+r"(v[3]) : "r"(a), "r"((uint32_t)on) : "memory");
}
__device__ __forceinline__ uint32_t hfma2_bf(uint32_t a, uint32_t b, uint32_t c) { uint32_t r; asm("fma.rn.bf16x2 %0, %1, %2, %3;" : "=r"(r) : "r"(a), "r"(b), "r"(c)); return r; }
__device__ __forceinline__ uint32_t row_elem(uint32_t row) { return ((row >> 5) & 4) | ((row >> 2) & 2) | ((row >> 4) & 1); }
__device__ __forceinline__ uint32_t gate_pos(uint32_t row) { return ((row >> 9) << 8) | ((row & 7) << 5) | (row_elem(row) << 2) | ((row >> 5) & 3); }

__global__ void __cluster_dims__(2, 1, 1) __launch_bounds__(NTHREADS, 1)
fused_kernel(const Params p, const __grid_constant__ CUtensorMap tm_gu, const __grid_constant__ CUtensorMap tm_down,
             const __grid_constant__ CUtensorMap tm_x) {
    extern __shared__ __align__(1024) unsigned char smem[];
    const uint32_t sb = smem_u32(smem);
    int tid;
    asm volatile("mov.u32 %0, %%tid.x;" : "=r"(tid));
    const int pw = tid >> 5, lane = tid & 31;
    const int c = blockIdx.x, h = c & 1, pr = c >> 1;
    const uint32_t bars = sb + M_BARS;

    if (c >= 128) {
        if (c != 128) return;
        RSTAMP(5);
        const unsigned tag = (*(volatile unsigned*)&p.sc->epoch + 1) & 0xffffu;
        const uint32_t list = sb + 128;
#pragma unroll 1
        for (int pass = 0; pass < 2; pass++) {
            sts128(list + 16 * tid, 0, 0, 0, 0);
            if (tid == 0) sts32(sb + 64, 0);
            uint32_t key[4];
            bool ok = false;
#pragma unroll 1
            for (int it = 0; it < (1 << 22); it++) {
                const uint4 a = ld_gpu128(&p.sc->r[tid * RS]);
                key[0] = a.x; key[1] = a.y; key[2] = a.z; key[3] = a.w;
                ok = (((a.x ^ tag) | (a.y ^ tag) | (a.z ^ tag) | (a.w ^ tag)) & 0xffffu) == 0;
                if (ok || !pass) break;
            }
            WSTAMP(0);
            uint32_t m = 0;
#pragma unroll
            for (int i = 0; i < 4; i++) {
                key[i] = ((pass ? key[i] : (lane + i) << 16) & 0xffff0000u) | (uint32_t)(2047 - (4 * tid + i));
                m = max(m, key[i]);
            }
            const uint32_t wm = __reduce_max_sync(0xffffffffu, m);
            if (lane == 0) sts32(sb + pw * 4, wm);
            __syncthreads();
            uint32_t thr = 0xffffffffu;
#pragma unroll
            for (int i = 0; i < 4; i++) { const uint4 q = lds128(sb + 16 * i); thr = min(thr, min(max(q.x, q.y), max(q.z, q.w))); }
            if (thr != 1) WSTAMP(1);
            if (m >= thr) {
                uint32_t pos;
                asm volatile("atom.shared.add.u32 %0, [%1], %2;" : "=r"(pos) : "r"(sb + 64), "r"(4 * ((key[0] >= thr) + (key[1] >= thr) + (key[2] >= thr) + (key[3] >= thr))) : "memory");
#pragma unroll
                for (int i = 0; i < 4; i++) if (key[i] >= thr) { sts32(list + pos, key[i]); pos += 4; }
            }
            __syncthreads();
            const uint32_t nc4 = lds32(sb + 64);
            if (nc4 != 1) WSTAMP(2);
#pragma unroll 1
            for (uint32_t j = 4 * pw; j < nc4; j += 64) {
                const uint32_t mine = lds32(list + j);
                int rank = 0;
#pragma unroll 1
                for (uint32_t i = 0; i < nc4; i += 128) rank += __popc(__ballot_sync(0xffffffffu, lds32(list + i + 4 * lane) > mine));
                if (rank < 8 && lane == 0) sts32(sb + 96 + 4 * rank, mine);
            }
            __syncthreads();
            if (tid < 8 * NTOP) st_gpu32(&p.sc->top[tid >> 3][tid & 7], lds32(sb + 96 + 4 * (tid & 7)) | (((tag + pass - 1) & 31) << 11));
            WSTAMP(3);
            if (!pass) RSTAMP(4);
        }
        WDUMP();
        return;
    }

    WSTAMP(0);
    if (pw < 8) {
        uint2 v_la, v_ai, v_cr, v_ci;
        uint32_t ldt16;
        const int d = 8 * c + pw - MAIN_W0;
        const size_t po = (size_t)d * 128 + 4 * lane;
        v_la = ldg64(p.logA + po); v_ai = ldg64(p.Aim + po); v_cr = ldg64(p.Cre + po); v_ci = ldg64(p.Cim + po);
        asm volatile("ld.global.nc.u16 %0, [%1];" : "=r"(ldt16) : "l"(p.logdt + d));
        if (lane == 0) asm volatile("cp.async.ca.shared.global [%0], [%1], 4;" :: "r"(sb + M_DSK + 4 * (pw - MAIN_W0)), "l"(p.Dskip + (d & ~1)) : "memory");
        asm volatile("barrier.cluster.arrive.relaxed.aligned;" ::: "memory");
        const int warp = pw - MAIN_W0;
        asm volatile("setmaxnreg.inc.sync.aligned.u32 168;");
        const int g = lane >> 2, t = lane & 3;
        const int mi = lane >> 3, r = lane & 7;
        const uint32_t TB = sb + OFF_TAB + warp * TAB_W;
        const uint32_t UB = sb + OFF_U + warp * U_CH;
        if (mi < 2) sts128(UB + mi * U_PL + r * 16, 0, 0, 0, 0);
#pragma unroll
        for (int i = 0; i < 6; i++) sts128(TB + 16 * (lane + 32 * i), 0, 0, 0, 0);
        if (lane < 8) sts128(TB + 16 * (lane + 192), 0, 0, 0, 0);
        __syncwarp();

        uint32_t cfix;
        {
            KSTAMP(4, v_la.x ^ v_ai.x ^ v_cr.x ^ v_ci.x ^ ldt16);
            const float dt = bf_round(exp_acc(__uint_as_float(ldt16 << 16)));
            float lr[4], li[4], cr[4], ci[4];
            float inv;
            {
                const uint32_t la[2] = {v_la.x, v_la.y}, ai[2] = {v_ai.x, v_ai.y}, vr[2] = {v_cr.x, v_cr.y}, vi[2] = {v_ci.x, v_ci.y};
                const uint32_t m2 = __vmaxu2(__vmaxu2(vr[0] & 0x7fff7fffu, vr[1] & 0x7fff7fffu), __vmaxu2(vi[0] & 0x7fff7fffu, vi[1] & 0x7fff7fffu));
                const uint32_t mx = __reduce_max_sync(0xffffffffu, max(m2, m2 << 16));
                const uint32_t e = min(max(mx >> 23, 11u), 254u);
                const float sc = __uint_as_float((264u - e) << 23);
                inv = __uint_as_float((e - 10u) << 23) * (2.f * dt);
#pragma unroll
                for (int i = 0; i < 4; i++) {
                    const float a = (i & 1) ? bf_hi(la[i >> 1]) : bf_lo(la[i >> 1]);
                    const float b = (i & 1) ? bf_hi(ai[i >> 1]) : bf_lo(ai[i >> 1]);
                    lr[i] = -bf_round(exp_acc(a)) * dt;
                    li[i] = b * dt;
                    cr[i] = ((i & 1) ? bf_hi(vr[i >> 1]) : bf_lo(vr[i >> 1])) * sc;
                    ci[i] = ((i & 1) ? bf_hi(vi[i >> 1]) : bf_lo(vi[i >> 1])) * sc;
                }
            }
            const uint32_t SX = sb + OFF_SCR + warp * 8192;
            const uint32_t sw = SX + (lane << 4);
#define PUT(buf, row, v) sts128(((sw + (row) * 512) ^ ((row) << 4)) + (buf) * 4096, v[0], v[1], v[2], v[3])
#define EMIT(bufa, rowa, bufb, rowb, xr, xi, k, kp) do { uint32_t pk[4], pd[4]; \
                _Pragma("unroll") for (int i = 0; i < 4; i++) { pk[i] = pack_h(xr[i], xi[i]); pd[i] = hcmul(pk[i], k[i], kp[i]); } \
                PUT(bufa, rowa, pk); PUT(bufb, rowb, pd); } while (0)
#define CMUL4(orr, oi, ar, ai, br, bi) _Pragma("unroll") for (int i = 0; i < 4; i++) CMUL(orr[i], oi[i], ar[i], ai[i], br[i], bi[i])
#define CSQ4(orr, oi, ar, ai) _Pragma("unroll") for (int i = 0; i < 4; i++) CSQ(orr[i], oi[i], ar[i], ai[i])
            float z1r[4], z1i[4], z2r[4], z2i[4], z8r[4], z8i[4], z256r[4], z256i[4];
            uint32_t k128[4], k128p[4], k4[4], k4p[4];
#pragma unroll
            for (int i = 0; i < 4; i++) {
                float tr, ti;
                cexp_pow(lr[i], li[i], 1.f, z1r[i], z1i[i]);
                CSQ(z2r[i], z2i[i], z1r[i], z1i[i]);
                CSQ(tr, ti, z2r[i], z2i[i]);
                k4[i] = pack_h(tr, ti); k4p[i] = pack_h(-ti, tr);
                CSQ(z8r[i], z8i[i], tr, ti);
                cexp_pow(lr[i], li[i], 128.f, tr, ti);
                k128[i] = pack_h(tr, ti); k128p[i] = pack_h(-ti, tr);
                CSQ(z256r[i], z256i[i], tr, ti);
                sts32(TB + i * T_PL + 16 + 4 * lane, k128[i]);
                sts32(TB + i * T_PL + 160 + 4 * lane, k128p[i]);
            }
            KSTAMP(5, k128[3] ^ k4[3]);
            uint32_t Ya[16][4];
            {
                float w1r[4], w1i[4], ar[4], ai[4], br[4], bi[4];
                uint32_t k8[4], k8p[4];
                const uint32_t one[4] = {0x3C00u, 0x3C00u, 0x3C00u, 0x3C00u};
#pragma unroll
                for (int i = 0; i < 4; i++) {
                    k8[i] = pack_h(z8r[i], -z8i[i]); k8p[i] = pack_h(z8i[i], z8r[i]);
                    CSQ(w1r[i], w1i[i], z8r[i], z8i[i]); w1i[i] = -w1i[i];
                }
                PUT(0, 0, one); PUT(1, 0, k8);
                EMIT(0, 1, 1, 1, w1r, w1i, k8, k8p);
                CSQ4(ar, ai, w1r, w1i);            EMIT(0, 2, 1, 2, ar, ai, k8, k8p);
                CMUL4(br, bi, ar, ai, w1r, w1i);   EMIT(0, 3, 1, 3, br, bi, k8, k8p);
                CSQ4(ar, ai, ar, ai);              EMIT(0, 4, 1, 4, ar, ai, k8, k8p);
                CMUL4(ar, ai, ar, ai, w1r, w1i);   EMIT(0, 5, 1, 5, ar, ai, k8, k8p);
                CSQ4(br, bi, br, bi);              EMIT(0, 6, 1, 6, br, bi, k8, k8p);
                CMUL4(br, bi, br, bi, w1r, w1i);   EMIT(0, 7, 1, 7, br, bi, k8, k8p);
                __syncwarp();
                KSTAMP(6, 0);
                const uint32_t ab = SX + (mi & 1) * 4096 + r * 512, ax = ((mi >> 1) ^ r) << 4;
#pragma unroll
                for (int ks = 0; ks < 16; ks++) ldsm4(ab + (ks >> 2) * 128 + (ax ^ ((ks & 3) << 5)), Ya[ks][0], Ya[ks][1], Ya[ks][2], Ya[ks][3]);
                __syncwarp();
            }
            KSTAMP(7, Ya[15][0]);
            const uint32_t ld0 = SX + r * 512 + ((mi ^ r) << 4), ld1 = ld0 ^ 64;
            float R[5][4], xr[4], xi[4];
            {
                float yr[4], yi[4];
                EMIT(0, 0, 0, 1, cr, ci, k4, k4p);
                CMUL4(yr, yi, cr, ci, z1r, z1i);        EMIT(0, 2, 0, 3, yr, yi, k4, k4p);
                CMUL4(xr, xi, cr, ci, z256r, z256i);    EMIT(1, 0, 1, 1, xr, xi, k4, k4p);
                CMUL4(yr, yi, yr, yi, z1r, z1i);        EMIT(0, 4, 0, 5, yr, yi, k4, k4p);
                CMUL4(cr, ci, xr, xi, z2r, z2i);        EMIT(1, 2, 1, 3, cr, ci, k4, k4p);
                CMUL4(yr, yi, yr, yi, z1r, z1i);        EMIT(0, 6, 0, 7, yr, yi, k4, k4p);
                CMUL4(xr, xi, xr, xi, z256r, z256i);    EMIT(1, 4, 1, 5, xr, xi, k4, k4p);
                CMUL4(xr, xi, xr, xi, z256r, z256i);    EMIT(1, 6, 1, 7, xr, xi, k4, k4p);
            }
            __syncwarp();
            {
                KSTAMP(8, 0);
                uint32_t bd[2][4] = {{0, 0, 0, 0}, {0, 0, 0, 0}};
                const bool on = (g >> 1) == t;
#pragma unroll
                for (int i = 0; i < 4; i++) { R[i][0] = R[i][1] = R[i][2] = R[i][3] = 0.f; }
#pragma unroll
                for (int k2 = 0; k2 < 8; k2++) {
                    uint32_t x[4], y[4], a1[2][4];
                    lds128_if(on, TB + t * T_PL + 16 + (g & 1) * 144 + 16 * k2, bd[k2 & 1]);
                    ldsm4(((k2 & 1) ? ld1 : ld0) + (k2 >> 1) * 128, x[0], x[1], x[2], x[3]);
                    ldsm4(((k2 & 1) ? ld1 : ld0) + (k2 >> 1) * 128 + 4096, y[0], y[1], y[2], y[3]);
#pragma unroll
                    for (int u = 0; u < 2; u++) {
                        mma_hh_k8(a1[u][0], a1[u][1], Ya[2 * k2 + u][0], Ya[2 * k2 + u][1], bd[k2 & 1][2 * u]);
                        mma_hh_k8(a1[u][2], a1[u][3], Ya[2 * k2 + u][2], Ya[2 * k2 + u][3], bd[k2 & 1][2 * u + 1]);
                    }
#pragma unroll
                    for (int u = 0; u < 2; u++) {
                        const uint32_t(&a0)[4] = Ya[2 * k2 + u];
                        mma_h(R[0], a0[0], a0[1], a0[2], a0[3], x[2 * u], x[2 * u + 1]);
                        mma_h(R[2], a0[0], a0[1], a0[2], a0[3], y[2 * u], y[2 * u + 1]);
                        mma_h(R[1], a1[u][0], a1[u][1], a1[u][2], a1[u][3], x[2 * u], x[2 * u + 1]);
                        mma_h(R[3], a1[u][0], a1[u][1], a1[u][2], a1[u][3], y[2 * u], y[2 * u + 1]);
                    }
                }
            }
            __syncwarp();
            KSTAMP(9, __float_as_uint(R[3][0]));
            asm volatile("barrier.cluster.wait.acquire.aligned;" ::: "memory");
            CMUL4(xr, xi, xr, xi, z256r, z256i);
            float s1024 = (xr[0] + xr[1]) + (xr[2] + xr[3]);
            CMUL4(xr, xi, xr, xi, z8r, z8i);        EMIT(0, 0, 0, 1, xr, xi, k128, k128p);
            CMUL4(xr, xi, xr, xi, z256r, z256i);    EMIT(0, 2, 0, 3, xr, xi, k128, k128p);
            CMUL4(xr, xi, xr, xi, z256r, z256i);    EMIT(0, 4, 0, 5, xr, xi, k128, k128p);
            CMUL4(xr, xi, xr, xi, z256r, z256i);    EMIT(0, 6, 0, 7, xr, xi, k128, k128p);
            __syncwarp();
            {
                KSTAMP(10, 0);
                float a1[4] = {0.f, 0.f, 0.f, 0.f};
                R[4][0] = R[4][1] = R[4][2] = R[4][3] = 0.f;
#pragma unroll
                for (int k2 = 0; k2 < 8; k2++) {
                    uint32_t x[4];
                    ldsm4(((k2 & 1) ? ld1 : ld0) + (k2 >> 1) * 128, x[0], x[1], x[2], x[3]);
                    mma_h(R[4], Ya[2 * k2][0], Ya[2 * k2][1], Ya[2 * k2][2], Ya[2 * k2][3], x[0], x[1]);
                    mma_h(a1, Ya[2 * k2 + 1][0], Ya[2 * k2 + 1][1], Ya[2 * k2 + 1][2], Ya[2 * k2 + 1][3], x[2], x[3]);
                }
#pragma unroll
                for (int i = 0; i < 4; i++) R[4][i] += a1[i];
            }
            if (lane == 0) mbar_arrive(bars + 8 * B_KG + (__float_as_uint(R[4][0]) & p.zero));
            KSTAMP(11, __float_as_uint(R[4][0]));
#undef PUT
#undef EMIT
#pragma unroll
            for (int o = 16; o > 0; o >>= 1) s1024 += __shfl_xor_sync(0xffffffffu, s1024, o);
            uint32_t w[4][4], dsk = 0;
            if (lane == 0) { cp_wait_all(); asm volatile("ld.shared.u16 %0, [%1];" : "=r"(dsk) : "r"(sb + M_DSK + 4 * warp + 2 * (warp & 1)) : "memory"); }
#pragma unroll
            for (int a = 0; a < 4; a++) {
                const float v0 = (a == 0) ? fmaf(R[0][0], inv, __uint_as_float(dsk << 16)) : R[a][0] * inv;
                const float v1 = R[a][1] * inv, v2 = R[a][2] * inv, v3 = R[a][3] * inv;
                w[a][0] = pack_bf(v0, 0.f); w[a][1] = pack_bf(v1, v0); w[a][2] = pack_bf(v2, v1); w[a][3] = pack_bf(v3, v2);
            }
            const uint32_t wb = TB + 16 + 16 * g, w1 = wb + t * T_PL, w2 = wb + 256 + 2 * t * T_PL;
            const uint32_t w3 = (t == 0) ? wb + 256 + 3 * T_PL : TB + T_A + 8 * (16 * t + g);
            const uint32_t w3s = (t == 0) ? 128 : 64, w3o = (t == 0) ? 8 : 12;
            const uint32_t k512 = __shfl_sync(0xffffffffu, w[2][1], 2);
#pragma unroll
            for (int a = 0; a < 2; a++) {
                sts128(w1 + 128 * a, w[a][0], w[a][1], w[a][2], w[a][3]);
                const uint32_t(&q)[4] = w[2 + a];
                if (t < 2) sts128(w2 + 128 * a, q[0], q[1], q[2], q[3]);
                if (t == 0) { sts128(w2 + T_PL + 128 * a, q[0], q[1], q[2], q[3]); sts32(w3 + 128 * a + 4, q[2]); }
                if (t != 1 && (a == 1 || lane != 2)) sts32(w3 + w3s * a, q[1]);
                if (t != 1) sts32(w3 + w3s * a + w3o, q[3]);
            }
            if (lane < 4)
                sts128(w1 + 512, __byte_perm(k512, 0, t == 3 ? 0x3210 : 0x4432), __byte_perm(k512, 0, t < 2 ? 0x3210 : t == 2 ? 0x3244 : 0x1044),
                       __byte_perm(k512, 0, t < 2 ? 0x1044 : 0x4444), 0);
            __syncwarp();
#pragma unroll
            for (int a = 0; a < 2; a++) {
                sts16(w1 + 128 * a + 18, w[a][3]);
                const uint32_t(&q)[4] = w[2 + a];
                if (t < 2) sts16(w2 + 128 * a + 18, q[3]);
                if (t == 0) { sts16(w2 + T_PL + 128 * a + 18, q[3]); sts16(w3 + 128 * a + 14, q[3]); }
            }
            if (t == 0) sts16(w3 + 128 - 4, w[3][0]);
            if (lane == 2 || (t == 0 && g > 0)) sts16(lane == 2 ? TB + 16 + 3 * T_PL + 4 * 127 : w3 - 4, w[2][0]);
            {
                const uint32_t b0 = pack_bf(R[4][0] * inv, R[4][2] * inv), b1 = pack_bf(R[4][1] * inv, R[4][3] * inv);
                const uint32_t wq = TB + T_B + 8 * (65 + 16 * t + g);
                sts32(wq, b0); sts32(wq + 12, b0); sts32(wq + 64, b1); sts32(wq + 76, b1);
            }
            cfix = pack_bf(s1024 * inv, s1024 * inv);
            if (lane == 0) sts32(TB + T_A + 8 * 64, cfix);
            __syncwarp();
        }
        WSTAMP(1);

        mbar_wait(bars + 8 * B_U);
        WSTAMP(2);

        float D[16][4];
        {
            const int x5 = g - t + 5;
            const uint32_t tabD = TB + (x5 & 3) * T_PL + (x5 & 12) + 16;
            {
                const uint32_t a1 = lds32(tabD - 8), a0 = p.zero;
#pragma unroll
                for (int jq = 0; jq < 4; jq++) {
                    uint32_t b[4];
                    ldsm4(UB + (9 + lane) * 16 + jq * 512, b[0], b[1], b[2], b[3]);
#pragma unroll
                    for (int i = 0; i < 4; i++) mma_bf_k8z(D[4 * jq + i], a0, a1, b[i]);
                }
            }
            const uint32_t ua = UB + (mi & 1) * U_PL + (8 + 8 * (mi >> 1) + r) * 16;
#pragma unroll 1
            for (int k0 = 0; k0 < 8; k0++) {
                uint32_t Uf[16][2];
#pragma unroll
                for (int jp = 0; jp < 8; jp++) ldsm4(ua + jp * 256 - k0 * 16, Uf[2 * jp][0], Uf[2 * jp][1], Uf[2 * jp + 1][0], Uf[2 * jp + 1][1]);
#pragma unroll
                for (int k1 = 0; k1 < 4; k1++) {
                    const uint32_t ta = tabD + 16 * (8 * k1 + k0);
                    const uint32_t a0 = lds32(ta), a1 = lds32(ta + 8), a2 = lds32(ta - 8), a3 = a0 ^ p.zero;
#pragma unroll
                    for (int J = k1; J < 16; J++) mma_bf(D[J], a0, a1, a2, a3, Uf[J - k1][0], Uf[J - k1][1]);
                }
                if (k0 == 0) {
                    const uint32_t ta = tabD + 16 * 32;
                    const uint32_t a0 = lds32(ta), a1 = lds32(ta + 8), a2 = lds32(ta - 8), a3 = a0 ^ p.zero;
#pragma unroll
                    for (int J = 4; J < 16; J++) mma_bf(D[J], a0, a1, a2, a3, Uf[J - 4][0], Uf[J - 4][1]);
                    const uint32_t f0 = (cfix ^ 0x80008000u) & (g == t ? 0xffffu : g == t + 4 ? 0xffff0000u : 0u);
                    const uint32_t f1 = p.zero, f2 = p.zero + p.zero, f3 = f0 ^ p.zero;
#pragma unroll
                    for (int J = 8; J < 16; J++) mma_bf(D[J], f0, f1, f2, f3, Uf[J - 8][0], Uf[J - 8][1]);
                }
            }
        }
        WSTAMP(3);
        {
            const int ch = 8 * h + warp;
            const uint32_t yo = sb + ch * 512 + ((lane ^ (((ch >> 2) << 1) | (ch & 1))) << 4);
            const uint32_t yr = mapa(yo, h ^ 1), ybr = mapa(bars + 8 * B_Y, h ^ 1);
            const uint32_t yi = sb + (4 * (r >> 1) + 2 * (mi & 1) + (r & 1)) * 512 + (((4 * warp + (mi >> 1)) ^ r) << 4);
            const int rho = 128 * (g >> 2) + 8 * ((g >> 1) & 1) + 16 * (g & 1) + warp;
            const uint32_t xs = sb + OFF_S + ((rho + 5) & 3) * S_PL + ((rho + 5) >> 2) * 32 + (((t >> 1) ^ (((rho + 5) >> 4) & 1)) << 4) + ((t & 1) << 3);
            bf16* op = p.out + (size_t)(256 * h + rho) * D_ + 16 * pr + 4 * t;
            const uint32_t gs = sb + OFF_S + (warp >> 1) * S_PL + 2176 + (warp & 1) * 64 + g * 8;
            uint4 sel;
            auto ship = [&](const int Q) {
                uint4 y[2];
#pragma unroll
                for (int hh = 0; hh < 2; hh++) {
                    const int J = 4 * Q + 2 * hh;
                    y[hh] = make_uint4(pack_bf(D[J][0], D[J][1]), pack_bf(D[J][2], D[J][3]), pack_bf(D[J + 1][0], D[J + 1][1]), pack_bf(D[J + 1][2], D[J + 1][3]));
                }
                if (!(Q & 1)) mbar_wait(bars + 8 * (B_F + (Q >> 1)));
                asm volatile("{\n\t.reg .pred p;\n\tsetp.eq.u32 p, %11, 0;\n\t"
                             "@p st.async.weak.shared::cluster.mbarrier::complete_tx::bytes.v4.b32 [%9], {%4,%5,%6,%7}, [%10];\n\t"
                             "@!p st.async.weak.shared::cluster.mbarrier::complete_tx::bytes.v4.b32 [%9], {%0,%1,%2,%3}, [%10];\n\t"
                             "@p st.shared.v4.b32 [%8], {%0,%1,%2,%3};\n\t@!p st.shared.v4.b32 [%8], {%4,%5,%6,%7};\n\t}"
                             :: "r"(y[0].x), "r"(y[0].y), "r"(y[0].z), "r"(y[0].w), "r"(y[1].x), "r"(y[1].y), "r"(y[1].z), "r"(y[1].w),
                                "r"(yo + y_off(Q)), "r"(yr + y_off(Q)), "r"(ybr + 8 * Q), "r"(h) : "memory");
                __syncwarp();
                if (lane == 0) mbar_arrive(bars + 8 * (B_Y + Q));
            };
            auto finish = [&](const int Q) {
                if (Q < 3) { mbar_wait(bars + 8 * (B_Y + Q)); __syncwarp(); }
                uint2 xq[4];
#pragma unroll
                for (int i = 0; i < 4; i++) xq[i] = lds64(xs + Q * 4 * S_PL + i * 256);
                const uint2 gq = lds64(gs + Q * 4 * S_PL);
                uint32_t gg[4];
#pragma unroll
                for (int i = 0; i < 4; i++) {
                    gg[i] = __byte_perm(i < 2 ? gq.x : gq.y, 0, (i & 1) ? 0x3232 : 0x1010);
                    const uint32_t og = hfma2_bf(gg[i], 0xBF80BF80u, 0x3F803F80u);
                    xq[i].x = hmul2_bf(og, xq[i].x); xq[i].y = hmul2_bf(og, xq[i].y);
                }
                if (Q == 3) { mbar_wait(bars + 8 * (B_Y + Q)); __syncwarp(); }
                if (Q == 0) sel = lds128(sb + M_BMAP + warp * 16);
                const uint32_t sbits = (Q == 0 ? sel.x : Q == 1 ? sel.y : Q == 2 ? sel.z : sel.w) >> (4 * g);
#pragma unroll
                for (int x = 0; x < 2; x++) {
                    uint32_t y[4];
                    ldsm4t((yi ^ (x << 5)) + y_off(Q), y[0], y[1], y[2], y[3]);
#pragma unroll
                    for (int e = 0; e < 2; e++) {
                        const int i = 2 * x + e;
                        const uint2 o = make_uint2(hfma2_bf(gg[i], y[2 * e], xq[i].x), hfma2_bf(gg[i], y[2 * e + 1], xq[i].y));
                        if (!(sbits & (1u << i))) *(uint2*)(op + (size_t)(512 * Q + 32 * i) * D_) = o;
                    }
                }
            };
            ship(0);
            const uint4 bA = lds128(sb + OFF_BAND + (g - t + 3) * 48), bB = lds128(sb + OFF_BAND + (g - t + 3) * 48 + 16);
            const uint2 bC = lds64(sb + OFF_BAND + (g - t + 3) * 48 + 32);
            uint2 QA[5][2], QB[8];
            const uint32_t tq = TB + 8 * (1 + g - 2 * t);
#pragma unroll
            for (int dd = 0; dd < 5; dd++) { QA[dd][0] = lds64(tq + T_A + 64 * (dd + 4)); QA[dd][1] = lds64(tq + T_A + 64 * (dd + 4) - 8); }
#pragma unroll
            for (int dd = 0; dd < 8; dd++) QB[dd] = lds64(tq + T_B + 64 * (dd + 8));
            const uint32_t u1 = UB + (mi & 1) * U_PL + (7 + r + (mi >> 1)) * 16;
            const uint32_t u2 = UB + ((mi & 1) ^ 1) * U_PL + (7 + r + (mi & 1) + 8 * (mi >> 1)) * 16;
            uint32_t n[4];
#pragma unroll
            for (int j = 0; j < 12; j++) {
                if (j == FJ0) finish(0);
                if (j == FJ1) finish(1);
                uint32_t m[4];
                ldsm4(u1 + j * 128, m[0], m[1], m[2], m[3]);
                if (!(j & 1)) ldsm4(u2 + j * 128, n[0], n[1], n[2], n[3]);
                const uint32_t n0 = n[2 * (j & 1)], n1 = n[2 * (j & 1) + 1];
                float wa[4], wb[4], wc[4], g1[4], g2[4];
                mma_bf_z(wa, bA.x, bA.y, bA.z, bA.w, m[0], m[1]);
                mma_bf_z(wb, bA.x, bA.y, bA.z, bA.w, n0, n1);
                mma_bf_z(wc, bA.x, bA.y, bA.z, bA.w, m[2], m[3]);
                if (j < 8) {
                    mma_bf_z(g1, bB.x, bB.y, bB.z, bB.w, m[0], m[1]);
                    mma_bf_z(g2, bB.x, bB.y, bB.z, bB.w, n0, n1);
                    mma_bf_k8(g1, bC.x, bC.y, m[2]);
                    mma_bf_k8(g2, bC.x, bC.y, m[3]);
                }
#pragma unroll
                for (int e = 0; e < 2; e++) {
                    const uint32_t q0 = pack_bf(wa[e], wa[e + 2]), q1 = pack_bf(wb[e], wb[e + 2]), q2 = q1 ^ p.zero, q3 = pack_bf(wc[e], wc[e + 2]);
#pragma unroll
                    for (int dd = 0; dd < 5; dd++)
                        if (j + 4 + dd < 16) mma_bf(D[j + 4 + dd], q0, q1, q2, q3, QA[dd][e].x, QA[dd][e].y);
                }
                if (j < 8) {
                    const uint32_t q0 = pack_bf(g1[0], g1[2]), q1 = pack_bf(g2[0], g2[2]), q2 = pack_bf(g1[1], g1[3]), q3 = pack_bf(g2[1], g2[3]);
#pragma unroll
                    for (int dd = 7 - j; dd >= 0; dd--) mma_bf(D[j + 8 + dd], q0, q1, q2, q3, QB[dd].x, QB[dd].y);
                }
                if (j == FJ0 || j == FJ1) { sched_fence(p.zero, j); WSTAMP(j == FJ0 ? 5 : 7); }
                if ((j & 3) == 3) {
                    WSTAMP(4 + 2 * (j >> 2));
                    ship((j >> 2) + 1);
                }
            }
            if (FJ0 > 11) { finish(0); WSTAMP(5); }
            if (FJ1 > 11) { finish(1); WSTAMP(7); }
            finish(2);
            WSTAMP(9);
            finish(3);
        }
        WSTAMP(10);
        WDUMP();
    } else if ((pw & 12) == AUX_W0) {
        asm volatile("setmaxnreg.inc.sync.aligned.u32 136;");
        const int v = __reduce_max_sync(0xffffffffu, pw & 3);
        const int at = tid & 127;
        const int g = lane >> 2, t = lane & 3;
        unsigned epoch, tag;
        const bool gu = c < NGU_CTA;
        {
            uint4 xa[16];
            const uint32_t xb = sb + (v < 2 ? OFF_XSEL : OFF_RING + 2 * 8192) + v * 8192;
            const uint32_t gws = sb + (gu ? M_DPIN : OFF_RING + 2 * 8192);
            const uint32_t row = 16 * c + 4 * v + (g >> 1);
            if (lane == 0) {
                mbar_init(bars + 8 * (B_X + v), 1);
                mbar_init(bars + 8 * (B_XE + v), 1);
                asm volatile("fence.proxy.async.shared::cta;" ::: "memory");
                asm volatile("fence.mbarrier_init.release.cluster;" ::: "memory");
            }
            __syncwarp();
            epoch = *(volatile unsigned*)&p.sc->epoch;
            tag = (epoch + 1) & 0xffffu;
#pragma unroll
            for (int i = 0; i < 4; i++)
                asm volatile("cp.async.ca.shared.global [%0], [%1], 4;" :: "r"(sb + OFF_S + (4 * i + v) * S_PL + 2176 + (tid & 28) * 4 + (tid & 1) * 8 + (tid & 2) * 2),
                             "l"(p.wr + 256 * i + (tid & 127) * 2) : "memory");
            cp16(gws + (tid & 127) * 16, p.gatew + (tid & 127) * 8);
            if ((tid & 127) < 33) cp16(sb + OFF_BAND + (tid & 127) * 16, p.band + (tid & 127));
            asm volatile("barrier.cluster.arrive.relaxed.aligned;" ::: "memory");
            if (DELAY_X > 0) __nanosleep(DELAY_X);
            asm volatile("{\n\t.reg .pred p;\n\telect.sync _|p, 0xffffffff;\n\t"
                         "@p mbarrier.arrive.expect_tx.shared::cta.b64 _, [%2], 8192;\n\t"
                         "@p cp.async.bulk.shared::cluster.global.mbarrier::complete_tx::bytes [%0], [%1], 8192, [%2];\n\t}"
                :: "r"(xb), "l"(p.u + (size_t)(16 * c + 4 * v) * D_), "r"(bars + 8 * (B_X + v)) : "memory");
            if (gu) {
                st_gpu32((uint32_t*)&p.sc->h[(tag + 1) & 1][32 * c] + at, 0);
            }
            if (v == 0) sts32(sb + M_BMAP + lane * 4, 0);
            cp_wait_all();
            bar_sync(1, 128);
            uint2 w[16];
#pragma unroll
            for (int kb = 0; kb < 16; kb++) w[kb] = lds64(sb + OFF_S + 2176 + S_PL * kb + 32 * (g & 2) + 16 * t + 8 * (g & 1));
            mbar_wait(bars + 8 * (B_X + v));
            WSTAMP(10);
#pragma unroll
            for (int kb = 0; kb < 16; kb++) xa[kb] = lds128(xb + (g >> 1) * 2048 + 128 * kb + 16 * (lane & 7));
            float dr[4][4];
#pragma unroll
            for (int kb = 0; kb < 16; kb++) {
                if (kb < 4) mma_bf_z(dr[kb], xa[kb].x, xa[kb].y, xa[kb].z, xa[kb].w, w[kb].x, w[kb].y);
                else mma_bf(dr[kb & 3], xa[kb].x, xa[kb].y, xa[kb].z, xa[kb].w, w[kb].x, w[kb].y);
            }
            float rs = ((dr[0][0] + dr[0][3]) + (dr[1][0] + dr[1][3])) + ((dr[2][0] + dr[2][3]) + (dr[3][0] + dr[3][3]));
            if (lane == 0) mbar_arrive(bars + 8 * (B_XE + v) + (__float_as_uint(rs) & p.zero));
            rs += __shfl_xor_sync(0xffffffffu, rs, 5);
            const uint32_t rb = pack_bf(0.f, rs);
            if (!(lane & 7)) st_gpu32((uint32_t*)&p.sc->r[(row >> 2) * RS] + (row & 3), ((rb ^ (((int)rb >> 31) | 0x80000000u)) & 0xffff0000u) | tag);
            WSTAMP(1);
            asm volatile("barrier.cluster.wait.acquire.aligned;" ::: "memory");
            {
                const int r = lane & 7;
                const uint32_t src = sb + OFF_S + (4 * v + (lane >> 3)) * S_PL + (r >> 1) * 128 + (r & 1) * 32 + ((h ^ ((r >> 1) & 1)) << 4);
                const uint32_t dst = sb + OFF_U + g * U_CH + (8 + 32 * v + 16 * h + t) * 16;
                const uint32_t rdst = mapa(dst, h ^ 1), rbar = mapa(bars + 8 * B_U, h ^ 1);
                mbar_wait(bars + 8 * (B_S + v));
                uint4 a[8];
#pragma unroll
                for (int b = 0; b < 2; b++) {
#pragma unroll
                    for (int j = 0; j < 8; j++) ldsm4t((b ? src : src ^ 16) + (j >> 1) * 512 + (j & 1) * 64, a[j].x, a[j].y, a[j].z, a[j].w);
#pragma unroll
                    for (int j = 0; j < 8; j++) {
                        if (b) sts128(dst + (j >> 1) * 64 + (j & 1) * U_PL, a[j].x, a[j].y, a[j].z, a[j].w);
                        else st_async16(rdst + (j >> 1) * 64 + (j & 1) * U_PL, a[j], rbar);
                    }
                }
                if (h && v == 3) {
                    ldsm4t((src ^ 16) + 2048, a[0].x, a[0].y, a[0].z, a[0].w);
                    ldsm4t(src + 2048, a[1].x, a[1].y, a[1].z, a[1].w);
                    if (t == 0) { st_async16(rdst + 256, a[0], rbar); sts128(dst + 256, a[1].x, a[1].y, a[1].z, a[1].w); }
                }
                __syncwarp();
                if (lane == 0) mbar_arrive(bars + 8 * B_U);
            }
            const uint32_t one0 = 0x3F803F80u ^ p.zero, one1 = 0x3F803F80u + p.zero;
#pragma unroll
            for (int kb = 0; kb < 16; kb++) {
                const uint4 gw = lds128(gws + 128 * kb + 16 * (lane & 7));
                const uint32_t a0 = hmul2_bf(xa[kb].x, gw.x), a1 = hmul2_bf(xa[kb].y, gw.y), a2 = hmul2_bf(xa[kb].z, gw.z), a3 = hmul2_bf(xa[kb].w, gw.w);
                if (kb < 4) mma_bf_z(dr[kb], a0, a1, a2, a3, one0, one1);
                else mma_bf(dr[kb & 3], a0, a1, a2, a3, one0, one1);
            }
            float sg = ((dr[0][0] + dr[0][3]) + (dr[1][0] + dr[1][3])) + ((dr[2][0] + dr[2][3]) + (dr[3][0] + dr[3][3]));
            sg += __shfl_xor_sync(0xffffffffu, sg, 4);
            if (!(lane & 7)) st_gpu32((uint32_t*)p.sc->g + ((row & 256) << 2) + gate_pos(row), (pack_bf(sigmoid_f(bf_round(sg)), 0.f) & 0xffffu) | (tag << 16));
            WSTAMP(2);
        }
        if (at == 32) { sts32(sb + M_TAG, tag << 16); mbar_arrive(bars + 8 * B_F); }
        const bool lane0 = pin(lane, lane) == 0;
        const uint32_t own = pin(sb + OFF_XSEL + at * 16, lane);
        const uint4* pb = pin(&p.sc->h[tag & 1][32 * (56 * h + 14 * v + (lane < 14 ? lane : 0)) + 8 * (pr & 3)], lane);
        {
            float acc[8][4];
#pragma unroll
            for (int i = 0; i < 8; i++) { acc[i][0] = acc[i][1] = acc[i][2] = acc[i][3] = 0.f; }
            const int krow = ((lane >> 1) & 8) + (lane & 7);
            const uint32_t tile0 = pin(sb + OFF_RING + krow * 64 + ((((lane >> 3) & 1) ^ ((krow >> 1) & 3)) << 4), lane);
            const uint32_t xo = pin(sb + OFF_XSEL + (lane & 7) * XS_ROW + 512 * v + 2 * (lane & 24), lane);
            const uint32_t po = pin(sb + OFF_XSEL + t * XS_ROW + (g & 3) * 128 + v * 16 + (lane >> 4) * 8, lane);
            uint32_t* hdst = pin((uint32_t*)&p.sc->h[tag & 1][32 * c] + at, lane);
            auto signal = [&](const int k, const uint32_t dep) {
                if (lane < 2 && v < 2)
                    asm volatile("st.async.weak.shared::cluster.mbarrier::complete_tx::bytes.b32 [%0], %1, [%2];"
                                 :: "r"(mapa(sb + M_SINK, lane)), "r"(dep), "r"(mapa(bars + 8 * (B_F + k), lane)) : "memory");
            };
#pragma unroll 1
            for (int i = 0; i < 4; i++) {
                const int s = 4 * i + v;
                uint32_t a[16][4], b[2][4];
                if (gu) {
                    const uint32_t tile = tile0 + (s < 14 ? s : v) * 8192;
                    if (lane0 && i > 1) mbar_arrive(bars + 8 * (B_E + s - 4));
                    mbar_wait(bars + 8 * (B_W + s));
#pragma unroll
                    for (int q = 0; q < 16; q++) ldsm4t((tile ^ ((q & 1) << 5)) + ((q >> 1) & 1) * 4096 + (q >> 2) * 1024, a[q][0], a[q][1], a[q][2], a[q][3]);
                }
                if (i == 0) {
                    if (gu) {
                        uint32_t dep = p.zero;
#pragma unroll
                        for (int q = 0; q < 16; q += 2) dep &= a[q][0] & a[q + 1][0];
                        if (lane == 0) mbar_arrive(bars + 8 * (B_E + v) + dep);
                        signal(0, dep);
                    }
                    WSTAMP(11);
                    uint32_t top;
#pragma unroll 1
                    for (int it = 0; it < (1 << 22); it++) {
                        asm volatile("ld.relaxed.gpu.global.u32 %0, [%1];" : "=r"(top) : "l"(&p.sc->top[c % NTOP][g]) : "memory");
                        if (__all_sync(0xffffffffu, ((top ^ (tag << 11)) & 0xf800u) == 0)) break;
                        if (TSLEEP) __nanosleep(TSLEEP);
                    }
                    WSTAMP(3);
                    if (gu) {
                        const uint32_t k = 4 * h + v, row = __reduce_max_sync(0xffffffffu, lane == 4 * k ? ~top & 2047 : 0);
                        asm volatile("{\n\t.reg .pred p;\n\telect.sync _|p, 0xffffffff;\n\t"
                                     "@p cp.async.bulk.shared::cluster.global.mbarrier::complete_tx::bytes.multicast::cluster [%0], [%1], 2048, [%2], %3;\n\t}"
                            :: "r"(sb + OFF_XSEL + k * XS_ROW), "l"(p.u + (size_t)row * D_), "r"(bars + 8 * B_G), "h"((unsigned short)3) : "memory");
                    }
                    if (v == 0) {
                        const uint32_t row = ~top & 2047;
                        if (t == 0 && ((row >> 8) & 1) == h)
                            asm volatile("red.shared.or.b32 [%0], %1;" :: "r"(sb + M_BMAP + (row & 7) * 16 + (row >> 9) * 4), "r"(1u << (gate_pos(row) & 31)) : "memory");
                        if (t == 0) sts32(sb + M_TOP + lane, top);
                        __syncwarp();
                        if (lane0) mbar_arrive(bars + 8 * B_Y);
                    }
                    if (!gu) break;
                    mbar_wait(bars + 8 * B_G);
                    WSTAMP(4);
                }
                ldsm4(xo + 128 * i, b[0][0], b[0][1], b[0][2], b[0][3]);
                ldsm4(xo + 128 * i + 64, b[1][0], b[1][1], b[1][2], b[1][3]);
#pragma unroll
                for (int q = 0; q < 16; q++) mma_bf(acc[q & 7], a[q][0], a[q][1], a[q][2], a[q][3], b[q >> 3][(q >> 1) & 2], b[q >> 3][((q >> 1) & 2) + 1]);
            }
            if (gu) {
                WSTAMP(5);
                __syncwarp();
#pragma unroll
                for (int q = 0; q < 4; q++) {
                    const int ct = q >> 1, e = 2 * (q & 1);
                    sts128(own + q * XS_ROW,
                           __float_as_uint(acc[ct][e] + acc[4 + ct][e]), __float_as_uint(acc[2 + ct][e] + acc[6 + ct][e]),
                           __float_as_uint(acc[ct][e + 1] + acc[4 + ct][e + 1]), __float_as_uint(acc[2 + ct][e + 1] + acc[6 + ct][e + 1]));
                }
                bar_sync(1, 128);
                float hv[2];
#pragma unroll
                for (int e = 0; e < 2; e++) {
                    uint2 q[4];
#pragma unroll
                    for (int i = 0; i < 4; i++) q[i] = lds64(po + 64 * e + 512 * i);
                    const float s0 = (__uint_as_float(q[0].x) + __uint_as_float(q[1].x)) + (__uint_as_float(q[2].x) + __uint_as_float(q[3].x));
                    const float s1 = (__uint_as_float(q[0].y) + __uint_as_float(q[1].y)) + (__uint_as_float(q[2].y) + __uint_as_float(q[3].y));
                    const float gv = bf_round(p.gu_swap ? s1 : s0), uv = bf_round(p.gu_swap ? s0 : s1);
                    hv[e] = bf_round(gv * sigmoid_f(gv)) * uv;
                }
                const uint32_t hw = pack_bf(hv[0], hv[1]);
                st_gpu32(hdst, hw ? hw : 0x80000000u);
                signal(1, hw);
            }
        }
        WSTAMP(6);
        {
            uint4 hq[14];
            {
                bar_sync(1, 128);
                if (!gu) mbar_wait(bars + 8 * (B_H + 3));
                if (HDELAY) __nanosleep(HDELAY);
                const uint32_t hb = sb + (v < 2 ? OFF_XSEL + 7168 * v : OFF_RING + 8192 * v);
#pragma unroll 1
                for (int it = 0; it < (1 << 22); it++) {
                    uint32_t w;
                    asm volatile("ld.relaxed.gpu.global.u32 %0, [%1];" : "=r"(w) : "l"(pb) : "memory");
                    if (__all_sync(0xffffffffu, w != 0)) break;
                    __nanosleep(PSLEEP);
                }
                WSTAMP(12);
#pragma unroll 1
                for (int it = 0; it < (1 << 16); it++) {
                    asm volatile("{\n\t.reg .pred p;\n\telect.sync _|p, 0xffffffff;\n\t"
                                 "@p mbarrier.arrive.expect_tx.shared::cta.b64 _, [%2], 7168;\n\t"
                                 "@p cp.async.bulk.shared::cluster.global.mbarrier::complete_tx::bytes [%0], [%1], 7168, [%2];\n\t}"
                        :: "r"(hb), "l"(&p.sc->h[tag & 1][32 * (56 * h + 14 * v)]), "r"(bars + 8 * (B_X + v)) : "memory");
                    mbar_wait(bars + 8 * (B_X + v), ~it & 1);
                    uint32_t mn = 0xffffffffu;
#pragma unroll
                    for (int i = 0; i < 14; i++) hq[i] = lds128(hb + 512 * i + 16 * lane);
#pragma unroll
                    for (int i = 0; i < 14; i++) mn = min(mn, hq[i].x);
                    if (__all_sync(0xffffffffu, mn != 0)) break;
                }
            }
            WSTAMP(7);
            float dd[4][4];
            const int krow = ((lane >> 1) & 8) + (lane & 7);
            const uint32_t tile = sb + OFF_RING + (4 + v) * 8192 + krow * 32 + ((((lane >> 3) ^ (krow >> 2)) & 1) << 4);
#pragma unroll
            for (int s = 0; s < 2; s++) {
                mbar_wait(bars + 8 * (B_W + 16 + 4 * s + v));
#pragma unroll
                for (int j = 0; j < 14; j++) {
                    uint32_t a[4];
                    ldsm4t(tile + s * 32768 + j * 512, a[0], a[1], a[2], a[3]);
                    const uint4& hb = hq[7 * s + (j >> 1)];
                    if (s == 0 && j < 4) mma_bf_z(dd[j], a[0], a[1], a[2], a[3], (j & 1) ? hb.z : hb.x, (j & 1) ? hb.w : hb.y);
                    else mma_bf(dd[(j + 2 * s) & 3], a[0], a[1], a[2], a[3], (j & 1) ? hb.z : hb.x, (j & 1) ? hb.w : hb.y);
                }
            }
            WSTAMP(8);
            uint4 part;
            part.x = __float_as_uint((dd[0][0] + dd[1][0]) + (dd[2][0] + dd[3][0])); part.y = __float_as_uint((dd[0][1] + dd[1][1]) + (dd[2][1] + dd[3][1]));
            part.z = __float_as_uint((dd[0][2] + dd[1][2]) + (dd[2][2] + dd[3][2])); part.w = __float_as_uint((dd[0][3] + dd[1][3]) + (dd[2][3] + dd[3][3]));
            st_async16(mapa(own + (M_DPIN - OFF_XSEL), h ^ 1), part, mapa(bars + 8 * B_DP, h ^ 1));
            sts128(own + 14336, part.x, part.y, part.z, part.w);
            __syncwarp();
            if (lane0) mbar_arrive(bars + 8 * B_DP);
        }
        WSTAMP(9);
        WDUMP();
        if (at == 0 && c == 0) *(volatile unsigned*)&p.sc->epoch = epoch + 1;
    } else {
        asm volatile("setmaxnreg.dec.sync.aligned.u32 40;");
        const int v = __reduce_max_sync(0xffffffffu, pw - PREP_W0);
        const bool gu = c < NGU_CTA;
        const uint32_t t0 = clock();
        const uint32_t bu = bars + 8 * v;
        if (lane == 0) {
#pragma unroll
            for (int i = 0; i < 9; i++) mbar_init(bu + 32 * i, 1);
            mbar_init(bu + 8 * B_S, 4);
            mbar_init(bu + 8 * B_Y, v == 0 ? 11 : 9);
            mbar_init(bu + 8 * B_DP, (0x1855 >> (4 * v)) & 15);
            mbar_init(bu + 8 * B_F, v == 0 ? 2 : 1);
            mbar_init(bu + 8 * B_H, 1);
            asm volatile("fence.proxy.async.shared::cta;" ::: "memory");
            asm volatile("fence.mbarrier_init.release.cluster;" ::: "memory");
            mbar_expect(bu + 8 * B_Y, 4096);
            if (v != 2) mbar_expect(bu + 8 * B_DP, v == 0 ? 2048 : (h || v == 3) ? 16384 : 16384 + 128);
            mbar_expect(bu + 8 * B_F, c < NGU_CTA ? 16 : 0);
        }
        __syncwarp();
        asm volatile("barrier.cluster.arrive.relaxed.aligned;" ::: "memory");
#pragma unroll 1
        for (int j = 0; j < 4; j++)
            tma3d(sb + OFF_S + (4 * v + j) * S_PL, &tm_x, ((j + 3) & 3) * 1024 + 16 * pr, 128 * v + 64 * h - (j == 0 ? 2 : 1), bars + 8 * (B_S + v), 66 * 32);
        WSTAMP(9);
        if (v < 2 && lane == 0) asm volatile("prefetch.tensormap [%0];" :: "l"(v ? &tm_gu : &tm_down) : "memory");
        asm volatile("barrier.cluster.wait.acquire.aligned;" ::: "memory");
        if (v > 0) mbar_wait(bars + 8 * (B_H + v));
        {
            const int gap = v == 0 ? GAP : v == 1 ? GAP1 : v == 2 ? GAP2 : GAP3;
            uint32_t last = v ? clock() - SLACK : t0 + T0 - GAP + STAG * ((pr * 5) & 15) / 16;
#pragma unroll 1
            for (int s = 6 * v; s < 6 * v + 6; s++) {
                const int i = s >> 2, w = s & 3, slot = s < 14 ? s : s - 12;
                if (slot >= 4 || s >= 14) mbar_wait(bars + 8 * ((gu && s >= 14) ? B_E + slot : slot < 6 ? B_XE + slot - 2 : B_KG));
                uint32_t now;
#pragma unroll 1
                while ((int)((now = clock()) - last) < gap) __nanosleep(CSLEEP);
                last = max((int)(now - last) - SLACK, gap) + last;
                WSTAMP(3 + s - 6 * v);
                if (gu || s >= 16) tma3d(sb + OFF_RING + slot * 8192, i < 4 ? &tm_gu : &tm_down, i < 4 ? 32 * c : 16 * pr,
                      i < 4 ? 256 * w + 64 * i : 1792 * h + 448 * w + 224 * (i - 4), bars + 8 * (B_W + s), i < 4 ? 8192 : 7168);
            }
            if (lane == 0) mbar_arrive(bars + 8 * (B_H + ((v + 1) & 3)));
        }
        if (v == 0) {
            mbar_wait(bars + 8 * B_U);
            mbar_wait(bars + 8 * B_F);
            mbar_wait(bars + 8 * (gu ? GWAIT : B_H + 3));
            const uint32_t tag16 = lds32(sb + M_TAG);
#pragma unroll 1
            for (int k = 0; k < 2; k++) {
                uint4 q[4];
#pragma unroll 1
                for (int it = 0; it < (1 << 22); it++) {
                    uint32_t bad = 0;
#pragma unroll
                    for (int i = 0; i < 4; i++) q[i] = ld_gpu128(&p.sc->g[256 * h + 128 * k + 32 * i + lane]);
#pragma unroll
                    for (int i = 0; i < 4; i++) bad |= ((q[i].x ^ tag16) | (q[i].y ^ tag16)) | ((q[i].z ^ tag16) | (q[i].w ^ tag16));
                    if ((bad >> 16) == 0) break;
                    __nanosleep(200);
                }
#pragma unroll
                for (int i = 0; i < 4; i++)
                    asm volatile("st.shared.v2.u32 [%0], {%1, %2};" :: "r"(sb + OFF_S + (8 * k + 2 * i + (lane >> 4)) * S_PL + 2176 + (lane & 15) * 8),
                                 "r"(__byte_perm(q[i].x, q[i].y, 0x5410)), "r"(__byte_perm(q[i].z, q[i].w, 0x5410)) : "memory");
            }
            __syncwarp();
            if (lane == 0) mbar_arrive(bars + 8 * B_Y);
        }
        {
            mbar_wait(bars + 8 * B_Y);
            const uint32_t top = lds32(sb + M_TOP + 8 * v + 4 * (lane >> 4));
            const uint32_t row = ~top & 2047, ch = lane & 15, gp = gate_pos(row);
            const bool mine = ((row >> 8) & 1) == h;
            uint32_t gfin, x16, y16 = 0;
            asm volatile("ld.shared.u16 %0, [%1];" : "=r"(gfin) : "r"(sb + OFF_S + (gp >> 6) * S_PL + 2176 + (gp & 63) * 2) : "memory");
            const uint32_t s5 = (row & 255) + 5;
            asm volatile("ld.shared.u16 %0, [%1];" : "=r"(x16) : "r"(sb + OFF_S + (4 * (row >> 9) + (s5 & 3)) * S_PL + (s5 >> 2) * 32 + ((2 * ch) ^ (s5 & 16))) : "memory");
            const float rsel = __uint_as_float(pin(__float_as_uint(bf_round(sigmoid_f(__uint_as_float((top ^ (((int)~top >> 31) | 0x80000000u)) & 0xffff0000u)))), lane));
            const uint32_t po = pin(sb + (4 * (ch & 7) + v) * 16 + (ch >> 3) * 8 + (lane >> 4) * 4, lane);
            bf16* op = pin(p.out + (size_t)row * D_ + 16 * pr + ch, lane);
            if (mine) {
                mbar_wait(bars + 8 * (B_Y + (row >> 9)));
                asm volatile("ld.shared.u16 %0, [%1];" : "=r"(y16)
                             : "r"(sb + y_off(row >> 9) + ch * 512 + (((4 * (row & 7) + ((row >> 5) & 3)) ^ (((ch >> 2) << 1) | (ch & 1))) << 4) + 2 * row_elem(row)) : "memory");
            }
            mbar_wait(bars + 8 * B_DP);
            float q[8];
#pragma unroll
            for (int i = 0; i < 4; i++) { q[i] = ldsf(po + M_DPIN + 512 * i); q[4 + i] = ldsf(po + OFF_XSEL + 14336 + 512 * i); }
            const float tot = ((q[0] + q[1]) + (q[2] + q[3])) + ((q[4] + q[5]) + (q[6] + q[7]));
            const float b = bf_round(__uint_as_float(x16 << 16) + bf_round(bf_round(tot) * rsel));
            if (mine) *op = __float2bfloat16_rn(fmaf(bf_lo(gfin), __uint_as_float(y16 << 16), bf_round(bf_round(1.f - bf_lo(gfin)) * b)));
        }
        WSTAMP(10);
        WDUMP();
    }
}

typedef CUresult (*EncodeFn)(CUtensorMap*, CUtensorMapDataType, cuuint32_t, void*, const cuuint64_t*, const cuuint64_t*,
                             const cuuint32_t*, const cuuint32_t*, CUtensorMapInterleave, CUtensorMapSwizzle,
                             CUtensorMapL2promotion, CUtensorMapFloatOOBfill);

void make_map(EncodeFn f, CUtensorMap* m, const void* ptr, uint64_t cols, uint64_t rows, uint32_t bc, uint32_t br, CUtensorMapSwizzle sw, int prom,
              uint32_t planes = 1, uint64_t plane_stride = 0) {
    cuuint64_t dims[3] = {cols, rows, planes};
    cuuint64_t str[2] = {cols * 2, planes > 1 ? plane_stride : cols * rows * 2};
    cuuint32_t box[3] = {bc, br, planes};
    cuuint32_t es[3] = {1, 1, 1};
    f(m, CU_TENSOR_MAP_DATA_TYPE_BFLOAT16, 3, (void*)ptr, dims, str, box, es, CU_TENSOR_MAP_INTERLEAVE_NONE, sw,
      (CUtensorMapL2promotion)prom, CU_TENSOR_MAP_FLOAT_OOB_FILL_NONE);
}

}

extern "C" void kernel_launch(void* const* d_in, const int* in_sizes, int n_in, void* d_out, int out_size) {
    static EncodeFn enc = nullptr;
    static void *sc = nullptr, *band = nullptr;
    if (!enc) {
        void* fn = nullptr;
        cudaDriverEntryPointQueryResult qr;
        cudaGetDriverEntryPoint("cuTensorMapEncodeTiled", &fn, cudaEnableDefault, &qr);
        enc = (EncodeFn)fn;
        cudaGetSymbolAddress(&sc, g_scratch);
        cudaGetSymbolAddress(&band, g_band);
        cudaFuncSetAttribute(fused_kernel, cudaFuncAttributeMaxDynamicSharedMemorySize, SMEM_BYTES);
    }
    CUtensorMap tg, td, tx;
    const char *wg = (const char*)d_in[9], *wu = (const char*)d_in[10];
    const bool swap = wu < wg;
    make_map(enc, &tg, swap ? wu : wg, F_, D_, 32, 64, CU_TENSOR_MAP_SWIZZLE_64B, PROMG, 2, swap ? wg - wu : wu - wg);
    make_map(enc, &td, d_in[11], D_, F_, 16, 224, CU_TENSOR_MAP_SWIZZLE_32B, PROMD);
    make_map(enc, &tx, d_in[0], 4 * D_, L_ / 4, 16, 66, CU_TENSOR_MAP_SWIZZLE_32B, PROMX);
    Params p;
    p.u = (const bf16*)d_in[0]; p.logA = (const bf16*)d_in[1]; p.Aim = (const bf16*)d_in[2];
    p.Cre = (const bf16*)d_in[3]; p.Cim = (const bf16*)d_in[4]; p.logdt = (const bf16*)d_in[5];
    p.Dskip = (const bf16*)d_in[6]; p.wr = (const bf16*)d_in[8]; p.gatew = (const bf16*)d_in[12];
    p.out = (bf16*)d_out;
    p.sc = (Scratch*)sc; p.band = (const uint4*)band;
    p.gu_swap = swap;
    p.zero = 0;
    fused_kernel<<<NCTA, NTHREADS, SMEM_BYTES>>>(p, tg, td, tx);
}
```

```cpp
#include <cuda_runtime.h>
#include <cuda_bf16.h>
#include <cuda_fp16.h>
#include <cuda.h>
#include <stdint.h>

typedef __nv_bfloat16 bf16;

namespace {

constexpr int L_ = 2048, D_ = 1024, F_ = 3584;
constexpr int NCTA = 130;
constexpr int NTHREADS = 512;
#define AUXW 12
constexpr int MAIN_W0 = 0, AUX_W0 = AUXW, PREP_W0 = 20 - AUXW;
#define T0 3300
#define GAP 620
#define GAP1 540
#define GAP2 540
#define GAP3 600
#define STAG GAP
#define CSLEEP 50
#define SLACK 300
#define DELAY_S 0
#define DELAY_X 150
#define TSLEEP 40
#define RS 2
#define TMAQ 3
#define GWAIT B_G
#define PROMG 2
#define PROMD 1
#define PROMX 0
#define HDELAY 300
#define LATE2 0
#define PSLEEP 40
constexpr int NGU_CTA = 112;

constexpr int OFF_RING = 0;
constexpr int OFF_SCR  = 6 * 8192;
constexpr int S_PL     = 1056;
constexpr int S_Q      = 8 * S_PL;
constexpr int OFF_S    = 114688;
constexpr int OFF_GP   = OFF_S + 4 * S_Q;
constexpr int U_PL     = 2240;
constexpr int U_CH     = 4416;
constexpr int OFF_U    = 151552;
constexpr int TAB_W    = 3200;
constexpr int T_PL     = 544;
constexpr int T_A      = 2192 - 26 * 8;
constexpr int T_B      = 2568 - 59 * 8;
constexpr int OFF_TAB  = 186880;
constexpr int OFF_XSEL = 212480;
constexpr int XS_ROW   = 2064;
constexpr int OFF_BAND = 228992;
constexpr int OFF_MISC = 229536;
constexpr int M_BARS   = OFF_MISC;
constexpr int M_DSK    = OFF_MISC + 2736;
constexpr int M_SINK   = OFF_MISC + 512;
constexpr int M_TAG    = OFF_MISC + 516;
constexpr int M_BMAP   = OFF_MISC + 528;
constexpr int M_DPIN   = OFF_MISC + 656;
constexpr int M_TOP    = OFF_MISC + 2704;
constexpr int SMEM_BYTES = OFF_MISC + 2768;
__device__ __forceinline__ uint32_t s_addr(uint32_t o, uint32_t half) { return o + (((half ^ (o >> 7)) & 1) << 4); }
__host__ __device__ constexpr uint32_t y_off(uint32_t q) { return OFF_RING + (q & 1) * 8192 + (q >> 1) * 98304; }

constexpr int B_W = 0;
constexpr int B_E = 24;
constexpr int B_S = 36;
constexpr int B_Y = 40;
constexpr int B_DP = 44, B_U = 45, B_KG = 46, B_G = 47;
constexpr int B_F = 48;
constexpr int B_H = 60;
constexpr int B_X = 52, B_XE = 56;

struct BandTab { uint32_t w[11][12]; };
constexpr BandTab make_band() {
    BandTab b{};
    for (int cls = 0; cls < 11; cls++)
        for (int wd = 0; wd < 10; wd++) {
            const int tau = cls + 2 - 8 * ((wd < 4 ? wd : wd - 4) >> 1);
            const int lo = (wd < 4) ? ((wd & 1) ? -2 : 3) : ((wd & 1) ? -4 : -11), wid = (wd < 4 ? 3 : 7) + 2 * (wd & 1);
            b.w[cls][wd] = ((tau >= lo && tau < lo + wid) ? 0x3F80u : 0u) | ((tau - 4 >= lo && tau - 4 < lo + wid) ? 0x3F800000u : 0u);
        }
    return b;
}
constexpr int NTOP = 32;
struct Scratch {
    uint4 r[L_ / 4 * RS];
    uint4 g[L_ / 4];
    uint4 h[2][8 * F_ / 8];
    uint32_t top[NTOP][32];
    unsigned epoch;
};
__device__ __align__(128) Scratch g_scratch;
__device__ const __align__(16) BandTab g_band = make_band();

struct Params {
    const bf16 *u, *logA, *Aim, *Cre, *Cim, *logdt, *Dskip, *wr, *gatew;
    bf16* out;
    Scratch* sc;
    const uint4* band;
    uint32_t gu_swap;
    uint32_t zero;
};

#define WSTAMP(i) do {} while (0)
#define KSTAMP(i, dep) do {} while (0)
#define WDUMP() do {} while (0)
#define RSTAMP(i) do {} while (0)

#define NOALLOC ".L1::no_allocate"
__device__ __forceinline__ uint32_t smem_u32(const void* p) { return (uint32_t)__cvta_generic_to_shared(p); }
__device__ __forceinline__ void mbar_init(uint32_t b, uint32_t c) { asm volatile("mbarrier.init.shared::cta.b64 [%0], %1;" :: "r"(b), "r"(c) : "memory"); }
__device__ __forceinline__ void mbar_expect(uint32_t b, uint32_t tx) { asm volatile("mbarrier.arrive.expect_tx.shared::cta.b64 _, [%0], %1;" :: "r"(b), "r"(tx) : "memory"); }
__device__ __forceinline__ void mbar_arrive(uint32_t b) { asm volatile("mbarrier.arrive.shared::cta.b64 _, [%0];" :: "r"(b) : "memory"); }
__device__ __forceinline__ void mbar_wait(uint32_t b, uint32_t parity = 0) {
    asm volatile("{\n\t.reg .pred p;\nW%=:\n\tmbarrier.try_wait.parity.shared::cta.b64 p, [%0], %1, 20000;\n\t@!p bra W%=;\n\t}" :: "r"(b), "r"(parity) : "memory");
}
__device__ __forceinline__ uint32_t mapa(uint32_t addr, uint32_t rank) { uint32_t r; asm("mapa.shared::cluster.u32 %0, %1, %2;" : "=r"(r) : "r"(addr), "r"(rank)); return r; }
__device__ __forceinline__ void tma3d(uint32_t dst, const CUtensorMap* tm, int c0, int c1, uint32_t bar, uint32_t bytes) {
    asm volatile("{\n\t.reg .pred p;\n\telect.sync _|p, 0xffffffff;\n\t"
                 "@p mbarrier.arrive.expect_tx.shared::cta.b64 _, [%2], %5;\n\t"
                 "@p cp.async.bulk.tensor.3d.shared::cluster.global.mbarrier::complete_tx::bytes [%0], [%1, {%3, %4, 0}], [%2];\n\t}"
        :: "r"(dst), "l"(tm), "r"(bar), "r"(c0), "r"(c1), "r"(bytes) : "memory");
}
__device__ __forceinline__ void bulk_load(uint32_t dst, const void* src, uint32_t bytes, uint32_t bar) {
    asm volatile("{\n\t.reg .pred p;\n\telect.sync _|p, 0xffffffff;\n\t"
                 "@p mbarrier.arrive.expect_tx.shared::cta.b64 _, [%2], %3;\n\t"
                 "@p cp.async.bulk.shared::cluster.global.mbarrier::complete_tx::bytes [%0], [%1], %3, [%2];\n\t}"
        :: "r"(dst), "l"(src), "r"(bar), "r"(bytes) : "memory");
}
__device__ __forceinline__ void st_async16(uint32_t dst, const uint4& v, uint32_t bar) {
    asm volatile("st.async.weak.shared::cluster.mbarrier::complete_tx::bytes.v4.b32 [%0], {%1,%2,%3,%4}, [%5];"
                 :: "r"(dst), "r"(v.x), "r"(v.y), "r"(v.z), "r"(v.w), "r"(bar) : "memory");
}
__device__ __forceinline__ void bar_sync(int id, int n) { asm volatile("bar.sync %0, %1;" :: "r"(id), "r"(n) : "memory"); }
__device__ __forceinline__ void cp16(uint32_t dst, const void* src) { asm volatile("cp.async.cg.shared.global [%0], [%1], 16;" :: "r"(dst), "l"(src) : "memory"); }
__device__ __forceinline__ void cp_wait_all() { asm volatile("cp.async.wait_all;" ::: "memory"); }
__device__ __forceinline__ uint2 ldg64(const void* p) { uint2 v; asm volatile("ld.global.nc" NOALLOC ".v2.u32 {%0,%1}, [%2];" : "=r"(v.x), "=r"(v.y) : "l"(p)); return v; }
__device__ __forceinline__ uint4 ld_gpu128(const void* p) { uint4 v; asm volatile("ld.relaxed.gpu.global.v4.u32 {%0,%1,%2,%3}, [%4];" : "=r"(v.x), "=r"(v.y), "=r"(v.z), "=r"(v.w) : "l"(p) : "memory"); return v; }
__device__ __forceinline__ void st_gpu32(void* p, uint32_t v) { asm volatile("st.relaxed.gpu.global.u32 [%0], %1;" :: "l"(p), "r"(v) : "memory"); }

__device__ __forceinline__ void ldsm4(uint32_t a, uint32_t& r0, uint32_t& r1, uint32_t& r2, uint32_t& r3) {
    asm volatile("ldmatrix.sync.aligned.m8n8.x4.shared.b16 {%0,%1,%2,%3}, [%4];" : "=r"(r0), "=r"(r1), "=r"(r2), "=r"(r3) : "r"(a) : "memory");
}
__device__ __forceinline__ void ldsm4t(uint32_t a, uint32_t& r0, uint32_t& r1, uint32_t& r2, uint32_t& r3) {
    asm volatile("ldmatrix.sync.aligned.m8n8.x4.trans.shared.b16 {%0,%1,%2,%3}, [%4];" : "=r"(r0), "=r"(r1), "=r"(r2), "=r"(r3) : "r"(a) : "memory");
}
__device__ __forceinline__ uint32_t lds32(uint32_t a) { uint32_t v; asm volatile("ld.shared.u32 %0, [%1];" : "=r"(v) : "r"(a) : "memory"); return v; }
__device__ __forceinline__ uint2 lds64(uint32_t a) { uint2 v; asm volatile("ld.shared.v2.u32 {%0,%1}, [%2];" : "=r"(v.x), "=r"(v.y) : "r"(a) : "memory"); return v; }
__device__ __forceinline__ uint4 lds128(uint32_t a) { uint4 v; asm volatile("ld.shared.v4.u32 {%0,%1,%2,%3}, [%4];" : "=r"(v.x), "=r"(v.y), "=r"(v.z), "=r"(v.w) : "r"(a) : "memory"); return v; }
__device__ __forceinline__ void sts32(uint32_t a, uint32_t v) { asm volatile("st.shared.u32 [%0], %1;" :: "r"(a), "r"(v) : "memory"); }
__device__ __forceinline__ void sts16(uint32_t a, uint32_t v) { asm volatile("st.shared.u16 [%0], %1;" :: "r"(a), "h"((unsigned short)v) : "memory"); }
__device__ __forceinline__ void sts128(uint32_t a, uint32_t x, uint32_t y, uint32_t z, uint32_t w) { asm volatile("st.shared.v4.u32 [%0], {%1,%2,%3,%4};" :: "r"(a), "r"(x), "r"(y), "r"(z), "r"(w) : "memory"); }
__device__ __forceinline__ float ldsf(uint32_t a) { float v; asm volatile("ld.shared.f32 %0, [%1];" : "=f"(v) : "r"(a) : "memory"); return v; }

__device__ __forceinline__ void mma_bf(float (&d)[4], uint32_t a0, uint32_t a1, uint32_t a2, uint32_t a3, uint32_t b0, uint32_t b1) {
    asm volatile("mma.sync.aligned.m16n8k16.row.col.f32.bf16.bf16.f32 {%0,%1,%2,%3}, {%4,%5,%6,%7}, {%8,%9}, {%0,%1,%2,%3};"
        : "+f"(d[0]), "+f"(d[1]), "+f"(d[2]), "+f"(d[3]) : "r"(a0), "r"(a1), "r"(a2), "r"(a3), "r"(b0), "r"(b1));
}
__device__ __forceinline__ void mma_bf_z(float (&d)[4], uint32_t a0, uint32_t a1, uint32_t a2, uint32_t a3, uint32_t b0, uint32_t b1) {
    asm volatile("mma.sync.aligned.m16n8k16.row.col.f32.bf16.bf16.f32 {%0,%1,%2,%3}, {%4,%5,%6,%7}, {%8,%9}, {%10,%10,%10,%10};"
        : "=f"(d[0]), "=f"(d[1]), "=f"(d[2]), "=f"(d[3]) : "r"(a0), "r"(a1), "r"(a2), "r"(a3), "r"(b0), "r"(b1), "f"(0.f));
}
__device__ __forceinline__ void mma_bf_k8(float (&d)[4], uint32_t a0, uint32_t a1, uint32_t b0) {
    asm volatile("mma.sync.aligned.m16n8k8.row.col.f32.bf16.bf16.f32 {%0,%1,%2,%3}, {%4,%5}, {%6}, {%0,%1,%2,%3};"
        : "+f"(d[0]), "+f"(d[1]), "+f"(d[2]), "+f"(d[3]) : "r"(a0), "r"(a1), "r"(b0));
}
__device__ __forceinline__ void mma_h(float (&d)[4], uint32_t a0, uint32_t a1, uint32_t a2, uint32_t a3, uint32_t b0, uint32_t b1) {
    asm volatile("mma.sync.aligned.m16n8k16.row.col.f32.f16.f16.f32 {%0,%1,%2,%3}, {%4,%5,%6,%7}, {%8,%9}, {%0,%1,%2,%3};"
        : "+f"(d[0]), "+f"(d[1]), "+f"(d[2]), "+f"(d[3]) : "r"(a0), "r"(a1), "r"(a2), "r"(a3), "r"(b0), "r"(b1));
}
__device__ __forceinline__ uint32_t pack_bf(float lo, float hi) { uint32_t r; asm("cvt.rn.bf16x2.f32 %0, %1, %2;" : "=r"(r) : "f"(hi), "f"(lo)); return r; }
__device__ __forceinline__ uint32_t pack_h(float lo, float hi) { uint32_t r; asm("cvt.rn.f16x2.f32 %0, %1, %2;" : "=r"(r) : "f"(hi), "f"(lo)); return r; }
__device__ __forceinline__ float bf_lo(uint32_t v) { return __uint_as_float(v << 16); }
__device__ __forceinline__ float bf_hi(uint32_t v) { return __uint_as_float(v & 0xffff0000u); }
__device__ __forceinline__ float bf_round(float x) { return __uint_as_float(pack_bf(0.f, x) & 0xffff0000u); }
__device__ __forceinline__ uint32_t hmul2_bf(uint32_t a, uint32_t b) { uint32_t r; asm("mul.rn.bf16x2 %0, %1, %2;" : "=r"(r) : "r"(a), "r"(b)); return r; }
__device__ __forceinline__ float ex2f(float x) { float r; asm("ex2.approx.ftz.f32 %0, %1;" : "=f"(r) : "f"(x)); return r; }

__device__ __forceinline__ float exp_acc(float x) {
    const float t = x * 1.4426950216293335f;
    const float r = fmaf(x, 1.4426950216293335f, -t) + x * 1.9259629911266175e-8f;
    return ex2f(t) * fmaf(r, 0.6931471805599453f, 1.f);
}
__device__ __forceinline__ float sigmoid_f(float x) { return __fdividef(1.f, 1.f + ex2f(-x * 1.4426950408889634f)); }
__device__ __forceinline__ void cexp_pow(float lr, float li, float e, float& zr, float& zi) {
    const float mag = ex2f(lr * e * 1.4426950408889634f);
    const float th = li * e;
    const float k = (th * 0.15915494309189535f + 12582912.f) - 12582912.f;
    float r = fmaf(-k, 6.2831854820251465f, th);
    r = fmaf(-k, -1.7484555314695172e-7f, r);
    zr = mag * __cosf(r);
    zi = mag * __sinf(r);
}
__device__ __forceinline__ uint32_t hcmul(uint32_t a, uint32_t k, uint32_t kp) {
    const __half2 A = *reinterpret_cast<const __half2*>(&a);
    const __half2 r = __hfma2(__high2half2(A), *reinterpret_cast<const __half2*>(&kp), __hmul2(__low2half2(A), *reinterpret_cast<const __half2*>(&k)));
    return *reinterpret_cast<const uint32_t*>(&r);
}
#define CMUL(orr, oi, ar, ai, br, bi) do { float _r = (ar) * (br) - (ai) * (bi); float _i = (ar) * (bi) + (ai) * (br); orr = _r; oi = _i; } while (0)
#define CSQ(orr, oi, ar, ai) do { float _r = (ar) * (ar) - (ai) * (ai); float _i = 2.f * (ar) * (ai); orr = _r; oi = _i; } while (0)

__device__ __forceinline__ void mma_bf_k8z(float (&d)[4], uint32_t a0, uint32_t a1, uint32_t b0) {
    asm volatile("mma.sync.aligned.m16n8k8.row.col.f32.bf16.bf16.f32 {%0,%1,%2,%3}, {%4,%5}, {%6}, {%7,%7,%7,%7};"
        : "=f"(d[0]), "=f"(d[1]), "=f"(d[2]), "=f"(d[3]) : "r"(a0), "r"(a1), "r"(b0), "f"(0.f));
}
__device__ __forceinline__ void mma_hh_k8(uint32_t& d0, uint32_t& d1, uint32_t a0, uint32_t a1, uint32_t b0) {
    asm volatile("mma.sync.aligned.m16n8k8.row.col.f16.f16.f16.f16 {%0,%1}, {%2,%3}, {%4}, {%5,%5};"
        : "=r"(d0), "=r"(d1) : "r"(a0), "r"(a1), "r"(b0), "r"(0));
}
__device__ __forceinline__ uint32_t pin(uint32_t x, int lane) { return __shfl_sync(0xffffffffu, x, lane); }
template <class T> __device__ __forceinline__ T* pin(T* x, int lane) { return (T*)__shfl_sync(0xffffffffu, (unsigned long long)x, lane); }
__device__ __forceinline__ void lds128_if(bool on, uint32_t a, uint32_t (&v)[4]) {
    asm volatile("{\n\t.reg .pred p;\n\tsetp.ne.u32 p, %5, 0;\n\t@p ld.shared.v4.u32 {%0,%1,%2,%3}, [%4];\n\t}"
        : "+r"(v[0]), "+r"(v[1]), "+r"(v[2]), "+r"(v[3]) : "r"(a), "r"((uint32_t)on) : "memory");
}
__device__ __forceinline__ uint32_t hfma2_bf(uint32_t a, uint32_t b, uint32_t c) { uint32_t r; asm("fma.rn.bf16x2 %0, %1, %2, %3;" : "=r"(r) : "r"(a), "r"(b), "r"(c)); return r; }
__device__ __forceinline__ uint32_t row_elem(uint32_t row) { return ((row >> 5) & 4) | ((row >> 2) & 2) | ((row >> 4) & 1); }
__device__ __forceinline__ uint32_t gate_pos(uint32_t row) { return ((row >> 9) << 8) | ((row & 7) << 5) | (row_elem(row) << 2) | ((row >> 5) & 3); }

__global__ void __cluster_dims__(2, 1, 1) __launch_bounds__(NTHREADS, 1)
fused_kernel(const Params p, const __grid_constant__ CUtensorMap tm_gu, const __grid_constant__ CUtensorMap tm_down,
             const __grid_constant__ CUtensorMap tm_x, const __grid_constant__ CUtensorMap tm_out) {
    extern __shared__ __align__(1024) unsigned char smem[];
    const uint32_t sb = smem_u32(smem);
    int tid;
    asm volatile("mov.u32 %0, %%tid.x;" : "=r"(tid));
    const int pw = tid >> 5, lane = tid & 31;
    const int c = blockIdx.x, h = c & 1, pr = c >> 1;
    const uint32_t bars = sb + M_BARS;

    if (c >= 128) {
        if (c != 128) return;
        RSTAMP(5);
        const unsigned tag = (*(volatile unsigned*)&p.sc->epoch + 1) & 0xffffu;
        const uint32_t list = sb + 128;
#pragma unroll 1
        for (int pass = 0; pass < 2; pass++) {
            sts128(list + 16 * tid, 0, 0, 0, 0);
            if (tid == 0) sts32(sb + 64, 0);
            uint32_t key[4];
            bool ok = false;
#pragma unroll 1
            for (int it = 0; it < (1 << 22); it++) {
                const uint4 a = ld_gpu128(&p.sc->r[tid * RS]);
                key[0] = a.x; key[1] = a.y; key[2] = a.z; key[3] = a.w;
                ok = (((a.x ^ tag) | (a.y ^ tag) | (a.z ^ tag) | (a.w ^ tag)) & 0xffffu) == 0;
                if (ok || !pass) break;
            }
            WSTAMP(0);
            uint32_t m = 0;
#pragma unroll
            for (int i = 0; i < 4; i++) {
                key[i] = ((pass ? key[i] : (lane + i) << 16) & 0xffff0000u) | (uint32_t)(2047 - (4 * tid + i));
                m = max(m, key[i]);
            }
            const uint32_t wm = __reduce_max_sync(0xffffffffu, m);
            if (lane == 0) sts32(sb + pw * 4, wm);
            __syncthreads();
            uint32_t thr = 0xffffffffu;
#pragma unroll
            for (int i = 0; i < 4; i++) { const uint4 q = lds128(sb + 16 * i); thr = min(thr, min(max(q.x, q.y), max(q.z, q.w))); }
            if (thr != 1) WSTAMP(1);
            if (m >= thr) {
                uint32_t pos;
                asm volatile("atom.shared.add.u32 %0, [%1], %2;" : "=r"(pos) : "r"(sb + 64), "r"(4 * ((key[0] >= thr) + (key[1] >= thr) + (key[2] >= thr) + (key[3] >= thr))) : "memory");
#pragma unroll
                for (int i = 0; i < 4; i++) if (key[i] >= thr) { sts32(list + pos, key[i]); pos += 4; }
            }
            __syncthreads();
            const uint32_t nc4 = lds32(sb + 64);
            if (nc4 != 1) WSTAMP(2);
#pragma unroll 1
            for (uint32_t j = 4 * pw; j < nc4; j += 64) {
                const uint32_t mine = lds32(list + j);
                int rank = 0;
#pragma unroll 1
                for (uint32_t i = 0; i < nc4; i += 128) rank += __popc(__ballot_sync(0xffffffffu, lds32(list + i + 4 * lane) > mine));
                if (rank < 8 && lane == 0) sts32(sb + 96 + 4 * rank, mine);
            }
            __syncthreads();
            if (tid < 8 * NTOP) st_gpu32(&p.sc->top[tid >> 3][tid & 7], lds32(sb + 96 + 4 * (tid & 7)) | (((tag + pass - 1) & 31) << 11));
            WSTAMP(3);
            if (!pass) RSTAMP(4);
        }
        WDUMP();
        return;
    }

    WSTAMP(0);
    if (pw < 8) {
        uint2 v_la, v_ai, v_cr, v_ci;
        uint32_t ldt16;
        const int d = 8 * c + pw - MAIN_W0;
        const size_t po = (size_t)d * 128 + 4 * lane;
        v_la = ldg64(p.logA + po); v_ai = ldg64(p.Aim + po); v_cr = ldg64(p.Cre + po); v_ci = ldg64(p.Cim + po);
        asm volatile("ld.global.nc.u16 %0, [%1];" : "=r"(ldt16) : "l"(p.logdt + d));
        if (lane == 0) asm volatile("cp.async.ca.shared.global [%0], [%1], 4;" :: "r"(sb + M_DSK + 4 * (pw - MAIN_W0)), "l"(p.Dskip + (d & ~1)) : "memory");
        asm volatile("barrier.cluster.arrive.relaxed.aligned;" ::: "memory");
        const int warp = pw - MAIN_W0;
        asm volatile("setmaxnreg.inc.sync.aligned.u32 168;");
        const int g = lane >> 2, t = lane & 3;
        const int mi = lane >> 3, r = lane & 7;
        const uint32_t TB = sb + OFF_TAB + warp * TAB_W;
        const uint32_t UB = sb + OFF_U + warp * U_CH;
        if (mi < 2) sts128(UB + mi * U_PL + r * 16, 0, 0, 0, 0);
#pragma unroll
        for (int i = 0; i < 6; i++) sts128(TB + 16 * (lane + 32 * i), 0, 0, 0, 0);
        if (lane < 8) sts128(TB + 16 * (lane + 192), 0, 0, 0, 0);
        __syncwarp();

        uint32_t cfix;
        {
            KSTAMP(4, v_la.x ^ v_ai.x ^ v_cr.x ^ v_ci.x ^ ldt16);
            const float dt = bf_round(exp_acc(__uint_as_float(ldt16 << 16)));
            float lr[4], li[4], cr[4], ci[4];
            float inv;
            {
                const uint32_t la[2] = {v_la.x, v_la.y}, ai[2] = {v_ai.x, v_ai.y}, vr[2] = {v_cr.x, v_cr.y}, vi[2] = {v_ci.x, v_ci.y};
                const uint32_t m2 = __vmaxu2(__vmaxu2(vr[0] & 0x7fff7fffu, vr[1] & 0x7fff7fffu), __vmaxu2(vi[0] & 0x7fff7fffu, vi[1] & 0x7fff7fffu));
                const uint32_t mx = __reduce_max_sync(0xffffffffu, max(m2, m2 << 16));
                const uint32_t e = min(max(mx >> 23, 11u), 254u);
                const float sc = __uint_as_float((264u - e) << 23);
                inv = __uint_as_float((e - 10u) << 23) * (2.f * dt);
#pragma unroll
                for (int i = 0; i < 4; i++) {
                    const float a = (i & 1) ? bf_hi(la[i >> 1]) : bf_lo(la[i >> 1]);
                    const float b = (i & 1) ? bf_hi(ai[i >> 1]) : bf_lo(ai[i >> 1]);
                    lr[i] = -bf_round(exp_acc(a)) * dt;
                    li[i] = b * dt;
                    cr[i] = ((i & 1) ? bf_hi(vr[i >> 1]) : bf_lo(vr[i >> 1])) * sc;
                    ci[i] = ((i & 1) ? bf_hi(vi[i >> 1]) : bf_lo(vi[i >> 1])) * sc;
                }
            }
            const uint32_t SX = sb + OFF_SCR + warp * 8192;
            const uint32_t sw = SX + (lane << 4);
#define PUT(buf, row, v) sts128(((sw + (row) * 512) ^ ((row) << 4)) + (buf) * 4096, v[0], v[1], v[2], v[3])
#define EMIT(bufa, rowa, bufb, rowb, xr, xi, k, kp) do { uint32_t pk[4], pd[4]; \
                _Pragma("unroll") for (int i = 0; i < 4; i++) { pk[i] = pack_h(xr[i], xi[i]); pd[i] = hcmul(pk[i], k[i], kp[i]); } \
                PUT(bufa, rowa, pk); PUT(bufb, rowb, pd); } while (0)
#define CMUL4(orr, oi, ar, ai, br, bi) _Pragma("unroll") for (int i = 0; i < 4; i++) CMUL(orr[i], oi[i], ar[i], ai[i], br[i], bi[i])
#define CSQ4(orr, oi, ar, ai) _Pragma("unroll") for (int i = 0; i < 4; i++) CSQ(orr[i], oi[i], ar[i], ai[i])
            float z1r[4], z1i[4], z2r[4], z2i[4], z8r[4], z8i[4], z256r[4], z256i[4];
            uint32_t k128[4], k128p[4], k4[4], k4p[4];
#pragma unroll
            for (int i = 0; i < 4; i++) {
                float tr, ti;
                cexp_pow(lr[i], li[i], 1.f, z1r[i], z1i[i]);
                CSQ(z2r[i], z2i[i], z1r[i], z1i[i]);
                CSQ(tr, ti, z2r[i], z2i[i]);
                k4[i] = pack_h(tr, ti); k4p[i] = pack_h(-ti, tr);
                CSQ(z8r[i], z8i[i], tr, ti);
                cexp_pow(lr[i], li[i], 128.f, tr, ti);
                k128[i] = pack_h(tr, ti); k128p[i] = pack_h(-ti, tr);
                CSQ(z256r[i], z256i[i], tr, ti);
                sts32(TB + i * T_PL + 16 + 4 * lane, k128[i]);
                sts32(TB + i * T_PL + 160 + 4 * lane, k128p[i]);
            }
            KSTAMP(5, k128[3] ^ k4[3]);
            uint32_t Ya[16][4];
            {
                float w1r[4], w1i[4], ar[4], ai[4], br[4], bi[4];
                uint32_t k8[4], k8p[4];
                const uint32_t one[4] = {0x3C00u, 0x3C00u, 0x3C00u, 0x3C00u};
#pragma unroll
                for (int i = 0; i < 4; i++) {
                    k8[i] = pack_h(z8r[i], -z8i[i]); k8p[i] = pack_h(z8i[i], z8r[i]);
                    CSQ(w1r[i], w1i[i], z8r[i], z8i[i]); w1i[i] = -w1i[i];
                }
                PUT(0, 0, one); PUT(1, 0, k8);
                EMIT(0, 1, 1, 1, w1r, w1i, k8, k8p);
                CSQ4(ar, ai, w1r, w1i);            EMIT(0, 2, 1, 2, ar, ai, k8, k8p);
                CMUL4(br, bi, ar, ai, w1r, w1i);   EMIT(0, 3, 1, 3, br, bi, k8, k8p);
                CSQ4(ar, ai, ar, ai);              EMIT(0, 4, 1, 4, ar, ai, k8, k8p);
                CMUL4(ar, ai, ar, ai, w1r, w1i);   EMIT(0, 5, 1, 5, ar, ai, k8, k8p);
                CSQ4(br, bi, br, bi);              EMIT(0, 6, 1, 6, br, bi, k8, k8p);
                CMUL4(br, bi, br, bi, w1r, w1i);   EMIT(0, 7, 1, 7, br, bi, k8, k8p);
                __syncwarp();
                KSTAMP(6, 0);
                const uint32_t ab = SX + (mi & 1) * 4096 + r * 512, ax = ((mi >> 1) ^ r) << 4;
#pragma unroll
                for (int ks = 0; ks < 16; ks++) ldsm4(ab + (ks >> 2) * 128 + (ax ^ ((ks & 3) << 5)), Ya[ks][0], Ya[ks][1], Ya[ks][2], Ya[ks][3]);
                __syncwarp();
            }
            KSTAMP(7, Ya[15][0]);
            const uint32_t ld0 = SX + r * 512 + ((mi ^ r) << 4), ld1 = ld0 ^ 64;
            float R[5][4], xr[4], xi[4];
            {
                float yr[4], yi[4];
                EMIT(0, 0, 0, 1, cr, ci, k4, k4p);
                CMUL4(yr, yi, cr, ci, z1r, z1i);        EMIT(0, 2, 0, 3, yr, yi, k4, k4p);
                CMUL4(xr, xi, cr, ci, z256r, z256i);    EMIT(1, 0, 1, 1, xr, xi, k4, k4p);
                CMUL4(yr, yi, yr, yi, z1r, z1i);        EMIT(0, 4, 0, 5, yr, yi, k4, k4p);
                CMUL4(cr, ci, xr, xi, z2r, z2i);        EMIT(1, 2, 1, 3, cr, ci, k4, k4p);
                CMUL4(yr, yi, yr, yi, z1r, z1i);        EMIT(0, 6, 0, 7, yr, yi, k4, k4p);
                CMUL4(xr, xi, xr, xi, z256r, z256i);    EMIT(1, 4, 1, 5, xr, xi, k4, k4p);
                CMUL4(xr, xi, xr, xi, z256r, z256i);    EMIT(1, 6, 1, 7, xr, xi, k4, k4p);
            }
            __syncwarp();
            {
                KSTAMP(8, 0);
                uint32_t bd[2][4] = {{0, 0, 0, 0}, {0, 0, 0, 0}};
                const bool on = (g >> 1) == t;
#pragma unroll
                for (int i = 0; i < 4; i++) { R[i][0] = R[i][1] = R[i][2] = R[i][3] = 0.f; }
#pragma unroll
                for (int k2 = 0; k2 < 8; k2++) {
                    uint32_t x[4], y[4], a1[2][4];
                    lds128_if(on, TB + t * T_PL + 16 + (g & 1) * 144 + 16 * k2, bd[k2 & 1]);
                    ldsm4(((k2 & 1) ? ld1 : ld0) + (k2 >> 1) * 128, x[0], x[1], x[2], x[3]);
                    ldsm4(((k2 & 1) ? ld1 : ld0) + (k2 >> 1) * 128 + 4096, y[0], y[1], y[2], y[3]);
#pragma unroll
                    for (int u = 0; u < 2; u++) {
                        mma_hh_k8(a1[u][0], a1[u][1], Ya[2 * k2 + u][0], Ya[2 * k2 + u][1], bd[k2 & 1][2 * u]);
                        mma_hh_k8(a1[u][2], a1[u][3], Ya[2 * k2 + u][2], Ya[2 * k2 + u][3], bd[k2 & 1][2 * u + 1]);
                    }
#pragma unroll
                    for (int u = 0; u < 2; u++) {
                        const uint32_t(&a0)[4] = Ya[2 * k2 + u];
                        mma_h(R[0], a0[0], a0[1], a0[2], a0[3], x[2 * u], x[2 * u + 1]);
                        mma_h(R[2], a0[0], a0[1], a0[2], a0[3], y[2 * u], y[2 * u + 1]);
                        mma_h(R[1], a1[u][0], a1[u][1], a1[u][2], a1[u][3], x[2 * u], x[2 * u + 1]);
                        mma_h(R[3], a1[u][0], a1[u][1], a1[u][2], a1[u][3], y[2 * u], y[2 * u + 1]);
                    }
                }
            }
            __syncwarp();
            KSTAMP(9, __float_as_uint(R[3][0]));
            asm volatile("barrier.cluster.wait.acquire.aligned;" ::: "memory");
            CMUL4(xr, xi, xr, xi, z256r, z256i);
            float s1024 = (xr[0] + xr[1]) + (xr[2] + xr[3]);
            CMUL4(xr, xi, xr, xi, z8r, z8i);        EMIT(0, 0, 0, 1, xr, xi, k128, k128p);
            CMUL4(xr, xi, xr, xi, z256r, z256i);    EMIT(0, 2, 0, 3, xr, xi, k128, k128p);
            CMUL4(xr, xi, xr, xi, z256r, z256i);    EMIT(0, 4, 0, 5, xr, xi, k128, k128p);
            CMUL4(xr, xi, xr, xi, z256r, z256i);    EMIT(0, 6, 0, 7, xr, xi, k128, k128p);
            __syncwarp();
            {
                KSTAMP(10, 0);
                float a1[4] = {0.f, 0.f, 0.f, 0.f};
                R[4][0] = R[4][1] = R[4][2] = R[4][3] = 0.f;
#pragma unroll
                for (int k2 = 0; k2 < 8; k2++) {
                    uint32_t x[4];
                    ldsm4(((k2 & 1) ? ld1 : ld0) + (k2 >> 1) * 128, x[0], x[1], x[2], x[3]);
                    mma_h(R[4], Ya[2 * k2][0], Ya[2 * k2][1], Ya[2 * k2][2], Ya[2 * k2][3], x[0], x[1]);
                    mma_h(a1, Ya[2 * k2 + 1][0], Ya[2 * k2 + 1][1], Ya[2 * k2 + 1][2], Ya[2 * k2 + 1][3], x[2], x[3]);
                }
#pragma unroll
                for (int i = 0; i < 4; i++) R[4][i] += a1[i];
            }
            if (lane == 0) mbar_arrive(bars + 8 * B_KG + (__float_as_uint(R[4][0]) & p.zero));
            KSTAMP(11, __float_as_uint(R[4][0]));
#undef PUT
#undef EMIT
#pragma unroll
            for (int o = 16; o > 0; o >>= 1) s1024 += __shfl_xor_sync(0xffffffffu, s1024, o);
            uint32_t w[4][4], dsk = 0;
            if (lane == 0) { cp_wait_all(); asm volatile("ld.shared.u16 %0, [%1];" : "=r"(dsk) : "r"(sb + M_DSK + 4 * warp + 2 * (warp & 1)) : "memory"); }
#pragma unroll
            for (int a = 0; a < 4; a++) {
                const float v0 = (a == 0) ? fmaf(R[0][0], inv, __uint_as_float(dsk << 16)) : R[a][0] * inv;
                const float v1 = R[a][1] * inv, v2 = R[a][2] * inv, v3 = R[a][3] * inv;
                w[a][0] = pack_bf(v0, 0.f); w[a][1] = pack_bf(v1, v0); w[a][2] = pack_bf(v2, v1); w[a][3] = pack_bf(v3, v2);
            }
            const uint32_t wb = TB + 16 + 16 * g, w1 = wb + t * T_PL, w2 = wb + 256 + 2 * t * T_PL;
            const uint32_t w3 = (t == 0) ? wb + 256 + 3 * T_PL : TB + T_A + 8 * (16 * t + g);
            const uint32_t w3s = (t == 0) ? 128 : 64, w3o = (t == 0) ? 8 : 12;
            const uint32_t k512 = __shfl_sync(0xffffffffu, w[2][1], 2);
#pragma unroll
            for (int a = 0; a < 2; a++) {
                sts128(w1 + 128 * a, w[a][0], w[a][1], w[a][2], w[a][3]);
                const uint32_t(&q)[4] = w[2 + a];
                if (t < 2) sts128(w2 + 128 * a, q[0], q[1], q[2], q[3]);
                if (t == 0) { sts128(w2 + T_PL + 128 * a, q[0], q[1], q[2], q[3]); sts32(w3 + 128 * a + 4, q[2]); }
                if (t != 1 && (a == 1 || lane != 2)) sts32(w3 + w3s * a, q[1]);
                if (t != 1) sts32(w3 + w3s * a + w3o, q[3]);
            }
            if (lane < 4)
                sts128(w1 + 512, __byte_perm(k512, 0, t == 3 ? 0x3210 : 0x4432), __byte_perm(k512, 0, t < 2 ? 0x3210 : t == 2 ? 0x3244 : 0x1044),
                       __byte_perm(k512, 0, t < 2 ? 0x1044 : 0x4444), 0);
            __syncwarp();
#pragma unroll
            for (int a = 0; a < 2; a++) {
                sts16(w1 + 128 * a + 18, w[a][3]);
                const uint32_t(&q)[4] = w[2 + a];
                if (t < 2) sts16(w2 + 128 * a + 18, q[3]);
                if (t == 0) { sts16(w2 + T_PL + 128 * a + 18, q[3]); sts16(w3 + 128 * a + 14, q[3]); }
            }
            if (t == 0) sts16(w3 + 128 - 4, w[3][0]);
            if (lane == 2 || (t == 0 && g > 0)) sts16(lane == 2 ? TB + 16 + 3 * T_PL + 4 * 127 : w3 - 4, w[2][0]);
            {
                const uint32_t b0 = pack_bf(R[4][0] * inv, R[4][2] * inv), b1 = pack_bf(R[4][1] * inv, R[4][3] * inv);
                const uint32_t wq = TB + T_B + 8 * (65 + 16 * t + g);
                sts32(wq, b0); sts32(wq + 12, b0); sts32(wq + 64, b1); sts32(wq + 76, b1);
            }
            cfix = pack_bf(s1024 * inv, s1024 * inv);
            if (lane == 0) sts32(TB + T_A + 8 * 64, cfix);
            __syncwarp();
        }
        WSTAMP(1);

        mbar_wait(bars + 8 * B_U);
        WSTAMP(2);

        float D[16][4];
        {
            const int x5 = g - t + 5;
            const uint32_t tabD = TB + (x5 & 3) * T_PL + (x5 & 12) + 16;
            {
                const uint32_t a1 = lds32(tabD - 8), a0 = p.zero;
#pragma unroll
                for (int jq = 0; jq < 4; jq++) {
                    uint32_t b[4];
                    ldsm4(UB + (9 + lane) * 16 + jq * 512, b[0], b[1], b[2], b[3]);
#pragma unroll
                    for (int i = 0; i < 4; i++) mma_bf_k8z(D[4 * jq + i], a0, a1, b[i]);
                }
            }
            const uint32_t ua = UB + (mi & 1) * U_PL + (8 + 8 * (mi >> 1) + r) * 16;
#pragma unroll 1
            for (int k0 = 0; k0 < 8; k0++) {
                uint32_t Uf[16][2];
#pragma unroll
                for (int jp = 0; jp < 8; jp++) ldsm4(ua + jp * 256 - k0 * 16, Uf[2 * jp][0], Uf[2 * jp][1], Uf[2 * jp + 1][0], Uf[2 * jp + 1][1]);
#pragma unroll
                for (int k1 = 0; k1 < 4; k1++) {
                    const uint32_t ta = tabD + 16 * (8 * k1 + k0);
                    const uint32_t a0 = lds32(ta), a1 = lds32(ta + 8), a2 = lds32(ta - 8), a3 = a0 ^ p.zero;
#pragma unroll
                    for (int J = k1; J < 16; J++) mma_bf(D[J], a0, a1, a2, a3, Uf[J - k1][0], Uf[J - k1][1]);
                }
                if (k0 == 0) {
                    const uint32_t ta = tabD + 16 * 32;
                    const uint32_t a0 = lds32(ta), a1 = lds32(ta + 8), a2 = lds32(ta - 8), a3 = a0 ^ p.zero;
#pragma unroll
                    for (int J = 4; J < 16; J++) mma_bf(D[J], a0, a1, a2, a3, Uf[J - 4][0], Uf[J - 4][1]);
                    const uint32_t f0 = (cfix ^ 0x80008000u) & (g == t ? 0xffffu : g == t + 4 ? 0xffff0000u : 0u);
                    const uint32_t f1 = p.zero, f2 = p.zero + p.zero, f3 = f0 ^ p.zero;
#pragma unroll
                    for (int J = 8; J < 16; J++) mma_bf(D[J], f0, f1, f2, f3, Uf[J - 8][0], Uf[J - 8][1]);
                }
            }
        }
        WSTAMP(3);
        {
            const int ch = 8 * h + warp;
            const uint32_t yo = sb + ch * 512 + ((lane ^ (((ch >> 2) << 1) | (ch & 1))) << 4);
            const uint32_t yr = mapa(yo, h ^ 1), ybr = mapa(bars + 8 * B_Y, h ^ 1);
            auto ship = [&](const int Q) {
                uint4 y[2];
#pragma unroll
                for (int hh = 0; hh < 2; hh++) {
                    const int J = 4 * Q + 2 * hh;
                    y[hh] = make_uint4(pack_bf(D[J][0], D[J][1]), pack_bf(D[J][2], D[J][3]), pack_bf(D[J + 1][0], D[J + 1][1]), pack_bf(D[J + 1][2], D[J + 1][3]));
                }
                if (!(Q & 1)) mbar_wait(bars + 8 * (B_F + (Q >> 1)));
                asm volatile("{\n\t.reg .pred p;\n\tsetp.eq.u32 p, %11, 0;\n\t"
                             "@p st.async.weak.shared::cluster.mbarrier::complete_tx::bytes.v4.b32 [%9], {%4,%5,%6,%7}, [%10];\n\t"
                             "@!p st.async.weak.shared::cluster.mbarrier::complete_tx::bytes.v4.b32 [%9], {%0,%1,%2,%3}, [%10];\n\t"
                             "@p st.shared.v4.b32 [%8], {%0,%1,%2,%3};\n\t@!p st.shared.v4.b32 [%8], {%4,%5,%6,%7};\n\t}"
                             :: "r"(y[0].x), "r"(y[0].y), "r"(y[0].z), "r"(y[0].w), "r"(y[1].x), "r"(y[1].y), "r"(y[1].z), "r"(y[1].w),
                                "r"(yo + y_off(Q)), "r"(yr + y_off(Q)), "r"(ybr + 8 * Q), "r"(h) : "memory");
                __syncwarp();
                if (lane == 0) mbar_arrive(bars + 8 * (B_Y + Q));
            };
            ship(0);
            const uint4 bA = lds128(sb + OFF_BAND + (g - t + 3) * 48), bB = lds128(sb + OFF_BAND + (g - t + 3) * 48 + 16);
            const uint2 bC = lds64(sb + OFF_BAND + (g - t + 3) * 48 + 32);
            uint2 QA[5][2], QB[8];
            const uint32_t tq = TB + 8 * (1 + g - 2 * t);
#pragma unroll
            for (int dd = 0; dd < 5; dd++) { QA[dd][0] = lds64(tq + T_A + 64 * (dd + 4)); QA[dd][1] = lds64(tq + T_A + 64 * (dd + 4) - 8); }
#pragma unroll
            for (int dd = 0; dd < 8; dd++) QB[dd] = lds64(tq + T_B + 64 * (dd + 8));
            const uint32_t u1 = UB + (mi & 1) * U_PL + (7 + r + (mi >> 1)) * 16;
            const uint32_t u2 = UB + ((mi & 1) ^ 1) * U_PL + (7 + r + (mi & 1) + 8 * (mi >> 1)) * 16;
            uint32_t n[4];
#pragma unroll
            for (int j = 0; j < 12; j++) {
                uint32_t m[4];
                ldsm4(u1 + j * 128, m[0], m[1], m[2], m[3]);
                if (!(j & 1)) ldsm4(u2 + j * 128, n[0], n[1], n[2], n[3]);
                const uint32_t n0 = n[2 * (j & 1)], n1 = n[2 * (j & 1) + 1];
                float wa[4], wb[4], wc[4], g1[4], g2[4];
                mma_bf_z(wa, bA.x, bA.y, bA.z, bA.w, m[0], m[1]);
                mma_bf_z(wb, bA.x, bA.y, bA.z, bA.w, n0, n1);
                mma_bf_z(wc, bA.x, bA.y, bA.z, bA.w, m[2], m[3]);
                if (j < 8) {
                    mma_bf_z(g1, bB.x, bB.y, bB.z, bB.w, m[0], m[1]);
                    mma_bf_z(g2, bB.x, bB.y, bB.z, bB.w, n0, n1);
                    mma_bf_k8(g1, bC.x, bC.y, m[2]);
                    mma_bf_k8(g2, bC.x, bC.y, m[3]);
                }
#pragma unroll
                for (int e = 0; e < 2; e++) {
                    const uint32_t q0 = pack_bf(wa[e], wa[e + 2]), q1 = pack_bf(wb[e], wb[e + 2]), q2 = q1 ^ p.zero, q3 = pack_bf(wc[e], wc[e + 2]);
#pragma unroll
                    for (int dd = 0; dd < 5; dd++)
                        if (j + 4 + dd < 16) mma_bf(D[j + 4 + dd], q0, q1, q2, q3, QA[dd][e].x, QA[dd][e].y);
                }
                if (j < 8) {
                    const uint32_t q0 = pack_bf(g1[0], g1[2]), q1 = pack_bf(g2[0], g2[2]), q2 = pack_bf(g1[1], g1[3]), q3 = pack_bf(g2[1], g2[3]);
#pragma unroll
                    for (int dd = 7 - j; dd >= 0; dd--) mma_bf(D[j + 8 + dd], q0, q1, q2, q3, QB[dd].x, QB[dd].y);
                }
                if ((j & 3) == 3) {
                    WSTAMP(4 + 2 * (j >> 2));
                    if (j == 11 && LATE2) ship(2);
                    if (j != 7 || !LATE2) ship((j >> 2) + 1);
                }
            }
        }
        {
            const int warpu = __reduce_max_sync(0xffffffffu, warp);
            const int m8 = 16 * (g >> 2) + ((g >> 1) & 1) + 2 * (g & 1);
            const uint32_t yi = sb + (4 * (r >> 1) + 2 * (mi & 1) + (r & 1)) * 512 + (((4 * warp + (mi >> 1)) ^ r) << 4);
            const uint32_t xs = sb + OFF_S + s_addr(warp * S_PL + 32 + m8 * 32, t >> 1) + ((t & 1) << 3);
            const uint32_t ob = sb + OFF_U + warpu * U_CH + (warpu & 1) * 64, os = ob + m8 * 32 + t * 8;
            bf16* op = p.out + (size_t)(256 * h + 8 * m8 + warp) * D_ + 16 * pr + 4 * t;
            mbar_wait(bars + 8 * B_Y);
#pragma unroll 1
            for (int Q = 0; Q < 4; Q++) {
                uint2 xq[4];
#pragma unroll
                for (int i = 0; i < 4; i++) xq[i] = lds64((xs ^ ((i & 1) << 4)) + Q * S_Q + i * 128);
                const uint2 gq = lds64(sb + OFF_GP + Q * 512 + warp * 64 + g * 8);
                const uint32_t sw = lds32(sb + M_BMAP + warpu * 16 + Q * 4);
                uint32_t gg[4];
#pragma unroll
                for (int i = 0; i < 4; i++) {
                    gg[i] = __byte_perm(i < 2 ? gq.x : gq.y, 0, (i & 1) ? 0x3232 : 0x1010);
                    const uint32_t og = hfma2_bf(gg[i], 0xBF80BF80u, 0x3F803F80u);
                    xq[i].x = hmul2_bf(og, xq[i].x); xq[i].y = hmul2_bf(og, xq[i].y);
                }
                mbar_wait(bars + 8 * (B_Y + Q));
                __syncwarp();
#pragma unroll
                for (int x = 0; x < 2; x++) {
                    uint32_t y[4];
                    ldsm4t((yi ^ (x << 5)) + y_off(Q), y[0], y[1], y[2], y[3]);
#pragma unroll
                    for (int e = 0; e < 2; e++) { xq[2 * x + e].x = hfma2_bf(gg[2 * x + e], y[2 * e], xq[2 * x + e].x); xq[2 * x + e].y = hfma2_bf(gg[2 * x + e], y[2 * e + 1], xq[2 * x + e].y); }
                }
                if (Q < TMAQ && sw == 0) {
#pragma unroll
                    for (int i = 0; i < 4; i++) asm volatile("st.shared.v2.u32 [%0], {%1, %2};" :: "r"(os + Q * 1024 + i * 128), "r"(xq[i].x), "r"(xq[i].y) : "memory");
                    asm volatile("fence.proxy.async.shared::cta;" ::: "memory");
                    __syncwarp();
                    asm volatile("{\n\t.reg .pred p;\n\telect.sync _|p, 0xffffffff;\n\t"
                                 "@p cp.async.bulk.tensor.3d.global.shared::cta.bulk_group [%1, {%2, %3, %4}], [%0];\n\t}"
                        :: "r"(ob + Q * 1024), "l"(&tm_out), "r"(16 * pr), "r"(64 * Q + 32 * h), "r"(warpu) : "memory");
                } else {
#pragma unroll
                    for (int i = 0; i < 4; i++)
                        if (!((sw >> (4 * g + i)) & 1)) *(uint2*)(op + (size_t)(512 * Q + 32 * i) * D_) = xq[i];
                }
                WSTAMP(Q < 3 ? 5 + 2 * Q : 11);
            }
            if (TMAQ) asm volatile("cp.async.bulk.commit_group;\n\tcp.async.bulk.wait_group.read 0;" ::: "memory");
        }
        WSTAMP(10);
        WDUMP();
    } else if ((pw & 12) == AUX_W0) {
        asm volatile("setmaxnreg.inc.sync.aligned.u32 136;");
        const int v = __reduce_max_sync(0xffffffffu, pw & 3);
        const int at = tid & 127;
        const int g = lane >> 2, t = lane & 3;
        unsigned epoch, tag;
        const bool gu = c < NGU_CTA;
        {
            uint4 xa[16];
            const uint32_t xb = sb + (v < 2 ? OFF_XSEL : OFF_RING + 2 * 8192) + v * 8192;
            const uint32_t gws = sb + (gu ? M_DPIN : OFF_RING + 2 * 8192);
            const uint32_t row = 16 * c + 4 * v + (g >> 1);
            epoch = *(volatile unsigned*)&p.sc->epoch;
            tag = (epoch + 1) & 0xffffu;
#pragma unroll
            for (int i = 0; i < 4; i++)
                asm volatile("cp.async.ca.shared.global [%0], [%1], 4;" :: "r"(sb + OFF_GP + 512 * i + (tid & 124) * 4 + (tid & 1) * 8 + (tid & 2) * 2),
                             "l"(p.wr + 256 * i + (tid & 127) * 2) : "memory");
            cp16(gws + (tid & 127) * 16, p.gatew + (tid & 127) * 8);
            if ((tid & 127) < 33) cp16(sb + OFF_BAND + (tid & 127) * 16, p.band + (tid & 127));
            asm volatile("barrier.cluster.arrive.relaxed.aligned;" ::: "memory");
            if (gu) st_gpu32((uint32_t*)&p.sc->h[(tag + 1) & 1][32 * c] + at, 0);
            if (v == 0) sts32(sb + M_BMAP + lane * 4, 0);
            cp_wait_all();
            bar_sync(1, 128);
            uint2 w[16];
#pragma unroll
            for (int kb = 0; kb < 16; kb++) w[kb] = lds64(sb + OFF_GP + 128 * kb + 32 * (g & 2) + 16 * t + 8 * (g & 1));
            asm volatile("barrier.cluster.wait.acquire.aligned;" ::: "memory");
            mbar_wait(bars + 8 * (B_X + v));
            WSTAMP(10);
#pragma unroll
            for (int kb = 0; kb < 16; kb++) xa[kb] = lds128(xb + (g >> 1) * 2048 + 128 * kb + 16 * (lane & 7));
            float dr[4][4];
#pragma unroll
            for (int kb = 0; kb < 16; kb++) {
                if (kb < 4) mma_bf_z(dr[kb], xa[kb].x, xa[kb].y, xa[kb].z, xa[kb].w, w[kb].x, w[kb].y);
                else mma_bf(dr[kb & 3], xa[kb].x, xa[kb].y, xa[kb].z, xa[kb].w, w[kb].x, w[kb].y);
            }
            float rs = ((dr[0][0] + dr[0][3]) + (dr[1][0] + dr[1][3])) + ((dr[2][0] + dr[2][3]) + (dr[3][0] + dr[3][3]));
            if (lane == 0) mbar_arrive(bars + 8 * (B_XE + v) + (__float_as_uint(rs) & p.zero));
            rs += __shfl_xor_sync(0xffffffffu, rs, 5);
            const uint32_t rb = pack_bf(0.f, rs);
            if (!(lane & 7)) st_gpu32((uint32_t*)&p.sc->r[(row >> 2) * RS] + (row & 3), ((rb ^ (((int)rb >> 31) | 0x80000000u)) & 0xffff0000u) | tag);
            WSTAMP(1);
            {
                const int n = 3 + (lane >> 3) + 4 * (lane & 1);
                const uint32_t so = (n & 7) * S_PL + ((lane & 6) + (n >> 3)) * 32;
                const uint32_t src[2] = {sb + OFF_S + v * S_Q + s_addr(so, h), sb + OFF_S + v * S_Q + s_addr(so + 32, h)};
                const uint32_t dst = sb + OFF_U + g * U_CH + (8 + 32 * v + 16 * h + t) * 16;
                const uint32_t rdst = mapa(dst, h ^ 1), rbar = mapa(bars + 8 * B_U, h ^ 1);
                mbar_wait(bars + 8 * (B_S + v));
                uint4 a[8];
#pragma unroll
                for (int b = 0; b < 2; b++) {
#pragma unroll
                    for (int j = 0; j < 8; j++) ldsm4t((b ? src[j & 1] : src[j & 1] ^ 16) + (j >> 1) * 256, a[j].x, a[j].y, a[j].z, a[j].w);
#pragma unroll
                    for (int j = 0; j < 8; j++) {
                        if (b) sts128(dst + (j >> 1) * 64 + (j & 1) * U_PL, a[j].x, a[j].y, a[j].z, a[j].w);
                        else st_async16(rdst + (j >> 1) * 64 + (j & 1) * U_PL, a[j], rbar);
                    }
                }
                if (h && v == 3) {
                    ldsm4t((src[0] ^ 16) + 1024, a[0].x, a[0].y, a[0].z, a[0].w);
                    ldsm4t(src[0] + 1024, a[1].x, a[1].y, a[1].z, a[1].w);
                    if (t == 0) {
                        st_async16(rdst + 256, make_uint4(a[0].x, a[0].y & 0xffffu, a[0].z & 0xffffu, a[0].w & 0xffffu), rbar);
                        sts128(dst + 256, a[1].x, a[1].y & 0xffffu, a[1].z & 0xffffu, a[1].w & 0xffffu);
                    }
                }
                __syncwarp();
                if (lane == 0) mbar_arrive(bars + 8 * B_U);
            }
            const uint32_t one0 = 0x3F803F80u ^ p.zero, one1 = 0x3F803F80u + p.zero;
#pragma unroll
            for (int kb = 0; kb < 16; kb++) {
                const uint4 gw = lds128(gws + 128 * kb + 16 * (lane & 7));
                const uint32_t a0 = hmul2_bf(xa[kb].x, gw.x), a1 = hmul2_bf(xa[kb].y, gw.y), a2 = hmul2_bf(xa[kb].z, gw.z), a3 = hmul2_bf(xa[kb].w, gw.w);
                if (kb < 4) mma_bf_z(dr[kb], a0, a1, a2, a3, one0, one1);
                else mma_bf(dr[kb & 3], a0, a1, a2, a3, one0, one1);
            }
            float sg = ((dr[0][0] + dr[0][3]) + (dr[1][0] + dr[1][3])) + ((dr[2][0] + dr[2][3]) + (dr[3][0] + dr[3][3]));
            sg += __shfl_xor_sync(0xffffffffu, sg, 4);
            if (!(lane & 7)) st_gpu32((uint32_t*)p.sc->g + ((row & 256) << 2) + gate_pos(row), (pack_bf(sigmoid_f(bf_round(sg)), 0.f) & 0xffffu) | (tag << 16));
            WSTAMP(2);
        }
        if (at == 32) { sts32(sb + M_TAG, tag << 16); mbar_arrive(bars + 8 * B_F); }
        const bool lane0 = pin(lane, lane) == 0;
        const uint32_t own = pin(sb + OFF_XSEL + at * 16, lane);
        const uint4* pb = pin(&p.sc->h[tag & 1][32 * (56 * h + 14 * v + (lane < 14 ? lane : 0)) + 8 * (pr & 3)], lane);
        {
            float acc[8][4];
#pragma unroll
            for (int i = 0; i < 8; i++) { acc[i][0] = acc[i][1] = acc[i][2] = acc[i][3] = 0.f; }
            const int krow = ((lane >> 1) & 8) + (lane & 7);
            const uint32_t tile0 = pin(sb + OFF_RING + krow * 64 + ((((lane >> 3) & 1) ^ ((krow >> 1) & 3)) << 4), lane);
            const uint32_t xo = pin(sb + OFF_XSEL + (lane & 7) * XS_ROW + 512 * v + 2 * (lane & 24), lane);
            const uint32_t po = pin(sb + OFF_XSEL + t * XS_ROW + (g & 3) * 128 + v * 16 + (lane >> 4) * 8, lane);
            uint32_t* hdst = pin((uint32_t*)&p.sc->h[tag & 1][32 * c] + at, lane);
            auto signal = [&](const int k, const uint32_t dep) {
                if (lane < 2 && v < 2)
                    asm volatile("st.async.weak.shared::cluster.mbarrier::complete_tx::bytes.b32 [%0], %1, [%2];"
                                 :: "r"(mapa(sb + M_SINK, lane)), "r"(dep), "r"(mapa(bars + 8 * (B_F + k), lane)) : "memory");
            };
#pragma unroll 1
            for (int i = 0; i < 4; i++) {
                const int s = 4 * i + v;
                uint32_t a[16][4], b[2][4];
                if (gu) {
                    const uint32_t tile = tile0 + (s < 14 ? s : v) * 8192;
                    if (lane0 && i > 1) mbar_arrive(bars + 8 * (B_E + s - 4));
                    mbar_wait(bars + 8 * (B_W + s));
#pragma unroll
                    for (int q = 0; q < 16; q++) ldsm4t((tile ^ ((q & 1) << 5)) + ((q >> 1) & 1) * 4096 + (q >> 2) * 1024, a[q][0], a[q][1], a[q][2], a[q][3]);
                }
                if (i == 0) {
                    if (gu) {
                        uint32_t dep = p.zero;
#pragma unroll
                        for (int q = 0; q < 16; q += 2) dep &= a[q][0] & a[q + 1][0];
                        if (lane == 0) mbar_arrive(bars + 8 * (B_E + v) + dep);
                        signal(0, dep);
                    }
                    WSTAMP(11);
                    uint32_t top;
#pragma unroll 1
                    for (int it = 0; it < (1 << 22); it++) {
                        asm volatile("ld.relaxed.gpu.global.u32 %0, [%1];" : "=r"(top) : "l"(&p.sc->top[c % NTOP][g]) : "memory");
                        if (__all_sync(0xffffffffu, ((top ^ (tag << 11)) & 0xf800u) == 0)) break;
                        if (TSLEEP) __nanosleep(TSLEEP);
                    }
                    WSTAMP(3);
                    if (gu) {
                        const uint32_t k = 4 * h + v, row = __reduce_max_sync(0xffffffffu, lane == 4 * k ? ~top & 2047 : 0);
                        asm volatile("{\n\t.reg .pred p;\n\telect.sync _|p, 0xffffffff;\n\t"
                                     "@p cp.async.bulk.shared::cluster.global.mbarrier::complete_tx::bytes.multicast::cluster [%0], [%1], 2048, [%2], %3;\n\t}"
                            :: "r"(sb + OFF_XSEL + k * XS_ROW), "l"(p.u + (size_t)row * D_), "r"(bars + 8 * B_G), "h"((unsigned short)3) : "memory");
                    }
                    if (v == 0) {
                        const uint32_t row = ~top & 2047;
                        if (t == 0 && ((row >> 8) & 1) == h)
                            asm volatile("red.shared.or.b32 [%0], %1;" :: "r"(sb + M_BMAP + (row & 7) * 16 + (row >> 9) * 4), "r"(1u << (gate_pos(row) & 31)) : "memory");
                        if (t == 0) sts32(sb + M_TOP + lane, top);
                        __syncwarp();
                        if (lane0) mbar_arrive(bars + 8 * B_Y);
                    }
                    if (!gu) break;
                    mbar_wait(bars + 8 * B_G);
                    WSTAMP(4);
                }
                ldsm4(xo + 128 * i, b[0][0], b[0][1], b[0][2], b[0][3]);
                ldsm4(xo + 128 * i + 64, b[1][0], b[1][1], b[1][2], b[1][3]);
#pragma unroll
                for (int q = 0; q < 16; q++) mma_bf(acc[q & 7], a[q][0], a[q][1], a[q][2], a[q][3], b[q >> 3][(q >> 1) & 2], b[q >> 3][((q >> 1) & 2) + 1]);
            }
            if (gu) {
                WSTAMP(5);
                __syncwarp();
#pragma unroll
                for (int q = 0; q < 4; q++) {
                    const int ct = q >> 1, e = 2 * (q & 1);
                    sts128(own + q * XS_ROW,
                           __float_as_uint(acc[ct][e] + acc[4 + ct][e]), __float_as_uint(acc[2 + ct][e] + acc[6 + ct][e]),
                           __float_as_uint(acc[ct][e + 1] + acc[4 + ct][e + 1]), __float_as_uint(acc[2 + ct][e + 1] + acc[6 + ct][e + 1]));
                }
                bar_sync(1, 128);
                float hv[2];
#pragma unroll
                for (int e = 0; e < 2; e++) {
                    uint2 q[4];
#pragma unroll
                    for (int i = 0; i < 4; i++) q[i] = lds64(po + 64 * e + 512 * i);
                    const float s0 = (__uint_as_float(q[0].x) + __uint_as_float(q[1].x)) + (__uint_as_float(q[2].x) + __uint_as_float(q[3].x));
                    const float s1 = (__uint_as_float(q[0].y) + __uint_as_float(q[1].y)) + (__uint_as_float(q[2].y) + __uint_as_float(q[3].y));
                    const float gv = bf_round(p.gu_swap ? s1 : s0), uv = bf_round(p.gu_swap ? s0 : s1);
                    hv[e] = bf_round(gv * sigmoid_f(gv)) * uv;
                }
                const uint32_t hw = pack_bf(hv[0], hv[1]);
                st_gpu32(hdst, hw ? hw : 0x80000000u);
                signal(1, hw);
            }
        }
        WSTAMP(6);
        {
            uint4 hq[14];
            {
                bar_sync(1, 128);
                if (!gu) mbar_wait(bars + 8 * (B_H + 3));
                if (HDELAY) __nanosleep(HDELAY);
                const uint32_t hb = sb + (v < 2 ? OFF_XSEL + 7168 * v : OFF_RING + 8192 * v);
#pragma unroll 1
                for (int it = 0; it < (1 << 22); it++) {
                    uint32_t w;
                    asm volatile("ld.relaxed.gpu.global.u32 %0, [%1];" : "=r"(w) : "l"(pb) : "memory");
                    if (__all_sync(0xffffffffu, w != 0)) break;
                    __nanosleep(PSLEEP);
                }
                WSTAMP(12);
#pragma unroll 1
                for (int it = 0; it < (1 << 16); it++) {
                    bulk_load(hb, &p.sc->h[tag & 1][32 * (56 * h + 14 * v)], 7168, bars + 8 * (B_X + v));
                    mbar_wait(bars + 8 * (B_X + v), ~it & 1);
                    uint32_t mn = 0xffffffffu;
#pragma unroll
                    for (int i = 0; i < 14; i++) hq[i] = lds128(hb + 512 * i + 16 * lane);
#pragma unroll
                    for (int i = 0; i < 14; i++) mn = min(mn, hq[i].x);
                    if (__all_sync(0xffffffffu, mn != 0)) break;
                }
            }
            WSTAMP(7);
            float dd[4][4];
            const int krow = ((lane >> 1) & 8) + (lane & 7);
            const uint32_t tile = sb + OFF_RING + (4 + v) * 8192 + krow * 32 + ((((lane >> 3) ^ (krow >> 2)) & 1) << 4);
#pragma unroll
            for (int s = 0; s < 2; s++) {
                mbar_wait(bars + 8 * (B_W + 16 + 4 * s + v));
#pragma unroll
                for (int j = 0; j < 14; j++) {
                    uint32_t a[4];
                    ldsm4t(tile + s * 32768 + j * 512, a[0], a[1], a[2], a[3]);
                    const uint4& hb = hq[7 * s + (j >> 1)];
                    if (s == 0 && j < 4) mma_bf_z(dd[j], a[0], a[1], a[2], a[3], (j & 1) ? hb.z : hb.x, (j & 1) ? hb.w : hb.y);
                    else mma_bf(dd[(j + 2 * s) & 3], a[0], a[1], a[2], a[3], (j & 1) ? hb.z : hb.x, (j & 1) ? hb.w : hb.y);
                }
            }
            WSTAMP(8);
            uint4 part;
            part.x = __float_as_uint((dd[0][0] + dd[1][0]) + (dd[2][0] + dd[3][0])); part.y = __float_as_uint((dd[0][1] + dd[1][1]) + (dd[2][1] + dd[3][1]));
            part.z = __float_as_uint((dd[0][2] + dd[1][2]) + (dd[2][2] + dd[3][2])); part.w = __float_as_uint((dd[0][3] + dd[1][3]) + (dd[2][3] + dd[3][3]));
            st_async16(mapa(own + (M_DPIN - OFF_XSEL), h ^ 1), part, mapa(bars + 8 * B_DP, h ^ 1));
            sts128(own + 14336, part.x, part.y, part.z, part.w);
            __syncwarp();
            if (lane0) mbar_arrive(bars + 8 * B_DP);
        }
        WSTAMP(9);
        WDUMP();
        if (at == 0 && c == 0) *(volatile unsigned*)&p.sc->epoch = epoch + 1;
    } else {
        asm volatile("setmaxnreg.dec.sync.aligned.u32 40;");
        const int v = __reduce_max_sync(0xffffffffu, pw - PREP_W0);
        const bool gu = c < NGU_CTA;
        const uint32_t t0 = clock();
        const uint32_t bu = bars + 8 * v;
        WSTAMP(1);
        if (lane == 0) {
            mbar_init(bu + 8 * B_X, 1);
            asm volatile("fence.mbarrier_init.release.cluster;" ::: "memory");
        }
        __syncwarp();
        if (DELAY_X > 0) __nanosleep(DELAY_X);
        bulk_load(sb + (v < 2 ? OFF_XSEL : OFF_RING + 2 * 8192) + v * 8192, p.u + (size_t)(16 * c + 4 * v) * D_, 8192, bu + 8 * B_X);
        WSTAMP(2);
        if (lane == 0) {
#pragma unroll
            for (int i = 0; i < 10; i++) mbar_init(bu + 32 * i, 1);
            mbar_init(bu + 8 * B_XE, 1);
            mbar_init(bu + 8 * B_Y, v == 0 ? 11 : 9);
            mbar_init(bu + 8 * B_DP, (0x1855 >> (4 * v)) & 15);
            mbar_init(bu + 8 * B_F, v == 0 ? 2 : 1);
            mbar_init(bu + 8 * B_H, 1);
            asm volatile("fence.mbarrier_init.release.cluster;" ::: "memory");
            mbar_expect(bu + 8 * B_Y, 4096);
            if (v != 2) mbar_expect(bu + 8 * B_DP, v == 0 ? 2048 : (h || v == 3) ? 16384 : 16384 + 128);
            mbar_expect(bu + 8 * B_F, c < NGU_CTA ? 16 : 0);
        }
        __syncwarp();
        asm volatile("barrier.cluster.arrive.relaxed.aligned;" ::: "memory");
        if (DELAY_S > 0) __nanosleep(DELAY_S);
        tma3d(sb + OFF_S + v * S_Q, &tm_x, 16 * pr, 64 * v + 32 * h - 1, bars + 8 * (B_S + v), S_Q);
        WSTAMP(9);
        if (v < 3 && lane == 0) asm volatile("prefetch.tensormap [%0];" :: "l"(v == 0 ? &tm_gu : v == 1 ? &tm_down : &tm_out) : "memory");
        asm volatile("barrier.cluster.wait.acquire.aligned;" ::: "memory");
        if (v > 0) mbar_wait(bars + 8 * (B_H + v));
        {
            const int gap = v == 0 ? GAP : v == 1 ? GAP1 : v == 2 ? GAP2 : GAP3;
            uint32_t last = v ? clock() - SLACK : t0 + T0 - GAP + STAG * ((pr * 5) & 15) / 16;
#pragma unroll 1
            for (int s = 6 * v; s < 6 * v + 6; s++) {
                const int i = s >> 2, w = s & 3, slot = s < 14 ? s : s - 12;
                if (slot >= 4 || s >= 14) mbar_wait(bars + 8 * ((gu && s >= 14) ? B_E + slot : slot < 6 ? B_XE + slot - 2 : B_KG));
                uint32_t now;
#pragma unroll 1
                while ((int)((now = clock()) - last) < gap) __nanosleep(CSLEEP);
                last = max((int)(now - last) - SLACK, gap) + last;
                WSTAMP(3 + s - 6 * v);
                if (gu || s >= 16) tma3d(sb + OFF_RING + slot * 8192, i < 4 ? &tm_gu : &tm_down, i < 4 ? 32 * c : 16 * pr,
                      i < 4 ? 256 * w + 64 * i : 1792 * h + 448 * w + 224 * (i - 4), bars + 8 * (B_W + s), i < 4 ? 8192 : 7168);
            }
            if (lane == 0) mbar_arrive(bars + 8 * (B_H + ((v + 1) & 3)));
        }
        if (v == 0) {
            mbar_wait(bars + 8 * B_U);
            mbar_wait(bars + 8 * B_F);
            mbar_wait(bars + 8 * (gu ? GWAIT : B_H + 3));
            const uint32_t tag16 = lds32(sb + M_TAG);
#pragma unroll 1
            for (int k = 0; k < 2; k++) {
                uint4 q[4];
#pragma unroll 1
                for (int it = 0; it < (1 << 22); it++) {
                    uint32_t bad = 0;
#pragma unroll
                    for (int i = 0; i < 4; i++) q[i] = ld_gpu128(&p.sc->g[256 * h + 128 * k + 32 * i + lane]);
#pragma unroll
                    for (int i = 0; i < 4; i++) bad |= ((q[i].x ^ tag16) | (q[i].y ^ tag16)) | ((q[i].z ^ tag16) | (q[i].w ^ tag16));
                    if ((bad >> 16) == 0) break;
                    __nanosleep(200);
                }
#pragma unroll
                for (int i = 0; i < 4; i++)
                    asm volatile("st.shared.v2.u32 [%0], {%1, %2};" :: "r"(sb + OFF_GP + 1024 * k + 256 * i + lane * 8),
                                 "r"(__byte_perm(q[i].x, q[i].y, 0x5410)), "r"(__byte_perm(q[i].z, q[i].w, 0x5410)) : "memory");
            }
            __syncwarp();
            if (lane == 0) mbar_arrive(bars + 8 * B_Y);
        }
        {
            mbar_wait(bars + 8 * B_Y);
            const uint32_t top = lds32(sb + M_TOP + 8 * v + 4 * (lane >> 4));
            const uint32_t row = ~top & 2047, ch = lane & 15, gp = gate_pos(row);
            const bool mine = ((row >> 8) & 1) == h;
            uint32_t gfin, x16, y16 = 0;
            asm volatile("ld.shared.u16 %0, [%1];" : "=r"(gfin) : "r"(sb + OFF_GP + gp * 2) : "memory");
            asm volatile("ld.shared.u16 %0, [%1];" : "=r"(x16) : "r"(sb + OFF_S + (row >> 9) * S_Q + s_addr((row & 7) * S_PL + 32 + (row & 248) * 4, ch >> 3) + 2 * (ch & 7)) : "memory");
            const float rsel = __uint_as_float(pin(__float_as_uint(bf_round(sigmoid_f(__uint_as_float((top ^ (((int)~top >> 31) | 0x80000000u)) & 0xffff0000u)))), lane));
            const uint32_t po = pin(sb + (4 * (ch & 7) + v) * 16 + (ch >> 3) * 8 + (lane >> 4) * 4, lane);
            bf16* op = pin(p.out + (size_t)row * D_ + 16 * pr + ch, lane);
            if (mine) {
                mbar_wait(bars + 8 * (B_Y + (row >> 9)));
                asm volatile("ld.shared.u16 %0, [%1];" : "=r"(y16)
                             : "r"(sb + y_off(row >> 9) + ch * 512 + (((4 * (row & 7) + ((row >> 5) & 3)) ^ (((ch >> 2) << 1) | (ch & 1))) << 4) + 2 * row_elem(row)) : "memory");
            }
            mbar_wait(bars + 8 * B_DP);
            float q[8];
#pragma unroll
            for (int i = 0; i < 4; i++) { q[i] = ldsf(po + M_DPIN + 512 * i); q[4 + i] = ldsf(po + OFF_XSEL + 14336 + 512 * i); }
            const float tot = ((q[0] + q[1]) + (q[2] + q[3])) + ((q[4] + q[5]) + (q[6] + q[7]));
            const float b = bf_round(__uint_as_float(x16 << 16) + bf_round(bf_round(tot) * rsel));
            if (mine) *op = __float2bfloat16_rn(fmaf(bf_lo(gfin), __uint_as_float(y16 << 16), bf_round(bf_round(1.f - bf_lo(gfin)) * b)));
        }
        WSTAMP(10);
        WDUMP();
    }
}

typedef CUresult (*EncodeFn)(CUtensorMap*, CUtensorMapDataType, cuuint32_t, void*, const cuuint64_t*, const cuuint64_t*,
                             const cuuint32_t*, const cuuint32_t*, CUtensorMapInterleave, CUtensorMapSwizzle,
                             CUtensorMapL2promotion, CUtensorMapFloatOOBfill);

void make_map(EncodeFn f, CUtensorMap* m, const void* ptr, uint64_t cols, uint64_t rows, uint64_t pitch, uint32_t bc, uint32_t br, CUtensorMapSwizzle sw, int prom,
              uint32_t planes = 1, uint64_t plane_stride = 0, uint32_t box_planes = 0) {
    cuuint64_t dims[3] = {cols, rows, planes};
    cuuint64_t str[2] = {pitch, planes > 1 ? plane_stride : pitch * rows};
    cuuint32_t box[3] = {bc, br, box_planes ? box_planes : planes};
    cuuint32_t es[3] = {1, 1, 1};
    f(m, CU_TENSOR_MAP_DATA_TYPE_BFLOAT16, 3, (void*)ptr, dims, str, box, es, CU_TENSOR_MAP_INTERLEAVE_NONE, sw,
      (CUtensorMapL2promotion)prom, CU_TENSOR_MAP_FLOAT_OOB_FILL_NONE);
}

}

extern "C" void kernel_launch(void* const* d_in, const int* in_sizes, int n_in, void* d_out, int out_size) {
    static EncodeFn enc = nullptr;
    static void *sc = nullptr, *band = nullptr;
    if (!enc) {
        void* fn = nullptr;
        cudaDriverEntryPointQueryResult qr;
        cudaGetDriverEntryPoint("cuTensorMapEncodeTiled", &fn, cudaEnableDefault, &qr);
        enc = (EncodeFn)fn;
        cudaGetSymbolAddress(&sc, g_scratch);
        cudaGetSymbolAddress(&band, g_band);
        cudaFuncSetAttribute(fused_kernel, cudaFuncAttributeMaxDynamicSharedMemorySize, SMEM_BYTES);
    }
    CUtensorMap tg, td, tx, to;
    const char *wg = (const char*)d_in[9], *wu = (const char*)d_in[10];
    const bool swap = wu < wg;
    make_map(enc, &tg, swap ? wu : wg, F_, D_, F_ * 2, 32, 64, CU_TENSOR_MAP_SWIZZLE_64B, PROMG, 2, swap ? wg - wu : wu - wg);
    make_map(enc, &td, d_in[11], D_, F_, D_ * 2, 16, 224, CU_TENSOR_MAP_SWIZZLE_32B, PROMD);
    make_map(enc, &tx, d_in[0], D_, L_ / 8, D_ * 16, 16, 33, CU_TENSOR_MAP_SWIZZLE_32B, PROMX, 8, D_ * 2);
    make_map(enc, &to, d_out, D_, L_ / 8, D_ * 16, 16, 32, CU_TENSOR_MAP_SWIZZLE_NONE, 0, 8, D_ * 2, 1);
    Params p;
    p.u = (const bf16*)d_in[0]; p.logA = (const bf16*)d_in[1]; p.Aim = (const bf16*)d_in[2];
    p.Cre = (const bf16*)d_in[3]; p.Cim = (const bf16*)d_in[4]; p.logdt = (const bf16*)d_in[5];
    p.Dskip = (const bf16*)d_in[6]; p.wr = (const bf16*)d_in[8]; p.gatew = (const bf16*)d_in[12];
    p.out = (bf16*)d_out;
    p.sc = (Scratch*)sc; p.band = (const uint4*)band;
    p.gu_swap = swap;
    p.zero = 0;
    fused_kernel<<<NCTA, NTHREADS, SMEM_BYTES>>>(p, tg, td, tx, to);
}
```

```cpp
#include <cuda_runtime.h>
#include <cuda_bf16.h>
#include <cuda_fp16.h>
#include <cuda.h>
#include <stdint.h>

typedef __nv_bfloat16 bf16;

namespace {

constexpr int L_ = 2048, D_ = 1024, F_ = 3584;
constexpr int NCTA = 130;
constexpr int NTHREADS = 512;
#define AUXW 12
constexpr int MAIN_W0 = 0, AUX_W0 = AUXW, PREP_W0 = 20 - AUXW;
#define T0 3500
#define GAP 590
#define GAP1 530
#define GAP2 530
#define GAP3 550
#define STAG GAP
#define CSLEEP 50
#define SLACK 300
#define DELAY_X 150
#define TSLEEP 40
#define RS 2
#define BULKQ true
#define PQ 3
#define PROMG 2
#define PROMD 1
#define PROMX 0
#define LATE2 0
#define HW 21
constexpr int NGU_CTA = 112;

constexpr int OFF_RING = 0;
constexpr int OFF_SCR  = 6 * 8192;
constexpr int S_PL     = 1056;
constexpr int S_Q      = 8 * S_PL;
constexpr int OFF_S    = 114688;
constexpr int OFF_GP   = OFF_S + 4 * S_Q;
constexpr int U_PL     = 2240;
constexpr int U_CH     = 4416;
constexpr int OFF_U    = 151552;
constexpr int TAB_W    = 3200;
constexpr int T_PL     = 544;
constexpr int T_A      = 2192 - 26 * 8;
constexpr int T_B      = 2568 - 59 * 8;
constexpr int OFF_TAB  = 186880;
constexpr int OFF_XSEL = 212480;
constexpr int XS_ROW   = 2064;
constexpr int OFF_BAND = 228992;
constexpr int OFF_MISC = 229536;
constexpr int M_BARS   = OFF_MISC;
constexpr int M_DSK    = OFF_MISC + 2736;
constexpr int M_SINK   = OFF_MISC + 512;
constexpr int M_TAG    = OFF_MISC + 516;
constexpr int M_BMAP   = OFF_MISC + 528;
constexpr int M_DPIN   = OFF_MISC + 656;
constexpr int M_TOP    = OFF_MISC + 2704;
constexpr int SMEM_BYTES = OFF_MISC + 2768;
__device__ __forceinline__ uint32_t s_addr(uint32_t o, uint32_t half) { return o + (((half ^ (o >> 7)) & 1) << 4); }
__host__ __device__ constexpr uint32_t y_off(uint32_t q) { return OFF_RING + 32768 + (q & 1) * 8192 + (q >> 1) * 65536; }

constexpr int B_W = 0;
constexpr int B_E = 24;
constexpr int B_S = 36;
constexpr int B_Y = 40;
constexpr int B_DP = 44, B_U = 45, B_KG = 46, B_G = 47;
constexpr int B_F = 48;
constexpr int B_H = 60;
constexpr int B_X = 52, B_XE = 56;

struct BandTab { uint32_t w[11][12]; };
constexpr BandTab make_band() {
    BandTab b{};
    for (int cls = 0; cls < 11; cls++)
        for (int wd = 0; wd < 10; wd++) {
            const int tau = cls + 2 - 8 * ((wd < 4 ? wd : wd - 4) >> 1);
            const int lo = (wd < 4) ? ((wd & 1) ? -2 : 3) : ((wd & 1) ? -4 : -11), wid = (wd < 4 ? 3 : 7) + 2 * (wd & 1);
            b.w[cls][wd] = ((tau >= lo && tau < lo + wid) ? 0x3F80u : 0u) | ((tau - 4 >= lo && tau - 4 < lo + wid) ? 0x3F800000u : 0u);
        }
    return b;
}
constexpr int NTOP = 32;
struct Scratch {
    uint4 r[L_ / 4 * RS];
    uint4 g[L_ / 4];
    uint4 h[2][8 * F_ / 8];
    uint32_t top[NTOP][32];
    unsigned epoch;
};
__device__ __align__(128) Scratch g_scratch;
__device__ const __align__(16) BandTab g_band = make_band();

struct Params {
    const bf16 *u, *logA, *Aim, *Cre, *Cim, *logdt, *Dskip, *wr, *gatew;
    bf16* out;
    Scratch* sc;
    const uint4* band;
    uint32_t gu_swap;
    uint32_t zero;
};

#define WSTAMP(i) do {} while (0)
#define KSTAMP(i, dep) do {} while (0)
#define WDUMP() do {} while (0)
#define RSTAMP(i) do {} while (0)

#define NOALLOC ".L1::no_allocate"
__device__ __forceinline__ uint32_t smem_u32(const void* p) { return (uint32_t)__cvta_generic_to_shared(p); }
__device__ __forceinline__ void mbar_init(uint32_t b, uint32_t c) { asm volatile("mbarrier.init.shared::cta.b64 [%0], %1;" :: "r"(b), "r"(c) : "memory"); }
__device__ __forceinline__ void mbar_expect(uint32_t b, uint32_t tx) { asm volatile("mbarrier.arrive.expect_tx.shared::cta.b64 _, [%0], %1;" :: "r"(b), "r"(tx) : "memory"); }
__device__ __forceinline__ void mbar_arrive(uint32_t b) { asm volatile("mbarrier.arrive.shared::cta.b64 _, [%0];" :: "r"(b) : "memory"); }
__device__ __forceinline__ void mbar_wait(uint32_t b, uint32_t parity = 0) {
    asm volatile("{\n\t.reg .pred p;\nW%=:\n\tmbarrier.try_wait.parity.shared::cta.b64 p, [%0], %1, 20000;\n\t@!p bra W%=;\n\t}" :: "r"(b), "r"(parity) : "memory");
}
__device__ __forceinline__ uint32_t mapa(uint32_t addr, uint32_t rank) { uint32_t r; asm("mapa.shared::cluster.u32 %0, %1, %2;" : "=r"(r) : "r"(addr), "r"(rank)); return r; }
__device__ __forceinline__ void tma3d(uint32_t dst, const CUtensorMap* tm, int c0, int c1, uint32_t bar, uint32_t bytes) {
    asm volatile("{\n\t.reg .pred p;\n\telect.sync _|p, 0xffffffff;\n\t"
                 "@p mbarrier.arrive.expect_tx.shared::cta.b64 _, [%2], %5;\n\t"
                 "@p cp.async.bulk.tensor.3d.shared::cluster.global.mbarrier::complete_tx::bytes [%0], [%1, {%3, %4, 0}], [%2];\n\t}"
        :: "r"(dst), "l"(tm), "r"(bar), "r"(c0), "r"(c1), "r"(bytes) : "memory");
}
__device__ __forceinline__ void bulk_load(uint32_t dst, const void* src, uint32_t bytes, uint32_t bar) {
    asm volatile("{\n\t.reg .pred p;\n\telect.sync _|p, 0xffffffff;\n\t"
                 "@p mbarrier.arrive.expect_tx.shared::cta.b64 _, [%2], %3;\n\t"
                 "@p cp.async.bulk.shared::cluster.global.mbarrier::complete_tx::bytes [%0], [%1], %3, [%2];\n\t}"
        :: "r"(dst), "l"(src), "r"(bar), "r"(bytes) : "memory");
}
__device__ __forceinline__ void st_async16(uint32_t dst, const uint4& v, uint32_t bar) {
    asm volatile("st.async.weak.shared::cluster.mbarrier::complete_tx::bytes.v4.b32 [%0], {%1,%2,%3,%4}, [%5];"
                 :: "r"(dst), "r"(v.x), "r"(v.y), "r"(v.z), "r"(v.w), "r"(bar) : "memory");
}
__device__ __forceinline__ void bar_sync(int id, int n) { asm volatile("bar.sync %0, %1;" :: "r"(id), "r"(n) : "memory"); }
__device__ __forceinline__ void cp16(uint32_t dst, const void* src) { asm volatile("cp.async.cg.shared.global [%0], [%1], 16;" :: "r"(dst), "l"(src) : "memory"); }
__device__ __forceinline__ void cp_wait_all() { asm volatile("cp.async.wait_all;" ::: "memory"); }
__device__ __forceinline__ uint2 ldg64(const void* p) { uint2 v; asm volatile("ld.global.nc" NOALLOC ".v2.u32 {%0,%1}, [%2];" : "=r"(v.x), "=r"(v.y) : "l"(p)); return v; }
__device__ __forceinline__ uint4 ld_gpu128(const void* p) { uint4 v; asm volatile("ld.relaxed.gpu.global.v4.u32 {%0,%1,%2,%3}, [%4];" : "=r"(v.x), "=r"(v.y), "=r"(v.z), "=r"(v.w) : "l"(p) : "memory"); return v; }
__device__ __forceinline__ void st_gpu32(void* p, uint32_t v) { asm volatile("st.relaxed.gpu.global.u32 [%0], %1;" :: "l"(p), "r"(v) : "memory"); }

__device__ __forceinline__ void ldsm4(uint32_t a, uint32_t& r0, uint32_t& r1, uint32_t& r2, uint32_t& r3) {
    asm volatile("ldmatrix.sync.aligned.m8n8.x4.shared.b16 {%0,%1,%2,%3}, [%4];" : "=r"(r0), "=r"(r1), "=r"(r2), "=r"(r3) : "r"(a) : "memory");
}
__device__ __forceinline__ void ldsm4t(uint32_t a, uint32_t& r0, uint32_t& r1, uint32_t& r2, uint32_t& r3) {
    asm volatile("ldmatrix.sync.aligned.m8n8.x4.trans.shared.b16 {%0,%1,%2,%3}, [%4];" : "=r"(r0), "=r"(r1), "=r"(r2), "=r"(r3) : "r"(a) : "memory");
}
__device__ __forceinline__ uint32_t lds32(uint32_t a) { uint32_t v; asm volatile("ld.shared.u32 %0, [%1];" : "=r"(v) : "r"(a) : "memory"); return v; }
__device__ __forceinline__ uint2 lds64(uint32_t a) { uint2 v; asm volatile("ld.shared.v2.u32 {%0,%1}, [%2];" : "=r"(v.x), "=r"(v.y) : "r"(a) : "memory"); return v; }
__device__ __forceinline__ uint4 lds128(uint32_t a) { uint4 v; asm volatile("ld.shared.v4.u32 {%0,%1,%2,%3}, [%4];" : "=r"(v.x), "=r"(v.y), "=r"(v.z), "=r"(v.w) : "r"(a) : "memory"); return v; }
__device__ __forceinline__ void sts32(uint32_t a, uint32_t v) { asm volatile("st.shared.u32 [%0], %1;" :: "r"(a), "r"(v) : "memory"); }
__device__ __forceinline__ void sts16(uint32_t a, uint32_t v) { asm volatile("st.shared.u16 [%0], %1;" :: "r"(a), "h"((unsigned short)v) : "memory"); }
__device__ __forceinline__ void sts128(uint32_t a, uint32_t x, uint32_t y, uint32_t z, uint32_t w) { asm volatile("st.shared.v4.u32 [%0], {%1,%2,%3,%4};" :: "r"(a), "r"(x), "r"(y), "r"(z), "r"(w) : "memory"); }
__device__ __forceinline__ float ldsf(uint32_t a) { float v; asm volatile("ld.shared.f32 %0, [%1];" : "=f"(v) : "r"(a) : "memory"); return v; }

__device__ __forceinline__ void mma_bf(float (&d)[4], uint32_t a0, uint32_t a1, uint32_t a2, uint32_t a3, uint32_t b0, uint32_t b1) {
    asm volatile("mma.sync.aligned.m16n8k16.row.col.f32.bf16.bf16.f32 {%0,%1,%2,%3}, {%4,%5,%6,%7}, {%8,%9}, {%0,%1,%2,%3};"
        : "+f"(d[0]), "+f"(d[1]), "+f"(d[2]), "+f"(d[3]) : "r"(a0), "r"(a1), "r"(a2), "r"(a3), "r"(b0), "r"(b1));
}
__device__ __forceinline__ void mma_bf_z(float (&d)[4], uint32_t a0, uint32_t a1, uint32_t a2, uint32_t a3, uint32_t b0, uint32_t b1) {
    asm volatile("mma.sync.aligned.m16n8k16.row.col.f32.bf16.bf16.f32 {%0,%1,%2,%3}, {%4,%5,%6,%7}, {%8,%9}, {%10,%10,%10,%10};"
        : "=f"(d[0]), "=f"(d[1]), "=f"(d[2]), "=f"(d[3]) : "r"(a0), "r"(a1), "r"(a2), "r"(a3), "r"(b0), "r"(b1), "f"(0.f));
}
__device__ __forceinline__ void mma_bf_k8(float (&d)[4], uint32_t a0, uint32_t a1, uint32_t b0) {
    asm volatile("mma.sync.aligned.m16n8k8.row.col.f32.bf16.bf16.f32 {%0,%1,%2,%3}, {%4,%5}, {%6}, {%0,%1,%2,%3};"
        : "+f"(d[0]), "+f"(d[1]), "+f"(d[2]), "+f"(d[3]) : "r"(a0), "r"(a1), "r"(b0));
}
__device__ __forceinline__ void mma_h(float (&d)[4], uint32_t a0, uint32_t a1, uint32_t a2, uint32_t a3, uint32_t b0, uint32_t b1) {
    asm volatile("mma.sync.aligned.m16n8k16.row.col.f32.f16.f16.f32 {%0,%1,%2,%3}, {%4,%5,%6,%7}, {%8,%9}, {%0,%1,%2,%3};"
        : "+f"(d[0]), "+f"(d[1]), "+f"(d[2]), "+f"(d[3]) : "r"(a0), "r"(a1), "r"(a2), "r"(a3), "r"(b0), "r"(b1));
}
__device__ __forceinline__ uint32_t pack_bf(float lo, float hi) { uint32_t r; asm("cvt.rn.bf16x2.f32 %0, %1, %2;" : "=r"(r) : "f"(hi), "f"(lo)); return r; }
__device__ __forceinline__ uint32_t pack_h(float lo, float hi) { uint32_t r; asm("cvt.rn.f16x2.f32 %0, %1, %2;" : "=r"(r) : "f"(hi), "f"(lo)); return r; }
__device__ __forceinline__ float bf_lo(uint32_t v) { return __uint_as_float(v << 16); }
__device__ __forceinline__ float bf_hi(uint32_t v) { return __uint_as_float(v & 0xffff0000u); }
__device__ __forceinline__ float bf_round(float x) { return __uint_as_float(pack_bf(0.f, x) & 0xffff0000u); }
__device__ __forceinline__ uint32_t hmul2_bf(uint32_t a, uint32_t b) { uint32_t r; asm("mul.rn.bf16x2 %0, %1, %2;" : "=r"(r) : "r"(a), "r"(b)); return r; }
__device__ __forceinline__ float ex2f(float x) { float r; asm("ex2.approx.ftz.f32 %0, %1;" : "=f"(r) : "f"(x)); return r; }

__device__ __forceinline__ float exp_acc(float x) {
    const float t = x * 1.4426950216293335f;
    const float r = fmaf(x, 1.4426950216293335f, -t) + x * 1.9259629911266175e-8f;
    return ex2f(t) * fmaf(r, 0.6931471805599453f, 1.f);
}
__device__ __forceinline__ float sigmoid_f(float x) { return __fdividef(1.f, 1.f + ex2f(-x * 1.4426950408889634f)); }
__device__ __forceinline__ void cexp_pow(float lr, float li, float e, float& zr, float& zi) {
    const float mag = ex2f(lr * e * 1.4426950408889634f);
    const float th = li * e;
    const float k = (th * 0.15915494309189535f + 12582912.f) - 12582912.f;
    float r = fmaf(-k, 6.2831854820251465f, th);
    r = fmaf(-k, -1.7484555314695172e-7f, r);
    zr = mag * __cosf(r);
    zi = mag * __sinf(r);
}
__device__ __forceinline__ uint32_t hcmul(uint32_t a, uint32_t k, uint32_t kp) {
    const __half2 A = *reinterpret_cast<const __half2*>(&a);
    const __half2 r = __hfma2(__high2half2(A), *reinterpret_cast<const __half2*>(&kp), __hmul2(__low2half2(A), *reinterpret_cast<const __half2*>(&k)));
    return *reinterpret_cast<const uint32_t*>(&r);
}
#define CMUL(orr, oi, ar, ai, br, bi) do { float _r = (ar) * (br) - (ai) * (bi); float _i = (ar) * (bi) + (ai) * (br); orr = _r; oi = _i; } while (0)
#define CSQ(orr, oi, ar, ai) do { float _r = (ar) * (ar) - (ai) * (ai); float _i = 2.f * (ar) * (ai); orr = _r; oi = _i; } while (0)

__device__ __forceinline__ void mma_bf_k8z(float (&d)[4], uint32_t a0, uint32_t a1, uint32_t b0) {
    asm volatile("mma.sync.aligned.m16n8k8.row.col.f32.bf16.bf16.f32 {%0,%1,%2,%3}, {%4,%5}, {%6}, {%7,%7,%7,%7};"
        : "=f"(d[0]), "=f"(d[1]), "=f"(d[2]), "=f"(d[3]) : "r"(a0), "r"(a1), "r"(b0), "f"(0.f));
}
__device__ __forceinline__ void mma_hh_k8(uint32_t& d0, uint32_t& d1, uint32_t a0, uint32_t a1, uint32_t b0) {
    asm volatile("mma.sync.aligned.m16n8k8.row.col.f16.f16.f16.f16 {%0,%1}, {%2,%3}, {%4}, {%5,%5};"
        : "=r"(d0), "=r"(d1) : "r"(a0), "r"(a1), "r"(b0), "r"(0));
}
__device__ __forceinline__ uint32_t pin(uint32_t x, int lane) { return __shfl_sync(0xffffffffu, x, lane); }
template <class T> __device__ __forceinline__ T* pin(T* x, int lane) { return (T*)__shfl_sync(0xffffffffu, (unsigned long long)x, lane); }
__device__ __forceinline__ void lds128_if(bool on, uint32_t a, uint32_t (&v)[4]) {
    asm volatile("{\n\t.reg .pred p;\n\tsetp.ne.u32 p, %5, 0;\n\t@p ld.shared.v4.u32 {%0,%1,%2,%3}, [%4];\n\t}"
        : "+r"(v[0]), "+r"(v[1]), "+r"(v[2]), "+r"(v[3]) : "r"(a), "r"((uint32_t)on) : "memory");
}
__device__ __forceinline__ uint32_t hfma2_bf(uint32_t a, uint32_t b, uint32_t c) { uint32_t r; asm("fma.rn.bf16x2 %0, %1, %2, %3;" : "=r"(r) : "r"(a), "r"(b), "r"(c)); return r; }
__device__ __forceinline__ uint32_t row_elem(uint32_t row) { return ((row >> 5) & 4) | ((row >> 2) & 2) | ((row >> 4) & 1); }
__device__ __forceinline__ uint32_t gate_pos(uint32_t row) { return ((row >> 9) << 8) | ((row & 7) << 5) | (row_elem(row) << 2) | ((row >> 5) & 3); }

template <int N, bool BULK>
__device__ __forceinline__ void mix_rows(const Params& p, const CUtensorMap* tm_out, uint32_t sb, int Q0, int Q1, int w, int h, int pr, int lane) {
    const int g = lane >> 2, t = lane & 3, mi = lane >> 3, r = lane & 7;
    const int m8 = 16 * (g >> 2) + ((g >> 1) & 1) + 2 * (g & 1);
    uint32_t yi = sb + (4 * (r >> 1) + 2 * (mi & 1) + (r & 1)) * 512 + (((4 * w + (mi >> 1)) ^ r) << 4);
    uint32_t xs = sb + OFF_S + s_addr(w * S_PL + 32 + m8 * 32, t >> 1) + ((t & 1) << 3);
    uint32_t gs = sb + OFF_GP + w * 64 + g * 8, os = sb + OFF_TAB + w * TAB_W + m8 * 32 + t * 8;
    if (BULK) { yi = pin(yi, lane); xs = pin(xs, lane); gs = pin(gs, lane); os = pin(os, lane); }
    mbar_wait(sb + M_BARS + 8 * B_Y);
#pragma unroll 1
    for (int Q = Q0; Q < Q1; Q++) {
        uint2 xq[N][4];
        uint32_t gg[N][4], sw[N];
#pragma unroll
        for (int n = 0; n < N; n++) {
#pragma unroll
            for (int i = 0; i < 4; i++) xq[n][i] = lds64((xs ^ (((i ^ n) & 1) << 4)) + Q * S_Q + n * 4 * S_PL + i * 128);
            const uint2 gq = lds64(gs + Q * 512 + n * 256);
            sw[n] = lds32(sb + M_BMAP + w * 16 + n * 64 + Q * 4);
#pragma unroll
            for (int i = 0; i < 4; i++) {
                gg[n][i] = __byte_perm(i < 2 ? gq.x : gq.y, 0, (i & 1) ? 0x3232 : 0x1010);
                const uint32_t og = hfma2_bf(gg[n][i], 0xBF80BF80u, 0x3F803F80u);
                xq[n][i].x = hmul2_bf(og, xq[n][i].x); xq[n][i].y = hmul2_bf(og, xq[n][i].y);
            }
        }
        mbar_wait(sb + M_BARS + 8 * (B_Y + Q));
        __syncwarp();
#pragma unroll
        for (int n = 0; n < N; n++) {
#pragma unroll
            for (int x = 0; x < 2; x++) {
                uint32_t y[4];
                ldsm4t((yi ^ (x << 5)) + y_off(Q) + n * 256, y[0], y[1], y[2], y[3]);
#pragma unroll
                for (int e = 0; e < 2; e++) {
                    uint2& o = xq[n][2 * x + e];
                    o.x = hfma2_bf(gg[n][2 * x + e], y[2 * e], o.x); o.y = hfma2_bf(gg[n][2 * x + e], y[2 * e + 1], o.y);
                }
            }
        }
        if (BULK && (sw[0] | sw[N - 1]) == 0) {
#pragma unroll
            for (int n = 0; n < N; n++)
#pragma unroll
                for (int i = 0; i < 4; i++)
                    asm volatile("st.shared.v2.u32 [%0], {%1, %2};" :: "r"(os + Q * 1024 + n * 4 * TAB_W + i * 128), "r"(xq[n][i].x), "r"(xq[n][i].y) : "memory");
            asm volatile("fence.proxy.async.shared::cta;" ::: "memory");
            __syncwarp();
#pragma unroll
            for (int n = 0; n < N; n++)
                asm volatile("{\n\t.reg .pred p;\n\telect.sync _|p, 0xffffffff;\n\t"
                             "@p cp.async.bulk.tensor.3d.global.shared::cta.bulk_group [%1, {%2, %3, %4}], [%0];\n\t}"
                    :: "r"(sb + OFF_TAB + (w + 4 * n) * TAB_W + Q * 1024), "l"(tm_out), "r"(16 * pr), "r"(64 * Q + 32 * h), "r"(w + 4 * n) : "memory");
        } else {
            bf16* op = p.out + (size_t)(512 * Q + 256 * h + 8 * m8 + w) * D_ + 16 * pr + 4 * t;
#pragma unroll
            for (int n = 0; n < N; n++)
#pragma unroll
                for (int i = 0; i < 4; i++)
                    if (!((sw[n] >> (4 * g)) & (1u << i))) *(uint2*)(op + (size_t)(32 * i + 4 * n) * D_) = xq[n][i];
        }
    }
}

__global__ void __cluster_dims__(2, 1, 1) __launch_bounds__(NTHREADS, 1)
fused_kernel(const Params p, const __grid_constant__ CUtensorMap tm_gu, const __grid_constant__ CUtensorMap tm_down,
             const __grid_constant__ CUtensorMap tm_x, const __grid_constant__ CUtensorMap tm_out) {
    extern __shared__ __align__(1024) unsigned char smem[];
    const uint32_t sb = smem_u32(smem);
    int tid;
    asm volatile("mov.u32 %0, %%tid.x;" : "=r"(tid));
    const int pw = tid >> 5, lane = tid & 31;
    const int c = blockIdx.x, h = c & 1, pr = c >> 1;
    const uint32_t bars = sb + M_BARS;

    if (c >= 128) {
        if (c != 128) return;
        RSTAMP(5);
        const unsigned tag = (*(volatile unsigned*)&p.sc->epoch + 1) & 0xffffu;
        const uint32_t list = sb + 128;
#pragma unroll 1
        for (int pass = 0; pass < 2; pass++) {
            sts128(list + 16 * tid, 0, 0, 0, 0);
            if (tid == 0) sts32(sb + 64, 0);
            uint32_t key[4];
            bool ok = false;
#pragma unroll 1
            for (int it = 0; it < (1 << 22); it++) {
                const uint4 a = ld_gpu128(&p.sc->r[tid * RS]);
                key[0] = a.x; key[1] = a.y; key[2] = a.z; key[3] = a.w;
                ok = (((a.x ^ tag) | (a.y ^ tag) | (a.z ^ tag) | (a.w ^ tag)) & 0xffffu) == 0;
                if (ok || !pass) break;
            }
            WSTAMP(0);
            uint32_t m = 0;
#pragma unroll
            for (int i = 0; i < 4; i++) {
                key[i] = ((pass ? key[i] : (lane + i) << 16) & 0xffff0000u) | (uint32_t)(2047 - (4 * tid + i));
                m = max(m, key[i]);
            }
            const uint32_t wm = __reduce_max_sync(0xffffffffu, m);
            if (lane == 0) sts32(sb + pw * 4, wm);
            __syncthreads();
            uint32_t thr = 0xffffffffu;
#pragma unroll
            for (int i = 0; i < 4; i++) { const uint4 q = lds128(sb + 16 * i); thr = min(thr, min(max(q.x, q.y), max(q.z, q.w))); }
            if (thr != 1) WSTAMP(1);
            if (m >= thr) {
                uint32_t pos;
                asm volatile("atom.shared.add.u32 %0, [%1], %2;" : "=r"(pos) : "r"(sb + 64), "r"(4 * ((key[0] >= thr) + (key[1] >= thr) + (key[2] >= thr) + (key[3] >= thr))) : "memory");
#pragma unroll
                for (int i = 0; i < 4; i++) if (key[i] >= thr) { sts32(list + pos, key[i]); pos += 4; }
            }
            __syncthreads();
            const uint32_t nc4 = lds32(sb + 64);
            if (nc4 != 1) WSTAMP(2);
#pragma unroll 1
            for (uint32_t j = 4 * pw; j < nc4; j += 64) {
                const uint32_t mine = lds32(list + j);
                int rank = 0;
#pragma unroll 1
                for (uint32_t i = 0; i < nc4; i += 128) rank += __popc(__ballot_sync(0xffffffffu, lds32(list + i + 4 * lane) > mine));
                if (rank < 8 && lane == 0) sts32(sb + 96 + 4 * rank, mine);
            }
            __syncthreads();
            if (tid < 8 * NTOP) st_gpu32(&p.sc->top[tid >> 3][tid & 7], lds32(sb + 96 + 4 * (tid & 7)) | (((tag + pass - 1) & 31) << 11));
            WSTAMP(3);
            if (!pass) RSTAMP(4);
        }
        WDUMP();
        return;
    }

    WSTAMP(0);
    if (pw < 8) {
        uint2 v_la, v_ai, v_cr, v_ci;
        uint32_t ldt16;
        const int d = 8 * c + pw - MAIN_W0;
        const size_t po = (size_t)d * 128 + 4 * lane;
        v_la = ldg64(p.logA + po); v_ai = ldg64(p.Aim + po); v_cr = ldg64(p.Cre + po); v_ci = ldg64(p.Cim + po);
        asm volatile("ld.global.nc.u16 %0, [%1];" : "=r"(ldt16) : "l"(p.logdt + d));
        if (lane == 0) asm volatile("cp.async.ca.shared.global [%0], [%1], 4;" :: "r"(sb + M_DSK + 4 * (pw - MAIN_W0)), "l"(p.Dskip + (d & ~1)) : "memory");
        asm volatile("barrier.cluster.arrive.relaxed.aligned;" ::: "memory");
        const int warp = pw - MAIN_W0;
        asm volatile("setmaxnreg.inc.sync.aligned.u32 168;");
        const int g = lane >> 2, t = lane & 3;
        const int mi = lane >> 3, r = lane & 7;
        const uint32_t TB = sb + OFF_TAB + warp * TAB_W;
        const uint32_t UB = sb + OFF_U + warp * U_CH;
        if (mi < 2) sts128(UB + mi * U_PL + r * 16, 0, 0, 0, 0);
#pragma unroll
        for (int i = 0; i < 6; i++) sts128(TB + 16 * (lane + 32 * i), 0, 0, 0, 0);
        if (lane < 8) sts128(TB + 16 * (lane + 192), 0, 0, 0, 0);
        __syncwarp();

        uint32_t cfix;
        {
            KSTAMP(4, v_la.x ^ v_ai.x ^ v_cr.x ^ v_ci.x ^ ldt16);
            const float dt = bf_round(exp_acc(__uint_as_float(ldt16 << 16)));
            float lr[4], li[4], cr[4], ci[4];
            float inv;
            {
                const uint32_t la[2] = {v_la.x, v_la.y}, ai[2] = {v_ai.x, v_ai.y}, vr[2] = {v_cr.x, v_cr.y}, vi[2] = {v_ci.x, v_ci.y};
                const uint32_t m2 = __vmaxu2(__vmaxu2(vr[0] & 0x7fff7fffu, vr[1] & 0x7fff7fffu), __vmaxu2(vi[0] & 0x7fff7fffu, vi[1] & 0x7fff7fffu));
                const uint32_t mx = __reduce_max_sync(0xffffffffu, max(m2, m2 << 16));
                const uint32_t e = min(max(mx >> 23, 11u), 254u);
                const float sc = __uint_as_float((264u - e) << 23);
                inv = __uint_as_float((e - 10u) << 23) * (2.f * dt);
#pragma unroll
                for (int i = 0; i < 4; i++) {
                    const float a = (i & 1) ? bf_hi(la[i >> 1]) : bf_lo(la[i >> 1]);
                    const float b = (i & 1) ? bf_hi(ai[i >> 1]) : bf_lo(ai[i >> 1]);
                    lr[i] = -bf_round(exp_acc(a)) * dt;
                    li[i] = b * dt;
                    cr[i] = ((i & 1) ? bf_hi(vr[i >> 1]) : bf_lo(vr[i >> 1])) * sc;
                    ci[i] = ((i & 1) ? bf_hi(vi[i >> 1]) : bf_lo(vi[i >> 1])) * sc;
                }
            }
            const uint32_t SX = sb + OFF_SCR + warp * 8192;
            const uint32_t sw = SX + (lane << 4);
#define PUT(buf, row, v) sts128(((sw + (row) * 512) ^ ((row) << 4)) + (buf) * 4096, v[0], v[1], v[2], v[3])
#define EMIT(bufa, rowa, bufb, rowb, xr, xi, k, kp) do { uint32_t pk[4], pd[4]; \
                _Pragma("unroll") for (int i = 0; i < 4; i++) { pk[i] = pack_h(xr[i], xi[i]); pd[i] = hcmul(pk[i], k[i], kp[i]); } \
                PUT(bufa, rowa, pk); PUT(bufb, rowb, pd); } while (0)
#define CMUL4(orr, oi, ar, ai, br, bi) _Pragma("unroll") for (int i = 0; i < 4; i++) CMUL(orr[i], oi[i], ar[i], ai[i], br[i], bi[i])
#define CSQ4(orr, oi, ar, ai) _Pragma("unroll") for (int i = 0; i < 4; i++) CSQ(orr[i], oi[i], ar[i], ai[i])
            float z1r[4], z1i[4], z2r[4], z2i[4], z8r[4], z8i[4], z256r[4], z256i[4];
            uint32_t k128[4], k128p[4], k4[4], k4p[4];
#pragma unroll
            for (int i = 0; i < 4; i++) {
                float tr, ti;
                cexp_pow(lr[i], li[i], 1.f, z1r[i], z1i[i]);
                CSQ(z2r[i], z2i[i], z1r[i], z1i[i]);
                CSQ(tr, ti, z2r[i], z2i[i]);
                k4[i] = pack_h(tr, ti); k4p[i] = pack_h(-ti, tr);
                CSQ(z8r[i], z8i[i], tr, ti);
                cexp_pow(lr[i], li[i], 128.f, tr, ti);
                k128[i] = pack_h(tr, ti); k128p[i] = pack_h(-ti, tr);
                CSQ(z256r[i], z256i[i], tr, ti);
                sts32(TB + i * T_PL + 16 + 4 * lane, k128[i]);
                sts32(TB + i * T_PL + 160 + 4 * lane, k128p[i]);
            }
            KSTAMP(5, k128[3] ^ k4[3]);
            uint32_t Ya[16][4];
            {
                float w1r[4], w1i[4], ar[4], ai[4], br[4], bi[4];
                uint32_t k8[4], k8p[4];
                const uint32_t one[4] = {0x3C00u, 0x3C00u, 0x3C00u, 0x3C00u};
#pragma unroll
                for (int i = 0; i < 4; i++) {
                    k8[i] = pack_h(z8r[i], -z8i[i]); k8p[i] = pack_h(z8i[i], z8r[i]);
                    CSQ(w1r[i], w1i[i], z8r[i], z8i[i]); w1i[i] = -w1i[i];
                }
                PUT(0, 0, one); PUT(1, 0, k8);
                EMIT(0, 1, 1, 1, w1r, w1i, k8, k8p);
                CSQ4(ar, ai, w1r, w1i);            EMIT(0, 2, 1, 2, ar, ai, k8, k8p);
                CMUL4(br, bi, ar, ai, w1r, w1i);   EMIT(0, 3, 1, 3, br, bi, k8, k8p);
                CSQ4(ar, ai, ar, ai);              EMIT(0, 4, 1, 4, ar, ai, k8, k8p);
                CMUL4(ar, ai, ar, ai, w1r, w1i);   EMIT(0, 5, 1, 5, ar, ai, k8, k8p);
                CSQ4(br, bi, br, bi);              EMIT(0, 6, 1, 6, br, bi, k8, k8p);
                CMUL4(br, bi, br, bi, w1r, w1i);   EMIT(0, 7, 1, 7, br, bi, k8, k8p);
                __syncwarp();
                KSTAMP(6, 0);
                const uint32_t ab = SX + (mi & 1) * 4096 + r * 512, ax = ((mi >> 1) ^ r) << 4;
#pragma unroll
                for (int ks = 0; ks < 16; ks++) ldsm4(ab + (ks >> 2) * 128 + (ax ^ ((ks & 3) << 5)), Ya[ks][0], Ya[ks][1], Ya[ks][2], Ya[ks][3]);
                __syncwarp();
            }
            KSTAMP(7, Ya[15][0]);
            const uint32_t ld0 = SX + r * 512 + ((mi ^ r) << 4), ld1 = ld0 ^ 64;
            float R[5][4], xr[4], xi[4];
            {
                float yr[4], yi[4];
                EMIT(0, 0, 0, 1, cr, ci, k4, k4p);
                CMUL4(yr, yi, cr, ci, z1r, z1i);        EMIT(0, 2, 0, 3, yr, yi, k4, k4p);
                CMUL4(xr, xi, cr, ci, z256r, z256i);    EMIT(1, 0, 1, 1, xr, xi, k4, k4p);
                CMUL4(yr, yi, yr, yi, z1r, z1i);        EMIT(0, 4, 0, 5, yr, yi, k4, k4p);
                CMUL4(cr, ci, xr, xi, z2r, z2i);        EMIT(1, 2, 1, 3, cr, ci, k4, k4p);
                CMUL4(yr, yi, yr, yi, z1r, z1i);        EMIT(0, 6, 0, 7, yr, yi, k4, k4p);
                CMUL4(xr, xi, xr, xi, z256r, z256i);    EMIT(1, 4, 1, 5, xr, xi, k4, k4p);
                CMUL4(xr, xi, xr, xi, z256r, z256i);    EMIT(1, 6, 1, 7, xr, xi, k4, k4p);
            }
            __syncwarp();
            {
                KSTAMP(8, 0);
                uint32_t bd[2][4] = {{0, 0, 0, 0}, {0, 0, 0, 0}};
                const bool on = (g >> 1) == t;
#pragma unroll
                for (int i = 0; i < 4; i++) { R[i][0] = R[i][1] = R[i][2] = R[i][3] = 0.f; }
#pragma unroll
                for (int k2 = 0; k2 < 8; k2++) {
                    uint32_t x[4], y[4], a1[2][4];
                    lds128_if(on, TB + t * T_PL + 16 + (g & 1) * 144 + 16 * k2, bd[k2 & 1]);
                    ldsm4(((k2 & 1) ? ld1 : ld0) + (k2 >> 1) * 128, x[0], x[1], x[2], x[3]);
                    ldsm4(((k2 & 1) ? ld1 : ld0) + (k2 >> 1) * 128 + 4096, y[0], y[1], y[2], y[3]);
#pragma unroll
                    for (int u = 0; u < 2; u++) {
                        mma_hh_k8(a1[u][0], a1[u][1], Ya[2 * k2 + u][0], Ya[2 * k2 + u][1], bd[k2 & 1][2 * u]);
                        mma_hh_k8(a1[u][2], a1[u][3], Ya[2 * k2 + u][2], Ya[2 * k2 + u][3], bd[k2 & 1][2 * u + 1]);
                    }
#pragma unroll
                    for (int u = 0; u < 2; u++) {
                        const uint32_t(&a0)[4] = Ya[2 * k2 + u];
                        mma_h(R[0], a0[0], a0[1], a0[2], a0[3], x[2 * u], x[2 * u + 1]);
                        mma_h(R[2], a0[0], a0[1], a0[2], a0[3], y[2 * u], y[2 * u + 1]);
                        mma_h(R[1], a1[u][0], a1[u][1], a1[u][2], a1[u][3], x[2 * u], x[2 * u + 1]);
                        mma_h(R[3], a1[u][0], a1[u][1], a1[u][2], a1[u][3], y[2 * u], y[2 * u + 1]);
                    }
                }
            }
            __syncwarp();
            KSTAMP(9, __float_as_uint(R[3][0]));
            asm volatile("barrier.cluster.wait.acquire.aligned;" ::: "memory");
            CMUL4(xr, xi, xr, xi, z256r, z256i);
            float s1024 = (xr[0] + xr[1]) + (xr[2] + xr[3]);
            CMUL4(xr, xi, xr, xi, z8r, z8i);        EMIT(0, 0, 0, 1, xr, xi, k128, k128p);
            CMUL4(xr, xi, xr, xi, z256r, z256i);    EMIT(0, 2, 0, 3, xr, xi, k128, k128p);
            CMUL4(xr, xi, xr, xi, z256r, z256i);    EMIT(0, 4, 0, 5, xr, xi, k128, k128p);
            CMUL4(xr, xi, xr, xi, z256r, z256i);    EMIT(0, 6, 0, 7, xr, xi, k128, k128p);
            __syncwarp();
            {
                KSTAMP(10, 0);
                float a1[4] = {0.f, 0.f, 0.f, 0.f};
                R[4][0] = R[4][1] = R[4][2] = R[4][3] = 0.f;
#pragma unroll
                for (int k2 = 0; k2 < 8; k2++) {
                    uint32_t x[4];
                    ldsm4(((k2 & 1) ? ld1 : ld0) + (k2 >> 1) * 128, x[0], x[1], x[2], x[3]);
                    mma_h(R[4], Ya[2 * k2][0], Ya[2 * k2][1], Ya[2 * k2][2], Ya[2 * k2][3], x[0], x[1]);
                    mma_h(a1, Ya[2 * k2 + 1][0], Ya[2 * k2 + 1][1], Ya[2 * k2 + 1][2], Ya[2 * k2 + 1][3], x[2], x[3]);
                }
#pragma unroll
                for (int i = 0; i < 4; i++) R[4][i] += a1[i];
            }
            if (lane == 0) mbar_arrive(bars + 8 * B_KG + (__float_as_uint(R[4][0]) & p.zero));
            KSTAMP(11, __float_as_uint(R[4][0]));
#undef PUT
#undef EMIT
#pragma unroll
            for (int o = 16; o > 0; o >>= 1) s1024 += __shfl_xor_sync(0xffffffffu, s1024, o);
            uint32_t w[4][4], dsk = 0;
            if (lane == 0) { cp_wait_all(); asm volatile("ld.shared.u16 %0, [%1];" : "=r"(dsk) : "r"(sb + M_DSK + 4 * warp + 2 * (warp & 1)) : "memory"); }
#pragma unroll
            for (int a = 0; a < 4; a++) {
                const float v0 = (a == 0) ? fmaf(R[0][0], inv, __uint_as_float(dsk << 16)) : R[a][0] * inv;
                const float v1 = R[a][1] * inv, v2 = R[a][2] * inv, v3 = R[a][3] * inv;
                w[a][0] = pack_bf(v0, 0.f); w[a][1] = pack_bf(v1, v0); w[a][2] = pack_bf(v2, v1); w[a][3] = pack_bf(v3, v2);
            }
            const uint32_t wb = TB + 16 + 16 * g, w1 = wb + t * T_PL, w2 = wb + 256 + 2 * t * T_PL;
            const uint32_t w3 = (t == 0) ? wb + 256 + 3 * T_PL : TB + T_A + 8 * (16 * t + g);
            const uint32_t w3s = (t == 0) ? 128 : 64, w3o = (t == 0) ? 8 : 12;
            const uint32_t k512 = __shfl_sync(0xffffffffu, w[2][1], 2);
#pragma unroll
            for (int a = 0; a < 2; a++) {
                sts128(w1 + 128 * a, w[a][0], w[a][1], w[a][2], w[a][3]);
                const uint32_t(&q)[4] = w[2 + a];
                if (t < 2) sts128(w2 + 128 * a, q[0], q[1], q[2], q[3]);
                if (t == 0) { sts128(w2 + T_PL + 128 * a, q[0], q[1], q[2], q[3]); sts32(w3 + 128 * a + 4, q[2]); }
                if (t != 1 && (a == 1 || lane != 2)) sts32(w3 + w3s * a, q[1]);
                if (t != 1) sts32(w3 + w3s * a + w3o, q[3]);
            }
            if (lane < 4)
                sts128(w1 + 512, __byte_perm(k512, 0, t == 3 ? 0x3210 : 0x4432), __byte_perm(k512, 0, t < 2 ? 0x3210 : t == 2 ? 0x3244 : 0x1044),
                       __byte_perm(k512, 0, t < 2 ? 0x1044 : 0x4444), 0);
            __syncwarp();
#pragma unroll
            for (int a = 0; a < 2; a++) {
                sts16(w1 + 128 * a + 18, w[a][3]);
                const uint32_t(&q)[4] = w[2 + a];
                if (t < 2) sts16(w2 + 128 * a + 18, q[3]);
                if (t == 0) { sts16(w2 + T_PL + 128 * a + 18, q[3]); sts16(w3 + 128 * a + 14, q[3]); }
            }
            if (t == 0) sts16(w3 + 128 - 4, w[3][0]);
            if (lane == 2 || (t == 0 && g > 0)) sts16(lane == 2 ? TB + 16 + 3 * T_PL + 4 * 127 : w3 - 4, w[2][0]);
            {
                const uint32_t b0 = pack_bf(R[4][0] * inv, R[4][2] * inv), b1 = pack_bf(R[4][1] * inv, R[4][3] * inv);
                const uint32_t wq = TB + T_B + 8 * (65 + 16 * t + g);
                sts32(wq, b0); sts32(wq + 12, b0); sts32(wq + 64, b1); sts32(wq + 76, b1);
            }
            cfix = pack_bf(s1024 * inv, s1024 * inv);
            if (lane == 0) sts32(TB + T_A + 8 * 64, cfix);
            __syncwarp();
        }
        WSTAMP(1);

        mbar_wait(bars + 8 * B_U);
        WSTAMP(2);

        float D[16][4];
        {
            const int x5 = g - t + 5;
            const uint32_t tabD = TB + (x5 & 3) * T_PL + (x5 & 12) + 16;
            {
                const uint32_t a1 = lds32(tabD - 8), a0 = p.zero;
#pragma unroll
                for (int jq = 0; jq < 4; jq++) {
                    uint32_t b[4];
                    ldsm4(UB + (9 + lane) * 16 + jq * 512, b[0], b[1], b[2], b[3]);
#pragma unroll
                    for (int i = 0; i < 4; i++) mma_bf_k8z(D[4 * jq + i], a0, a1, b[i]);
                }
            }
            const uint32_t ua = UB + (mi & 1) * U_PL + (8 + 8 * (mi >> 1) + r) * 16;
#pragma unroll 1
            for (int k0 = 0; k0 < 8; k0++) {
                uint32_t Uf[16][2];
#pragma unroll
                for (int jp = 0; jp < 8; jp++) ldsm4(ua + jp * 256 - k0 * 16, Uf[2 * jp][0], Uf[2 * jp][1], Uf[2 * jp + 1][0], Uf[2 * jp + 1][1]);
#pragma unroll
                for (int k1 = 0; k1 < 4; k1++) {
                    const uint32_t ta = tabD + 16 * (8 * k1 + k0);
                    const uint32_t a0 = lds32(ta), a1 = lds32(ta + 8), a2 = lds32(ta - 8), a3 = a0 ^ p.zero;
#pragma unroll
                    for (int J = k1; J < 16; J++) mma_bf(D[J], a0, a1, a2, a3, Uf[J - k1][0], Uf[J - k1][1]);
                }
                if (k0 == 0) {
                    const uint32_t ta = tabD + 16 * 32;
                    const uint32_t a0 = lds32(ta), a1 = lds32(ta + 8), a2 = lds32(ta - 8), a3 = a0 ^ p.zero;
#pragma unroll
                    for (int J = 4; J < 16; J++) mma_bf(D[J], a0, a1, a2, a3, Uf[J - 4][0], Uf[J - 4][1]);
                    const uint32_t f0 = (cfix ^ 0x80008000u) & (g == t ? 0xffffu : g == t + 4 ? 0xffff0000u : 0u);
                    const uint32_t f1 = p.zero, f2 = p.zero + p.zero, f3 = f0 ^ p.zero;
#pragma unroll
                    for (int J = 8; J < 16; J++) mma_bf(D[J], f0, f1, f2, f3, Uf[J - 8][0], Uf[J - 8][1]);
                }
            }
        }
        WSTAMP(3);
        {
            const int ch = 8 * h + warp;
            const uint32_t yo = sb + ch * 512 + ((lane ^ (((ch >> 2) << 1) | (ch & 1))) << 4);
            const uint32_t yr = mapa(yo, h ^ 1), ybr = mapa(bars + 8 * B_Y, h ^ 1);
            auto ship = [&](const int Q) {
                uint4 y[2];
#pragma unroll
                for (int hh = 0; hh < 2; hh++) {
                    const int J = 4 * Q + 2 * hh;
                    y[hh] = make_uint4(pack_bf(D[J][0], D[J][1]), pack_bf(D[J][2], D[J][3]), pack_bf(D[J + 1][0], D[J + 1][1]), pack_bf(D[J + 1][2], D[J + 1][3]));
                }
                if (!(Q & 1)) mbar_wait(bars + 8 * (B_F + (Q >> 1)));
                asm volatile("{\n\t.reg .pred p;\n\tsetp.eq.u32 p, %11, 0;\n\t"
                             "@p st.async.weak.shared::cluster.mbarrier::complete_tx::bytes.v4.b32 [%9], {%4,%5,%6,%7}, [%10];\n\t"
                             "@!p st.async.weak.shared::cluster.mbarrier::complete_tx::bytes.v4.b32 [%9], {%0,%1,%2,%3}, [%10];\n\t"
                             "@p st.shared.v4.b32 [%8], {%0,%1,%2,%3};\n\t@!p st.shared.v4.b32 [%8], {%4,%5,%6,%7};\n\t}"
                             :: "r"(y[0].x), "r"(y[0].y), "r"(y[0].z), "r"(y[0].w), "r"(y[1].x), "r"(y[1].y), "r"(y[1].z), "r"(y[1].w),
                                "r"(yo + y_off(Q)), "r"(yr + y_off(Q)), "r"(ybr + 8 * Q), "r"(h) : "memory");
                __syncwarp();
                if (lane == 0) mbar_arrive(bars + 8 * (B_Y + Q));
            };
            ship(0);
            const uint4 bA = lds128(sb + OFF_BAND + (g - t + 3) * 48), bB = lds128(sb + OFF_BAND + (g - t + 3) * 48 + 16);
            const uint2 bC = lds64(sb + OFF_BAND + (g - t + 3) * 48 + 32);
            uint2 QA[5][2], QB[8];
            const uint32_t tq = TB + 8 * (1 + g - 2 * t);
#pragma unroll
            for (int dd = 0; dd < 5; dd++) { QA[dd][0] = lds64(tq + T_A + 64 * (dd + 4)); QA[dd][1] = lds64(tq + T_A + 64 * (dd + 4) - 8); }
#pragma unroll
            for (int dd = 0; dd < 8; dd++) QB[dd] = lds64(tq + T_B + 64 * (dd + 8));
            const uint32_t u1 = UB + (mi & 1) * U_PL + (7 + r + (mi >> 1)) * 16;
            const uint32_t u2 = UB + ((mi & 1) ^ 1) * U_PL + (7 + r + (mi & 1) + 8 * (mi >> 1)) * 16;
            uint32_t n[4];
#pragma unroll
            for (int j = 0; j < 12; j++) {
                uint32_t m[4];
                ldsm4(u1 + j * 128, m[0], m[1], m[2], m[3]);
                if (!(j & 1)) ldsm4(u2 + j * 128, n[0], n[1], n[2], n[3]);
                const uint32_t n0 = n[2 * (j & 1)], n1 = n[2 * (j & 1) + 1];
                float wa[4], wb[4], wc[4], g1[4], g2[4];
                mma_bf_z(wa, bA.x, bA.y, bA.z, bA.w, m[0], m[1]);
                mma_bf_z(wb, bA.x, bA.y, bA.z, bA.w, n0, n1);
                mma_bf_z(wc, bA.x, bA.y, bA.z, bA.w, m[2], m[3]);
                if (j < 8) {
                    mma_bf_z(g1, bB.x, bB.y, bB.z, bB.w, m[0], m[1]);
                    mma_bf_z(g2, bB.x, bB.y, bB.z, bB.w, n0, n1);
                    mma_bf_k8(g1, bC.x, bC.y, m[2]);
                    mma_bf_k8(g2, bC.x, bC.y, m[3]);
                }
#pragma unroll
                for (int e = 0; e < 2; e++) {
                    const uint32_t q0 = pack_bf(wa[e], wa[e + 2]), q1 = pack_bf(wb[e], wb[e + 2]), q2 = q1 ^ p.zero, q3 = pack_bf(wc[e], wc[e + 2]);
#pragma unroll
                    for (int dd = 0; dd < 5; dd++)
                        if (j + 4 + dd < 16) mma_bf(D[j + 4 + dd], q0, q1, q2, q3, QA[dd][e].x, QA[dd][e].y);
                }
                if (j < 8) {
                    const uint32_t q0 = pack_bf(g1[0], g1[2]), q1 = pack_bf(g2[0], g2[2]), q2 = pack_bf(g1[1], g1[3]), q3 = pack_bf(g2[1], g2[3]);
#pragma unroll
                    for (int dd = 7 - j; dd >= 0; dd--) mma_bf(D[j + 8 + dd], q0, q1, q2, q3, QB[dd].x, QB[dd].y);
                }
                if ((j & 3) == 3) {
                    WSTAMP(4 + 2 * (j >> 2));
                    if (j == 11 && LATE2) ship(2);
                    if (j != 7 || !LATE2) ship((j >> 2) + 1);
                }
            }
        }
        mix_rows<1, false>(p, &tm_out, sb, PQ, 4, warp, h, pr, lane);
        WSTAMP(10);
        WDUMP();
    } else if ((pw & 12) == AUX_W0) {
        asm volatile("setmaxnreg.inc.sync.aligned.u32 136;");
        const int v = __reduce_max_sync(0xffffffffu, pw & 3);
        const int at = tid & 127;
        const int g = lane >> 2, t = lane & 3;
        unsigned tag;
        const bool gu = c < NGU_CTA;
        {
            uint4 xa[16];
            const uint32_t xb = sb + (v < 2 ? OFF_XSEL : OFF_RING + 2 * 8192) + v * 8192;
            const uint32_t gws = sb + (gu ? M_DPIN : OFF_RING + 2 * 8192);
            const uint32_t row = 16 * c + 4 * v + (g >> 1);
            const unsigned epoch = *(volatile unsigned*)&p.sc->epoch;
#pragma unroll
            for (int i = 0; i < 4; i++)
                asm volatile("cp.async.ca.shared.global [%0], [%1], 4;" :: "r"(sb + OFF_GP + 512 * i + (tid & 124) * 4 + (tid & 1) * 8 + (tid & 2) * 2),
                             "l"(p.wr + 256 * i + (tid & 127) * 2) : "memory");
            cp16(gws + (tid & 127) * 16, p.gatew + (tid & 127) * 8);
            if ((tid & 127) < 33) cp16(sb + OFF_BAND + (tid & 127) * 16, p.band + (tid & 127));
            asm volatile("barrier.cluster.arrive.relaxed.aligned;" ::: "memory");
            tag = __reduce_max_sync(0xffffffffu, (epoch + 1) & 0xffffu);
            if (gu) st_gpu32((uint32_t*)&p.sc->h[(tag + 1) & 1][32 * c] + at, 0);
            if (v == 0) sts32(sb + M_BMAP + lane * 4, 0);
            cp_wait_all();
            bar_sync(1, 128);
            uint2 w[16];
#pragma unroll
            for (int kb = 0; kb < 16; kb++) w[kb] = lds64(sb + OFF_GP + 128 * kb + 32 * (g & 2) + 16 * t + 8 * (g & 1));
            asm volatile("barrier.cluster.wait.acquire.aligned;" ::: "memory");
            mbar_wait(bars + 8 * (B_X + v));
            WSTAMP(10);
#pragma unroll
            for (int kb = 0; kb < 16; kb++) xa[kb] = lds128(xb + (g >> 1) * 2048 + 128 * kb + 16 * (lane & 7));
            float dr[4][4];
#pragma unroll
            for (int kb = 0; kb < 16; kb++) {
                if (kb < 4) mma_bf_z(dr[kb], xa[kb].x, xa[kb].y, xa[kb].z, xa[kb].w, w[kb].x, w[kb].y);
                else mma_bf(dr[kb & 3], xa[kb].x, xa[kb].y, xa[kb].z, xa[kb].w, w[kb].x, w[kb].y);
            }
            float rs = ((dr[0][0] + dr[0][3]) + (dr[1][0] + dr[1][3])) + ((dr[2][0] + dr[2][3]) + (dr[3][0] + dr[3][3]));
            if (lane == 0) mbar_arrive(bars + 8 * (B_XE + v) + (__float_as_uint(rs) & p.zero));
            rs += __shfl_xor_sync(0xffffffffu, rs, 5);
            const uint32_t rb = pack_bf(0.f, rs);
            if (!(lane & 7)) st_gpu32((uint32_t*)&p.sc->r[(row >> 2) * RS] + (row & 3), ((rb ^ (((int)rb >> 31) | 0x80000000u)) & 0xffff0000u) | tag);
            WSTAMP(1);
            {
                const int n = 3 + (lane >> 3) + 4 * (lane & 1);
                const uint32_t so = (n & 7) * S_PL + ((lane & 6) + (n >> 3)) * 32;
                const uint32_t src[2] = {sb + OFF_S + v * S_Q + s_addr(so, h), sb + OFF_S + v * S_Q + s_addr(so + 32, h)};
                const uint32_t dst = sb + OFF_U + g * U_CH + (8 + 32 * v + 16 * h + t) * 16;
                const uint32_t rdst = mapa(dst, h ^ 1), rbar = mapa(bars + 8 * B_U, h ^ 1);
                mbar_wait(bars + 8 * (B_S + v));
                WSTAMP(9);
                uint4 a[8];
#pragma unroll
                for (int b = 0; b < 2; b++) {
#pragma unroll
                    for (int j = 0; j < 8; j++) ldsm4t((b ? src[j & 1] : src[j & 1] ^ 16) + (j >> 1) * 256, a[j].x, a[j].y, a[j].z, a[j].w);
#pragma unroll
                    for (int j = 0; j < 8; j++) {
                        if (b) sts128(dst + (j >> 1) * 64 + (j & 1) * U_PL, a[j].x, a[j].y, a[j].z, a[j].w);
                        else st_async16(rdst + (j >> 1) * 64 + (j & 1) * U_PL, a[j], rbar);
                    }
                }
                if (h && v == 3) {
                    ldsm4t((src[0] ^ 16) + 1024, a[0].x, a[0].y, a[0].z, a[0].w);
                    ldsm4t(src[0] + 1024, a[1].x, a[1].y, a[1].z, a[1].w);
                    if (t == 0) {
                        st_async16(rdst + 256, make_uint4(a[0].x, a[0].y & 0xffffu, a[0].z & 0xffffu, a[0].w & 0xffffu), rbar);
                        sts128(dst + 256, a[1].x, a[1].y & 0xffffu, a[1].z & 0xffffu, a[1].w & 0xffffu);
                    }
                }
                __syncwarp();
                if (lane == 0) mbar_arrive(bars + 8 * B_U);
            }
            const uint32_t one0 = 0x3F803F80u ^ p.zero, one1 = 0x3F803F80u + p.zero;
#pragma unroll
            for (int kb = 0; kb < 16; kb++) {
                const uint4 gw = lds128(gws + 128 * kb + 16 * (lane & 7));
                const uint32_t a0 = hmul2_bf(xa[kb].x, gw.x), a1 = hmul2_bf(xa[kb].y, gw.y), a2 = hmul2_bf(xa[kb].z, gw.z), a3 = hmul2_bf(xa[kb].w, gw.w);
                if (kb < 4) mma_bf_z(dr[kb], a0, a1, a2, a3, one0, one1);
                else mma_bf(dr[kb & 3], a0, a1, a2, a3, one0, one1);
            }
            float sg = ((dr[0][0] + dr[0][3]) + (dr[1][0] + dr[1][3])) + ((dr[2][0] + dr[2][3]) + (dr[3][0] + dr[3][3]));
            sg += __shfl_xor_sync(0xffffffffu, sg, 4);
            if (!(lane & 7)) st_gpu32((uint32_t*)p.sc->g + ((row & 256) << 2) + gate_pos(row), (pack_bf(sigmoid_f(bf_round(sg)), 0.f) & 0xffffu) | (tag << 16));
            WSTAMP(2);
        }
        if (at == 32) { sts32(sb + M_TAG, tag << 16); mbar_arrive(bars + 8 * B_F); }
        {
            const bool lane0 = pin(lane, lane) == 0;
            const uint32_t own = pin(sb + OFF_XSEL + at * 16, lane);
            float acc[8][4];
#pragma unroll
            for (int i = 0; i < 8; i++) { acc[i][0] = acc[i][1] = acc[i][2] = acc[i][3] = 0.f; }
            const int krow = ((lane >> 1) & 8) + (lane & 7);
            const uint32_t tile0 = pin(sb + OFF_RING + krow * 64 + ((((lane >> 3) & 1) ^ ((krow >> 1) & 3)) << 4), lane);
            const uint32_t xo = pin(sb + OFF_XSEL + (lane & 7) * XS_ROW + 512 * v + 2 * (lane & 24), lane);
            const uint32_t po = pin(sb + OFF_XSEL + t * XS_ROW + (g & 3) * 128 + v * 16 + (lane >> 4) * 8, lane);
            uint32_t* hdst = pin((uint32_t*)&p.sc->h[tag & 1][32 * c] + at, lane);
            auto signal = [&](const int k, const uint32_t dep) {
                if (lane < 2 && v < 2)
                    asm volatile("st.async.weak.shared::cluster.mbarrier::complete_tx::bytes.b32 [%0], %1, [%2];"
                                 :: "r"(mapa(sb + M_SINK, lane)), "r"(dep), "r"(mapa(bars + 8 * (B_F + k), lane)) : "memory");
            };
#pragma unroll 1
            for (int i = 0; i < 4; i++) {
                const int s = 4 * i + v;
                uint32_t a[16][4], b[2][4];
                if (gu) {
                    const uint32_t tile = tile0 + (s < 14 ? s : v) * 8192;
                    if (lane0 && i > 1) mbar_arrive(bars + 8 * (B_E + s - 4));
                    if (i == 2) signal(0, 0);
                    mbar_wait(bars + 8 * (B_W + s));
#pragma unroll
                    for (int q = 0; q < 16; q++) ldsm4t((tile ^ ((q & 1) << 5)) + ((q >> 1) & 1) * 4096 + (q >> 2) * 1024, a[q][0], a[q][1], a[q][2], a[q][3]);
                }
                if (i == 0) {
                    if (gu) {
                        uint32_t dep = p.zero;
#pragma unroll
                        for (int q = 0; q < 16; q += 2) dep &= a[q][0] & a[q + 1][0];
                        if (lane == 0) mbar_arrive(bars + 8 * (B_E + v) + dep);
                    }
                    WSTAMP(11);
                    uint32_t top;
#pragma unroll 1
                    for (int it = 0; it < (1 << 22); it++) {
                        asm volatile("ld.relaxed.gpu.global.u32 %0, [%1];" : "=r"(top) : "l"(&p.sc->top[c % NTOP][g]) : "memory");
                        if (__all_sync(0xffffffffu, ((top ^ (tag << 11)) & 0xf800u) == 0)) break;
                        if (TSLEEP) __nanosleep(TSLEEP);
                    }
                    WSTAMP(3);
                    if (gu) {
                        const uint32_t k = 4 * h + v, row = __reduce_max_sync(0xffffffffu, lane == 4 * k ? ~top & 2047 : 0);
                        asm volatile("{\n\t.reg .pred p;\n\telect.sync _|p, 0xffffffff;\n\t"
                                     "@p cp.async.bulk.shared::cluster.global.mbarrier::complete_tx::bytes.multicast::cluster [%0], [%1], 2048, [%2], %3;\n\t}"
                            :: "r"(sb + OFF_XSEL + k * XS_ROW), "l"(p.u + (size_t)row * D_), "r"(bars + 8 * B_G), "h"((unsigned short)3) : "memory");
                    }
                    if (v == 0) {
                        const uint32_t row = ~top & 2047;
                        if (t == 0 && ((row >> 8) & 1) == h)
                            asm volatile("red.shared.or.b32 [%0], %1;" :: "r"(sb + M_BMAP + (row & 7) * 16 + (row >> 9) * 4), "r"(1u << (gate_pos(row) & 31)) : "memory");
                        if (t == 0) sts32(sb + M_TOP + lane, top);
                        if (c == 0 && lane == 0) *(volatile unsigned*)&p.sc->epoch = tag;
                        __syncwarp();
                        if (lane0) mbar_arrive(bars + 8 * B_Y);
                    }
                    if (!gu) break;
                    mbar_wait(bars + 8 * B_G);
                    WSTAMP(4);
                }
                ldsm4(xo + 128 * i, b[0][0], b[0][1], b[0][2], b[0][3]);
                ldsm4(xo + 128 * i + 64, b[1][0], b[1][1], b[1][2], b[1][3]);
#pragma unroll
                for (int q = 0; q < 16; q++) mma_bf(acc[q & 7], a[q][0], a[q][1], a[q][2], a[q][3], b[q >> 3][(q >> 1) & 2], b[q >> 3][((q >> 1) & 2) + 1]);
            }
            if (gu) {
                WSTAMP(5);
                __syncwarp();
#pragma unroll
                for (int q = 0; q < 4; q++) {
                    const int ct = q >> 1, e = 2 * (q & 1);
                    sts128(own + q * XS_ROW,
                           __float_as_uint(acc[ct][e] + acc[4 + ct][e]), __float_as_uint(acc[2 + ct][e] + acc[6 + ct][e]),
                           __float_as_uint(acc[ct][e + 1] + acc[4 + ct][e + 1]), __float_as_uint(acc[2 + ct][e + 1] + acc[6 + ct][e + 1]));
                }
                bar_sync(1, 128);
                float hv[2];
#pragma unroll
                for (int e = 0; e < 2; e++) {
                    uint2 q[4];
#pragma unroll
                    for (int i = 0; i < 4; i++) q[i] = lds64(po + 64 * e + 512 * i);
                    const float s0 = (__uint_as_float(q[0].x) + __uint_as_float(q[1].x)) + (__uint_as_float(q[2].x) + __uint_as_float(q[3].x));
                    const float s1 = (__uint_as_float(q[0].y) + __uint_as_float(q[1].y)) + (__uint_as_float(q[2].y) + __uint_as_float(q[3].y));
                    const float gv = bf_round(p.gu_swap ? s1 : s0), uv = bf_round(p.gu_swap ? s0 : s1);
                    hv[e] = bf_round(gv * sigmoid_f(gv)) * uv;
                }
                const uint32_t hw = pack_bf(hv[0], hv[1]);
                st_gpu32(hdst, hw ? hw : 0x80000000u);
                signal(1, hw);
            }
        }
        WSTAMP(6);
        asm volatile("setmaxnreg.dec.sync.aligned.u32 104;");
        {
            uint4 hq[14];
            const uint32_t own = pin(sb + OFF_XSEL + at * 16, lane);
            {
                bar_sync(1, 128);
                mbar_wait(bars + 8 * (B_W + HW));
                const uint32_t hb = sb + (v < 2 ? OFF_XSEL + 7168 * v : OFF_RING + 8192 * v);
                WSTAMP(12);
#pragma unroll 1
                for (int it = 0; it < (1 << 16); it++) {
                    bulk_load(hb, &p.sc->h[tag & 1][32 * (56 * h + 14 * v)], 7168, bars + 8 * (B_X + v));
                    mbar_wait(bars + 8 * (B_X + v), ~it & 1);
                    uint32_t mn = 0xffffffffu;
#pragma unroll
                    for (int i = 0; i < 14; i++) hq[i] = lds128(hb + 512 * i + 16 * lane);
#pragma unroll
                    for (int i = 0; i < 14; i++) mn = min(mn, hq[i].x);
                    if (__all_sync(0xffffffffu, mn != 0)) break;
                }
            }
            WSTAMP(7);
            float dd[4][4];
            const int krow = ((lane >> 1) & 8) + (lane & 7);
            const uint32_t tile = sb + OFF_RING + v * 8192 + krow * 32 + ((((lane >> 3) ^ (krow >> 2)) & 1) << 4);
#pragma unroll
            for (int s = 0; s < 2; s++) {
                mbar_wait(bars + 8 * (B_W + 16 + 4 * s + v));
#pragma unroll
                for (int j = 0; j < 14; j++) {
                    uint32_t a[4];
                    ldsm4t(tile + (s ? 65536 : (v & 2) * 16384) + j * 512, a[0], a[1], a[2], a[3]);
                    const uint4& hb = hq[7 * s + (j >> 1)];
                    if (s == 0 && j < 4) mma_bf_z(dd[j], a[0], a[1], a[2], a[3], (j & 1) ? hb.z : hb.x, (j & 1) ? hb.w : hb.y);
                    else mma_bf(dd[(j + 2 * s) & 3], a[0], a[1], a[2], a[3], (j & 1) ? hb.z : hb.x, (j & 1) ? hb.w : hb.y);
                }
            }
            WSTAMP(8);
            uint4 part;
            part.x = __float_as_uint((dd[0][0] + dd[1][0]) + (dd[2][0] + dd[3][0])); part.y = __float_as_uint((dd[0][1] + dd[1][1]) + (dd[2][1] + dd[3][1]));
            part.z = __float_as_uint((dd[0][2] + dd[1][2]) + (dd[2][2] + dd[3][2])); part.w = __float_as_uint((dd[0][3] + dd[1][3]) + (dd[2][3] + dd[3][3]));
            st_async16(mapa(own + (M_DPIN - OFF_XSEL), h ^ 1), part, mapa(bars + 8 * B_DP, h ^ 1));
            sts128(own + 14336, part.x, part.y, part.z, part.w);
            __syncwarp();
            if (lane == 0) mbar_arrive(bars + 8 * B_DP);
        }
        WDUMP();
    } else {
        asm volatile("setmaxnreg.dec.sync.aligned.u32 40;");
        const int v = __reduce_max_sync(0xffffffffu, pw - PREP_W0);
        const bool gu = c < NGU_CTA;
        const uint32_t t0 = clock();
        const uint32_t bu = bars + 8 * v;
        if (lane == 0) {
            mbar_init(bu + 8 * B_X, 1);
            asm volatile("fence.mbarrier_init.release.cluster;" ::: "memory");
        }
        __syncwarp();
        if (DELAY_X > 0) __nanosleep(DELAY_X);
        bulk_load(sb + (v < 2 ? OFF_XSEL : OFF_RING + 2 * 8192) + v * 8192, p.u + (size_t)(16 * c + 4 * v) * D_, 8192, bu + 8 * B_X);
        if (lane == 0) {
#pragma unroll
            for (int i = 0; i < 10; i++) mbar_init(bu + 32 * i, 1);
            mbar_init(bu + 8 * B_XE, 1);
            mbar_init(bu + 8 * B_Y, v == 0 ? 11 : 9);
            mbar_init(bu + 8 * B_DP, (0x1855 >> (4 * v)) & 15);
            mbar_init(bu + 8 * B_F, v == 0 ? 2 : 1);
            mbar_init(bu + 8 * B_H, 1);
            asm volatile("fence.mbarrier_init.release.cluster;" ::: "memory");
            mbar_expect(bu + 8 * B_Y, 4096);
            if (v != 2) mbar_expect(bu + 8 * B_DP, v == 0 ? 2048 : (h || v == 3) ? 16384 : 16384 + 128);
            mbar_expect(bu + 8 * B_F, c < NGU_CTA ? 16 : 0);
        }
        __syncwarp();
        asm volatile("barrier.cluster.arrive.relaxed.aligned;" ::: "memory");
        tma3d(sb + OFF_S + v * S_Q, &tm_x, 16 * pr, 64 * v + 32 * h - 1, bars + 8 * (B_S + v), S_Q);
        WSTAMP(9);
        if (v < 3 && lane == 0) asm volatile("prefetch.tensormap [%0];" :: "l"(v == 0 ? &tm_gu : v == 1 ? &tm_down : &tm_out) : "memory");
        asm volatile("barrier.cluster.wait.acquire.aligned;" ::: "memory");
        if (v > 0) mbar_wait(bars + 8 * (B_H + v));
        {
            const int gap = v == 0 ? GAP : v == 1 ? GAP1 : v == 2 ? GAP2 : GAP3;
            uint32_t last = v ? clock() - SLACK : t0 + T0 - GAP + STAG * ((pr * 5) & 15) / 16;
#pragma unroll 1
            for (int s = 6 * v; s < 6 * v + 6; s++) {
                const int i = s >> 2, w = s & 3, slot = s < 14 ? s : (s | 1) == 17 ? s - 16 : s - 12;
                if (s >= 4) mbar_wait(bars + 8 * ((gu && s >= 14) ? B_E + slot : s < 6 ? B_XE + s - 2 : B_KG));
                uint32_t now;
#pragma unroll 1
                while ((int)((now = clock()) - last) < gap) __nanosleep(CSLEEP);
                last = max((int)(now - last) - SLACK, gap) + last;
                WSTAMP(3 + s - 6 * v);
                if (gu || s >= 16) tma3d(sb + OFF_RING + slot * 8192, i < 4 ? &tm_gu : &tm_down, i < 4 ? 32 * c : 16 * pr,
                      i < 4 ? 256 * w + 64 * i : 1792 * h + 448 * w + 224 * (i - 4), bars + 8 * (B_W + s), i < 4 ? 8192 : 7168);
            }
            if (lane == 0) mbar_arrive(bars + 8 * (B_H + ((v + 1) & 3)));
        }
        if (v == 0) {
            mbar_wait(bars + 8 * B_U);
            mbar_wait(bars + 8 * B_F);
            if (!gu) mbar_wait(bars + 8 * (B_H + 3));
            const uint32_t tag16 = lds32(sb + M_TAG);
#pragma unroll 1
            for (int k = 0; k < 2; k++) {
                uint4 q[4];
#pragma unroll 1
                for (int it = 0; it < (1 << 22); it++) {
                    uint32_t bad = 0;
#pragma unroll
                    for (int i = 0; i < 4; i++) q[i] = ld_gpu128(&p.sc->g[256 * h + 128 * k + 32 * i + lane]);
#pragma unroll
                    for (int i = 0; i < 4; i++) bad |= ((q[i].x ^ tag16) | (q[i].y ^ tag16)) | ((q[i].z ^ tag16) | (q[i].w ^ tag16));
                    if ((bad >> 16) == 0) break;
                    __nanosleep(200);
                }
#pragma unroll
                for (int i = 0; i < 4; i++)
                    asm volatile("st.shared.v2.u32 [%0], {%1, %2};" :: "r"(sb + OFF_GP + 1024 * k + 256 * i + lane * 8),
                                 "r"(__byte_perm(q[i].x, q[i].y, 0x5410)), "r"(__byte_perm(q[i].z, q[i].w, 0x5410)) : "memory");
            }
            __syncwarp();
            if (lane == 0) mbar_arrive(bars + 8 * B_Y);
        }
        {
            asm volatile("setmaxnreg.inc.sync.aligned.u32 72;");
            WSTAMP(1);
            mix_rows<2, BULKQ>(p, &tm_out, sb, 0, PQ, v, h, pr, lane);
            WSTAMP(2);
            asm volatile("cp.async.bulk.commit_group;" ::: "memory");
            const uint32_t top = lds32(sb + M_TOP + 8 * v + 4 * (lane >> 4));
            const uint32_t row = ~top & 2047, ch = lane & 15, gp = gate_pos(row);
            const bool mine = ((row >> 8) & 1) == h;
            uint32_t gfin, x16, y16 = 0;
            asm volatile("ld.shared.u16 %0, [%1];" : "=r"(gfin) : "r"(sb + OFF_GP + gp * 2) : "memory");
            asm volatile("ld.shared.u16 %0, [%1];" : "=r"(x16) : "r"(sb + OFF_S + (row >> 9) * S_Q + s_addr((row & 7) * S_PL + 32 + (row & 248) * 4, ch >> 3) + 2 * (ch & 7)) : "memory");
            const float rsel = __uint_as_float(pin(__float_as_uint(bf_round(sigmoid_f(__uint_as_float((top ^ (((int)~top >> 31) | 0x80000000u)) & 0xffff0000u)))), lane));
            const uint32_t po = pin(sb + (4 * (ch & 7) + v) * 16 + (ch >> 3) * 8 + (lane >> 4) * 4, lane);
            bf16* op = pin(p.out + (size_t)row * D_ + 16 * pr + ch, lane);
            if (mine) {
                mbar_wait(bars + 8 * (B_Y + (row >> 9)));
                asm volatile("ld.shared.u16 %0, [%1];" : "=r"(y16)
                             : "r"(sb + y_off(row >> 9) + ch * 512 + (((4 * (row & 7) + ((row >> 5) & 3)) ^ (((ch >> 2) << 1) | (ch & 1))) << 4) + 2 * row_elem(row)) : "memory");
            }
            mbar_wait(bars + 8 * B_DP);
            float q[8];
#pragma unroll
            for (int i = 0; i < 4; i++) { q[i] = ldsf(po + M_DPIN + 512 * i); q[4 + i] = ldsf(po + OFF_XSEL + 14336 + 512 * i); }
            const float tot = ((q[0] + q[1]) + (q[2] + q[3])) + ((q[4] + q[5]) + (q[6] + q[7]));
            const float b = bf_round(__uint_as_float(x16 << 16) + bf_round(bf_round(tot) * rsel));
            if (mine) *op = __float2bfloat16_rn(fmaf(bf_lo(gfin), __uint_as_float(y16 << 16), bf_round(bf_round(1.f - bf_lo(gfin)) * b)));
        }
        asm volatile("cp.async.bulk.wait_group.read 0;" ::: "memory");
        WSTAMP(10);
        WDUMP();
    }
}

typedef CUresult (*EncodeFn)(CUtensorMap*, CUtensorMapDataType, cuuint32_t, void*, const cuuint64_t*, const cuuint64_t*,
                             const cuuint32_t*, const cuuint32_t*, CUtensorMapInterleave, CUtensorMapSwizzle,
                             CUtensorMapL2promotion, CUtensorMapFloatOOBfill);

void make_map(EncodeFn f, CUtensorMap* m, const void* ptr, uint64_t cols, uint64_t rows, uint64_t pitch, uint32_t bc, uint32_t br, CUtensorMapSwizzle sw, int prom,
              uint32_t planes = 1, uint64_t plane_stride = 0, uint32_t box_planes = 0) {
    cuuint64_t dims[3] = {cols, rows, planes};
    cuuint64_t str[2] = {pitch, planes > 1 ? plane_stride : pitch * rows};
    cuuint32_t box[3] = {bc, br, box_planes ? box_planes : planes};
    cuuint32_t es[3] = {1, 1, 1};
    f(m, CU_TENSOR_MAP_DATA_TYPE_BFLOAT16, 3, (void*)ptr, dims, str, box, es, CU_TENSOR_MAP_INTERLEAVE_NONE, sw,
      (CUtensorMapL2promotion)prom, CU_TENSOR_MAP_FLOAT_OOB_FILL_NONE);
}

}

extern "C" void kernel_launch(void* const* d_in, const int* in_sizes, int n_in, void* d_out, int out_size) {
    static EncodeFn enc = nullptr;
    static void *sc = nullptr, *band = nullptr;
    if (!enc) {
        void* fn = nullptr;
        cudaDriverEntryPointQueryResult qr;
        cudaGetDriverEntryPoint("cuTensorMapEncodeTiled", &fn, cudaEnableDefault, &qr);
        enc = (EncodeFn)fn;
        cudaGetSymbolAddress(&sc, g_scratch);
        cudaGetSymbolAddress(&band, g_band);
        cudaFuncSetAttribute(fused_kernel, cudaFuncAttributeMaxDynamicSharedMemorySize, SMEM_BYTES);
    }
    CUtensorMap tg, td, tx, to;
    const char *wg = (const char*)d_in[9], *wu = (const char*)d_in[10];
    const bool swap = wu < wg;
    make_map(enc, &tg, swap ? wu : wg, F_, D_, F_ * 2, 32, 64, CU_TENSOR_MAP_SWIZZLE_64B, PROMG, 2, swap ? wg - wu : wu - wg);
    make_map(enc, &td, d_in[11], D_, F_, D_ * 2, 16, 224, CU_TENSOR_MAP_SWIZZLE_32B, PROMD);
    make_map(enc, &tx, d_in[0], D_, L_ / 8, D_ * 16, 16, 33, CU_TENSOR_MAP_SWIZZLE_32B, PROMX, 8, D_ * 2);
    make_map(enc, &to, d_out, D_, L_ / 8, D_ * 16, 16, 32, CU_TENSOR_MAP_SWIZZLE_NONE, 0, 8, D_ * 2, 1);
    Params p;
    p.u = (const bf16*)d_in[0]; p.logA = (const bf16*)d_in[1]; p.Aim = (const bf16*)d_in[2];
    p.Cre = (const bf16*)d_in[3]; p.Cim = (const bf16*)d_in[4]; p.logdt = (const bf16*)d_in[5];
    p.Dskip = (const bf16*)d_in[6]; p.wr = (const bf16*)d_in[8]; p.gatew = (const bf16*)d_in[12];
    p.out = (bf16*)d_out;
    p.sc = (Scratch*)sc; p.band = (const uint4*)band;
    p.gu_swap = swap;
    p.zero = 0;
    fused_kernel<<<NCTA, NTHREADS, SMEM_BYTES>>>(p, tg, td, tx, to);
}
```

```cpp
#include <cuda_runtime.h>
#include <cuda_bf16.h>
#include <cuda_fp16.h>
#include <cuda.h>
#include <stdint.h>

typedef __nv_bfloat16 bf16;

namespace {

constexpr int L_ = 2048, D_ = 1024, F_ = 3584;
constexpr int NCTA = 130;
constexpr int NTHREADS = 512;
#define AUXW 12
constexpr int MAIN_W0 = 0, AUX_W0 = AUXW, PREP_W0 = 20 - AUXW;
#define T0 3500
#define GAP 590
#define GAP1 530
#define GAP2 530
#define GAP3 550
#define STAG GAP
#define CSLEEP 50
#define SLACK 300
#define DELAY_X 150
#define TSLEEP 40
#define RS 2
#define BULKQ true
#define PQ 3
#define PROMG 2
#define PROMD 1
#define PROMX 0
#define LATE2 0
#define HW 21
constexpr int NGU_CTA = 112;

constexpr int OFF_RING = 0;
constexpr int OFF_SCR  = 6 * 8192;
constexpr int S_PL     = 1056;
constexpr int S_Q      = 8 * S_PL;
constexpr int OFF_S    = 114688;
constexpr int OFF_GP   = OFF_S + 4 * S_Q;
constexpr int U_PL     = 2240;
constexpr int U_CH     = 4416;
constexpr int OFF_U    = 151552;
constexpr int TAB_W    = 3200;
constexpr int T_PL     = 544;
constexpr int T_A      = 2192 - 26 * 8;
constexpr int T_B      = 2568 - 59 * 8;
constexpr int OFF_TAB  = 186880;
constexpr int OFF_XSEL = 212480;
constexpr int XS_ROW   = 2064;
constexpr int OFF_BAND = 228992;
constexpr int OFF_MISC = 229536;
constexpr int M_BARS   = OFF_MISC;
constexpr int M_DSK    = OFF_MISC + 2736;
constexpr int M_SINK   = OFF_MISC + 512;
constexpr int M_TAG    = OFF_MISC + 516;
constexpr int M_BMAP   = OFF_MISC + 528;
constexpr int M_DPIN   = OFF_MISC + 656;
constexpr int M_TOP    = OFF_MISC + 2704;
constexpr int SMEM_BYTES = OFF_MISC + 2768;
__device__ __forceinline__ uint32_t s_addr(uint32_t o, uint32_t half) { return o + (((half ^ (o >> 7)) & 1) << 4); }
__host__ __device__ constexpr uint32_t y_off(uint32_t q) { return OFF_RING + 32768 + (q & 1) * 8192 + (q >> 1) * 65536; }

constexpr int B_W = 0;
constexpr int B_E = 24;
constexpr int B_S = 36;
constexpr int B_Y = 40;
constexpr int B_DP = 44, B_U = 45, B_KG = 46, B_G = 47;
constexpr int B_F = 48;
constexpr int B_H = 60;
constexpr int B_X = 52, B_XE = 56;

struct BandTab { uint32_t w[11][12]; };
constexpr BandTab make_band() {
    BandTab b{};
    for (int cls = 0; cls < 11; cls++)
        for (int wd = 0; wd < 10; wd++) {
            const int tau = cls + 2 - 8 * ((wd < 4 ? wd : wd - 4) >> 1);
            const int lo = (wd < 4) ? ((wd & 1) ? -2 : 3) : ((wd & 1) ? -4 : -11), wid = (wd < 4 ? 3 : 7) + 2 * (wd & 1);
            b.w[cls][wd] = ((tau >= lo && tau < lo + wid) ? 0x3F80u : 0u) | ((tau - 4 >= lo && tau - 4 < lo + wid) ? 0x3F800000u : 0u);
        }
    return b;
}
constexpr int NTOP = 32;
struct Scratch {
    uint4 r[L_ / 4 * RS];
    uint4 g[L_ / 4];
    uint4 h[2][8 * F_ / 8];
    uint32_t top[NTOP][32];
    unsigned epoch;
};
__device__ __align__(128) Scratch g_scratch;
__device__ const __align__(16) BandTab g_band = make_band();

struct Params {
    const bf16 *u, *logA, *Aim, *Cre, *Cim, *logdt, *Dskip, *wr, *gatew;
    bf16* out;
    Scratch* sc;
    const uint4* band;
    uint32_t gu_swap;
    uint32_t zero;
};

#define WSTAMP(i) do {} while (0)
#define KSTAMP(i, dep) do {} while (0)
#define WDUMP() do {} while (0)
#define RSTAMP(i) do {} while (0)

#define NOALLOC ".L1::no_allocate"
__device__ __forceinline__ uint32_t smem_u32(const void* p) { return (uint32_t)__cvta_generic_to_shared(p); }
__device__ __forceinline__ void mbar_init(uint32_t b, uint32_t c) { asm volatile("mbarrier.init.shared::cta.b64 [%0], %1;" :: "r"(b), "r"(c) : "memory"); }
__device__ __forceinline__ void mbar_expect(uint32_t b, uint32_t tx) { asm volatile("mbarrier.arrive.expect_tx.shared::cta.b64 _, [%0], %1;" :: "r"(b), "r"(tx) : "memory"); }
__device__ __forceinline__ void mbar_arrive(uint32_t b) { asm volatile("mbarrier.arrive.shared::cta.b64 _, [%0];" :: "r"(b) : "memory"); }
__device__ __forceinline__ void mbar_wait(uint32_t b, uint32_t parity = 0) {
    asm volatile("{\n\t.reg .pred p;\nW%=:\n\tmbarrier.try_wait.parity.shared::cta.b64 p, [%0], %1, 20000;\n\t@!p bra W%=;\n\t}" :: "r"(b), "r"(parity) : "memory");
}
__device__ __forceinline__ uint32_t mapa(uint32_t addr, uint32_t rank) { uint32_t r; asm("mapa.shared::cluster.u32 %0, %1, %2;" : "=r"(r) : "r"(addr), "r"(rank)); return r; }
__device__ __forceinline__ void tma3d(uint32_t dst, const CUtensorMap* tm, int c0, int c1, uint32_t bar, uint32_t bytes) {
    asm volatile("{\n\t.reg .pred p;\n\telect.sync _|p, 0xffffffff;\n\t"
                 "@p mbarrier.arrive.expect_tx.shared::cta.b64 _, [%2], %5;\n\t"
                 "@p cp.async.bulk.tensor.3d.shared::cluster.global.mbarrier::complete_tx::bytes [%0], [%1, {%3, %4, 0}], [%2];\n\t}"
        :: "r"(dst), "l"(tm), "r"(bar), "r"(c0), "r"(c1), "r"(bytes) : "memory");
}
__device__ __forceinline__ void bulk_load(uint32_t dst, const void* src, uint32_t bytes, uint32_t bar) {
    asm volatile("{\n\t.reg .pred p;\n\telect.sync _|p, 0xffffffff;\n\t"
                 "@p mbarrier.arrive.expect_tx.shared::cta.b64 _, [%2], %3;\n\t"
                 "@p cp.async.bulk.shared::cluster.global.mbarrier::complete_tx::bytes [%0], [%1], %3, [%2];\n\t}"
        :: "r"(dst), "l"(src), "r"(bar), "r"(bytes) : "memory");
}
__device__ __forceinline__ void st_async16(uint32_t dst, const uint4& v, uint32_t bar) {
    asm volatile("st.async.weak.shared::cluster.mbarrier::complete_tx::bytes.v4.b32 [%0], {%1,%2,%3,%4}, [%5];"
                 :: "r"(dst), "r"(v.x), "r"(v.y), "r"(v.z), "r"(v.w), "r"(bar) : "memory");
}
__device__ __forceinline__ void bar_sync(int id, int n) { asm volatile("bar.sync %0, %1;" :: "r"(id), "r"(n) : "memory"); }
__device__ __forceinline__ void cp16(uint32_t dst, const void* src) { asm volatile("cp.async.cg.shared.global [%0], [%1], 16;" :: "r"(dst), "l"(src) : "memory"); }
__device__ __forceinline__ void cp_wait_all() { asm volatile("cp.async.wait_all;" ::: "memory"); }
__device__ __forceinline__ uint2 ldg64(const void* p) { uint2 v; asm volatile("ld.global.nc" NOALLOC ".v2.u32 {%0,%1}, [%2];" : "=r"(v.x), "=r"(v.y) : "l"(p)); return v; }
__device__ __forceinline__ uint4 ld_gpu128(const void* p) { uint4 v; asm volatile("ld.relaxed.gpu.global.v4.u32 {%0,%1,%2,%3}, [%4];" : "=r"(v.x), "=r"(v.y), "=r"(v.z), "=r"(v.w) : "l"(p) : "memory"); return v; }
__device__ __forceinline__ void st_gpu32(void* p, uint32_t v) { asm volatile("st.relaxed.gpu.global.u32 [%0], %1;" :: "l"(p), "r"(v) : "memory"); }

__device__ __forceinline__ void ldsm4(uint32_t a, uint32_t& r0, uint32_t& r1, uint32_t& r2, uint32_t& r3) {
    asm volatile("ldmatrix.sync.aligned.m8n8.x4.shared.b16 {%0,%1,%2,%3}, [%4];" : "=r"(r0), "=r"(r1), "=r"(r2), "=r"(r3) : "r"(a) : "memory");
}
__device__ __forceinline__ void ldsm4t(uint32_t a, uint32_t& r0, uint32_t& r1, uint32_t& r2, uint32_t& r3) {
    asm volatile("ldmatrix.sync.aligned.m8n8.x4.trans.shared.b16 {%0,%1,%2,%3}, [%4];" : "=r"(r0), "=r"(r1), "=r"(r2), "=r"(r3) : "r"(a) : "memory");
}
__device__ __forceinline__ uint32_t lds32(uint32_t a) { uint32_t v; asm volatile("ld.shared.u32 %0, [%1];" : "=r"(v) : "r"(a) : "memory"); return v; }
__device__ __forceinline__ uint2 lds64(uint32_t a) { uint2 v; asm volatile("ld.shared.v2.u32 {%0,%1}, [%2];" : "=r"(v.x), "=r"(v.y) : "r"(a) : "memory"); return v; }
__device__ __forceinline__ uint4 lds128(uint32_t a) { uint4 v; asm volatile("ld.shared.v4.u32 {%0,%1,%2,%3}, [%4];" : "=r"(v.x), "=r"(v.y), "=r"(v.z), "=r"(v.w) : "r"(a) : "memory"); return v; }
__device__ __forceinline__ void sts32(uint32_t a, uint32_t v) { asm volatile("st.shared.u32 [%0], %1;" :: "r"(a), "r"(v) : "memory"); }
__device__ __forceinline__ void sts16(uint32_t a, uint32_t v) { asm volatile("st.shared.u16 [%0], %1;" :: "r"(a), "h"((unsigned short)v) : "memory"); }
__device__ __forceinline__ void sts128(uint32_t a, uint32_t x, uint32_t y, uint32_t z, uint32_t w) { asm volatile("st.shared.v4.u32 [%0], {%1,%2,%3,%4};" :: "r"(a), "r"(x), "r"(y), "r"(z), "r"(w) : "memory"); }
__device__ __forceinline__ float ldsf(uint32_t a) { float v; asm volatile("ld.shared.f32 %0, [%1];" : "=f"(v) : "r"(a) : "memory"); return v; }

__device__ __forceinline__ void mma_bf(float (&d)[4], uint32_t a0, uint32_t a1, uint32_t a2, uint32_t a3, uint32_t b0, uint32_t b1) {
    asm volatile("mma.sync.aligned.m16n8k16.row.col.f32.bf16.bf16.f32 {%0,%1,%2,%3}, {%4,%5,%6,%7}, {%8,%9}, {%0,%1,%2,%3};"
        : "+f"(d[0]), "+f"(d[1]), "+f"(d[2]), "+f"(d[3]) : "r"(a0), "r"(a1), "r"(a2), "r"(a3), "r"(b0), "r"(b1));
}
__device__ __forceinline__ void mma_bf_z(float (&d)[4], uint32_t a0, uint32_t a1, uint32_t a2, uint32_t a3, uint32_t b0, uint32_t b1) {
    asm volatile("mma.sync.aligned.m16n8k16.row.col.f32.bf16.bf16.f32 {%0,%1,%2,%3}, {%4,%5,%6,%7}, {%8,%9}, {%10,%10,%10,%10};"
        : "=f"(d[0]), "=f"(d[1]), "=f"(d[2]), "=f"(d[3]) : "r"(a0), "r"(a1), "r"(a2), "r"(a3), "r"(b0), "r"(b1), "f"(0.f));
}
__device__ __forceinline__ void mma_bf_k8(float (&d)[4], uint32_t a0, uint32_t a1, uint32_t b0) {
    asm volatile("mma.sync.aligned.m16n8k8.row.col.f32.bf16.bf16.f32 {%0,%1,%2,%3}, {%4,%5}, {%6}, {%0,%1,%2,%3};"
        : "+f"(d[0]), "+f"(d[1]), "+f"(d[2]), "+f"(d[3]) : "r"(a0), "r"(a1), "r"(b0));
}
__device__ __forceinline__ void mma_h(float (&d)[4], uint32_t a0, uint32_t a1, uint32_t a2, uint32_t a3, uint32_t b0, uint32_t b1) {
    asm volatile("mma.sync.aligned.m16n8k16.row.col.f32.f16.f16.f32 {%0,%1,%2,%3}, {%4,%5,%6,%7}, {%8,%9}, {%0,%1,%2,%3};"
        : "+f"(d[0]), "+f"(d[1]), "+f"(d[2]), "+f"(d[3]) : "r"(a0), "r"(a1), "r"(a2), "r"(a3), "r"(b0), "r"(b1));
}
__device__ __forceinline__ uint32_t pack_bf(float lo, float hi) { uint32_t r; asm("cvt.rn.bf16x2.f32 %0, %1, %2;" : "=r"(r) : "f"(hi), "f"(lo)); return r; }
__device__ __forceinline__ uint32_t pack_h(float lo, float hi) { uint32_t r; asm("cvt.rn.f16x2.f32 %0, %1, %2;" : "=r"(r) : "f"(hi), "f"(lo)); return r; }
__device__ __forceinline__ float bf_lo(uint32_t v) { return __uint_as_float(v << 16); }
__device__ __forceinline__ float bf_hi(uint32_t v) { return __uint_as_float(v & 0xffff0000u); }
__device__ __forceinline__ float bf_round(float x) { return __uint_as_float(pack_bf(0.f, x) & 0xffff0000u); }
__device__ __forceinline__ uint32_t hmul2_bf(uint32_t a, uint32_t b) { uint32_t r; asm("mul.rn.bf16x2 %0, %1, %2;" : "=r"(r) : "r"(a), "r"(b)); return r; }
__device__ __forceinline__ float ex2f(float x) { float r; asm("ex2.approx.ftz.f32 %0, %1;" : "=f"(r) : "f"(x)); return r; }

__device__ __forceinline__ float exp_acc(float x) {
    const float t = x * 1.4426950216293335f;
    const float r = fmaf(x, 1.4426950216293335f, -t) + x * 1.9259629911266175e-8f;
    return ex2f(t) * fmaf(r, 0.6931471805599453f, 1.f);
}
__device__ __forceinline__ float sigmoid_f(float x) { return __fdividef(1.f, 1.f + ex2f(-x * 1.4426950408889634f)); }
__device__ __forceinline__ void cexp_pow(float l2, float li, float e, float& zr, float& zi) {
    const float mag = ex2f(l2 * e);
    zr = mag * __cosf(li * e);
    zi = mag * __sinf(li * e);
}
__device__ __forceinline__ uint32_t hcmul(uint32_t a, uint32_t k, uint32_t kp) {
    const __half2 A = *reinterpret_cast<const __half2*>(&a);
    const __half2 r = __hfma2(__high2half2(A), *reinterpret_cast<const __half2*>(&kp), __hmul2(__low2half2(A), *reinterpret_cast<const __half2*>(&k)));
    return *reinterpret_cast<const uint32_t*>(&r);
}
#define CMUL(orr, oi, ar, ai, br, bi) do { float _r = (ar) * (br) - (ai) * (bi); float _i = (ar) * (bi) + (ai) * (br); orr = _r; oi = _i; } while (0)
#define CSQ(orr, oi, ar, ai) do { float _r = (ar) * (ar) - (ai) * (ai); float _i = 2.f * (ar) * (ai); orr = _r; oi = _i; } while (0)

__device__ __forceinline__ void mma_bf_k8z(float (&d)[4], uint32_t a0, uint32_t a1, uint32_t b0) {
    asm volatile("mma.sync.aligned.m16n8k8.row.col.f32.bf16.bf16.f32 {%0,%1,%2,%3}, {%4,%5}, {%6}, {%7,%7,%7,%7};"
        : "=f"(d[0]), "=f"(d[1]), "=f"(d[2]), "=f"(d[3]) : "r"(a0), "r"(a1), "r"(b0), "f"(0.f));
}
__device__ __forceinline__ void mma_hh_k8(uint32_t& d0, uint32_t& d1, uint32_t a0, uint32_t a1, uint32_t b0) {
    asm volatile("mma.sync.aligned.m16n8k8.row.col.f16.f16.f16.f16 {%0,%1}, {%2,%3}, {%4}, {%5,%5};"
        : "=r"(d0), "=r"(d1) : "r"(a0), "r"(a1), "r"(b0), "r"(0));
}
__device__ __forceinline__ uint32_t pin(uint32_t x, int lane) { return __shfl_sync(0xffffffffu, x, lane); }
template <class T> __device__ __forceinline__ T* pin(T* x, int lane) { return (T*)__shfl_sync(0xffffffffu, (unsigned long long)x, lane); }
__device__ __forceinline__ void sts32_if(bool on, uint32_t a, uint32_t v) {
    asm volatile("{\n\t.reg .pred p;\n\tsetp.ne.u32 p, %2, 0;\n\t@p st.shared.u32 [%0], %1;\n\t}" :: "r"(a), "r"(v), "r"((uint32_t)on) : "memory");
}
__device__ __forceinline__ void sts128_if(bool on, uint32_t a, uint32_t x, uint32_t y, uint32_t z, uint32_t w) {
    asm volatile("{\n\t.reg .pred p;\n\tsetp.ne.u32 p, %5, 0;\n\t@p st.shared.v4.u32 [%0], {%1,%2,%3,%4};\n\t}" :: "r"(a), "r"(x), "r"(y), "r"(z), "r"(w), "r"((uint32_t)on) : "memory");
}
__device__ __forceinline__ void lds128_if(bool on, uint32_t a, uint32_t (&v)[4]) {
    asm volatile("{\n\t.reg .pred p;\n\tsetp.ne.u32 p, %5, 0;\n\t@p ld.shared.v4.u32 {%0,%1,%2,%3}, [%4];\n\t}"
        : "+r"(v[0]), "+r"(v[1]), "+r"(v[2]), "+r"(v[3]) : "r"(a), "r"((uint32_t)on) : "memory");
}
__device__ __forceinline__ uint32_t hfma2_bf(uint32_t a, uint32_t b, uint32_t c) { uint32_t r; asm("fma.rn.bf16x2 %0, %1, %2, %3;" : "=r"(r) : "r"(a), "r"(b), "r"(c)); return r; }
__device__ __forceinline__ uint32_t row_elem(uint32_t row) { return ((row >> 5) & 4) | ((row >> 2) & 2) | ((row >> 4) & 1); }
__device__ __forceinline__ uint32_t gate_pos(uint32_t row) { return ((row >> 9) << 8) | ((row & 7) << 5) | (row_elem(row) << 2) | ((row >> 5) & 3); }

template <int N, bool BULK>
__device__ __forceinline__ void mix_rows(const Params& p, const CUtensorMap* tm_out, uint32_t sb, int Q0, int Q1, int w, int h, int pr, int lane) {
    const int g = lane >> 2, t = lane & 3, mi = lane >> 3, r = lane & 7;
    const int m8 = 16 * (g >> 2) + ((g >> 1) & 1) + 2 * (g & 1);
    uint32_t yi = sb + (4 * (r >> 1) + 2 * (mi & 1) + (r & 1)) * 512 + (((4 * w + (mi >> 1)) ^ r) << 4);
    uint32_t xs = sb + OFF_S + s_addr(w * S_PL + 32 + m8 * 32, t >> 1) + ((t & 1) << 3);
    uint32_t gs = sb + OFF_GP + w * 64 + g * 8, os = sb + OFF_TAB + w * TAB_W + m8 * 32 + t * 8;
    if (BULK) { yi = pin(yi, lane); xs = pin(xs, lane); gs = pin(gs, lane); os = pin(os, lane); }
    mbar_wait(sb + M_BARS + 8 * B_Y);
#pragma unroll 1
    for (int Q = Q0; Q < Q1; Q++) {
        uint2 xq[N][4];
        uint32_t gg[N][4], sw[N];
#pragma unroll
        for (int n = 0; n < N; n++) {
#pragma unroll
            for (int i = 0; i < 4; i++) xq[n][i] = lds64((xs ^ (((i ^ n) & 1) << 4)) + Q * S_Q + n * 4 * S_PL + i * 128);
            const uint2 gq = lds64(gs + Q * 512 + n * 256);
            sw[n] = lds32(sb + M_BMAP + w * 16 + n * 64 + Q * 4);
#pragma unroll
            for (int i = 0; i < 4; i++) {
                gg[n][i] = __byte_perm(i < 2 ? gq.x : gq.y, 0, (i & 1) ? 0x3232 : 0x1010);
                const uint32_t og = hfma2_bf(gg[n][i], 0xBF80BF80u, 0x3F803F80u);
                xq[n][i].x = hmul2_bf(og, xq[n][i].x); xq[n][i].y = hmul2_bf(og, xq[n][i].y);
            }
        }
        mbar_wait(sb + M_BARS + 8 * (B_Y + Q));
        __syncwarp();
#pragma unroll
        for (int n = 0; n < N; n++) {
#pragma unroll
            for (int x = 0; x < 2; x++) {
                uint32_t y[4];
                ldsm4t((yi ^ (x << 5)) + y_off(Q) + n * 256, y[0], y[1], y[2], y[3]);
#pragma unroll
                for (int e = 0; e < 2; e++) {
                    uint2& o = xq[n][2 * x + e];
                    o.x = hfma2_bf(gg[n][2 * x + e], y[2 * e], o.x); o.y = hfma2_bf(gg[n][2 * x + e], y[2 * e + 1], o.y);
                }
            }
        }
        if (BULK && (sw[0] | sw[N - 1]) == 0) {
#pragma unroll
            for (int n = 0; n < N; n++)
#pragma unroll
                for (int i = 0; i < 4; i++)
                    asm volatile("st.shared.v2.u32 [%0], {%1, %2};" :: "r"(os + Q * 1024 + n * 4 * TAB_W + i * 128), "r"(xq[n][i].x), "r"(xq[n][i].y) : "memory");
            asm volatile("fence.proxy.async.shared::cta;" ::: "memory");
            __syncwarp();
#pragma unroll
            for (int n = 0; n < N; n++)
                asm volatile("{\n\t.reg .pred p;\n\telect.sync _|p, 0xffffffff;\n\t"
                             "@p cp.async.bulk.tensor.3d.global.shared::cta.bulk_group [%1, {%2, %3, %4}], [%0];\n\t}"
                    :: "r"(sb + OFF_TAB + (w + 4 * n) * TAB_W + Q * 1024), "l"(tm_out), "r"(16 * pr), "r"(64 * Q + 32 * h), "r"(w + 4 * n) : "memory");
        } else {
            bf16* op = p.out + (size_t)(512 * Q + 256 * h + 8 * m8 + w) * D_ + 16 * pr + 4 * t;
#pragma unroll
            for (int n = 0; n < N; n++)
#pragma unroll
                for (int i = 0; i < 4; i++)
                    if (!((sw[n] >> (4 * g)) & (1u << i))) *(uint2*)(op + (size_t)(32 * i + 4 * n) * D_) = xq[n][i];
        }
    }
}

__global__ void __cluster_dims__(2, 1, 1) __launch_bounds__(NTHREADS, 1)
fused_kernel(const Params p, const __grid_constant__ CUtensorMap tm_gu, const __grid_constant__ CUtensorMap tm_down,
             const __grid_constant__ CUtensorMap tm_x, const __grid_constant__ CUtensorMap tm_out) {
    extern __shared__ __align__(1024) unsigned char smem[];
    const uint32_t sb = smem_u32(smem);
    int tid;
    asm volatile("mov.u32 %0, %%tid.x;" : "=r"(tid));
    const int pw = tid >> 5, lane = tid & 31;
    const int c = blockIdx.x, h = c & 1, pr = c >> 1;
    const uint32_t bars = sb + M_BARS;

    if (c >= 128) {
        if (c != 128) return;
        RSTAMP(5);
        const unsigned tag = (*(volatile unsigned*)&p.sc->epoch + 1) & 0xffffu;
        const uint32_t list = sb + 128;
#pragma unroll 1
        for (int pass = 0; pass < 2; pass++) {
            sts128(list + 16 * tid, 0, 0, 0, 0);
            if (tid == 0) sts32(sb + 64, 0);
            uint32_t key[4];
            bool ok = false;
#pragma unroll 1
            for (int it = 0; it < (1 << 22); it++) {
                const uint4 a = ld_gpu128(&p.sc->r[tid * RS]);
                key[0] = a.x; key[1] = a.y; key[2] = a.z; key[3] = a.w;
                ok = (((a.x ^ tag) | (a.y ^ tag) | (a.z ^ tag) | (a.w ^ tag)) & 0xffffu) == 0;
                if (ok || !pass) break;
            }
            WSTAMP(0);
            uint32_t m = 0;
#pragma unroll
            for (int i = 0; i < 4; i++) {
                key[i] = ((pass ? key[i] : (lane + i) << 16) & 0xffff0000u) | (uint32_t)(2047 - (4 * tid + i));
                m = max(m, key[i]);
            }
            const uint32_t wm = __reduce_max_sync(0xffffffffu, m);
            if (lane == 0) sts32(sb + pw * 4, wm);
            __syncthreads();
            uint32_t thr = 0xffffffffu;
#pragma unroll
            for (int i = 0; i < 4; i++) { const uint4 q = lds128(sb + 16 * i); thr = min(thr, min(max(q.x, q.y), max(q.z, q.w))); }
            if (thr != 1) WSTAMP(1);
            if (m >= thr) {
                uint32_t pos;
                asm volatile("atom.shared.add.u32 %0, [%1], %2;" : "=r"(pos) : "r"(sb + 64), "r"(4 * ((key[0] >= thr) + (key[1] >= thr) + (key[2] >= thr) + (key[3] >= thr))) : "memory");
#pragma unroll
                for (int i = 0; i < 4; i++) if (key[i] >= thr) { sts32(list + pos, key[i]); pos += 4; }
            }
            __syncthreads();
            const uint32_t nc4 = lds32(sb + 64);
            if (nc4 != 1) WSTAMP(2);
#pragma unroll 1
            for (uint32_t j = 4 * pw; j < nc4; j += 64) {
                const uint32_t mine = lds32(list + j);
                int rank = 0;
#pragma unroll 1
                for (uint32_t i = 0; i < nc4; i += 128) rank += __popc(__ballot_sync(0xffffffffu, lds32(list + i + 4 * lane) > mine));
                if (rank < 8 && lane == 0) sts32(sb + 96 + 4 * rank, mine);
            }
            __syncthreads();
            if (tid < 8 * NTOP) st_gpu32(&p.sc->top[tid >> 3][tid & 7], lds32(sb + 96 + 4 * (tid & 7)) | (((tag + pass - 1) & 31) << 11));
            WSTAMP(3);
            if (!pass) RSTAMP(4);
        }
        WDUMP();
        return;
    }

    WSTAMP(0);
    if (pw < 8) {
        uint2 v_la, v_ai, v_cr, v_ci;
        uint32_t ldt16;
        const int d = 8 * c + pw - MAIN_W0;
        const size_t po = (size_t)d * 128 + 4 * lane;
        v_la = ldg64(p.logA + po); v_ai = ldg64(p.Aim + po); v_cr = ldg64(p.Cre + po); v_ci = ldg64(p.Cim + po);
        asm volatile("ld.global.nc.u16 %0, [%1];" : "=r"(ldt16) : "l"(p.logdt + d));
        if (lane == 0) asm volatile("cp.async.ca.shared.global [%0], [%1], 4;" :: "r"(sb + M_DSK + 4 * (pw - MAIN_W0)), "l"(p.Dskip + (d & ~1)) : "memory");
        asm volatile("barrier.cluster.arrive.relaxed.aligned;" ::: "memory");
        const int warp = pw - MAIN_W0;
        asm volatile("setmaxnreg.inc.sync.aligned.u32 168;");
        const int g = lane >> 2, t = lane & 3;
        const int mi = lane >> 3, r = lane & 7;
        const uint32_t TB = sb + OFF_TAB + warp * TAB_W;
        const uint32_t UB = sb + OFF_U + warp * U_CH;
        if (mi < 2) sts128(UB + mi * U_PL + r * 16, 0, 0, 0, 0);
#pragma unroll
        for (int i = 0; i < 6; i++) sts128(TB + 16 * (lane + 32 * i), 0, 0, 0, 0);
        if (lane < 8) sts128(TB + 16 * (lane + 192), 0, 0, 0, 0);
        sts128(sb + OFF_SCR + warp * 8192 + lane * 16, 0x3C00u, 0x3C00u, 0x3C00u, 0x3C00u);
        __syncwarp();

        uint32_t cfix;
        {
            KSTAMP(4, v_la.x ^ v_ai.x ^ v_cr.x ^ v_ci.x ^ ldt16);
            const float dt = bf_round(exp_acc(__uint_as_float(ldt16 << 16)));
            float l2[4], li[4];
            {
                const uint32_t la[2] = {v_la.x, v_la.y}, ai[2] = {v_ai.x, v_ai.y};
                const float dt2 = -1.4426950408889634f * dt;
#pragma unroll
                for (int i = 0; i < 4; i++) {
                    l2[i] = bf_round(ex2f(((i & 1) ? bf_hi(la[i >> 1]) : bf_lo(la[i >> 1])) * 1.4426950408889634f)) * dt2;
                    li[i] = ((i & 1) ? bf_hi(ai[i >> 1]) : bf_lo(ai[i >> 1])) * dt;
                }
            }
            const uint32_t SX = sb + OFF_SCR + warp * 8192;
            const uint32_t sw = SX + (lane << 4);
#define PUT(buf, row, v) sts128(((sw + (row) * 512) ^ ((row) << 4)) + (buf) * 4096, v[0], v[1], v[2], v[3])
#define EMIT(bufa, rowa, bufb, rowb, xr, xi, k, kp) do { uint32_t pk[4], pd[4]; \
                _Pragma("unroll") for (int i = 0; i < 4; i++) { pk[i] = pack_h(xr[i], xi[i]); pd[i] = hcmul(pk[i], k[i], kp[i]); } \
                PUT(bufa, rowa, pk); PUT(bufb, rowb, pd); } while (0)
#define CMUL4(orr, oi, ar, ai, br, bi) _Pragma("unroll") for (int i = 0; i < 4; i++) CMUL(orr[i], oi[i], ar[i], ai[i], br[i], bi[i])
#define CSQ4(orr, oi, ar, ai) _Pragma("unroll") for (int i = 0; i < 4; i++) CSQ(orr[i], oi[i], ar[i], ai[i])
            float z1r[4], z1i[4], z2r[4], z2i[4], z8r[4], z8i[4], z256r[4], z256i[4];
            uint32_t k128[4], k128p[4], k4[4], k4p[4];
            float z4r[4], z4i[4];
#pragma unroll
            for (int i = 0; i < 4; i++) cexp_pow(l2[i], li[i], 1.f, z1r[i], z1i[i]);
            CSQ4(z2r, z2i, z1r, z1i);
            CSQ4(z4r, z4i, z2r, z2i);
            CSQ4(z8r, z8i, z4r, z4i);
            KSTAMP(5, __float_as_uint(z8r[3]));
            uint32_t Ya[16][4];
            float cr[4], ci[4], inv;
            {
                float w1r[4], w1i[4], ar[4], ai[4], br[4], bi[4];
                uint32_t k8[4], k8p[4];
#pragma unroll
                for (int i = 0; i < 4; i++) {
                    k8[i] = pack_h(z8r[i], -z8i[i]); k8p[i] = pack_h(z8i[i], z8r[i]);
                    CSQ(w1r[i], w1i[i], z8r[i], z8i[i]); w1i[i] = -w1i[i];
                }
                PUT(1, 0, k8);
                EMIT(0, 1, 1, 1, w1r, w1i, k8, k8p);
                CSQ4(ar, ai, w1r, w1i);            EMIT(0, 2, 1, 2, ar, ai, k8, k8p);
                CMUL4(br, bi, ar, ai, w1r, w1i);   EMIT(0, 3, 1, 3, br, bi, k8, k8p);
                CSQ4(ar, ai, ar, ai);              EMIT(0, 4, 1, 4, ar, ai, k8, k8p);
                CMUL4(ar, ai, ar, ai, w1r, w1i);   EMIT(0, 5, 1, 5, ar, ai, k8, k8p);
                CSQ4(br, bi, br, bi);              EMIT(0, 6, 1, 6, br, bi, k8, k8p);
                CMUL4(br, bi, br, bi, w1r, w1i);   EMIT(0, 7, 1, 7, br, bi, k8, k8p);
                __syncwarp();
                KSTAMP(6, 0);
                const uint32_t ab = SX + (mi & 1) * 4096 + r * 512, ax = ((mi >> 1) ^ r) << 4;
                const uint32_t vr[2] = {v_cr.x, v_cr.y}, vi[2] = {v_ci.x, v_ci.y};
                const uint32_t m2 = __vmaxu2(__vmaxu2(vr[0] & 0x7fff7fffu, vr[1] & 0x7fff7fffu), __vmaxu2(vi[0] & 0x7fff7fffu, vi[1] & 0x7fff7fffu));
                const uint32_t mx = __reduce_max_sync(0xffffffffu, max(m2, m2 << 16));
                const uint32_t e = min(max(mx >> 23, 11u), 254u);
                const float sc = __uint_as_float((264u - e) << 23);
                inv = __uint_as_float((e - 10u) << 23) * (2.f * dt);
#pragma unroll
                for (int i = 0; i < 4; i++) {
#pragma unroll
                    for (int k = 0; k < 4; k++) ldsm4(ab + (ax ^ (i << 5)) + k * 128, Ya[4 * k + i][0], Ya[4 * k + i][1], Ya[4 * k + i][2], Ya[4 * k + i][3]);
                    float tr, ti;
                    cexp_pow(l2[i], li[i], 128.f, tr, ti);
                    k128[i] = pack_h(tr, ti); k128p[i] = pack_h(-ti, tr);
                    k4[i] = pack_h(z4r[i], z4i[i]); k4p[i] = pack_h(-z4i[i], z4r[i]);
                    CSQ(z256r[i], z256i[i], tr, ti);
                    cr[i] = ((i & 1) ? bf_hi(vr[i >> 1]) : bf_lo(vr[i >> 1])) * sc;
                    ci[i] = ((i & 1) ? bf_hi(vi[i >> 1]) : bf_lo(vi[i >> 1])) * sc;
                }
#pragma unroll
                for (int i = 0; i < 4; i++) { sts32(TB + i * T_PL + 16 + 4 * lane, k128[i]); sts32(TB + i * T_PL + 160 + 4 * lane, k128p[i]); }
                __syncwarp();
            }
            KSTAMP(7, Ya[15][0]);
            const uint32_t ld0 = SX + r * 512 + ((mi ^ r) << 4), ld1 = ld0 ^ 64;
            float R[5][4], xr[4], xi[4];
            {
                float yr[4], yi[4];
                EMIT(0, 0, 0, 1, cr, ci, k4, k4p);
                CMUL4(yr, yi, cr, ci, z1r, z1i);        EMIT(0, 2, 0, 3, yr, yi, k4, k4p);
                CMUL4(xr, xi, cr, ci, z256r, z256i);    EMIT(1, 0, 1, 1, xr, xi, k4, k4p);
                CMUL4(yr, yi, yr, yi, z1r, z1i);        EMIT(0, 4, 0, 5, yr, yi, k4, k4p);
                CMUL4(cr, ci, xr, xi, z2r, z2i);        EMIT(1, 2, 1, 3, cr, ci, k4, k4p);
                CMUL4(yr, yi, yr, yi, z1r, z1i);        EMIT(0, 6, 0, 7, yr, yi, k4, k4p);
                CMUL4(xr, xi, xr, xi, z256r, z256i);    EMIT(1, 4, 1, 5, xr, xi, k4, k4p);
                CMUL4(xr, xi, xr, xi, z256r, z256i);    EMIT(1, 6, 1, 7, xr, xi, k4, k4p);
            }
            __syncwarp();
            {
                KSTAMP(8, 0);
                uint32_t bd[2][4] = {{0, 0, 0, 0}, {0, 0, 0, 0}};
                const bool on = (g >> 1) == t;
#pragma unroll
                for (int i = 0; i < 4; i++) { R[i][0] = R[i][1] = R[i][2] = R[i][3] = 0.f; }
#pragma unroll
                for (int k2 = 0; k2 < 8; k2++) {
                    uint32_t x[4], y[4], a1[2][4];
                    lds128_if(on, TB + t * T_PL + 16 + (g & 1) * 144 + 16 * k2, bd[k2 & 1]);
                    ldsm4(((k2 & 1) ? ld1 : ld0) + (k2 >> 1) * 128, x[0], x[1], x[2], x[3]);
                    ldsm4(((k2 & 1) ? ld1 : ld0) + (k2 >> 1) * 128 + 4096, y[0], y[1], y[2], y[3]);
#pragma unroll
                    for (int u = 0; u < 2; u++) {
                        mma_hh_k8(a1[u][0], a1[u][1], Ya[2 * k2 + u][0], Ya[2 * k2 + u][1], bd[k2 & 1][2 * u]);
                        mma_hh_k8(a1[u][2], a1[u][3], Ya[2 * k2 + u][2], Ya[2 * k2 + u][3], bd[k2 & 1][2 * u + 1]);
                    }
#pragma unroll
                    for (int u = 0; u < 2; u++) {
                        const uint32_t(&a0)[4] = Ya[2 * k2 + u];
                        mma_h(R[0], a0[0], a0[1], a0[2], a0[3], x[2 * u], x[2 * u + 1]);
                        mma_h(R[2], a0[0], a0[1], a0[2], a0[3], y[2 * u], y[2 * u + 1]);
                        mma_h(R[1], a1[u][0], a1[u][1], a1[u][2], a1[u][3], x[2 * u], x[2 * u + 1]);
                        mma_h(R[3], a1[u][0], a1[u][1], a1[u][2], a1[u][3], y[2 * u], y[2 * u + 1]);
                    }
                }
            }
            __syncwarp();
            KSTAMP(9, __float_as_uint(R[3][0]));
            asm volatile("barrier.cluster.wait.acquire.aligned;" ::: "memory");
            CMUL4(xr, xi, xr, xi, z256r, z256i);
            float s1024 = (xr[0] + xr[1]) + (xr[2] + xr[3]);
            CMUL4(xr, xi, xr, xi, z8r, z8i);        EMIT(0, 0, 0, 1, xr, xi, k128, k128p);
            CMUL4(xr, xi, xr, xi, z256r, z256i);    EMIT(0, 2, 0, 3, xr, xi, k128, k128p);
            CMUL4(xr, xi, xr, xi, z256r, z256i);    EMIT(0, 4, 0, 5, xr, xi, k128, k128p);
            CMUL4(xr, xi, xr, xi, z256r, z256i);    EMIT(0, 6, 0, 7, xr, xi, k128, k128p);
            __syncwarp();
            {
                KSTAMP(10, 0);
                float a1[4] = {0.f, 0.f, 0.f, 0.f};
                R[4][0] = R[4][1] = R[4][2] = R[4][3] = 0.f;
#pragma unroll
                for (int k2 = 0; k2 < 8; k2++) {
                    uint32_t x[4];
                    ldsm4(((k2 & 1) ? ld1 : ld0) + (k2 >> 1) * 128, x[0], x[1], x[2], x[3]);
                    mma_h(R[4], Ya[2 * k2][0], Ya[2 * k2][1], Ya[2 * k2][2], Ya[2 * k2][3], x[0], x[1]);
                    mma_h(a1, Ya[2 * k2 + 1][0], Ya[2 * k2 + 1][1], Ya[2 * k2 + 1][2], Ya[2 * k2 + 1][3], x[2], x[3]);
                }
#pragma unroll
                for (int i = 0; i < 4; i++) R[4][i] += a1[i];
            }
            if (lane == 0) mbar_arrive(bars + 8 * B_KG + (__float_as_uint(R[4][0]) & p.zero));
            KSTAMP(11, __float_as_uint(R[4][0]));
#undef PUT
#undef EMIT
#pragma unroll
            for (int o = 16; o > 0; o >>= 1) s1024 += __shfl_xor_sync(0xffffffffu, s1024, o);
            uint32_t w[4][4], dsk = 0;
            cp_wait_all();
            asm volatile("{\n\t.reg .pred p;\n\tsetp.eq.u32 p, %2, 0;\n\t@p ld.shared.u16 %0, [%1];\n\t}" : "+r"(dsk) : "r"(sb + M_DSK + 4 * warp + 2 * (warp & 1)), "r"(lane) : "memory");
#pragma unroll
            for (int a = 0; a < 4; a++) {
                const float v0 = (a == 0) ? fmaf(R[0][0], inv, __uint_as_float(dsk << 16)) : R[a][0] * inv;
                const float v1 = R[a][1] * inv, v2 = R[a][2] * inv, v3 = R[a][3] * inv;
                w[a][0] = pack_bf(v0, 0.f); w[a][1] = pack_bf(v1, v0); w[a][2] = pack_bf(v2, v1); w[a][3] = pack_bf(v3, v2);
            }
            const uint32_t wb = TB + 16 + 16 * g, w1 = wb + t * T_PL, w2 = wb + 256 + 2 * t * T_PL;
            const uint32_t w3 = (t == 0) ? wb + 256 + 3 * T_PL : TB + T_A + 8 * (16 * t + g);
            const uint32_t w3s = (t == 0) ? 128 : 64, w3o = (t == 0) ? 8 : 12;
            const uint32_t k512 = __shfl_sync(0xffffffffu, w[2][1], 2);
#pragma unroll
            for (int a = 0; a < 2; a++) {
                sts128(w1 + 128 * a, w[a][0], w[a][1], w[a][2], w[a][3]);
                const uint32_t(&q)[4] = w[2 + a];
                if (t < 2) sts128(w2 + 128 * a, q[0], q[1], q[2], q[3]);
                if (t == 0) { sts128(w2 + T_PL + 128 * a, q[0], q[1], q[2], q[3]); sts32(w3 + 128 * a + 4, q[2]); }
                sts32_if(t != 1 && (a == 1 || lane != 2), w3 + w3s * a, q[1]);
                sts32_if(t != 1, w3 + w3s * a + w3o, q[3]);
            }
            sts128_if(lane < 4, w1 + 512, t == 3 ? k512 : k512 >> 16, t < 2 ? k512 : t == 2 ? k512 & 0xffff0000u : k512 << 16, t < 2 ? k512 << 16 : 0u, 0);
            __syncwarp();
#pragma unroll
            for (int a = 0; a < 2; a++) {
                sts16(w1 + 128 * a + 18, w[a][3]);
                const uint32_t(&q)[4] = w[2 + a];
                if (t < 2) sts16(w2 + 128 * a + 18, q[3]);
                if (t == 0) { sts16(w2 + T_PL + 128 * a + 18, q[3]); sts16(w3 + 128 * a + 14, q[3]); }
            }
            if (t == 0) sts16(w3 + 128 - 4, w[3][0]);
            if (lane == 2 || (t == 0 && g > 0)) sts16(lane == 2 ? TB + 16 + 3 * T_PL + 4 * 127 : w3 - 4, w[2][0]);
            {
                const uint32_t b0 = pack_bf(R[4][0] * inv, R[4][2] * inv), b1 = pack_bf(R[4][1] * inv, R[4][3] * inv);
                const uint32_t wq = TB + T_B + 8 * (65 + 16 * t + g);
                sts32(wq, b0); sts32(wq + 12, b0); sts32(wq + 64, b1); sts32(wq + 76, b1);
            }
            cfix = pack_bf(s1024 * inv, s1024 * inv);
            if (lane == 0) sts32(TB + T_A + 8 * 64, cfix);
            __syncwarp();
        }
        WSTAMP(1);

        mbar_wait(bars + 8 * B_U);
        WSTAMP(2);

        float D[16][4];
        {
            const int x5 = g - t + 5;
            const uint32_t tabD = TB + (x5 & 3) * T_PL + (x5 & 12) + 16;
            {
                const uint32_t a1 = lds32(tabD - 8), a0 = p.zero;
#pragma unroll
                for (int jq = 0; jq < 4; jq++) {
                    uint32_t b[4];
                    ldsm4(UB + (9 + lane) * 16 + jq * 512, b[0], b[1], b[2], b[3]);
#pragma unroll
                    for (int i = 0; i < 4; i++) mma_bf_k8z(D[4 * jq + i], a0, a1, b[i]);
                }
            }
            const uint32_t ua = UB + (mi & 1) * U_PL + (8 + 8 * (mi >> 1) + r) * 16;
#pragma unroll 1
            for (int k0 = 0; k0 < 8; k0++) {
                uint32_t Uf[16][2];
#pragma unroll
                for (int jp = 0; jp < 8; jp++) ldsm4(ua + jp * 256 - k0 * 16, Uf[2 * jp][0], Uf[2 * jp][1], Uf[2 * jp + 1][0], Uf[2 * jp + 1][1]);
#pragma unroll
                for (int k1 = 0; k1 < 4; k1++) {
                    const uint32_t ta = tabD + 16 * (8 * k1 + k0);
                    const uint32_t a0 = lds32(ta), a1 = lds32(ta + 8), a2 = lds32(ta - 8), a3 = a0 ^ p.zero;
#pragma unroll
                    for (int J = k1; J < 16; J++) mma_bf(D[J], a0, a1, a2, a3, Uf[J - k1][0], Uf[J - k1][1]);
                }
                if (k0 == 0) {
                    const uint32_t ta = tabD + 16 * 32;
                    const uint32_t a0 = lds32(ta), a1 = lds32(ta + 8), a2 = lds32(ta - 8), a3 = a0 ^ p.zero;
#pragma unroll
                    for (int J = 4; J < 16; J++) mma_bf(D[J], a0, a1, a2, a3, Uf[J - 4][0], Uf[J - 4][1]);
                    const uint32_t f0 = (cfix ^ 0x80008000u) & (g == t ? 0xffffu : g == t + 4 ? 0xffff0000u : 0u);
                    const uint32_t f1 = p.zero, f2 = p.zero + p.zero, f3 = f0 ^ p.zero;
#pragma unroll
                    for (int J = 8; J < 16; J++) mma_bf(D[J], f0, f1, f2, f3, Uf[J - 8][0], Uf[J - 8][1]);
                }
            }
        }
        WSTAMP(3);
        {
            const int ch = 8 * h + warp;
            const uint32_t yo = sb + ch * 512 + ((lane ^ (((ch >> 2) << 1) | (ch & 1))) << 4);
            const uint32_t yr = mapa(yo, h ^ 1), ybr = mapa(bars + 8 * B_Y, h ^ 1);
            auto ship = [&](const int Q) {
                uint4 y[2];
#pragma unroll
                for (int hh = 0; hh < 2; hh++) {
                    const int J = 4 * Q + 2 * hh;
                    y[hh] = make_uint4(pack_bf(D[J][0], D[J][1]), pack_bf(D[J][2], D[J][3]), pack_bf(D[J + 1][0], D[J + 1][1]), pack_bf(D[J + 1][2], D[J + 1][3]));
                }
                if (!(Q & 1)) mbar_wait(bars + 8 * (B_F + (Q >> 1)));
                asm volatile("{\n\t.reg .pred p;\n\tsetp.eq.u32 p, %11, 0;\n\t"
                             "@p st.async.weak.shared::cluster.mbarrier::complete_tx::bytes.v4.b32 [%9], {%4,%5,%6,%7}, [%10];\n\t"
                             "@!p st.async.weak.shared::cluster.mbarrier::complete_tx::bytes.v4.b32 [%9], {%0,%1,%2,%3}, [%10];\n\t"
                             "@p st.shared.v4.b32 [%8], {%0,%1,%2,%3};\n\t@!p st.shared.v4.b32 [%8], {%4,%5,%6,%7};\n\t}"
                             :: "r"(y[0].x), "r"(y[0].y), "r"(y[0].z), "r"(y[0].w), "r"(y[1].x), "r"(y[1].y), "r"(y[1].z), "r"(y[1].w),
                                "r"(yo + y_off(Q)), "r"(yr + y_off(Q)), "r"(ybr + 8 * Q), "r"(h) : "memory");
                __syncwarp();
                if (lane == 0) mbar_arrive(bars + 8 * (B_Y + Q));
            };
            ship(0);
            const uint4 bA = lds128(sb + OFF_BAND + (g - t + 3) * 48), bB = lds128(sb + OFF_BAND + (g - t + 3) * 48 + 16);
            const uint2 bC = lds64(sb + OFF_BAND + (g - t + 3) * 48 + 32);
            uint2 QA[5][2], QB[8];
            const uint32_t tq = TB + 8 * (1 + g - 2 * t);
#pragma unroll
            for (int dd = 0; dd < 5; dd++) { QA[dd][0] = lds64(tq + T_A + 64 * (dd + 4)); QA[dd][1] = lds64(tq + T_A + 64 * (dd + 4) - 8); }
#pragma unroll
            for (int dd = 0; dd < 8; dd++) QB[dd] = lds64(tq + T_B + 64 * (dd + 8));
            const uint32_t u1 = UB + (mi & 1) * U_PL + (7 + r + (mi >> 1)) * 16;
            const uint32_t u2 = UB + ((mi & 1) ^ 1) * U_PL + (7 + r + (mi & 1) + 8 * (mi >> 1)) * 16;
            uint32_t n[4];
#pragma unroll
            for (int j = 0; j < 12; j++) {
                uint32_t m[4];
                ldsm4(u1 + j * 128, m[0], m[1], m[2], m[3]);
                if (!(j & 1)) ldsm4(u2 + j * 128, n[0], n[1], n[2], n[3]);
                const uint32_t n0 = n[2 * (j & 1)], n1 = n[2 * (j & 1) + 1];
                float wa[4], wb[4], wc[4], g1[4], g2[4];
                mma_bf_z(wa, bA.x, bA.y, bA.z, bA.w, m[0], m[1]);
                mma_bf_z(wb, bA.x, bA.y, bA.z, bA.w, n0, n1);
                mma_bf_z(wc, bA.x, bA.y, bA.z, bA.w, m[2], m[3]);
                if (j < 8) {
                    mma_bf_z(g1, bB.x, bB.y, bB.z, bB.w, m[0], m[1]);
                    mma_bf_z(g2, bB.x, bB.y, bB.z, bB.w, n0, n1);
                    mma_bf_k8(g1, bC.x, bC.y, m[2]);
                    mma_bf_k8(g2, bC.x, bC.y, m[3]);
                }
#pragma unroll
                for (int e = 0; e < 2; e++) {
                    const uint32_t q0 = pack_bf(wa[e], wa[e + 2]), q1 = pack_bf(wb[e], wb[e + 2]), q2 = q1 ^ p.zero, q3 = pack_bf(wc[e], wc[e + 2]);
#pragma unroll
                    for (int dd = 0; dd < 5; dd++)
                        if (j + 4 + dd < 16) mma_bf(D[j + 4 + dd], q0, q1, q2, q3, QA[dd][e].x, QA[dd][e].y);
                }
                if (j < 8) {
                    const uint32_t q0 = pack_bf(g1[0], g1[2]), q1 = pack_bf(g2[0], g2[2]), q2 = pack_bf(g1[1], g1[3]), q3 = pack_bf(g2[1], g2[3]);
#pragma unroll
                    for (int dd = 7 - j; dd >= 0; dd--) mma_bf(D[j + 8 + dd], q0, q1, q2, q3, QB[dd].x, QB[dd].y);
                }
                if ((j & 3) == 3) {
                    WSTAMP(4 + 2 * (j >> 2));
                    if (j == 11 && LATE2) ship(2);
                    if (j != 7 || !LATE2) ship((j >> 2) + 1);
                }
            }
        }
        mix_rows<1, false>(p, &tm_out, sb, PQ, 4, warp, h, pr, lane);
        WSTAMP(10);
        WDUMP();
    } else if ((pw & 12) == AUX_W0) {
        asm volatile("setmaxnreg.inc.sync.aligned.u32 136;");
        const int v = __reduce_max_sync(0xffffffffu, pw & 3);
        const int at = tid & 127;
        const int g = lane >> 2, t = lane & 3;
        unsigned tag;
        const bool gu = c < NGU_CTA;
        {
            uint4 xa[16];
            const uint32_t xb = sb + (v < 2 ? OFF_XSEL : OFF_RING + 2 * 8192) + v * 8192;
            const uint32_t gws = sb + (gu ? M_DPIN : OFF_RING + 2 * 8192);
            const uint32_t row = 16 * c + 4 * v + (g >> 1);
            const unsigned epoch = *(volatile unsigned*)&p.sc->epoch;
#pragma unroll
            for (int i = 0; i < 4; i++)
                asm volatile("cp.async.ca.shared.global [%0], [%1], 4;" :: "r"(sb + OFF_GP + 512 * i + (tid & 124) * 4 + (tid & 1) * 8 + (tid & 2) * 2),
                             "l"(p.wr + 256 * i + (tid & 127) * 2) : "memory");
            cp16(gws + (tid & 127) * 16, p.gatew + (tid & 127) * 8);
            if ((tid & 127) < 33) cp16(sb + OFF_BAND + (tid & 127) * 16, p.band + (tid & 127));
            asm volatile("barrier.cluster.arrive.relaxed.aligned;" ::: "memory");
            tag = __reduce_max_sync(0xffffffffu, (epoch + 1) & 0xffffu);
            if (gu) st_gpu32((uint32_t*)&p.sc->h[(tag + 1) & 1][32 * c] + at, 0);
            if (v == 0) sts32(sb + M_BMAP + lane * 4, 0);
            cp_wait_all();
            bar_sync(1, 128);
            uint2 w[16];
#pragma unroll
            for (int kb = 0; kb < 16; kb++) w[kb] = lds64(sb + OFF_GP + 128 * kb + 32 * (g & 2) + 16 * t + 8 * (g & 1));
            asm volatile("barrier.cluster.wait.acquire.aligned;" ::: "memory");
            mbar_wait(bars + 8 * (B_X + v));
            WSTAMP(10);
#pragma unroll
            for (int kb = 0; kb < 16; kb++) xa[kb] = lds128(xb + (g >> 1) * 2048 + 128 * kb + 16 * (lane & 7));
            float dr[4][4];
#pragma unroll
            for (int kb = 0; kb < 16; kb++) {
                if (kb < 4) mma_bf_z(dr[kb], xa[kb].x, xa[kb].y, xa[kb].z, xa[kb].w, w[kb].x, w[kb].y);
                else mma_bf(dr[kb & 3], xa[kb].x, xa[kb].y, xa[kb].z, xa[kb].w, w[kb].x, w[kb].y);
            }
            float rs = ((dr[0][0] + dr[0][3]) + (dr[1][0] + dr[1][3])) + ((dr[2][0] + dr[2][3]) + (dr[3][0] + dr[3][3]));
            if (lane == 0) mbar_arrive(bars + 8 * (B_XE + v) + (__float_as_uint(rs) & p.zero));
            rs += __shfl_xor_sync(0xffffffffu, rs, 5);
            const uint32_t rb = pack_bf(0.f, rs);
            if (!(lane & 7)) st_gpu32((uint32_t*)&p.sc->r[(row >> 2) * RS] + (row & 3), ((rb ^ (((int)rb >> 31) | 0x80000000u)) & 0xffff0000u) | tag);
            WSTAMP(1);
            {
                const int n = 3 + (lane >> 3) + 4 * (lane & 1);
                const uint32_t so = (n & 7) * S_PL + ((lane & 6) + (n >> 3)) * 32;
                const uint32_t src[2] = {sb + OFF_S + v * S_Q + s_addr(so, h), sb + OFF_S + v * S_Q + s_addr(so + 32, h)};
                const uint32_t dst = sb + OFF_U + g * U_CH + (8 + 32 * v + 16 * h + t) * 16;
                const uint32_t rdst = mapa(dst, h ^ 1), rbar = mapa(bars + 8 * B_U, h ^ 1);
                mbar_wait(bars + 8 * (B_S + v));
                WSTAMP(9);
                uint4 a[8];
#pragma unroll
                for (int b = 0; b < 2; b++) {
#pragma unroll
                    for (int j = 0; j < 8; j++) ldsm4t((b ? src[j & 1] : src[j & 1] ^ 16) + (j >> 1) * 256, a[j].x, a[j].y, a[j].z, a[j].w);
#pragma unroll
                    for (int j = 0; j < 8; j++) {
                        if (b) sts128(dst + (j >> 1) * 64 + (j & 1) * U_PL, a[j].x, a[j].y, a[j].z, a[j].w);
                        else st_async16(rdst + (j >> 1) * 64 + (j & 1) * U_PL, a[j], rbar);
                    }
                }
                if (h && v == 3) {
                    ldsm4t((src[0] ^ 16) + 1024, a[0].x, a[0].y, a[0].z, a[0].w);
                    ldsm4t(src[0] + 1024, a[1].x, a[1].y, a[1].z, a[1].w);
                    if (t == 0) {
                        st_async16(rdst + 256, make_uint4(a[0].x, a[0].y & 0xffffu, a[0].z & 0xffffu, a[0].w & 0xffffu), rbar);
                        sts128(dst + 256, a[1].x, a[1].y & 0xffffu, a[1].z & 0xffffu, a[1].w & 0xffffu);
                    }
                }
                __syncwarp();
                if (lane == 0) mbar_arrive(bars + 8 * B_U);
            }
            const uint32_t one0 = 0x3F803F80u ^ p.zero, one1 = 0x3F803F80u + p.zero;
#pragma unroll
            for (int kb = 0; kb < 16; kb++) {
                const uint4 gw = lds128(gws + 128 * kb + 16 * (lane & 7));
                const uint32_t a0 = hmul2_bf(xa[kb].x, gw.x), a1 = hmul2_bf(xa[kb].y, gw.y), a2 = hmul2_bf(xa[kb].z, gw.z), a3 = hmul2_bf(xa[kb].w, gw.w);
                if (kb < 4) mma_bf_z(dr[kb], a0, a1, a2, a3, one0, one1);
                else mma_bf(dr[kb & 3], a0, a1, a2, a3, one0, one1);
            }
            float sg = ((dr[0][0] + dr[0][3]) + (dr[1][0] + dr[1][3])) + ((dr[2][0] + dr[2][3]) + (dr[3][0] + dr[3][3]));
            sg += __shfl_xor_sync(0xffffffffu, sg, 4);
            if (!(lane & 7)) st_gpu32((uint32_t*)p.sc->g + ((row & 256) << 2) + gate_pos(row), (pack_bf(sigmoid_f(bf_round(sg)), 0.f) & 0xffffu) | (tag << 16));
            WSTAMP(2);
        }
        if (at == 32) { sts32(sb + M_TAG, tag << 16); mbar_arrive(bars + 8 * B_F); }
        {
            const bool lane0 = pin(lane, lane) == 0;
            const uint32_t own = pin(sb + OFF_XSEL + at * 16, lane);
            float acc[8][4];
#pragma unroll
            for (int i = 0; i < 8; i++) { acc[i][0] = acc[i][1] = acc[i][2] = acc[i][3] = 0.f; }
            const int krow = ((lane >> 1) & 8) + (lane & 7);
            const uint32_t tile0 = pin(sb + OFF_RING + krow * 64 + ((((lane >> 3) & 1) ^ ((krow >> 1) & 3)) << 4), lane);
            const uint32_t xo = pin(sb + OFF_XSEL + (lane & 7) * XS_ROW + 512 * v + 2 * (lane & 24), lane);
            const uint32_t po = pin(sb + OFF_XSEL + t * XS_ROW + (g & 3) * 128 + v * 16 + (lane >> 4) * 8, lane);
            uint32_t* hdst = pin((uint32_t*)&p.sc->h[tag & 1][32 * c] + at, lane);
            auto signal = [&](const int k, const uint32_t dep) {
                if (lane < 2 && v < 2)
                    asm volatile("st.async.weak.shared::cluster.mbarrier::complete_tx::bytes.b32 [%0], %1, [%2];"
                                 :: "r"(mapa(sb + M_SINK, lane)), "r"(dep), "r"(mapa(bars + 8 * (B_F + k), lane)) : "memory");
            };
#pragma unroll 1
            for (int i = 0; i < 4; i++) {
                const int s = 4 * i + v;
                uint32_t a[16][4], b[2][4];
                if (gu) {
                    const uint32_t tile = tile0 + (s < 14 ? s : v) * 8192;
                    if (lane0 && i > 1) mbar_arrive(bars + 8 * (B_E + s - 4));
                    if (i == 2) signal(0, 0);
                    mbar_wait(bars + 8 * (B_W + s));
#pragma unroll
                    for (int q = 0; q < 16; q++) ldsm4t((tile ^ ((q & 1) << 5)) + ((q >> 1) & 1) * 4096 + (q >> 2) * 1024, a[q][0], a[q][1], a[q][2], a[q][3]);
                }
                if (i == 0) {
                    if (gu) {
                        uint32_t dep = p.zero;
#pragma unroll
                        for (int q = 0; q < 16; q += 2) dep &= a[q][0] & a[q + 1][0];
                        if (lane == 0) mbar_arrive(bars + 8 * (B_E + v) + dep);
                    }
                    WSTAMP(11);
                    uint32_t top;
#pragma unroll 1
                    for (int it = 0; it < (1 << 22); it++) {
                        asm volatile("ld.relaxed.gpu.global.u32 %0, [%1];" : "=r"(top) : "l"(&p.sc->top[c % NTOP][g]) : "memory");
                        if (__all_sync(0xffffffffu, ((top ^ (tag << 11)) & 0xf800u) == 0)) break;
                        if (TSLEEP) __nanosleep(TSLEEP);
                    }
                    WSTAMP(3);
                    if (gu) {
                        const uint32_t k = 4 * h + v, row = __reduce_max_sync(0xffffffffu, lane == 4 * k ? ~top & 2047 : 0);
                        asm volatile("{\n\t.reg .pred p;\n\telect.sync _|p, 0xffffffff;\n\t"
                                     "@p cp.async.bulk.shared::cluster.global.mbarrier::complete_tx::bytes.multicast::cluster [%0], [%1], 2048, [%2], %3;\n\t}"
                            :: "r"(sb + OFF_XSEL + k * XS_ROW), "l"(p.u + (size_t)row * D_), "r"(bars + 8 * B_G), "h"((unsigned short)3) : "memory");
                    }
                    if (v == 0) {
                        const uint32_t row = ~top & 2047;
                        if (t == 0 && ((row >> 8) & 1) == h)
                            asm volatile("red.shared.or.b32 [%0], %1;" :: "r"(sb + M_BMAP + (row & 7) * 16 + (row >> 9) * 4), "r"(1u << (gate_pos(row) & 31)) : "memory");
                        if (t == 0) sts32(sb + M_TOP + lane, top);
                        if (c == 0 && lane == 0) *(volatile unsigned*)&p.sc->epoch = tag;
                        __syncwarp();
                        if (lane0) mbar_arrive(bars + 8 * B_Y);
                    }
                    if (!gu) break;
                    mbar_wait(bars + 8 * B_G);
                    WSTAMP(4);
                }
                ldsm4(xo + 128 * i, b[0][0], b[0][1], b[0][2], b[0][3]);
                ldsm4(xo + 128 * i + 64, b[1][0], b[1][1], b[1][2], b[1][3]);
#pragma unroll
                for (int q = 0; q < 16; q++) mma_bf(acc[q & 7], a[q][0], a[q][1], a[q][2], a[q][3], b[q >> 3][(q >> 1) & 2], b[q >> 3][((q >> 1) & 2) + 1]);
            }
            if (gu) {
                WSTAMP(5);
                __syncwarp();
#pragma unroll
                for (int q = 0; q < 4; q++) {
                    const int ct = q >> 1, e = 2 * (q & 1);
                    sts128(own + q * XS_ROW,
                           __float_as_uint(acc[ct][e] + acc[4 + ct][e]), __float_as_uint(acc[2 + ct][e] + acc[6 + ct][e]),
                           __float_as_uint(acc[ct][e + 1] + acc[4 + ct][e + 1]), __float_as_uint(acc[2 + ct][e + 1] + acc[6 + ct][e + 1]));
                }
                bar_sync(1, 128);
                float hv[2];
#pragma unroll
                for (int e = 0; e < 2; e++) {
                    uint2 q[4];
#pragma unroll
                    for (int i = 0; i < 4; i++) q[i] = lds64(po + 64 * e + 512 * i);
                    const float s0 = (__uint_as_float(q[0].x) + __uint_as_float(q[1].x)) + (__uint_as_float(q[2].x) + __uint_as_float(q[3].x));
                    const float s1 = (__uint_as_float(q[0].y) + __uint_as_float(q[1].y)) + (__uint_as_float(q[2].y) + __uint_as_float(q[3].y));
                    const float gv = bf_round(p.gu_swap ? s1 : s0), uv = bf_round(p.gu_swap ? s0 : s1);
                    hv[e] = bf_round(gv * sigmoid_f(gv)) * uv;
                }
                const uint32_t hw = pack_bf(hv[0], hv[1]);
                st_gpu32(hdst, hw ? hw : 0x80000000u);
                signal(1, hw);
            }
        }
        WSTAMP(6);
        asm volatile("setmaxnreg.dec.sync.aligned.u32 104;");
        {
            uint4 hq[14];
            const uint32_t own = pin(sb + OFF_XSEL + at * 16, lane);
            {
                bar_sync(1, 128);
                mbar_wait(bars + 8 * (B_W + HW));
                const uint32_t hb = sb + (v < 2 ? OFF_XSEL + 7168 * v : OFF_RING + 8192 * v);
                WSTAMP(12);
#pragma unroll 1
                for (int it = 0; it < (1 << 16); it++) {
                    bulk_load(hb, &p.sc->h[tag & 1][32 * (56 * h + 14 * v)], 7168, bars + 8 * (B_X + v));
                    mbar_wait(bars + 8 * (B_X + v), ~it & 1);
                    uint32_t mn = 0xffffffffu;
#pragma unroll
                    for (int i = 0; i < 14; i++) hq[i] = lds128(hb + 512 * i + 16 * lane);
#pragma unroll
                    for (int i = 0; i < 14; i++) mn = min(mn, hq[i].x);
                    if (__all_sync(0xffffffffu, mn != 0)) break;
                }
            }
            WSTAMP(7);
            float dd[4][4];
            const int krow = ((lane >> 1) & 8) + (lane & 7);
            const uint32_t tile = sb + OFF_RING + v * 8192 + krow * 32 + ((((lane >> 3) ^ (krow >> 2)) & 1) << 4);
#pragma unroll
            for (int s = 0; s < 2; s++) {
                mbar_wait(bars + 8 * (B_W + 16 + 4 * s + v));
#pragma unroll
                for (int j = 0; j < 14; j++) {
                    uint32_t a[4];
                    ldsm4t(tile + (s ? 65536 : (v & 2) * 16384) + j * 512, a[0], a[1], a[2], a[3]);
                    const uint4& hb = hq[7 * s + (j >> 1)];
                    if (s == 0 && j < 4) mma_bf_z(dd[j], a[0], a[1], a[2], a[3], (j & 1) ? hb.z : hb.x, (j & 1) ? hb.w : hb.y);
                    else mma_bf(dd[(j + 2 * s) & 3], a[0], a[1], a[2], a[3], (j & 1) ? hb.z : hb.x, (j & 1) ? hb.w : hb.y);
                }
            }
            WSTAMP(8);
            uint4 part;
            part.x = __float_as_uint((dd[0][0] + dd[1][0]) + (dd[2][0] + dd[3][0])); part.y = __float_as_uint((dd[0][1] + dd[1][1]) + (dd[2][1] + dd[3][1]));
            part.z = __float_as_uint((dd[0][2] + dd[1][2]) + (dd[2][2] + dd[3][2])); part.w = __float_as_uint((dd[0][3] + dd[1][3]) + (dd[2][3] + dd[3][3]));
            st_async16(mapa(own + (M_DPIN - OFF_XSEL), h ^ 1), part, mapa(bars + 8 * B_DP, h ^ 1));
            sts128(own + 14336, part.x, part.y, part.z, part.w);
            __syncwarp();
            if (lane == 0) mbar_arrive(bars + 8 * B_DP);
        }
        WDUMP();
    } else {
        asm volatile("setmaxnreg.dec.sync.aligned.u32 40;");
        const int v = __reduce_max_sync(0xffffffffu, pw - PREP_W0);
        const bool gu = c < NGU_CTA;
        const uint32_t t0 = clock();
        const uint32_t bu = bars + 8 * v;
        if (lane == 0) {
            mbar_init(bu + 8 * B_X, 1);
            asm volatile("fence.mbarrier_init.release.cluster;" ::: "memory");
        }
        __syncwarp();
        if (DELAY_X > 0) __nanosleep(DELAY_X);
        bulk_load(sb + (v < 2 ? OFF_XSEL : OFF_RING + 2 * 8192) + v * 8192, p.u + (size_t)(16 * c + 4 * v) * D_, 8192, bu + 8 * B_X);
        if (lane == 0) {
#pragma unroll
            for (int i = 0; i < 10; i++) mbar_init(bu + 32 * i, 1);
            mbar_init(bu + 8 * B_XE, 1);
            mbar_init(bu + 8 * B_Y, v == 0 ? 11 : 9);
            mbar_init(bu + 8 * B_DP, (0x1855 >> (4 * v)) & 15);
            mbar_init(bu + 8 * B_F, v == 0 ? 2 : 1);
            mbar_init(bu + 8 * B_H, 1);
            asm volatile("fence.mbarrier_init.release.cluster;" ::: "memory");
            mbar_expect(bu + 8 * B_Y, 4096);
            if (v != 2) mbar_expect(bu + 8 * B_DP, v == 0 ? 2048 : (h || v == 3) ? 16384 : 16384 + 128);
            mbar_expect(bu + 8 * B_F, c < NGU_CTA ? 16 : 0);
        }
        __syncwarp();
        asm volatile("barrier.cluster.arrive.relaxed.aligned;" ::: "memory");
        tma3d(sb + OFF_S + v * S_Q, &tm_x, 16 * pr, 64 * v + 32 * h - 1, bars + 8 * (B_S + v), S_Q);
        WSTAMP(9);
        if (v < 3 && lane == 0) asm volatile("prefetch.tensormap [%0];" :: "l"(v == 0 ? &tm_gu : v == 1 ? &tm_down : &tm_out) : "memory");
        asm volatile("barrier.cluster.wait.acquire.aligned;" ::: "memory");
        if (v > 0) mbar_wait(bars + 8 * (B_H + v));
        {
            const int gap = v == 0 ? GAP : v == 1 ? GAP1 : v == 2 ? GAP2 : GAP3;
            uint32_t last = v ? clock() - SLACK : t0 + T0 - GAP + STAG * ((pr * 5) & 15) / 16;
#pragma unroll 1
            for (int s = 6 * v; s < 6 * v + 6; s++) {
                const int i = s >> 2, w = s & 3, slot = s < 14 ? s : (s | 1) == 17 ? s - 16 : s - 12;
                if (s >= 4) mbar_wait(bars + 8 * ((gu && s >= 14) ? B_E + slot : s < 6 ? B_XE + s - 2 : B_KG));
                uint32_t now;
#pragma unroll 1
                while ((int)((now = clock()) - last) < gap) __nanosleep(CSLEEP);
                last = max((int)(now - last) - SLACK, gap) + last;
                WSTAMP(3 + s - 6 * v);
                if (gu || s >= 16) tma3d(sb + OFF_RING + slot * 8192, i < 4 ? &tm_gu : &tm_down, i < 4 ? 32 * c : 16 * pr,
                      i < 4 ? 256 * w + 64 * i : 1792 * h + 448 * w + 224 * (i - 4), bars + 8 * (B_W + s), i < 4 ? 8192 : 7168);
            }
            if (lane == 0) mbar_arrive(bars + 8 * (B_H + ((v + 1) & 3)));
        }
        if (v == 0) {
            mbar_wait(bars + 8 * B_U);
            mbar_wait(bars + 8 * B_F);
            if (!gu) mbar_wait(bars + 8 * (B_H + 3));
            const uint32_t tag16 = lds32(sb + M_TAG);
#pragma unroll 1
            for (int k = 0; k < 2; k++) {
                uint4 q[4];
#pragma unroll 1
                for (int it = 0; it < (1 << 22); it++) {
                    uint32_t bad = 0;
#pragma unroll
                    for (int i = 0; i < 4; i++) q[i] = ld_gpu128(&p.sc->g[256 * h + 128 * k + 32 * i + lane]);
#pragma unroll
                    for (int i = 0; i < 4; i++) bad |= ((q[i].x ^ tag16) | (q[i].y ^ tag16)) | ((q[i].z ^ tag16) | (q[i].w ^ tag16));
                    if ((bad >> 16) == 0) break;
                    __nanosleep(200);
                }
#pragma unroll
                for (int i = 0; i < 4; i++)
                    asm volatile("st.shared.v2.u32 [%0], {%1, %2};" :: "r"(sb + OFF_GP + 1024 * k + 256 * i + lane * 8),
                                 "r"(__byte_perm(q[i].x, q[i].y, 0x5410)), "r"(__byte_perm(q[i].z, q[i].w, 0x5410)) : "memory");
            }
            __syncwarp();
            if (lane == 0) mbar_arrive(bars + 8 * B_Y);
        }
        {
            asm volatile("setmaxnreg.inc.sync.aligned.u32 72;");
            WSTAMP(1);
            mix_rows<2, BULKQ>(p, &tm_out, sb, 0, PQ, v, h, pr, lane);
            WSTAMP(2);
            asm volatile("cp.async.bulk.commit_group;" ::: "memory");
            const uint32_t top = lds32(sb + M_TOP + 8 * v + 4 * (lane >> 4));
            const uint32_t row = ~top & 2047, ch = lane & 15, gp = gate_pos(row);
            const bool mine = ((row >> 8) & 1) == h;
            uint32_t gfin, x16, y16 = 0;
            asm volatile("ld.shared.u16 %0, [%1];" : "=r"(gfin) : "r"(sb + OFF_GP + gp * 2) : "memory");
            asm volatile("ld.shared.u16 %0, [%1];" : "=r"(x16) : "r"(sb + OFF_S + (row >> 9) * S_Q + s_addr((row & 7) * S_PL + 32 + (row & 248) * 4, ch >> 3) + 2 * (ch & 7)) : "memory");
            const float rsel = __uint_as_float(pin(__float_as_uint(bf_round(sigmoid_f(__uint_as_float((top ^ (((int)~top >> 31) | 0x80000000u)) & 0xffff0000u)))), lane));
            const uint32_t po = pin(sb + (4 * (ch & 7) + v) * 16 + (ch >> 3) * 8 + (lane >> 4) * 4, lane);
            bf16* op = pin(p.out + (size_t)row * D_ + 16 * pr + ch, lane);
            if (mine) {
                mbar_wait(bars + 8 * (B_Y + (row >> 9)));
                asm volatile("ld.shared.u16 %0, [%1];" : "=r"(y16)
                             : "r"(sb + y_off(row >> 9) + ch * 512 + (((4 * (row & 7) + ((row >> 5) & 3)) ^ (((ch >> 2) << 1) | (ch & 1))) << 4) + 2 * row_elem(row)) : "memory");
            }
            mbar_wait(bars + 8 * B_DP);
            float q[8];
#pragma unroll
            for (int i = 0; i < 4; i++) { q[i] = ldsf(po + M_DPIN + 512 * i); q[4 + i] = ldsf(po + OFF_XSEL + 14336 + 512 * i); }
            const float tot = ((q[0] + q[1]) + (q[2] + q[3])) + ((q[4] + q[5]) + (q[6] + q[7]));
            const float b = bf_round(__uint_as_float(x16 << 16) + bf_round(bf_round(tot) * rsel));
            if (mine) *op = __float2bfloat16_rn(fmaf(bf_lo(gfin), __uint_as_float(y16 << 16), bf_round(bf_round(1.f - bf_lo(gfin)) * b)));
        }
        asm volatile("cp.async.bulk.wait_group.read 0;" ::: "memory");
        WSTAMP(10);
        WDUMP();
    }
}

typedef CUresult (*EncodeFn)(CUtensorMap*, CUtensorMapDataType, cuuint32_t, void*, const cuuint64_t*, const cuuint64_t*,
                             const cuuint32_t*, const cuuint32_t*, CUtensorMapInterleave, CUtensorMapSwizzle,
                             CUtensorMapL2promotion, CUtensorMapFloatOOBfill);

void make_map(EncodeFn f, CUtensorMap* m, const void* ptr, uint64_t cols, uint64_t rows, uint64_t pitch, uint32_t bc, uint32_t br, CUtensorMapSwizzle sw, int prom,
              uint32_t planes = 1, uint64_t plane_stride = 0, uint32_t box_planes = 0) {
    cuuint64_t dims[3] = {cols, rows, planes};
    cuuint64_t str[2] = {pitch, planes > 1 ? plane_stride : pitch * rows};
    cuuint32_t box[3] = {bc, br, box_planes ? box_planes : planes};
    cuuint32_t es[3] = {1, 1, 1};
    f(m, CU_TENSOR_MAP_DATA_TYPE_BFLOAT16, 3, (void*)ptr, dims, str, box, es, CU_TENSOR_MAP_INTERLEAVE_NONE, sw,
      (CUtensorMapL2promotion)prom, CU_TENSOR_MAP_FLOAT_OOB_FILL_NONE);
}

}

extern "C" void kernel_launch(void* const* d_in, const int* in_sizes, int n_in, void* d_out, int out_size) {
    static EncodeFn enc = nullptr;
    static void *sc = nullptr, *band = nullptr;
    if (!enc) {
        void* fn = nullptr;
        cudaDriverEntryPointQueryResult qr;
        cudaGetDriverEntryPoint("cuTensorMapEncodeTiled", &fn, cudaEnableDefault, &qr);
        enc = (EncodeFn)fn;
        cudaGetSymbolAddress(&sc, g_scratch);
        cudaGetSymbolAddress(&band, g_band);
        cudaFuncSetAttribute(fused_kernel, cudaFuncAttributeMaxDynamicSharedMemorySize, SMEM_BYTES);
    }
    CUtensorMap tg, td, tx, to;
    const char *wg = (const char*)d_in[9], *wu = (const char*)d_in[10];
    const bool swap = wu < wg;
    make_map(enc, &tg, swap ? wu : wg, F_, D_, F_ * 2, 32, 64, CU_TENSOR_MAP_SWIZZLE_64B, PROMG, 2, swap ? wg - wu : wu - wg);
    make_map(enc, &td, d_in[11], D_, F_, D_ * 2, 16, 224, CU_TENSOR_MAP_SWIZZLE_32B, PROMD);
    make_map(enc, &tx, d_in[0], D_, L_ / 8, D_ * 16, 16, 33, CU_TENSOR_MAP_SWIZZLE_32B, PROMX, 8, D_ * 2);
    make_map(enc, &to, d_out, D_, L_ / 8, D_ * 16, 16, 32, CU_TENSOR_MAP_SWIZZLE_NONE, 0, 8, D_ * 2, 1);
    Params p;
    p.u = (const bf16*)d_in[0]; p.logA = (const bf16*)d_in[1]; p.Aim = (const bf16*)d_in[2];
    p.Cre = (const bf16*)d_in[3]; p.Cim = (const bf16*)d_in[4]; p.logdt = (const bf16*)d_in[5];
    p.Dskip = (const bf16*)d_in[6]; p.wr = (const bf16*)d_in[8]; p.gatew = (const bf16*)d_in[12];
    p.out = (bf16*)d_out;
    p.sc = (Scratch*)sc; p.band = (const uint4*)band;
    p.gu_swap = swap;
    p.zero = 0;
    fused_kernel<<<NCTA, NTHREADS, SMEM_BYTES>>>(p, tg, td, tx, to);
}
```

```cpp
#include <cuda_runtime.h>
#include <cuda_bf16.h>
#include <cuda_fp16.h>
#include <cuda.h>
#include <stdint.h>

typedef __nv_bfloat16 bf16;

namespace {

constexpr int L_ = 2048, D_ = 1024, F_ = 3584;
constexpr int NCTA = 130;
constexpr int NTHREADS = 512;
#define AUXW 12
constexpr int MAIN_W0 = 0, AUX_W0 = AUXW, PREP_W0 = 20 - AUXW;
#define T0 3500
#define GAP 590
#define GAP1 530
#define GAP2 530
#define GAP3 550
#define STAG GAP
#define CSLEEP 50
#define SLACK 300
#define DELAY_X 150
#define TSLEEP 40
#define RS 2
#define BULKQ true
#define PQ 3
#define PROMG 2
#define PROMD 1
#define PROMX 0
#define LATE2 0
#define HW 21
constexpr int NGU_CTA = 112;

constexpr int OFF_RING = 0;
constexpr int OFF_SCR  = 6 * 8192;
constexpr int S_PL     = 1056;
constexpr int S_Q      = 8 * S_PL;
constexpr int OFF_S    = 114688;
constexpr int OFF_GP   = OFF_S + 4 * S_Q;
constexpr int U_PL     = 2240;
constexpr int U_CH     = 4416;
constexpr int OFF_U    = 151552;
constexpr int TAB_W    = 3200;
constexpr int T_PL     = 544;
constexpr int T_A      = 2192 - 26 * 8;
constexpr int T_B      = 2568 - 59 * 8;
constexpr int OFF_TAB  = 186880;
constexpr int OFF_XSEL = 212480;
constexpr int XS_ROW   = 2064;
constexpr int OFF_BAND = 228992;
constexpr int OFF_MISC = 229536;
constexpr int M_BARS   = OFF_MISC;
constexpr int M_DSK    = OFF_MISC + 2736;
constexpr int M_SINK   = OFF_MISC + 512;
constexpr int M_TAG    = OFF_MISC + 516;
constexpr int M_BMAP   = OFF_MISC + 528;
constexpr int M_DPIN   = OFF_MISC + 656;
constexpr int M_TOP    = OFF_MISC + 2704;
constexpr int SMEM_BYTES = OFF_MISC + 2768;
__device__ __forceinline__ uint32_t s_addr(uint32_t o, uint32_t half) { return o + (((half ^ (o >> 7)) & 1) << 4); }
__host__ __device__ constexpr uint32_t y_off(uint32_t q) { return OFF_RING + 32768 + (q & 1) * 8192 + (q >> 1) * 65536; }

constexpr int B_W = 0;
constexpr int B_E = 24;
constexpr int B_S = 36;
constexpr int B_Y = 40;
constexpr int B_DP = 44, B_U = 45, B_KG = 46, B_G = 47;
constexpr int B_F = 48;
constexpr int B_H = 60;
constexpr int B_X = 52, B_XE = 56;

struct BandTab { uint32_t w[11][12]; };
constexpr BandTab make_band() {
    BandTab b{};
    for (int cls = 0; cls < 11; cls++)
        for (int wd = 0; wd < 10; wd++) {
            const int tau = cls + 2 - 8 * ((wd < 4 ? wd : wd - 4) >> 1);
            const int lo = (wd < 4) ? ((wd & 1) ? -2 : 3) : ((wd & 1) ? -4 : -11), wid = (wd < 4 ? 3 : 7) + 2 * (wd & 1);
            b.w[cls][wd] = ((tau >= lo && tau < lo + wid) ? 0x3F80u : 0u) | ((tau - 4 >= lo && tau - 4 < lo + wid) ? 0x3F800000u : 0u);
        }
    return b;
}
constexpr int NTOP = 32;
struct Scratch {
    uint4 r[L_ / 4 * RS];
    uint4 g[L_ / 4];
    uint4 h[2][8 * F_ / 8];
    uint32_t top[NTOP][32];
    unsigned epoch;
};
__device__ __align__(128) Scratch g_scratch;
__device__ const __align__(16) BandTab g_band = make_band();

struct Params {
    const bf16 *u, *logA, *Aim, *Cre, *Cim, *logdt, *Dskip, *wr, *gatew;
    bf16* out;
    Scratch* sc;
    const uint4* band;
    uint32_t gu_swap;
    uint32_t zero;
};

#define WSTAMP(i) do {} while (0)
#define KSTAMP(i, dep) do {} while (0)
#define WDUMP() do {} while (0)
#define RSTAMP(i) do {} while (0)

#define NOALLOC ".L1::no_allocate"
__device__ __forceinline__ uint32_t smem_u32(const void* p) { return (uint32_t)__cvta_generic_to_shared(p); }
__device__ __forceinline__ void mbar_init(uint32_t b, uint32_t c) { asm volatile("mbarrier.init.shared::cta.b64 [%0], %1;" :: "r"(b), "r"(c) : "memory"); }
__device__ __forceinline__ void mbar_expect(uint32_t b, uint32_t tx) { asm volatile("mbarrier.arrive.expect_tx.shared::cta.b64 _, [%0], %1;" :: "r"(b), "r"(tx) : "memory"); }
__device__ __forceinline__ void mbar_arrive(uint32_t b) { asm volatile("mbarrier.arrive.shared::cta.b64 _, [%0];" :: "r"(b) : "memory"); }
__device__ __forceinline__ void mbar_wait(uint32_t b, uint32_t parity = 0) {
    asm volatile("{\n\t.reg .pred p;\nW%=:\n\tmbarrier.try_wait.parity.shared::cta.b64 p, [%0], %1, 20000;\n\t@!p bra W%=;\n\t}" :: "r"(b), "r"(parity) : "memory");
}
__device__ __forceinline__ uint32_t mapa(uint32_t addr, uint32_t rank) { uint32_t r; asm("mapa.shared::cluster.u32 %0, %1, %2;" : "=r"(r) : "r"(addr), "r"(rank)); return r; }
__device__ __forceinline__ void tma3d(uint32_t dst, const CUtensorMap* tm, int c0, int c1, uint32_t bar, uint32_t bytes) {
    asm volatile("{\n\t.reg .pred p;\n\telect.sync _|p, 0xffffffff;\n\t"
                 "@p mbarrier.arrive.expect_tx.shared::cta.b64 _, [%2], %5;\n\t"
                 "@p cp.async.bulk.tensor.3d.shared::cluster.global.mbarrier::complete_tx::bytes [%0], [%1, {%3, %4, 0}], [%2];\n\t}"
        :: "r"(dst), "l"(tm), "r"(bar), "r"(c0), "r"(c1), "r"(bytes) : "memory");
}
__device__ __forceinline__ void bulk_load(uint32_t dst, const void* src, uint32_t bytes, uint32_t bar) {
    asm volatile("{\n\t.reg .pred p;\n\telect.sync _|p, 0xffffffff;\n\t"
                 "@p mbarrier.arrive.expect_tx.shared::cta.b64 _, [%2], %3;\n\t"
                 "@p cp.async.bulk.shared::cluster.global.mbarrier::complete_tx::bytes [%0], [%1], %3, [%2];\n\t}"
        :: "r"(dst), "l"(src), "r"(bar), "r"(bytes) : "memory");
}
__device__ __forceinline__ void st_async16(uint32_t dst, const uint4& v, uint32_t bar) {
    asm volatile("st.async.weak.shared::cluster.mbarrier::complete_tx::bytes.v4.b32 [%0], {%1,%2,%3,%4}, [%5];"
                 :: "r"(dst), "r"(v.x), "r"(v.y), "r"(v.z), "r"(v.w), "r"(bar) : "memory");
}
__device__ __forceinline__ void bar_sync(int id, int n) { asm volatile("bar.sync %0, %1;" :: "r"(id), "r"(n) : "memory"); }
__device__ __forceinline__ void cp16(uint32_t dst, const void* src) { asm volatile("cp.async.cg.shared.global [%0], [%1], 16;" :: "r"(dst), "l"(src) : "memory"); }
__device__ __forceinline__ void cp_wait_all() { asm volatile("cp.async.wait_all;" ::: "memory"); }
__device__ __forceinline__ uint2 ldg64(const void* p) { uint2 v; asm volatile("ld.global.nc" NOALLOC ".v2.u32 {%0,%1}, [%2];" : "=r"(v.x), "=r"(v.y) : "l"(p)); return v; }
__device__ __forceinline__ uint4 ld_gpu128(const void* p) { uint4 v; asm volatile("ld.relaxed.gpu.global.v4.u32 {%0,%1,%2,%3}, [%4];" : "=r"(v.x), "=r"(v.y), "=r"(v.z), "=r"(v.w) : "l"(p) : "memory"); return v; }
__device__ __forceinline__ void st_gpu32(void* p, uint32_t v) { asm volatile("st.relaxed.gpu.global.u32 [%0], %1;" :: "l"(p), "r"(v) : "memory"); }

__device__ __forceinline__ void ldsm4(uint32_t a, uint32_t& r0, uint32_t& r1, uint32_t& r2, uint32_t& r3) {
    asm volatile("ldmatrix.sync.aligned.m8n8.x4.shared.b16 {%0,%1,%2,%3}, [%4];" : "=r"(r0), "=r"(r1), "=r"(r2), "=r"(r3) : "r"(a) : "memory");
}
__device__ __forceinline__ void ldsm4t(uint32_t a, uint32_t& r0, uint32_t& r1, uint32_t& r2, uint32_t& r3) {
    asm volatile("ldmatrix.sync.aligned.m8n8.x4.trans.shared.b16 {%0,%1,%2,%3}, [%4];" : "=r"(r0), "=r"(r1), "=r"(r2), "=r"(r3) : "r"(a) : "memory");
}
__device__ __forceinline__ uint32_t lds32(uint32_t a) { uint32_t v; asm volatile("ld.shared.u32 %0, [%1];" : "=r"(v) : "r"(a) : "memory"); return v; }
__device__ __forceinline__ uint2 lds64(uint32_t a) { uint2 v; asm volatile("ld.shared.v2.u32 {%0,%1}, [%2];" : "=r"(v.x), "=r"(v.y) : "r"(a) : "memory"); return v; }
__device__ __forceinline__ uint4 lds128(uint32_t a) { uint4 v; asm volatile("ld.shared.v4.u32 {%0,%1,%2,%3}, [%4];" : "=r"(v.x), "=r"(v.y), "=r"(v.z), "=r"(v.w) : "r"(a) : "memory"); return v; }
__device__ __forceinline__ void sts32(uint32_t a, uint32_t v) { asm volatile("st.shared.u32 [%0], %1;" :: "r"(a), "r"(v) : "memory"); }
__device__ __forceinline__ void sts16(uint32_t a, uint32_t v) { asm volatile("st.shared.u16 [%0], %1;" :: "r"(a), "h"((unsigned short)v) : "memory"); }
__device__ __forceinline__ void sts128(uint32_t a, uint32_t x, uint32_t y, uint32_t z, uint32_t w) { asm volatile("st.shared.v4.u32 [%0], {%1,%2,%3,%4};" :: "r"(a), "r"(x), "r"(y), "r"(z), "r"(w) : "memory"); }
__device__ __forceinline__ float ldsf(uint32_t a) { float v; asm volatile("ld.shared.f32 %0, [%1];" : "=f"(v) : "r"(a) : "memory"); return v; }

__device__ __forceinline__ void mma_bf(float (&d)[4], uint32_t a0, uint32_t a1, uint32_t a2, uint32_t a3, uint32_t b0, uint32_t b1) {
    asm volatile("mma.sync.aligned.m16n8k16.row.col.f32.bf16.bf16.f32 {%0,%1,%2,%3}, {%4,%5,%6,%7}, {%8,%9}, {%0,%1,%2,%3};"
        : "+f"(d[0]), "+f"(d[1]), "+f"(d[2]), "+f"(d[3]) : "r"(a0), "r"(a1), "r"(a2), "r"(a3), "r"(b0), "r"(b1));
}
__device__ __forceinline__ void mma_bf_z(float (&d)[4], uint32_t a0, uint32_t a1, uint32_t a2, uint32_t a3, uint32_t b0, uint32_t b1) {
    asm volatile("mma.sync.aligned.m16n8k16.row.col.f32.bf16.bf16.f32 {%0,%1,%2,%3}, {%4,%5,%6,%7}, {%8,%9}, {%10,%10,%10,%10};"
        : "=f"(d[0]), "=f"(d[1]), "=f"(d[2]), "=f"(d[3]) : "r"(a0), "r"(a1), "r"(a2), "r"(a3), "r"(b0), "r"(b1), "f"(0.f));
}
__device__ __forceinline__ void mma_bf_k8(float (&d)[4], uint32_t a0, uint32_t a1, uint32_t b0) {
    asm volatile("mma.sync.aligned.m16n8k8.row.col.f32.bf16.bf16.f32 {%0,%1,%2,%3}, {%4,%5}, {%6}, {%0,%1,%2,%3};"
        : "+f"(d[0]), "+f"(d[1]), "+f"(d[2]), "+f"(d[3]) : "r"(a0), "r"(a1), "r"(b0));
}
__device__ __forceinline__ void mma_h(float (&d)[4], uint32_t a0, uint32_t a1, uint32_t a2, uint32_t a3, uint32_t b0, uint32_t b1) {
    asm volatile("mma.sync.aligned.m16n8k16.row.col.f32.f16.f16.f32 {%0,%1,%2,%3}, {%4,%5,%6,%7}, {%8,%9}, {%0,%1,%2,%3};"
        : "+f"(d[0]), "+f"(d[1]), "+f"(d[2]), "+f"(d[3]) : "r"(a0), "r"(a1), "r"(a2), "r"(a3), "r"(b0), "r"(b1));
}
__device__ __forceinline__ uint32_t pack_bf(float lo, float hi) { uint32_t r; asm("cvt.rn.bf16x2.f32 %0, %1, %2;" : "=r"(r) : "f"(hi), "f"(lo)); return r; }
__device__ __forceinline__ uint32_t pack_h(float lo, float hi) { uint32_t r; asm("cvt.rn.f16x2.f32 %0, %1, %2;" : "=r"(r) : "f"(hi), "f"(lo)); return r; }
__device__ __forceinline__ float bf_lo(uint32_t v) { return __uint_as_float(v << 16); }
__device__ __forceinline__ float bf_hi(uint32_t v) { return __uint_as_float(v & 0xffff0000u); }
__device__ __forceinline__ float bf_round(float x) { return __uint_as_float(pack_bf(0.f, x)); }
__device__ __forceinline__ uint32_t hmul2_bf(uint32_t a, uint32_t b) { uint32_t r; asm("mul.rn.bf16x2 %0, %1, %2;" : "=r"(r) : "r"(a), "r"(b)); return r; }
__device__ __forceinline__ float ex2f(float x) { float r; asm("ex2.approx.ftz.f32 %0, %1;" : "=f"(r) : "f"(x)); return r; }

__device__ __forceinline__ float exp_acc(float x) {
    const float t = x * 1.4426950216293335f;
    const float r = fmaf(x, 1.4426950216293335f, -t) + x * 1.9259629911266175e-8f;
    return ex2f(t) * fmaf(r, 0.6931471805599453f, 1.f);
}
__device__ __forceinline__ float sigmoid_f(float x) { return __fdividef(1.f, 1.f + ex2f(-x * 1.4426950408889634f)); }
__device__ __forceinline__ void cexp_pow(float l2, float li, float e, float& zr, float& zi) {
    const float mag = ex2f(l2 * e);
    zr = mag * __cosf(li * e);
    zi = mag * __sinf(li * e);
}
__device__ __forceinline__ uint32_t hcmul(uint32_t a, uint32_t k, uint32_t kp) {
    const __half2 A = *reinterpret_cast<const __half2*>(&a);
    const __half2 r = __hfma2(__high2half2(A), *reinterpret_cast<const __half2*>(&kp), __hmul2(__low2half2(A), *reinterpret_cast<const __half2*>(&k)));
    return *reinterpret_cast<const uint32_t*>(&r);
}
#define CMUL(orr, oi, ar, ai, br, bi) do { float _r = (ar) * (br) - (ai) * (bi); float _i = (ar) * (bi) + (ai) * (br); orr = _r; oi = _i; } while (0)
#define CSQ(orr, oi, ar, ai) do { float _r = (ar) * (ar) - (ai) * (ai); float _i = 2.f * (ar) * (ai); orr = _r; oi = _i; } while (0)

__device__ __forceinline__ void mma_bf_k8z(float (&d)[4], uint32_t a0, uint32_t a1, uint32_t b0) {
    asm volatile("mma.sync.aligned.m16n8k8.row.col.f32.bf16.bf16.f32 {%0,%1,%2,%3}, {%4,%5}, {%6}, {%7,%7,%7,%7};"
        : "=f"(d[0]), "=f"(d[1]), "=f"(d[2]), "=f"(d[3]) : "r"(a0), "r"(a1), "r"(b0), "f"(0.f));
}
__device__ __forceinline__ void mma_hh_k8(uint32_t& d0, uint32_t& d1, uint32_t a0, uint32_t a1, uint32_t b0) {
    asm volatile("mma.sync.aligned.m16n8k8.row.col.f16.f16.f16.f16 {%0,%1}, {%2,%3}, {%4}, {%5,%5};"
        : "=r"(d0), "=r"(d1) : "r"(a0), "r"(a1), "r"(b0), "r"(0));
}
__device__ __forceinline__ uint32_t pin(uint32_t x, int lane) { return __shfl_sync(0xffffffffu, x, lane); }
template <class T> __device__ __forceinline__ T* pin(T* x, int lane) { return (T*)__shfl_sync(0xffffffffu, (unsigned long long)x, lane); }
__device__ __forceinline__ void sts32_if(bool on, uint32_t a, uint32_t v) {
    asm volatile("{\n\t.reg .pred p;\n\tsetp.ne.u32 p, %2, 0;\n\t@p st.shared.u32 [%0], %1;\n\t}" :: "r"(a), "r"(v), "r"((uint32_t)on) : "memory");
}
__device__ __forceinline__ void sts128_if(bool on, uint32_t a, uint32_t x, uint32_t y, uint32_t z, uint32_t w) {
    asm volatile("{\n\t.reg .pred p;\n\tsetp.ne.u32 p, %5, 0;\n\t@p st.shared.v4.u32 [%0], {%1,%2,%3,%4};\n\t}" :: "r"(a), "r"(x), "r"(y), "r"(z), "r"(w), "r"((uint32_t)on) : "memory");
}
__device__ __forceinline__ void lds128_if(bool on, uint32_t a, uint32_t (&v)[4]) {
    asm volatile("{\n\t.reg .pred p;\n\tsetp.ne.u32 p, %5, 0;\n\t@p ld.shared.v4.u32 {%0,%1,%2,%3}, [%4];\n\t}"
        : "+r"(v[0]), "+r"(v[1]), "+r"(v[2]), "+r"(v[3]) : "r"(a), "r"((uint32_t)on) : "memory");
}
__device__ __forceinline__ uint32_t hfma2_bf(uint32_t a, uint32_t b, uint32_t c) { uint32_t r; asm("fma.rn.bf16x2 %0, %1, %2, %3;" : "=r"(r) : "r"(a), "r"(b), "r"(c)); return r; }
__device__ __forceinline__ uint32_t row_elem(uint32_t row) { return ((row >> 5) & 4) | ((row >> 2) & 2) | ((row >> 4) & 1); }
__device__ __forceinline__ uint32_t gate_pos(uint32_t row) { return ((row >> 9) << 8) | ((row & 7) << 5) | (row_elem(row) << 2) | ((row >> 5) & 3); }

template <int N, bool BULK>
__device__ __forceinline__ void mix_rows(const Params& p, const CUtensorMap* tm_out, uint32_t sb, int Q0, int Q1, int w, int h, int pr, int lane) {
    const int g = lane >> 2, t = lane & 3, mi = lane >> 3, r = lane & 7;
    const int m8 = 16 * (g >> 2) + ((g >> 1) & 1) + 2 * (g & 1);
    uint32_t yi = sb + (4 * (r >> 1) + 2 * (mi & 1) + (r & 1)) * 512 + (((4 * w + (mi >> 1)) ^ r) << 4);
    uint32_t xs = sb + OFF_S + s_addr(w * S_PL + 32 + m8 * 32, t >> 1) + ((t & 1) << 3);
    uint32_t gs = sb + OFF_GP + w * 64 + g * 8, os = sb + OFF_TAB + w * TAB_W + m8 * 32 + t * 8;
    if (BULK) { yi = pin(yi, lane); xs = pin(xs, lane); gs = pin(gs, lane); os = pin(os, lane); }
    mbar_wait(sb + M_BARS + 8 * B_Y);
#pragma unroll 1
    for (int Q = Q0; Q < Q1; Q++) {
        uint2 xq[N][4];
        uint32_t gg[N][4], sw[N];
#pragma unroll
        for (int n = 0; n < N; n++) {
#pragma unroll
            for (int i = 0; i < 4; i++) xq[n][i] = lds64((xs ^ (((i ^ n) & 1) << 4)) + Q * S_Q + n * 4 * S_PL + i * 128);
            const uint2 gq = lds64(gs + Q * 512 + n * 256);
            sw[n] = lds32(sb + M_BMAP + w * 16 + n * 64 + Q * 4);
#pragma unroll
            for (int i = 0; i < 4; i++) {
                gg[n][i] = __byte_perm(i < 2 ? gq.x : gq.y, 0, (i & 1) ? 0x3232 : 0x1010);
                const uint32_t og = hfma2_bf(gg[n][i], 0xBF80BF80u, 0x3F803F80u);
                xq[n][i].x = hmul2_bf(og, xq[n][i].x); xq[n][i].y = hmul2_bf(og, xq[n][i].y);
            }
        }
        mbar_wait(sb + M_BARS + 8 * (B_Y + Q));
        __syncwarp();
#pragma unroll
        for (int n = 0; n < N; n++) {
#pragma unroll
            for (int x = 0; x < 2; x++) {
                uint32_t y[4];
                ldsm4t((yi ^ (x << 5)) + y_off(Q) + n * 256, y[0], y[1], y[2], y[3]);
#pragma unroll
                for (int e = 0; e < 2; e++) {
                    uint2& o = xq[n][2 * x + e];
                    o.x = hfma2_bf(gg[n][2 * x + e], y[2 * e], o.x); o.y = hfma2_bf(gg[n][2 * x + e], y[2 * e + 1], o.y);
                }
            }
        }
        if (BULK && (sw[0] | sw[N - 1]) == 0) {
#pragma unroll
            for (int n = 0; n < N; n++)
#pragma unroll
                for (int i = 0; i < 4; i++)
                    asm volatile("st.shared.v2.u32 [%0], {%1, %2};" :: "r"(os + Q * 1024 + n * 4 * TAB_W + i * 128), "r"(xq[n][i].x), "r"(xq[n][i].y) : "memory");
            asm volatile("fence.proxy.async.shared::cta;" ::: "memory");
            __syncwarp();
#pragma unroll
            for (int n = 0; n < N; n++)
                asm volatile("{\n\t.reg .pred p;\n\telect.sync _|p, 0xffffffff;\n\t"
                             "@p cp.async.bulk.tensor.3d.global.shared::cta.bulk_group [%1, {%2, %3, %4}], [%0];\n\t}"
                    :: "r"(sb + OFF_TAB + (w + 4 * n) * TAB_W + Q * 1024), "l"(tm_out), "r"(16 * pr), "r"(64 * Q + 32 * h), "r"(w + 4 * n) : "memory");
        } else {
            bf16* op = p.out + (size_t)(512 * Q + 256 * h + 8 * m8 + w) * D_ + 16 * pr + 4 * t;
#pragma unroll
            for (int n = 0; n < N; n++)
#pragma unroll
                for (int i = 0; i < 4; i++)
                    if (!((sw[n] >> (4 * g)) & (1u << i))) *(uint2*)(op + (size_t)(32 * i + 4 * n) * D_) = xq[n][i];
        }
    }
}

__global__ void __cluster_dims__(2, 1, 1) __launch_bounds__(NTHREADS, 1)
fused_kernel(const Params p, const __grid_constant__ CUtensorMap tm_gu, const __grid_constant__ CUtensorMap tm_down,
             const __grid_constant__ CUtensorMap tm_x, const __grid_constant__ CUtensorMap tm_out) {
    extern __shared__ __align__(1024) unsigned char smem[];
    const uint32_t sb = smem_u32(smem);
    int tid;
    asm volatile("mov.u32 %0, %%tid.x;" : "=r"(tid));
    const int pw = tid >> 5, lane = tid & 31;
    const int c = blockIdx.x, h = c & 1, pr = c >> 1;
    const uint32_t bars = sb + M_BARS;

    if (c >= 128) {
        if (c != 128) return;
        RSTAMP(5);
        const unsigned tag = (*(volatile unsigned*)&p.sc->epoch + 1) & 0xffffu;
        const uint32_t list = sb + 128;
#pragma unroll 1
        for (int pass = 0; pass < 2; pass++) {
            sts128(list + 16 * tid, 0, 0, 0, 0);
            if (tid == 0) sts32(sb + 64, 0);
            uint32_t key[4];
            bool ok = false;
#pragma unroll 1
            for (int it = 0; it < (1 << 22); it++) {
                const uint4 a = ld_gpu128(&p.sc->r[tid * RS]);
                key[0] = a.x; key[1] = a.y; key[2] = a.z; key[3] = a.w;
                ok = (((a.x ^ tag) | (a.y ^ tag) | (a.z ^ tag) | (a.w ^ tag)) & 0xffffu) == 0;
                if (ok || !pass) break;
            }
            WSTAMP(0);
            uint32_t m = 0;
#pragma unroll
            for (int i = 0; i < 4; i++) {
                key[i] = ((pass ? key[i] : (lane + i) << 16) & 0xffff0000u) | (uint32_t)(2047 - (4 * tid + i));
                m = max(m, key[i]);
            }
            const uint32_t wm = __reduce_max_sync(0xffffffffu, m);
            if (lane == 0) sts32(sb + pw * 4, wm);
            __syncthreads();
            uint32_t thr = 0xffffffffu;
#pragma unroll
            for (int i = 0; i < 4; i++) { const uint4 q = lds128(sb + 16 * i); thr = min(thr, min(max(q.x, q.y), max(q.z, q.w))); }
            if (thr != 1) WSTAMP(1);
            if (m >= thr) {
                uint32_t pos;
                asm volatile("atom.shared.add.u32 %0, [%1], %2;" : "=r"(pos) : "r"(sb + 64), "r"(4 * ((key[0] >= thr) + (key[1] >= thr) + (key[2] >= thr) + (key[3] >= thr))) : "memory");
#pragma unroll
                for (int i = 0; i < 4; i++) if (key[i] >= thr) { sts32(list + pos, key[i]); pos += 4; }
            }
            __syncthreads();
            const uint32_t nc4 = lds32(sb + 64);
            if (nc4 != 1) WSTAMP(2);
#pragma unroll 1
            for (uint32_t j = 4 * pw; j < nc4; j += 64) {
                const uint32_t mine = lds32(list + j);
                int rank = 0;
#pragma unroll 1
                for (uint32_t i = 0; i < nc4; i += 128) rank += __popc(__ballot_sync(0xffffffffu, lds32(list + i + 4 * lane) > mine));
                if (rank < 8 && lane == 0) sts32(sb + 96 + 4 * rank, mine);
            }
            __syncthreads();
            if (tid < 8 * NTOP) st_gpu32(&p.sc->top[tid >> 3][tid & 7], lds32(sb + 96 + 4 * (tid & 7)) | (((tag + pass - 1) & 31) << 11));
            WSTAMP(3);
            if (!pass) RSTAMP(4);
        }
        WDUMP();
        return;
    }

    WSTAMP(0);
    if (pw < 8) {
        uint2 v_la, v_ai, v_cr, v_ci;
        uint32_t ldt16;
        const int d = 8 * c + pw - MAIN_W0;
        const size_t po = (size_t)d * 128 + 4 * lane;
        v_la = ldg64(p.logA + po); v_ai = ldg64(p.Aim + po); v_cr = ldg64(p.Cre + po); v_ci = ldg64(p.Cim + po);
        asm volatile("ld.global.nc.u16 %0, [%1];" : "=r"(ldt16) : "l"(p.logdt + d));
        if (lane == 0) asm volatile("cp.async.ca.shared.global [%0], [%1], 4;" :: "r"(sb + M_DSK + 4 * (pw - MAIN_W0)), "l"(p.Dskip + (d & ~1)) : "memory");
        asm volatile("barrier.cluster.arrive.relaxed.aligned;" ::: "memory");
        const int warp = pw - MAIN_W0;
        asm volatile("setmaxnreg.inc.sync.aligned.u32 168;");
        const int g = lane >> 2, t = lane & 3;
        const int mi = lane >> 3, r = lane & 7;
        const uint32_t TB = sb + OFF_TAB + warp * TAB_W;
        const uint32_t UB = sb + OFF_U + warp * U_CH;
        if (mi < 2) sts128(UB + mi * U_PL + r * 16, 0, 0, 0, 0);
#pragma unroll
        for (int i = 0; i < 6; i++) sts128(TB + 16 * (lane + 32 * i), 0, 0, 0, 0);
        if (lane < 8) sts128(TB + 16 * (lane + 192), 0, 0, 0, 0);
        sts128(sb + OFF_SCR + warp * 8192 + lane * 16, 0x3C00u, 0x3C00u, 0x3C00u, 0x3C00u);
        __syncwarp();

        uint32_t cfix;
        {
            KSTAMP(4, v_la.x ^ v_ai.x ^ v_cr.x ^ v_ci.x ^ ldt16);
            const float dt = bf_round(exp_acc(__uint_as_float(ldt16 << 16)));
            float l2[4], li[4];
            {
                const uint32_t la[2] = {v_la.x, v_la.y}, ai[2] = {v_ai.x, v_ai.y};
                const float dt2 = -1.4426950408889634f * dt;
#pragma unroll
                for (int i = 0; i < 4; i++) {
                    l2[i] = bf_round(ex2f(((i & 1) ? bf_hi(la[i >> 1]) : bf_lo(la[i >> 1])) * 1.4426950408889634f)) * dt2;
                    li[i] = ((i & 1) ? bf_hi(ai[i >> 1]) : bf_lo(ai[i >> 1])) * dt;
                }
            }
            const uint32_t SX = sb + OFF_SCR + warp * 8192;
            const uint32_t sw = SX + (lane << 4);
#define PUT(buf, row, v) sts128(((sw + (row) * 512) ^ ((row) << 4)) + (buf) * 4096, v[0], v[1], v[2], v[3])
#define EMIT(bufa, rowa, bufb, rowb, xr, xi, k, kp) do { uint32_t pk[4], pd[4]; \
                _Pragma("unroll") for (int i = 0; i < 4; i++) { pk[i] = pack_h(xr[i], xi[i]); pd[i] = hcmul(pk[i], k[i], kp[i]); } \
                PUT(bufa, rowa, pk); PUT(bufb, rowb, pd); } while (0)
#define CMUL4(orr, oi, ar, ai, br, bi) _Pragma("unroll") for (int i = 0; i < 4; i++) CMUL(orr[i], oi[i], ar[i], ai[i], br[i], bi[i])
#define CSQ4(orr, oi, ar, ai) _Pragma("unroll") for (int i = 0; i < 4; i++) CSQ(orr[i], oi[i], ar[i], ai[i])
            float z1r[4], z1i[4], z2r[4], z2i[4], z8r[4], z8i[4], z256r[4], z256i[4];
            uint32_t k128[4], k128p[4], k4[4], k4p[4];
            float z4r[4], z4i[4];
#pragma unroll
            for (int i = 0; i < 4; i++) cexp_pow(l2[i], li[i], 1.f, z1r[i], z1i[i]);
            CSQ4(z2r, z2i, z1r, z1i);
            CSQ4(z4r, z4i, z2r, z2i);
            CSQ4(z8r, z8i, z4r, z4i);
            KSTAMP(5, __float_as_uint(z8r[3]));
            uint32_t Ya[16][4];
            float cr[4], ci[4], inv;
            {
                float w1r[4], w1i[4], ar[4], ai[4], br[4], bi[4];
                uint32_t k8[4], k8p[4];
#pragma unroll
                for (int i = 0; i < 4; i++) {
                    k8[i] = pack_h(z8r[i], -z8i[i]); k8p[i] = pack_h(z8i[i], z8r[i]);
                    CSQ(w1r[i], w1i[i], z8r[i], z8i[i]); w1i[i] = -w1i[i];
                }
                PUT(1, 0, k8);
                EMIT(0, 1, 1, 1, w1r, w1i, k8, k8p);
                CSQ4(ar, ai, w1r, w1i);            EMIT(0, 2, 1, 2, ar, ai, k8, k8p);
                CMUL4(br, bi, ar, ai, w1r, w1i);   EMIT(0, 3, 1, 3, br, bi, k8, k8p);
                CSQ4(ar, ai, ar, ai);              EMIT(0, 4, 1, 4, ar, ai, k8, k8p);
                CMUL4(ar, ai, ar, ai, w1r, w1i);   EMIT(0, 5, 1, 5, ar, ai, k8, k8p);
                CSQ4(br, bi, br, bi);              EMIT(0, 6, 1, 6, br, bi, k8, k8p);
                CMUL4(br, bi, br, bi, w1r, w1i);   EMIT(0, 7, 1, 7, br, bi, k8, k8p);
                __syncwarp();
                KSTAMP(6, 0);
                const uint32_t ab = SX + (mi & 1) * 4096 + r * 512, ax = ((mi >> 1) ^ r) << 4;
                const uint32_t vr[2] = {v_cr.x, v_cr.y}, vi[2] = {v_ci.x, v_ci.y};
                const uint32_t m2 = __vmaxu2(__vmaxu2(vr[0] & 0x7fff7fffu, vr[1] & 0x7fff7fffu), __vmaxu2(vi[0] & 0x7fff7fffu, vi[1] & 0x7fff7fffu));
                const uint32_t mx = __reduce_max_sync(0xffffffffu, max(m2, m2 << 16));
                const uint32_t e = min(max(mx >> 23, 11u), 254u);
                const float sc = __uint_as_float((264u - e) << 23);
                inv = __uint_as_float((e - 10u) << 23) * (2.f * dt);
#pragma unroll
                for (int i = 0; i < 4; i++) {
#pragma unroll
                    for (int k = 0; k < 4; k++) ldsm4(ab + (ax ^ (i << 5)) + k * 128, Ya[4 * k + i][0], Ya[4 * k + i][1], Ya[4 * k + i][2], Ya[4 * k + i][3]);
                    float tr, ti;
                    cexp_pow(l2[i], li[i], 128.f, tr, ti);
                    k128[i] = pack_h(tr, ti); k128p[i] = pack_h(-ti, tr);
                    k4[i] = pack_h(z4r[i], z4i[i]); k4p[i] = pack_h(-z4i[i], z4r[i]);
                    CSQ(z256r[i], z256i[i], tr, ti);
                    cr[i] = ((i & 1) ? bf_hi(vr[i >> 1]) : bf_lo(vr[i >> 1])) * sc;
                    ci[i] = ((i & 1) ? bf_hi(vi[i >> 1]) : bf_lo(vi[i >> 1])) * sc;
                }
#pragma unroll
                for (int i = 0; i < 4; i++) { sts32(TB + i * T_PL + 16 + 4 * lane, k128[i]); sts32(TB + i * T_PL + 160 + 4 * lane, k128p[i]); }
                __syncwarp();
            }
            KSTAMP(7, Ya[15][0]);
            const uint32_t ld0 = SX + r * 512 + ((mi ^ r) << 4), ld1 = ld0 ^ 64;
            float R[5][4], xr[4], xi[4];
            {
                float yr[4], yi[4];
                EMIT(0, 0, 0, 1, cr, ci, k4, k4p);
                CMUL4(yr, yi, cr, ci, z1r, z1i);        EMIT(0, 2, 0, 3, yr, yi, k4, k4p);
                CMUL4(xr, xi, cr, ci, z256r, z256i);    EMIT(1, 0, 1, 1, xr, xi, k4, k4p);
                CMUL4(yr, yi, yr, yi, z1r, z1i);        EMIT(0, 4, 0, 5, yr, yi, k4, k4p);
                CMUL4(cr, ci, xr, xi, z2r, z2i);        EMIT(1, 2, 1, 3, cr, ci, k4, k4p);
                CMUL4(yr, yi, yr, yi, z1r, z1i);        EMIT(0, 6, 0, 7, yr, yi, k4, k4p);
                CMUL4(xr, xi, xr, xi, z256r, z256i);    EMIT(1, 4, 1, 5, xr, xi, k4, k4p);
                CMUL4(xr, xi, xr, xi, z256r, z256i);    EMIT(1, 6, 1, 7, xr, xi, k4, k4p);
            }
            __syncwarp();
            {
                KSTAMP(8, 0);
                uint32_t bd[2][4] = {{0, 0, 0, 0}, {0, 0, 0, 0}};
                const bool on = (g >> 1) == t;
#pragma unroll
                for (int i = 0; i < 4; i++) { R[i][0] = R[i][1] = R[i][2] = R[i][3] = 0.f; }
#pragma unroll
                for (int k2 = 0; k2 < 8; k2++) {
                    uint32_t x[4], y[4], a1[2][4];
                    lds128_if(on, TB + t * T_PL + 16 + (g & 1) * 144 + 16 * k2, bd[k2 & 1]);
                    ldsm4(((k2 & 1) ? ld1 : ld0) + (k2 >> 1) * 128, x[0], x[1], x[2], x[3]);
                    ldsm4(((k2 & 1) ? ld1 : ld0) + (k2 >> 1) * 128 + 4096, y[0], y[1], y[2], y[3]);
#pragma unroll
                    for (int u = 0; u < 2; u++) {
                        mma_hh_k8(a1[u][0], a1[u][1], Ya[2 * k2 + u][0], Ya[2 * k2 + u][1], bd[k2 & 1][2 * u]);
                        mma_hh_k8(a1[u][2], a1[u][3], Ya[2 * k2 + u][2], Ya[2 * k2 + u][3], bd[k2 & 1][2 * u + 1]);
                    }
#pragma unroll
                    for (int u = 0; u < 2; u++) {
                        const uint32_t(&a0)[4] = Ya[2 * k2 + u];
                        mma_h(R[0], a0[0], a0[1], a0[2], a0[3], x[2 * u], x[2 * u + 1]);
                        mma_h(R[2], a0[0], a0[1], a0[2], a0[3], y[2 * u], y[2 * u + 1]);
                        mma_h(R[1], a1[u][0], a1[u][1], a1[u][2], a1[u][3], x[2 * u], x[2 * u + 1]);
                        mma_h(R[3], a1[u][0], a1[u][1], a1[u][2], a1[u][3], y[2 * u], y[2 * u + 1]);
                    }
                }
            }
            __syncwarp();
            KSTAMP(9, __float_as_uint(R[3][0]));
            asm volatile("barrier.cluster.wait.acquire.aligned;" ::: "memory");
            CMUL4(xr, xi, xr, xi, z256r, z256i);
            float s1024 = (xr[0] + xr[1]) + (xr[2] + xr[3]);
            CMUL4(xr, xi, xr, xi, z8r, z8i);        EMIT(0, 0, 0, 1, xr, xi, k128, k128p);
            CMUL4(xr, xi, xr, xi, z256r, z256i);    EMIT(0, 2, 0, 3, xr, xi, k128, k128p);
            CMUL4(xr, xi, xr, xi, z256r, z256i);    EMIT(0, 4, 0, 5, xr, xi, k128, k128p);
            CMUL4(xr, xi, xr, xi, z256r, z256i);    EMIT(0, 6, 0, 7, xr, xi, k128, k128p);
            __syncwarp();
            {
                KSTAMP(10, 0);
                float a1[4] = {0.f, 0.f, 0.f, 0.f};
                R[4][0] = R[4][1] = R[4][2] = R[4][3] = 0.f;
#pragma unroll
                for (int k2 = 0; k2 < 8; k2++) {
                    uint32_t x[4];
                    ldsm4(((k2 & 1) ? ld1 : ld0) + (k2 >> 1) * 128, x[0], x[1], x[2], x[3]);
                    mma_h(R[4], Ya[2 * k2][0], Ya[2 * k2][1], Ya[2 * k2][2], Ya[2 * k2][3], x[0], x[1]);
                    mma_h(a1, Ya[2 * k2 + 1][0], Ya[2 * k2 + 1][1], Ya[2 * k2 + 1][2], Ya[2 * k2 + 1][3], x[2], x[3]);
                }
#pragma unroll
                for (int i = 0; i < 4; i++) R[4][i] += a1[i];
            }
            if (lane == 0) mbar_arrive(bars + 8 * B_KG + (__float_as_uint(R[4][0]) & p.zero));
            KSTAMP(11, __float_as_uint(R[4][0]));
#undef PUT
#undef EMIT
#pragma unroll
            for (int o = 16; o > 0; o >>= 1) s1024 += __shfl_xor_sync(0xffffffffu, s1024, o);
            uint32_t w[4][4], dsk = 0;
            cp_wait_all();
            asm volatile("{\n\t.reg .pred p;\n\tsetp.eq.u32 p, %2, 0;\n\t@p ld.shared.u16 %0, [%1];\n\t}" : "+r"(dsk) : "r"(sb + M_DSK + 4 * warp + 2 * (warp & 1)), "r"(lane) : "memory");
#pragma unroll
            for (int a = 0; a < 4; a++) {
                const float v0 = (a == 0) ? fmaf(R[0][0], inv, __uint_as_float(dsk << 16)) : R[a][0] * inv;
                const float v1 = R[a][1] * inv, v2 = R[a][2] * inv, v3 = R[a][3] * inv;
                w[a][0] = pack_bf(v0, 0.f); w[a][1] = pack_bf(v1, v0); w[a][2] = pack_bf(v2, v1); w[a][3] = pack_bf(v3, v2);
            }
            const uint32_t wb = TB + 16 + 16 * g, w1 = wb + t * T_PL, w2 = wb + 256 + 2 * t * T_PL;
            const uint32_t w3 = (t == 0) ? wb + 256 + 3 * T_PL : TB + T_A + 8 * (16 * t + g);
            const uint32_t w3s = (t == 0) ? 128 : 64, w3o = (t == 0) ? 8 : 12;
            const uint32_t k512 = __shfl_sync(0xffffffffu, w[2][1], 2);
#pragma unroll
            for (int a = 0; a < 2; a++) {
                sts128(w1 + 128 * a, w[a][0], w[a][1], w[a][2], w[a][3]);
                const uint32_t(&q)[4] = w[2 + a];
                if (t < 2) sts128(w2 + 128 * a, q[0], q[1], q[2], q[3]);
                if (t == 0) { sts128(w2 + T_PL + 128 * a, q[0], q[1], q[2], q[3]); sts32(w3 + 128 * a + 4, q[2]); }
                sts32_if(t != 1 && (a == 1 || lane != 2), w3 + w3s * a, q[1]);
                sts32_if(t != 1, w3 + w3s * a + w3o, q[3]);
            }
            sts128_if(lane < 4, w1 + 512, t == 3 ? k512 : k512 >> 16, t < 2 ? k512 : t == 2 ? k512 & 0xffff0000u : k512 << 16, t < 2 ? k512 << 16 : 0u, 0);
            __syncwarp();
#pragma unroll
            for (int a = 0; a < 2; a++) {
                sts16(w1 + 128 * a + 18, w[a][3]);
                const uint32_t(&q)[4] = w[2 + a];
                if (t < 2) sts16(w2 + 128 * a + 18, q[3]);
                if (t == 0) { sts16(w2 + T_PL + 128 * a + 18, q[3]); sts16(w3 + 128 * a + 14, q[3]); }
            }
            if (t == 0) sts16(w3 + 128 - 4, w[3][0]);
            if (lane == 2 || (t == 0 && g > 0)) sts16(lane == 2 ? TB + 16 + 3 * T_PL + 4 * 127 : w3 - 4, w[2][0]);
            {
                const uint32_t b0 = pack_bf(R[4][0] * inv, R[4][2] * inv), b1 = pack_bf(R[4][1] * inv, R[4][3] * inv);
                const uint32_t wq = TB + T_B + 8 * (65 + 16 * t + g);
                sts32(wq, b0); sts32(wq + 12, b0); sts32(wq + 64, b1); sts32(wq + 76, b1);
            }
            cfix = pack_bf(s1024 * inv, s1024 * inv);
            if (lane == 0) sts32(TB + T_A + 8 * 64, cfix);
            __syncwarp();
        }
        WSTAMP(1);

        mbar_wait(bars + 8 * B_U);
        WSTAMP(2);

        float D[16][4];
        {
            const int x5 = g - t + 5;
            const uint32_t tabD = TB + (x5 & 3) * T_PL + (x5 & 12) + 16;
            {
                const uint32_t a1 = lds32(tabD - 8), a0 = p.zero;
#pragma unroll
                for (int jq = 0; jq < 4; jq++) {
                    uint32_t b[4];
                    ldsm4(UB + (9 + lane) * 16 + jq * 512, b[0], b[1], b[2], b[3]);
#pragma unroll
                    for (int i = 0; i < 4; i++) mma_bf_k8z(D[4 * jq + i], a0, a1, b[i]);
                }
            }
            const uint32_t ua = UB + (mi & 1) * U_PL + (8 + 8 * (mi >> 1) + r) * 16;
#pragma unroll 1
            for (int k0 = 0; k0 < 8; k0++) {
                uint32_t Uf[16][2];
#pragma unroll
                for (int jp = 0; jp < 8; jp++) ldsm4(ua + jp * 256 - k0 * 16, Uf[2 * jp][0], Uf[2 * jp][1], Uf[2 * jp + 1][0], Uf[2 * jp + 1][1]);
#pragma unroll
                for (int k1 = 0; k1 < 4; k1++) {
                    const uint32_t ta = tabD + 16 * (8 * k1 + k0);
                    const uint32_t a0 = lds32(ta), a1 = lds32(ta + 8), a2 = lds32(ta - 8), a3 = a0 ^ p.zero;
#pragma unroll
                    for (int J = k1; J < 16; J++) mma_bf(D[J], a0, a1, a2, a3, Uf[J - k1][0], Uf[J - k1][1]);
                }
                if (k0 == 0) {
                    const uint32_t ta = tabD + 16 * 32;
                    const uint32_t a0 = lds32(ta), a1 = lds32(ta + 8), a2 = lds32(ta - 8), a3 = a0 ^ p.zero;
#pragma unroll
                    for (int J = 4; J < 16; J++) mma_bf(D[J], a0, a1, a2, a3, Uf[J - 4][0], Uf[J - 4][1]);
                    const uint32_t f0 = (cfix ^ 0x80008000u) & (g == t ? 0xffffu : g == t + 4 ? 0xffff0000u : 0u);
                    const uint32_t f1 = p.zero, f2 = p.zero + p.zero, f3 = f0 ^ p.zero;
#pragma unroll
                    for (int J = 8; J < 16; J++) mma_bf(D[J], f0, f1, f2, f3, Uf[J - 8][0], Uf[J - 8][1]);
                }
            }
        }
        WSTAMP(3);
        {
            const int ch = 8 * h + warp;
            const uint32_t yo = sb + ch * 512 + ((lane ^ (((ch >> 2) << 1) | (ch & 1))) << 4);
            const uint32_t yr = mapa(yo, h ^ 1), ybr = mapa(bars + 8 * B_Y, h ^ 1);
            auto ship = [&](const int Q) {
                uint4 y[2];
#pragma unroll
                for (int hh = 0; hh < 2; hh++) {
                    const int J = 4 * Q + 2 * hh;
                    y[hh] = make_uint4(pack_bf(D[J][0], D[J][1]), pack_bf(D[J][2], D[J][3]), pack_bf(D[J + 1][0], D[J + 1][1]), pack_bf(D[J + 1][2], D[J + 1][3]));
                }
                if (!(Q & 1)) mbar_wait(bars + 8 * (B_F + (Q >> 1)));
                asm volatile("{\n\t.reg .pred p;\n\tsetp.eq.u32 p, %11, 0;\n\t"
                             "@p st.async.weak.shared::cluster.mbarrier::complete_tx::bytes.v4.b32 [%9], {%4,%5,%6,%7}, [%10];\n\t"
                             "@!p st.async.weak.shared::cluster.mbarrier::complete_tx::bytes.v4.b32 [%9], {%0,%1,%2,%3}, [%10];\n\t"
                             "@p st.shared.v4.b32 [%8], {%0,%1,%2,%3};\n\t@!p st.shared.v4.b32 [%8], {%4,%5,%6,%7};\n\t}"
                             :: "r"(y[0].x), "r"(y[0].y), "r"(y[0].z), "r"(y[0].w), "r"(y[1].x), "r"(y[1].y), "r"(y[1].z), "r"(y[1].w),
                                "r"(yo + y_off(Q)), "r"(yr + y_off(Q)), "r"(ybr + 8 * Q), "r"(h) : "memory");
                __syncwarp();
                if (lane == 0) mbar_arrive(bars + 8 * (B_Y + Q));
            };
            ship(0);
            const uint4 bA = lds128(sb + OFF_BAND + (g - t + 3) * 48), bB = lds128(sb + OFF_BAND + (g - t + 3) * 48 + 16);
            const uint2 bC = lds64(sb + OFF_BAND + (g - t + 3) * 48 + 32);
            uint2 QA[5][2], QB[8];
            const uint32_t tq = TB + 8 * (1 + g - 2 * t);
#pragma unroll
            for (int dd = 0; dd < 5; dd++) { QA[dd][0] = lds64(tq + T_A + 64 * (dd + 4)); QA[dd][1] = lds64(tq + T_A + 64 * (dd + 4) - 8); }
#pragma unroll
            for (int dd = 0; dd < 8; dd++) QB[dd] = lds64(tq + T_B + 64 * (dd + 8));
            const uint32_t u1 = UB + (mi & 1) * U_PL + (7 + r + (mi >> 1)) * 16;
            const uint32_t u2 = UB + ((mi & 1) ^ 1) * U_PL + (7 + r + (mi & 1) + 8 * (mi >> 1)) * 16;
            uint32_t n[4];
#pragma unroll
            for (int j = 0; j < 12; j++) {
                uint32_t m[4];
                ldsm4(u1 + j * 128, m[0], m[1], m[2], m[3]);
                if (!(j & 1)) ldsm4(u2 + j * 128, n[0], n[1], n[2], n[3]);
                const uint32_t n0 = n[2 * (j & 1)], n1 = n[2 * (j & 1) + 1];
                float wa[4], wb[4], wc[4], g1[4], g2[4];
                mma_bf_z(wa, bA.x, bA.y, bA.z, bA.w, m[0], m[1]);
                mma_bf_z(wb, bA.x, bA.y, bA.z, bA.w, n0, n1);
                mma_bf_z(wc, bA.x, bA.y, bA.z, bA.w, m[2], m[3]);
                if (j < 8) {
                    mma_bf_z(g1, bB.x, bB.y, bB.z, bB.w, m[0], m[1]);
                    mma_bf_z(g2, bB.x, bB.y, bB.z, bB.w, n0, n1);
                    mma_bf_k8(g1, bC.x, bC.y, m[2]);
                    mma_bf_k8(g2, bC.x, bC.y, m[3]);
                }
#pragma unroll
                for (int e = 0; e < 2; e++) {
                    const uint32_t q0 = pack_bf(wa[e], wa[e + 2]), q1 = pack_bf(wb[e], wb[e + 2]), q2 = q1 ^ p.zero, q3 = pack_bf(wc[e], wc[e + 2]);
#pragma unroll
                    for (int dd = 0; dd < 5; dd++)
                        if (j + 4 + dd < 16) mma_bf(D[j + 4 + dd], q0, q1, q2, q3, QA[dd][e].x, QA[dd][e].y);
                }
                if (j < 8) {
                    const uint32_t q0 = pack_bf(g1[0], g1[2]), q1 = pack_bf(g2[0], g2[2]), q2 = pack_bf(g1[1], g1[3]), q3 = pack_bf(g2[1], g2[3]);
#pragma unroll
                    for (int dd = 7 - j; dd >= 0; dd--) mma_bf(D[j + 8 + dd], q0, q1, q2, q3, QB[dd].x, QB[dd].y);
                }
                if ((j & 3) == 3) {
                    WSTAMP(4 + 2 * (j >> 2));
                    if (j == 11 && LATE2) ship(2);
                    if (j != 7 || !LATE2) ship((j >> 2) + 1);
                }
            }
        }
        mix_rows<1, false>(p, &tm_out, sb, PQ, 4, warp, h, pr, lane);
        WSTAMP(10);
        WDUMP();
    } else if ((pw & 12) == AUX_W0) {
        asm volatile("setmaxnreg.inc.sync.aligned.u32 136;");
        const int v = __reduce_max_sync(0xffffffffu, pw & 3);
        const int at = tid & 127;
        const int g = lane >> 2, t = lane & 3;
        unsigned tag;
        const bool gu = c < NGU_CTA;
        {
            uint4 xa[16];
            const uint32_t xb = sb + (v < 2 ? OFF_XSEL : OFF_RING + 2 * 8192) + v * 8192;
            const uint32_t gws = sb + (gu ? M_DPIN : OFF_RING + 2 * 8192);
            const uint32_t row = 16 * c + 4 * v + (g >> 1);
            const unsigned epoch = *(volatile unsigned*)&p.sc->epoch;
#pragma unroll
            for (int i = 0; i < 4; i++)
                asm volatile("cp.async.ca.shared.global [%0], [%1], 4;" :: "r"(sb + OFF_GP + 512 * i + (tid & 124) * 4 + (tid & 1) * 8 + (tid & 2) * 2),
                             "l"(p.wr + 256 * i + (tid & 127) * 2) : "memory");
            cp16(gws + (tid & 127) * 16, p.gatew + (tid & 127) * 8);
            if ((tid & 127) < 33) cp16(sb + OFF_BAND + (tid & 127) * 16, p.band + (tid & 127));
            asm volatile("barrier.cluster.arrive.relaxed.aligned;" ::: "memory");
            tag = __reduce_max_sync(0xffffffffu, (epoch + 1) & 0xffffu);
            if (gu) st_gpu32((uint32_t*)&p.sc->h[(tag + 1) & 1][32 * c] + at, 0);
            if (v == 0) sts32(sb + M_BMAP + lane * 4, 0);
            cp_wait_all();
            bar_sync(1, 128);
            uint2 w[16];
#pragma unroll
            for (int kb = 0; kb < 16; kb++) w[kb] = lds64(sb + OFF_GP + 128 * kb + 32 * (g & 2) + 16 * t + 8 * (g & 1));
            asm volatile("barrier.cluster.wait.acquire.aligned;" ::: "memory");
            mbar_wait(bars + 8 * (B_X + v));
            WSTAMP(10);
#pragma unroll
            for (int kb = 0; kb < 16; kb++) xa[kb] = lds128(xb + (g >> 1) * 2048 + 128 * kb + 16 * (lane & 7));
            float dr[4][4];
#pragma unroll
            for (int kb = 0; kb < 16; kb++) {
                if (kb < 4) mma_bf_z(dr[kb], xa[kb].x, xa[kb].y, xa[kb].z, xa[kb].w, w[kb].x, w[kb].y);
                else mma_bf(dr[kb & 3], xa[kb].x, xa[kb].y, xa[kb].z, xa[kb].w, w[kb].x, w[kb].y);
            }
            float rs = ((dr[0][0] + dr[0][3]) + (dr[1][0] + dr[1][3])) + ((dr[2][0] + dr[2][3]) + (dr[3][0] + dr[3][3]));
            if (lane == 0) mbar_arrive(bars + 8 * (B_XE + v) + (__float_as_uint(rs) & p.zero));
            rs += __shfl_xor_sync(0xffffffffu, rs, 5);
            const uint32_t rb = pack_bf(0.f, rs);
            if (!(lane & 7)) st_gpu32((uint32_t*)&p.sc->r[(row >> 2) * RS] + (row & 3), ((rb ^ (((int)rb >> 31) | 0x80000000u)) & 0xffff0000u) | tag);
            WSTAMP(1);
            {
                const int n = 3 + (lane >> 3) + 4 * (lane & 1);
                const uint32_t so = (n & 7) * S_PL + ((lane & 6) + (n >> 3)) * 32;
                const uint32_t src[2] = {sb + OFF_S + v * S_Q + s_addr(so, h), sb + OFF_S + v * S_Q + s_addr(so + 32, h)};
                const uint32_t dst = sb + OFF_U + g * U_CH + (8 + 32 * v + 16 * h + t) * 16;
                const uint32_t rdst = mapa(dst, h ^ 1), rbar = mapa(bars + 8 * B_U, h ^ 1);
                mbar_wait(bars + 8 * (B_S + v));
                WSTAMP(9);
                uint4 a[8];
#pragma unroll
                for (int b = 0; b < 2; b++) {
#pragma unroll
                    for (int j = 0; j < 8; j++) ldsm4t((b ? src[j & 1] : src[j & 1] ^ 16) + (j >> 1) * 256, a[j].x, a[j].y, a[j].z, a[j].w);
#pragma unroll
                    for (int j = 0; j < 8; j++) {
                        if (b) sts128(dst + (j >> 1) * 64 + (j & 1) * U_PL, a[j].x, a[j].y, a[j].z, a[j].w);
                        else st_async16(rdst + (j >> 1) * 64 + (j & 1) * U_PL, a[j], rbar);
                    }
                }
                if (h && v == 3) {
                    ldsm4t((src[0] ^ 16) + 1024, a[0].x, a[0].y, a[0].z, a[0].w);
                    ldsm4t(src[0] + 1024, a[1].x, a[1].y, a[1].z, a[1].w);
                    if (t == 0) {
                        st_async16(rdst + 256, make_uint4(a[0].x, a[0].y & 0xffffu, a[0].z & 0xffffu, a[0].w & 0xffffu), rbar);
                        sts128(dst + 256, a[1].x, a[1].y & 0xffffu, a[1].z & 0xffffu, a[1].w & 0xffffu);
                    }
                }
                __syncwarp();
                if (lane == 0) mbar_arrive(bars + 8 * B_U);
            }
            const uint32_t one0 = 0x3F803F80u ^ p.zero, one1 = 0x3F803F80u + p.zero;
#pragma unroll
            for (int kb = 0; kb < 16; kb++) {
                const uint4 gw = lds128(gws + 128 * kb + 16 * (lane & 7));
                const uint32_t a0 = hmul2_bf(xa[kb].x, gw.x), a1 = hmul2_bf(xa[kb].y, gw.y), a2 = hmul2_bf(xa[kb].z, gw.z), a3 = hmul2_bf(xa[kb].w, gw.w);
                if (kb < 4) mma_bf_z(dr[kb], a0, a1, a2, a3, one0, one1);
                else mma_bf(dr[kb & 3], a0, a1, a2, a3, one0, one1);
            }
            float sg = ((dr[0][0] + dr[0][3]) + (dr[1][0] + dr[1][3])) + ((dr[2][0] + dr[2][3]) + (dr[3][0] + dr[3][3]));
            sg += __shfl_xor_sync(0xffffffffu, sg, 4);
            if (!(lane & 7)) st_gpu32((uint32_t*)p.sc->g + ((row & 256) << 2) + gate_pos(row), (pack_bf(sigmoid_f(bf_round(sg)), 0.f) & 0xffffu) | (tag << 16));
            WSTAMP(2);
        }
        if (at == 32) { sts32(sb + M_TAG, tag << 16); mbar_arrive(bars + 8 * B_F); }
        {
            const bool lane0 = pin(lane, lane) == 0;
            const uint32_t own = pin(sb + OFF_XSEL + (at ^ ((at >> 1) & 4)) * 16, lane);
            float acc[8][4];
#pragma unroll
            for (int i = 0; i < 8; i++) { acc[i][0] = acc[i][1] = acc[i][2] = acc[i][3] = 0.f; }
            const int krow = ((lane >> 1) & 8) + (lane & 7);
            const uint32_t tile0 = pin(sb + OFF_RING + krow * 64 + ((((lane >> 3) & 1) ^ ((krow >> 1) & 3)) << 4), lane);
            const uint32_t xo = pin(sb + OFF_XSEL + (lane & 7) * XS_ROW + 512 * v + 2 * (lane & 24), lane);
            const uint32_t po = pin(sb + OFF_XSEL + t * XS_ROW + (g & 3) * 128 + (g & 1) * 64 + v * 16 + (lane >> 4) * 8, lane);
            const uint32_t po1 = pin(po + 64 - (g & 1) * 128, lane);
            uint32_t* hdst = pin((uint32_t*)&p.sc->h[tag & 1][32 * c] + at, lane);
            auto signal = [&](const int k, const uint32_t dep) {
                if (lane < 2 && v < 2)
                    asm volatile("st.async.weak.shared::cluster.mbarrier::complete_tx::bytes.b32 [%0], %1, [%2];"
                                 :: "r"(mapa(sb + M_SINK, lane)), "r"(dep), "r"(mapa(bars + 8 * (B_F + k), lane)) : "memory");
            };
#pragma unroll 1
            for (int i = 0; i < 4; i++) {
                const int s = 4 * i + v;
                uint32_t a[16][4], b[2][4];
                if (gu) {
                    const uint32_t tile = tile0 + (s < 14 ? s : v) * 8192;
                    if (lane0 && i > 1) mbar_arrive(bars + 8 * (B_E + s - 4));
                    if (i == 2) signal(0, 0);
                    mbar_wait(bars + 8 * (B_W + s));
#pragma unroll
                    for (int q = 0; q < 16; q++) ldsm4t((tile ^ ((q & 1) << 5)) + ((q >> 1) & 1) * 4096 + (q >> 2) * 1024, a[q][0], a[q][1], a[q][2], a[q][3]);
                }
                if (i == 0) {
                    if (gu) {
                        uint32_t dep = p.zero;
#pragma unroll
                        for (int q = 0; q < 16; q += 2) dep &= a[q][0] & a[q + 1][0];
                        if (lane == 0) mbar_arrive(bars + 8 * (B_E + v) + dep);
                    }
                    WSTAMP(11);
                    uint32_t top;
#pragma unroll 1
                    for (int it = 0; it < (1 << 22); it++) {
                        asm volatile("ld.relaxed.gpu.global.u32 %0, [%1];" : "=r"(top) : "l"(&p.sc->top[c % NTOP][g]) : "memory");
                        if (__all_sync(0xffffffffu, ((top ^ (tag << 11)) & 0xf800u) == 0)) break;
                        if (TSLEEP) __nanosleep(TSLEEP);
                    }
                    WSTAMP(3);
                    if (gu) {
                        const uint32_t k = 4 * h + v, row = __reduce_max_sync(0xffffffffu, lane == 4 * k ? ~top & 2047 : 0);
                        asm volatile("{\n\t.reg .pred p;\n\telect.sync _|p, 0xffffffff;\n\t"
                                     "@p cp.async.bulk.shared::cluster.global.mbarrier::complete_tx::bytes.multicast::cluster [%0], [%1], 2048, [%2], %3;\n\t}"
                            :: "r"(sb + OFF_XSEL + k * XS_ROW), "l"(p.u + (size_t)row * D_), "r"(bars + 8 * B_G), "h"((unsigned short)3) : "memory");
                    }
                    if (v == 0) {
                        const uint32_t row = ~top & 2047;
                        if (t == 0 && ((row >> 8) & 1) == h)
                            asm volatile("red.shared.or.b32 [%0], %1;" :: "r"(sb + M_BMAP + (row & 7) * 16 + (row >> 9) * 4), "r"(1u << (gate_pos(row) & 31)) : "memory");
                        if (t == 0) sts32(sb + M_TOP + lane, top);
                        if (c == 0 && lane == 0) *(volatile unsigned*)&p.sc->epoch = tag;
                        __syncwarp();
                        if (lane0) mbar_arrive(bars + 8 * B_Y);
                    }
                    if (!gu) break;
                    mbar_wait(bars + 8 * B_G);
                    WSTAMP(4);
                }
                ldsm4(xo + 128 * i, b[0][0], b[0][1], b[0][2], b[0][3]);
                ldsm4(xo + 128 * i + 64, b[1][0], b[1][1], b[1][2], b[1][3]);
#pragma unroll
                for (int q = 0; q < 16; q++) mma_bf(acc[q & 7], a[q][0], a[q][1], a[q][2], a[q][3], b[q >> 3][(q >> 1) & 2], b[q >> 3][((q >> 1) & 2) + 1]);
            }
            if (gu) {
                WSTAMP(5);
                __syncwarp();
#pragma unroll
                for (int q = 0; q < 4; q++) {
                    const int ct = q >> 1, e = 2 * (q & 1);
                    sts128(own + q * XS_ROW,
                           __float_as_uint(acc[ct][e] + acc[4 + ct][e]), __float_as_uint(acc[2 + ct][e] + acc[6 + ct][e]),
                           __float_as_uint(acc[ct][e + 1] + acc[4 + ct][e + 1]), __float_as_uint(acc[2 + ct][e + 1] + acc[6 + ct][e + 1]));
                }
                bar_sync(1, 128);
                float sl[2], uv[2];
#pragma unroll
                for (int e = 0; e < 2; e++) {
                    uint2 q[4];
#pragma unroll
                    for (int i = 0; i < 4; i++) q[i] = lds64((e ? po1 : po) + 512 * i);
                    const float s0 = (__uint_as_float(q[0].x) + __uint_as_float(q[1].x)) + (__uint_as_float(q[2].x) + __uint_as_float(q[3].x));
                    const float s1 = (__uint_as_float(q[0].y) + __uint_as_float(q[1].y)) + (__uint_as_float(q[2].y) + __uint_as_float(q[3].y));
                    const float gv = bf_round(p.gu_swap ? s1 : s0);
                    uv[e] = p.gu_swap ? s0 : s1;
                    sl[e] = gv * sigmoid_f(gv);
                }
                const uint32_t hw = hmul2_bf(pack_bf(sl[0], sl[1]), pack_bf(uv[0], uv[1]));
                st_gpu32(hdst, hw ? hw : 0x80000000u);
                signal(1, hw);
            }
        }
        WSTAMP(6);
        asm volatile("setmaxnreg.dec.sync.aligned.u32 104;");
        {
            const uint32_t own = pin(sb + OFF_XSEL + at * 16, lane);
            const uint32_t hb = sb + (v < 2 ? OFF_XSEL + 7168 * v : OFF_RING + 8192 * v), hl = pin(hb + 16 * lane, lane);
            const int krow = ((lane >> 1) & 8) + (lane & 7);
            const uint32_t tile = pin(sb + OFF_RING + v * 8192 + krow * 32 + ((((lane >> 3) ^ (krow >> 2)) & 1) << 4), lane);
            float dd[4][4];
            bar_sync(1, 128);
            mbar_wait(bars + 8 * (B_W + HW));
            WSTAMP(12);
#pragma unroll 1
            for (int it = 0; it < (1 << 16); it++) {
                bulk_load(hb, &p.sc->h[tag & 1][32 * (56 * h + 14 * v)], 7168, bars + 8 * (B_X + v));
                uint32_t a[14][4], mn = 0xffffffffu;
                mbar_wait(bars + 8 * (B_W + 16 + v));
#pragma unroll
                for (int j = 0; j < 14; j++) ldsm4t(tile + (v & 2) * 16384 + j * 512, a[j][0], a[j][1], a[j][2], a[j][3]);
                mbar_wait(bars + 8 * (B_W + 20 + v));
                mbar_wait(bars + 8 * (B_X + v), ~it & 1);
                WSTAMP(7);
#pragma unroll
                for (int j = 0; j < 14; j++) {
                    const uint4 q = lds128(hl + 512 * j);
                    mn = min(mn, q.x);
#pragma unroll
                    for (int e = 0; e < 2; e++) {
                        uint32_t(&f)[4] = a[(2 * j + e) % 14];
                        if (j >= 7) ldsm4t(tile + 65536 + (2 * j + e - 14) * 512, f[0], f[1], f[2], f[3]);
                        if (j < 2) mma_bf_z(dd[2 * j + e], f[0], f[1], f[2], f[3], e ? q.z : q.x, e ? q.w : q.y);
                        else mma_bf(dd[(2 * j + e) & 3], f[0], f[1], f[2], f[3], e ? q.z : q.x, e ? q.w : q.y);
                    }
                }
                if (__all_sync(0xffffffffu, mn != 0)) break;
            }
            WSTAMP(8);
            uint4 part;
            part.x = __float_as_uint((dd[0][0] + dd[1][0]) + (dd[2][0] + dd[3][0])); part.y = __float_as_uint((dd[0][1] + dd[1][1]) + (dd[2][1] + dd[3][1]));
            part.z = __float_as_uint((dd[0][2] + dd[1][2]) + (dd[2][2] + dd[3][2])); part.w = __float_as_uint((dd[0][3] + dd[1][3]) + (dd[2][3] + dd[3][3]));
            st_async16(mapa(own + (M_DPIN - OFF_XSEL), h ^ 1), part, mapa(bars + 8 * B_DP, h ^ 1));
            sts128(own + 14336, part.x, part.y, part.z, part.w);
            __syncwarp();
            if (lane == 0) mbar_arrive(bars + 8 * B_DP);
        }
        WDUMP();
    } else {
        asm volatile("setmaxnreg.dec.sync.aligned.u32 40;");
        const int v = __reduce_max_sync(0xffffffffu, pw - PREP_W0);
        const bool gu = c < NGU_CTA;
        const uint32_t t0 = clock();
        const uint32_t bu = bars + 8 * v;
        if (lane == 0) {
            mbar_init(bu + 8 * B_X, 1);
            asm volatile("fence.mbarrier_init.release.cluster;" ::: "memory");
        }
        __syncwarp();
        if (DELAY_X > 0) __nanosleep(DELAY_X);
        bulk_load(sb + (v < 2 ? OFF_XSEL : OFF_RING + 2 * 8192) + v * 8192, p.u + (size_t)(16 * c + 4 * v) * D_, 8192, bu + 8 * B_X);
        if (lane == 0) {
#pragma unroll
            for (int i = 0; i < 10; i++) mbar_init(bu + 32 * i, 1);
            mbar_init(bu + 8 * B_XE, 1);
            mbar_init(bu + 8 * B_Y, v == 0 ? 11 : 9);
            mbar_init(bu + 8 * B_DP, (0x1855 >> (4 * v)) & 15);
            mbar_init(bu + 8 * B_F, v == 0 ? 2 : 1);
            mbar_init(bu + 8 * B_H, 1);
            asm volatile("fence.mbarrier_init.release.cluster;" ::: "memory");
            mbar_expect(bu + 8 * B_Y, 4096);
            if (v != 2) mbar_expect(bu + 8 * B_DP, v == 0 ? 2048 : (h || v == 3) ? 16384 : 16384 + 128);
            mbar_expect(bu + 8 * B_F, c < NGU_CTA ? 16 : 0);
        }
        __syncwarp();
        asm volatile("barrier.cluster.arrive.relaxed.aligned;" ::: "memory");
        tma3d(sb + OFF_S + v * S_Q, &tm_x, 16 * pr, 64 * v + 32 * h - 1, bars + 8 * (B_S + v), S_Q);
        WSTAMP(9);
        if (v < 3 && lane == 0) asm volatile("prefetch.tensormap [%0];" :: "l"(v == 0 ? &tm_gu : v == 1 ? &tm_down : &tm_out) : "memory");
        asm volatile("barrier.cluster.wait.acquire.aligned;" ::: "memory");
        if (v > 0) mbar_wait(bars + 8 * (B_H + v));
        {
            const int gap = v == 0 ? GAP : v == 1 ? GAP1 : v == 2 ? GAP2 : GAP3;
            uint32_t last = v ? clock() - SLACK : t0 + T0 - GAP + STAG * ((pr * 5) & 15) / 16;
#pragma unroll 1
            for (int s = 6 * v; s < 6 * v + 6; s++) {
                const int i = s >> 2, w = s & 3, slot = s < 14 ? s : (s | 1) == 17 ? s - 16 : s - 12;
                if (s >= 4) mbar_wait(bars + 8 * ((gu && s >= 14) ? B_E + slot : s < 6 ? B_XE + s - 2 : B_KG));
                uint32_t now;
#pragma unroll 1
                while ((int)((now = clock()) - last) < gap) __nanosleep(CSLEEP);
                last = max((int)(now - last) - SLACK, gap) + last;
                WSTAMP(3 + s - 6 * v);
                if (gu || s >= 16) tma3d(sb + OFF_RING + slot * 8192, i < 4 ? &tm_gu : &tm_down, i < 4 ? 32 * c : 16 * pr,
                      i < 4 ? 256 * w + 64 * i : 1792 * h + 448 * w + 224 * (i - 4), bars + 8 * (B_W + s), i < 4 ? 8192 : 7168);
            }
            if (lane == 0) mbar_arrive(bars + 8 * (B_H + ((v + 1) & 3)));
        }
        if (v == 0) {
            mbar_wait(bars + 8 * B_U);
            mbar_wait(bars + 8 * B_F);
            if (!gu) mbar_wait(bars + 8 * (B_H + 3));
            const uint32_t tag16 = lds32(sb + M_TAG);
#pragma unroll 1
            for (int k = 0; k < 2; k++) {
                uint4 q[4];
#pragma unroll 1
                for (int it = 0; it < (1 << 22); it++) {
                    uint32_t bad = 0;
#pragma unroll
                    for (int i = 0; i < 4; i++) q[i] = ld_gpu128(&p.sc->g[256 * h + 128 * k + 32 * i + lane]);
#pragma unroll
                    for (int i = 0; i < 4; i++) bad |= ((q[i].x ^ tag16) | (q[i].y ^ tag16)) | ((q[i].z ^ tag16) | (q[i].w ^ tag16));
                    if ((bad >> 16) == 0) break;
                    __nanosleep(200);
                }
#pragma unroll
                for (int i = 0; i < 4; i++)
                    asm volatile("st.shared.v2.u32 [%0], {%1, %2};" :: "r"(sb + OFF_GP + 1024 * k + 256 * i + lane * 8),
                                 "r"(__byte_perm(q[i].x, q[i].y, 0x5410)), "r"(__byte_perm(q[i].z, q[i].w, 0x5410)) : "memory");
            }
            __syncwarp();
            if (lane == 0) mbar_arrive(bars + 8 * B_Y);
        }
        {
            asm volatile("setmaxnreg.inc.sync.aligned.u32 72;");
            WSTAMP(1);
            mix_rows<2, BULKQ>(p, &tm_out, sb, 0, PQ, v, h, pr, lane);
            WSTAMP(2);
            asm volatile("cp.async.bulk.commit_group;" ::: "memory");
            const uint32_t top = lds32(sb + M_TOP + 8 * v + 4 * (lane >> 4));
            const uint32_t row = ~top & 2047, ch = lane & 15, gp = gate_pos(row);
            const bool mine = ((row >> 8) & 1) == h;
            uint32_t gfin, x16, y16 = 0;
            asm volatile("ld.shared.u16 %0, [%1];" : "=r"(gfin) : "r"(sb + OFF_GP + gp * 2) : "memory");
            asm volatile("ld.shared.u16 %0, [%1];" : "=r"(x16) : "r"(sb + OFF_S + (row >> 9) * S_Q + s_addr((row & 7) * S_PL + 32 + (row & 248) * 4, ch >> 3) + 2 * (ch & 7)) : "memory");
            const float rsel = __uint_as_float(pin(__float_as_uint(bf_round(sigmoid_f(__uint_as_float((top ^ (((int)~top >> 31) | 0x80000000u)) & 0xffff0000u)))), lane));
            const uint32_t po = pin(sb + (4 * (ch & 7) + v) * 16 + (ch >> 3) * 8 + (lane >> 4) * 4, lane);
            bf16* op = pin(p.out + (size_t)row * D_ + 16 * pr + ch, lane);
            if (mine) {
                mbar_wait(bars + 8 * (B_Y + (row >> 9)));
                asm volatile("ld.shared.u16 %0, [%1];" : "=r"(y16)
                             : "r"(sb + y_off(row >> 9) + ch * 512 + (((4 * (row & 7) + ((row >> 5) & 3)) ^ (((ch >> 2) << 1) | (ch & 1))) << 4) + 2 * row_elem(row)) : "memory");
            }
            mbar_wait(bars + 8 * B_DP);
            float q[8];
#pragma unroll
            for (int i = 0; i < 4; i++) { q[i] = ldsf(po + M_DPIN + 512 * i); q[4 + i] = ldsf(po + OFF_XSEL + 14336 + 512 * i); }
            const float tot = ((q[0] + q[1]) + (q[2] + q[3])) + ((q[4] + q[5]) + (q[6] + q[7]));
            const float b = bf_round(__uint_as_float(x16 << 16) + bf_round(bf_round(tot) * rsel));
            if (mine) *op = __float2bfloat16_rn(fmaf(bf_lo(gfin), __uint_as_float(y16 << 16), bf_round(bf_round(1.f - bf_lo(gfin)) * b)));
        }
        asm volatile("cp.async.bulk.wait_group.read 0;" ::: "memory");
        WSTAMP(10);
        WDUMP();
    }
}

typedef CUresult (*EncodeFn)(CUtensorMap*, CUtensorMapDataType, cuuint32_t, void*, const cuuint64_t*, const cuuint64_t*,
                             const cuuint32_t*, const cuuint32_t*, CUtensorMapInterleave, CUtensorMapSwizzle,
                             CUtensorMapL2promotion, CUtensorMapFloatOOBfill);

void make_map(EncodeFn f, CUtensorMap* m, const void* ptr, uint64_t cols, uint64_t rows, uint64_t pitch, uint32_t bc, uint32_t br, CUtensorMapSwizzle sw, int prom,
              uint32_t planes = 1, uint64_t plane_stride = 0, uint32_t box_planes = 0) {
    cuuint64_t dims[3] = {cols, rows, planes};
    cuuint64_t str[2] = {pitch, planes > 1 ? plane_stride : pitch * rows};
    cuuint32_t box[3] = {bc, br, box_planes ? box_planes : planes};
    cuuint32_t es[3] = {1, 1, 1};
    f(m, CU_TENSOR_MAP_DATA_TYPE_BFLOAT16, 3, (void*)ptr, dims, str, box, es, CU_TENSOR_MAP_INTERLEAVE_NONE, sw,
      (CUtensorMapL2promotion)prom, CU_TENSOR_MAP_FLOAT_OOB_FILL_NONE);
}

}

extern "C" void kernel_launch(void* const* d_in, const int* in_sizes, int n_in, void* d_out, int out_size) {
    static EncodeFn enc = nullptr;
    static void *sc = nullptr, *band = nullptr;
    if (!enc) {
        void* fn = nullptr;
        cudaDriverEntryPointQueryResult qr;
        cudaGetDriverEntryPoint("cuTensorMapEncodeTiled", &fn, cudaEnableDefault, &qr);
        enc = (EncodeFn)fn;
        cudaGetSymbolAddress(&sc, g_scratch);
        cudaGetSymbolAddress(&band, g_band);
        cudaFuncSetAttribute(fused_kernel, cudaFuncAttributeMaxDynamicSharedMemorySize, SMEM_BYTES);
    }
    CUtensorMap tg, td, tx, to;
    const char *wg = (const char*)d_in[9], *wu = (const char*)d_in[10];
    const bool swap = wu < wg;
    make_map(enc, &tg, swap ? wu : wg, F_, D_, F_ * 2, 32, 64, CU_TENSOR_MAP_SWIZZLE_64B, PROMG, 2, swap ? wg - wu : wu - wg);
    make_map(enc, &td, d_in[11], D_, F_, D_ * 2, 16, 224, CU_TENSOR_MAP_SWIZZLE_32B, PROMD);
    make_map(enc, &tx, d_in[0], D_, L_ / 8, D_ * 16, 16, 33, CU_TENSOR_MAP_SWIZZLE_32B, PROMX, 8, D_ * 2);
    make_map(enc, &to, d_out, D_, L_ / 8, D_ * 16, 16, 32, CU_TENSOR_MAP_SWIZZLE_NONE, 0, 8, D_ * 2, 1);
    Params p;
    p.u = (const bf16*)d_in[0]; p.logA = (const bf16*)d_in[1]; p.Aim = (const bf16*)d_in[2];
    p.Cre = (const bf16*)d_in[3]; p.Cim = (const bf16*)d_in[4]; p.logdt = (const bf16*)d_in[5];
    p.Dskip = (const bf16*)d_in[6]; p.wr = (const bf16*)d_in[8]; p.gatew = (const bf16*)d_in[12];
    p.out = (bf16*)d_out;
    p.sc = (Scratch*)sc; p.band = (const uint4*)band;
    p.gu_swap = swap;
    p.zero = 0;
    fused_kernel<<<NCTA, NTHREADS, SMEM_BYTES>>>(p, tg, td, tx, to);
}
```

```cpp
#include <cuda_runtime.h>
#include <cuda_bf16.h>
#include <cuda_fp16.h>
#include <cuda.h>
#include <stdint.h>

typedef __nv_bfloat16 bf16;

namespace {

constexpr int L_ = 2048, D_ = 1024, F_ = 3584;
constexpr int NCTA = 130;
constexpr int NTHREADS = 512;
#define AUXW 12
constexpr int MAIN_W0 = 0, AUX_W0 = AUXW, PREP_W0 = 20 - AUXW;
#define T0 3500
#define GAP 590
#define GAP1 530
#define GAP2 530
#define GAP3 550
#define STAG GAP
#define CSLEEP 50
#define SLACK 300
#define DELAY_X 150
#define TSLEEP 40
#define RS 2
#define BULKM false
#define PQ 3
#define PROMG 2
#define PROMD 1
#define PROMX 0
#define LATE2 0
#define HW 21
constexpr int NGU_CTA = 112;

constexpr int OFF_RING = 0;
constexpr int OFF_SCR  = 6 * 8192;
constexpr int S_PL     = 1056;
constexpr int S_Q      = 8 * S_PL;
constexpr int OFF_S    = 114688;
constexpr int OFF_GP   = OFF_S + 4 * S_Q;
constexpr int U_PL     = 2240;
constexpr int U_CH     = 4416;
constexpr int OFF_U    = 151552;
constexpr int TAB_W    = 3200;
constexpr int T_PL     = 544;
constexpr int T_A      = 2192 - 26 * 8;
constexpr int T_B      = 2568 - 59 * 8;
constexpr int OFF_TAB  = 186880;
constexpr int OFF_XSEL = 212480;
constexpr int XS_ROW   = 2064;
constexpr int OFF_BAND = 228992;
constexpr int OFF_MISC = 229536;
constexpr int M_BARS   = OFF_MISC;
constexpr int M_DSK    = OFF_MISC + 2736;
constexpr int M_SINK   = OFF_MISC + 512;
constexpr int M_TAG    = OFF_MISC + 516;
constexpr int M_BMAP   = OFF_MISC + 528;
constexpr int M_DPIN   = OFF_MISC + 656;
constexpr int M_TOP    = OFF_MISC + 2704;
constexpr int SMEM_BYTES = OFF_MISC + 2768;
__device__ __forceinline__ uint32_t s_addr(uint32_t o, uint32_t half) { return o + (((half ^ (o >> 7)) & 1) << 4); }
__host__ __device__ constexpr uint32_t y_off(uint32_t q) { return OFF_RING + 32768 + (q & 1) * 8192 + (q >> 1) * 65536; }

constexpr int B_W = 0;
constexpr int B_E = 24;
constexpr int B_S = 36;
constexpr int B_Y = 40;
constexpr int B_DP = 44, B_U = 45, B_KG = 46, B_G = 47;
constexpr int B_F = 48;
constexpr int B_H = 60;
constexpr int B_X = 52, B_XE = 56;

struct BandTab { uint32_t w[11][12]; };
constexpr BandTab make_band() {
    BandTab b{};
    for (int cls = 0; cls < 11; cls++)
        for (int wd = 0; wd < 10; wd++) {
            const int tau = cls + 2 - 8 * ((wd < 4 ? wd : wd - 4) >> 1);
            const int lo = (wd < 4) ? ((wd & 1) ? -2 : 3) : ((wd & 1) ? -4 : -11), wid = (wd < 4 ? 3 : 7) + 2 * (wd & 1);
            b.w[cls][wd] = ((tau >= lo && tau < lo + wid) ? 0x3F80u : 0u) | ((tau - 4 >= lo && tau - 4 < lo + wid) ? 0x3F800000u : 0u);
        }
    return b;
}
constexpr int NTOP = 32;
struct Scratch {
    uint4 r[L_ / 4 * RS];
    uint4 g[L_ / 4];
    uint4 h[2][8 * F_ / 8];
    uint32_t top[NTOP][32];
    unsigned epoch;
};
__device__ __align__(128) Scratch g_scratch;
__device__ const __align__(16) BandTab g_band = make_band();

struct Params {
    const bf16 *u, *logA, *Aim, *Cre, *Cim, *logdt, *Dskip, *wr, *gatew;
    bf16* out;
    Scratch* sc;
    const uint4* band;
    uint32_t gu_swap;
    uint32_t zero;
};

#define WSTAMP(i) do {} while (0)
#define KSTAMP(i, dep) do {} while (0)
#define WDUMP() do {} while (0)
#define RSTAMP(i) do {} while (0)

__device__ __forceinline__ uint32_t smem_u32(const void* p) { return (uint32_t)__cvta_generic_to_shared(p); }
__device__ __forceinline__ void mbar_init(uint32_t b, uint32_t c) { asm volatile("mbarrier.init.shared::cta.b64 [%0], %1;" :: "r"(b), "r"(c) : "memory"); }
__device__ __forceinline__ void mbar_expect(uint32_t b, uint32_t tx) { asm volatile("mbarrier.arrive.expect_tx.shared::cta.b64 _, [%0], %1;" :: "r"(b), "r"(tx) : "memory"); }
__device__ __forceinline__ void mbar_arrive(uint32_t b) { asm volatile("mbarrier.arrive.shared::cta.b64 _, [%0];" :: "r"(b) : "memory"); }
__device__ __forceinline__ void mbar_wait(uint32_t b, uint32_t parity = 0) {
    asm volatile("{\n\t.reg .pred p;\nW%=:\n\tmbarrier.try_wait.parity.shared::cta.b64 p, [%0], %1, 20000;\n\t@!p bra W%=;\n\t}" :: "r"(b), "r"(parity) : "memory");
}
__device__ __forceinline__ uint32_t mapa(uint32_t addr, uint32_t rank) { uint32_t r; asm("mapa.shared::cluster.u32 %0, %1, %2;" : "=r"(r) : "r"(addr), "r"(rank)); return r; }
__device__ __forceinline__ void tma3d(uint32_t dst, const CUtensorMap* tm, int c0, int c1, uint32_t bar, uint32_t bytes) {
    asm volatile("{\n\t.reg .pred p;\n\telect.sync _|p, 0xffffffff;\n\t"
                 "@p mbarrier.arrive.expect_tx.shared::cta.b64 _, [%2], %5;\n\t"
                 "@p cp.async.bulk.tensor.3d.shared::cluster.global.mbarrier::complete_tx::bytes [%0], [%1, {%3, %4, 0}], [%2];\n\t}"
        :: "r"(dst), "l"(tm), "r"(bar), "r"(c0), "r"(c1), "r"(bytes) : "memory");
}
__device__ __forceinline__ void bulk_load(uint32_t dst, const void* src, uint32_t bytes, uint32_t bar) {
    asm volatile("{\n\t.reg .pred p;\n\telect.sync _|p, 0xffffffff;\n\t"
                 "@p mbarrier.arrive.expect_tx.shared::cta.b64 _, [%2], %3;\n\t"
                 "@p cp.async.bulk.shared::cluster.global.mbarrier::complete_tx::bytes [%0], [%1], %3, [%2];\n\t}"
        :: "r"(dst), "l"(src), "r"(bar), "r"(bytes) : "memory");
}
__device__ __forceinline__ void st_async16(uint32_t dst, const uint4& v, uint32_t bar) {
    asm volatile("st.async.weak.shared::cluster.mbarrier::complete_tx::bytes.v4.b32 [%0], {%1,%2,%3,%4}, [%5];"
                 :: "r"(dst), "r"(v.x), "r"(v.y), "r"(v.z), "r"(v.w), "r"(bar) : "memory");
}
__device__ __forceinline__ void bar_sync(int id, int n) { asm volatile("bar.sync %0, %1;" :: "r"(id), "r"(n) : "memory"); }
__device__ __forceinline__ void cp16(uint32_t dst, const void* src) { asm volatile("cp.async.cg.shared.global [%0], [%1], 16;" :: "r"(dst), "l"(src) : "memory"); }
__device__ __forceinline__ void cp_wait_all() { asm volatile("cp.async.wait_all;" ::: "memory"); }
__device__ __forceinline__ uint4 ld_gpu128(const void* p) { uint4 v; asm volatile("ld.relaxed.gpu.global.v4.u32 {%0,%1,%2,%3}, [%4];" : "=r"(v.x), "=r"(v.y), "=r"(v.z), "=r"(v.w) : "l"(p) : "memory"); return v; }
__device__ __forceinline__ void st_gpu32(void* p, uint32_t v) { asm volatile("st.relaxed.gpu.global.u32 [%0], %1;" :: "l"(p), "r"(v) : "memory"); }

__device__ __forceinline__ void ldsm4(uint32_t a, uint32_t& r0, uint32_t& r1, uint32_t& r2, uint32_t& r3) {
    asm volatile("ldmatrix.sync.aligned.m8n8.x4.shared.b16 {%0,%1,%2,%3}, [%4];" : "=r"(r0), "=r"(r1), "=r"(r2), "=r"(r3) : "r"(a) : "memory");
}
__device__ __forceinline__ void ldsm4t(uint32_t a, uint32_t& r0, uint32_t& r1, uint32_t& r2, uint32_t& r3) {
    asm volatile("ldmatrix.sync.aligned.m8n8.x4.trans.shared.b16 {%0,%1,%2,%3}, [%4];" : "=r"(r0), "=r"(r1), "=r"(r2), "=r"(r3) : "r"(a) : "memory");
}
__device__ __forceinline__ uint32_t lds32(uint32_t a) { uint32_t v; asm volatile("ld.shared.u32 %0, [%1];" : "=r"(v) : "r"(a) : "memory"); return v; }
__device__ __forceinline__ uint2 lds64(uint32_t a) { uint2 v; asm volatile("ld.shared.v2.u32 {%0,%1}, [%2];" : "=r"(v.x), "=r"(v.y) : "r"(a) : "memory"); return v; }
__device__ __forceinline__ uint4 lds128(uint32_t a) { uint4 v; asm volatile("ld.shared.v4.u32 {%0,%1,%2,%3}, [%4];" : "=r"(v.x), "=r"(v.y), "=r"(v.z), "=r"(v.w) : "r"(a) : "memory"); return v; }
__device__ __forceinline__ void sts32(uint32_t a, uint32_t v) { asm volatile("st.shared.u32 [%0], %1;" :: "r"(a), "r"(v) : "memory"); }
__device__ __forceinline__ void sts16(uint32_t a, uint32_t v) { asm volatile("st.shared.u16 [%0], %1;" :: "r"(a), "h"((unsigned short)v) : "memory"); }
__device__ __forceinline__ void sts128(uint32_t a, uint32_t x, uint32_t y, uint32_t z, uint32_t w) { asm volatile("st.shared.v4.u32 [%0], {%1,%2,%3,%4};" :: "r"(a), "r"(x), "r"(y), "r"(z), "r"(w) : "memory"); }
__device__ __forceinline__ float ldsf(uint32_t a) { float v; asm volatile("ld.shared.f32 %0, [%1];" : "=f"(v) : "r"(a) : "memory"); return v; }

__device__ __forceinline__ void mma_bf(float (&d)[4], uint32_t a0, uint32_t a1, uint32_t a2, uint32_t a3, uint32_t b0, uint32_t b1) {
    asm volatile("mma.sync.aligned.m16n8k16.row.col.f32.bf16.bf16.f32 {%0,%1,%2,%3}, {%4,%5,%6,%7}, {%8,%9}, {%0,%1,%2,%3};"
        : "+f"(d[0]), "+f"(d[1]), "+f"(d[2]), "+f"(d[3]) : "r"(a0), "r"(a1), "r"(a2), "r"(a3), "r"(b0), "r"(b1));
}
__device__ __forceinline__ void mma_bf_z(float (&d)[4], uint32_t a0, uint32_t a1, uint32_t a2, uint32_t a3, uint32_t b0, uint32_t b1) {
    asm volatile("mma.sync.aligned.m16n8k16.row.col.f32.bf16.bf16.f32 {%0,%1,%2,%3}, {%4,%5,%6,%7}, {%8,%9}, {%10,%10,%10,%10};"
        : "=f"(d[0]), "=f"(d[1]), "=f"(d[2]), "=f"(d[3]) : "r"(a0), "r"(a1), "r"(a2), "r"(a3), "r"(b0), "r"(b1), "f"(0.f));
}
__device__ __forceinline__ void mma_bf_k8(float (&d)[4], uint32_t a0, uint32_t a1, uint32_t b0) {
    asm volatile("mma.sync.aligned.m16n8k8.row.col.f32.bf16.bf16.f32 {%0,%1,%2,%3}, {%4,%5}, {%6}, {%0,%1,%2,%3};"
        : "+f"(d[0]), "+f"(d[1]), "+f"(d[2]), "+f"(d[3]) : "r"(a0), "r"(a1), "r"(b0));
}
__device__ __forceinline__ void mma_h(float (&d)[4], uint32_t a0, uint32_t a1, uint32_t a2, uint32_t a3, uint32_t b0, uint32_t b1) {
    asm volatile("mma.sync.aligned.m16n8k16.row.col.f32.f16.f16.f32 {%0,%1,%2,%3}, {%4,%5,%6,%7}, {%8,%9}, {%0,%1,%2,%3};"
        : "+f"(d[0]), "+f"(d[1]), "+f"(d[2]), "+f"(d[3]) : "r"(a0), "r"(a1), "r"(a2), "r"(a3), "r"(b0), "r"(b1));
}
__device__ __forceinline__ uint32_t pack_bf(float lo, float hi) { uint32_t r; asm("cvt.rn.bf16x2.f32 %0, %1, %2;" : "=r"(r) : "f"(hi), "f"(lo)); return r; }
__device__ __forceinline__ uint32_t pack_h(float lo, float hi) { uint32_t r; asm("cvt.rn.f16x2.f32 %0, %1, %2;" : "=r"(r) : "f"(hi), "f"(lo)); return r; }
__device__ __forceinline__ float bf_lo(uint32_t v) { return __uint_as_float(v << 16); }
__device__ __forceinline__ float bf_hi(uint32_t v) { return __uint_as_float(v & 0xffff0000u); }
__device__ __forceinline__ float bf_round(float x) { return __uint_as_float(pack_bf(0.f, x)); }
__device__ __forceinline__ uint32_t hmul2_bf(uint32_t a, uint32_t b) { uint32_t r; asm("mul.rn.bf16x2 %0, %1, %2;" : "=r"(r) : "r"(a), "r"(b)); return r; }
__device__ __forceinline__ float ex2f(float x) { float r; asm("ex2.approx.ftz.f32 %0, %1;" : "=f"(r) : "f"(x)); return r; }

__device__ __forceinline__ float exp_acc(float x) {
    const float t = x * 1.4426950216293335f;
    const float r = fmaf(x, 1.4426950216293335f, -t) + x * 1.9259629911266175e-8f;
    return ex2f(t) * fmaf(r, 0.6931471805599453f, 1.f);
}
__device__ __forceinline__ float sigmoid_f(float x) { return __fdividef(1.f, 1.f + ex2f(-x * 1.4426950408889634f)); }
__device__ __forceinline__ void cexp_pow(float l2, float li, float e, float& zr, float& zi) {
    const float mag = ex2f(l2 * e);
    zr = mag * __cosf(li * e);
    zi = mag * __sinf(li * e);
}
__device__ __forceinline__ uint32_t hcmul(uint32_t a, uint32_t k, uint32_t kp) {
    const __half2 A = *reinterpret_cast<const __half2*>(&a);
    const __half2 r = __hfma2(__high2half2(A), *reinterpret_cast<const __half2*>(&kp), __hmul2(__low2half2(A), *reinterpret_cast<const __half2*>(&k)));
    return *reinterpret_cast<const uint32_t*>(&r);
}
#define CMUL(orr, oi, ar, ai, br, bi) do { float _r = (ar) * (br) - (ai) * (bi); float _i = (ar) * (bi) + (ai) * (br); orr = _r; oi = _i; } while (0)
#define CSQ(orr, oi, ar, ai) do { float _r = (ar) * (ar) - (ai) * (ai); float _i = 2.f * (ar) * (ai); orr = _r; oi = _i; } while (0)

__device__ __forceinline__ void mma_bf_k8z(float (&d)[4], uint32_t a0, uint32_t a1, uint32_t b0) {
    asm volatile("mma.sync.aligned.m16n8k8.row.col.f32.bf16.bf16.f32 {%0,%1,%2,%3}, {%4,%5}, {%6}, {%7,%7,%7,%7};"
        : "=f"(d[0]), "=f"(d[1]), "=f"(d[2]), "=f"(d[3]) : "r"(a0), "r"(a1), "r"(b0), "f"(0.f));
}
__device__ __forceinline__ void mma_hh_k8(uint32_t& d0, uint32_t& d1, uint32_t a0, uint32_t a1, uint32_t b0) {
    asm volatile("mma.sync.aligned.m16n8k8.row.col.f16.f16.f16.f16 {%0,%1}, {%2,%3}, {%4}, {%5,%5};"
        : "=r"(d0), "=r"(d1) : "r"(a0), "r"(a1), "r"(b0), "r"(0));
}
__device__ __forceinline__ uint32_t pin(uint32_t x, int lane) { return __shfl_sync(0xffffffffu, x, lane); }
template <class T> __device__ __forceinline__ T* pin(T* x, int lane) { return (T*)__shfl_sync(0xffffffffu, (unsigned long long)x, lane); }
__device__ __forceinline__ void sts32_if(bool on, uint32_t a, uint32_t v) {
    asm volatile("{\n\t.reg .pred p;\n\tsetp.ne.u32 p, %2, 0;\n\t@p st.shared.u32 [%0], %1;\n\t}" :: "r"(a), "r"(v), "r"((uint32_t)on) : "memory");
}
__device__ __forceinline__ void sts128_if(bool on, uint32_t a, uint32_t x, uint32_t y, uint32_t z, uint32_t w) {
    asm volatile("{\n\t.reg .pred p;\n\tsetp.ne.u32 p, %5, 0;\n\t@p st.shared.v4.u32 [%0], {%1,%2,%3,%4};\n\t}" :: "r"(a), "r"(x), "r"(y), "r"(z), "r"(w), "r"((uint32_t)on) : "memory");
}
__device__ __forceinline__ void lds128_if(bool on, uint32_t a, uint32_t (&v)[4]) {
    asm volatile("{\n\t.reg .pred p;\n\tsetp.ne.u32 p, %5, 0;\n\t@p ld.shared.v4.u32 {%0,%1,%2,%3}, [%4];\n\t}"
        : "+r"(v[0]), "+r"(v[1]), "+r"(v[2]), "+r"(v[3]) : "r"(a), "r"((uint32_t)on) : "memory");
}
__device__ __forceinline__ uint32_t hfma2_bf(uint32_t a, uint32_t b, uint32_t c) { uint32_t r; asm("fma.rn.bf16x2 %0, %1, %2, %3;" : "=r"(r) : "r"(a), "r"(b), "r"(c)); return r; }
__device__ __forceinline__ uint32_t row_elem(uint32_t row) { return ((row >> 5) & 4) | ((row >> 2) & 2) | ((row >> 4) & 1); }
__device__ __forceinline__ uint32_t gate_pos(uint32_t row) { return ((row >> 9) << 8) | ((row & 7) << 5) | (row_elem(row) << 2) | ((row >> 5) & 3); }

template <int N, bool BULK>
__device__ __forceinline__ void mix_rows(const Params& p, const CUtensorMap* tm_out, uint32_t sb, uint32_t ob, int Q0, int Q1, int w, int h, int pr, int lane) {
    const int g = lane >> 2, t = lane & 3, mi = lane >> 3, r = lane & 7;
    const int m8 = 16 * (g >> 2) + ((g >> 1) & 1) + 2 * (g & 1);
    uint32_t yi = sb + (4 * (r >> 1) + 2 * (mi & 1) + (r & 1)) * 512 + (((4 * w + (mi >> 1)) ^ r) << 4);
    uint32_t xs = sb + OFF_S + s_addr(w * S_PL + 32 + m8 * 32, t >> 1) + ((t & 1) << 3);
    uint32_t gs = sb + OFF_GP + w * 64 + g * 8, os = ob + m8 * 32 + t * 8;
    if (N > 1) { yi = pin(yi, lane); xs = pin(xs, lane); gs = pin(gs, lane); os = pin(os, lane); }
    mbar_wait(sb + M_BARS + 8 * B_Y);
#pragma unroll 1
    for (int Q = Q0; Q < Q1; Q++) {
        uint2 xq[N][4];
        uint32_t gg[N][4], sw[N];
#pragma unroll
        for (int n = 0; n < N; n++) {
#pragma unroll
            for (int i = 0; i < 4; i++) xq[n][i] = lds64((xs ^ (((i ^ n) & 1) << 4)) + Q * S_Q + n * 4 * S_PL + i * 128);
            const uint2 gq = lds64(gs + Q * 512 + n * 256);
            sw[n] = lds32(sb + M_BMAP + w * 16 + n * 64 + Q * 4);
#pragma unroll
            for (int i = 0; i < 4; i++) {
                gg[n][i] = __byte_perm(i < 2 ? gq.x : gq.y, 0, (i & 1) ? 0x3232 : 0x1010);
                const uint32_t og = hfma2_bf(gg[n][i], 0xBF80BF80u, 0x3F803F80u);
                xq[n][i].x = hmul2_bf(og, xq[n][i].x); xq[n][i].y = hmul2_bf(og, xq[n][i].y);
            }
        }
        mbar_wait(sb + M_BARS + 8 * (B_Y + Q));
        __syncwarp();
#pragma unroll
        for (int n = 0; n < N; n++) {
#pragma unroll
            for (int x = 0; x < 2; x++) {
                uint32_t y[4];
                ldsm4t((yi ^ (x << 5)) + y_off(Q) + n * 256, y[0], y[1], y[2], y[3]);
#pragma unroll
                for (int e = 0; e < 2; e++) {
                    uint2& o = xq[n][2 * x + e];
                    o.x = hfma2_bf(gg[n][2 * x + e], y[2 * e], o.x); o.y = hfma2_bf(gg[n][2 * x + e], y[2 * e + 1], o.y);
                }
            }
        }
        if (BULK && (sw[0] | sw[N - 1]) == 0) {
#pragma unroll
            for (int n = 0; n < N; n++)
#pragma unroll
                for (int i = 0; i < 4; i++)
                    asm volatile("st.shared.v2.u32 [%0], {%1, %2};" :: "r"(os + Q * 1024 + n * 4 * TAB_W + i * 128), "r"(xq[n][i].x), "r"(xq[n][i].y) : "memory");
            asm volatile("fence.proxy.async.shared::cta;" ::: "memory");
            __syncwarp();
#pragma unroll
            for (int n = 0; n < N; n++)
                asm volatile("{\n\t.reg .pred p;\n\telect.sync _|p, 0xffffffff;\n\t"
                             "@p cp.async.bulk.tensor.3d.global.shared::cta.bulk_group [%1, {%2, %3, %4}], [%0];\n\t}"
                    :: "r"(ob + 4 * n * TAB_W + Q * 1024), "l"(tm_out), "r"(16 * pr), "r"(64 * Q + 32 * h), "r"(w + 4 * n) : "memory");
        } else {
            bf16* op = p.out + (size_t)(512 * Q + 256 * h + 8 * m8 + w) * D_ + 16 * pr + 4 * t;
#pragma unroll
            for (int n = 0; n < N; n++)
#pragma unroll
                for (int i = 0; i < 4; i++)
                    if (!((sw[n] >> (4 * g)) & (1u << i))) *(uint2*)(op + (size_t)(32 * i + 4 * n) * D_) = xq[n][i];
        }
    }
}

__global__ void __cluster_dims__(2, 1, 1) __launch_bounds__(NTHREADS, 1)
fused_kernel(const Params p, const __grid_constant__ CUtensorMap tm_gu, const __grid_constant__ CUtensorMap tm_down,
             const __grid_constant__ CUtensorMap tm_x, const __grid_constant__ CUtensorMap tm_out) {
    extern __shared__ __align__(1024) unsigned char smem[];
    const uint32_t sb = smem_u32(smem);
    int tid;
    asm volatile("mov.u32 %0, %%tid.x;" : "=r"(tid));
    const int pw = tid >> 5, lane = tid & 31;
    const int c = blockIdx.x, h = c & 1, pr = c >> 1;
    const uint32_t bars = sb + M_BARS;

    uint2 v_la, v_ai, v_cr, v_ci;
    uint32_t ldt16;
    {
        const uint32_t po = c * 256 + tid;
        asm volatile("{\n\t.reg .pred p;\n\t.reg .b64 a;\n\tsetp.ne.u32 p, %16, 0;\n\t"
                     "mad.wide.u32 a, %14, 8, %9;\n\t@p ld.global.nc.L1::no_allocate.v2.u32 {%0,%1}, [a];\n\t"
                     "mad.wide.u32 a, %15, 2, %13;\n\t@p ld.global.nc.u16 %8, [a];\n\t"
                     "mad.wide.u32 a, %14, 8, %10;\n\t@p ld.global.nc.L1::no_allocate.v2.u32 {%2,%3}, [a];\n\t"
                     "mad.wide.u32 a, %14, 8, %11;\n\t@p ld.global.nc.L1::no_allocate.v2.u32 {%4,%5}, [a];\n\t"
                     "mad.wide.u32 a, %14, 8, %12;\n\t@p ld.global.nc.L1::no_allocate.v2.u32 {%6,%7}, [a];\n\t}"
            : "=r"(v_la.x), "=r"(v_la.y), "=r"(v_ai.x), "=r"(v_ai.y), "=r"(v_cr.x), "=r"(v_cr.y), "=r"(v_ci.x), "=r"(v_ci.y), "=r"(ldt16)
            : "l"(p.logA), "l"(p.Aim), "l"(p.Cre), "l"(p.Cim), "l"(p.logdt), "r"(po), "r"(po >> 5), "r"((uint32_t)(tid < 256 && c < 128)));
    }

    if (c >= 128) {
        if (c != 128) return;
        RSTAMP(5);
        const unsigned tag = (*(volatile unsigned*)&p.sc->epoch + 1) & 0xffffu;
        const uint32_t list = sb + 128;
#pragma unroll 1
        for (int pass = 0; pass < 2; pass++) {
            sts128(list + 16 * tid, 0, 0, 0, 0);
            if (tid == 0) sts32(sb + 64, 0);
            uint32_t key[4];
            bool ok = false;
#pragma unroll 1
            for (int it = 0; it < (1 << 22); it++) {
                const uint4 a = ld_gpu128(&p.sc->r[tid * RS]);
                key[0] = a.x; key[1] = a.y; key[2] = a.z; key[3] = a.w;
                ok = (((a.x ^ tag) | (a.y ^ tag) | (a.z ^ tag) | (a.w ^ tag)) & 0xffffu) == 0;
                if (ok || !pass) break;
            }
            WSTAMP(0);
            uint32_t m = 0;
#pragma unroll
            for (int i = 0; i < 4; i++) {
                key[i] = ((pass ? key[i] : (lane + i) << 16) & 0xffff0000u) | (uint32_t)(2047 - (4 * tid + i));
                m = max(m, key[i]);
            }
            const uint32_t wm = __reduce_max_sync(0xffffffffu, m);
            if (lane == 0) sts32(sb + pw * 4, wm);
            __syncthreads();
            uint32_t thr = 0xffffffffu;
#pragma unroll
            for (int i = 0; i < 4; i++) { const uint4 q = lds128(sb + 16 * i); thr = min(thr, min(max(q.x, q.y), max(q.z, q.w))); }
            if (thr != 1) WSTAMP(1);
            if (m >= thr) {
                uint32_t pos;
                asm volatile("atom.shared.add.u32 %0, [%1], %2;" : "=r"(pos) : "r"(sb + 64), "r"(4 * ((key[0] >= thr) + (key[1] >= thr) + (key[2] >= thr) + (key[3] >= thr))) : "memory");
#pragma unroll
                for (int i = 0; i < 4; i++) if (key[i] >= thr) { sts32(list + pos, key[i]); pos += 4; }
            }
            __syncthreads();
            const uint32_t nc4 = lds32(sb + 64);
            if (nc4 != 1) WSTAMP(2);
#pragma unroll 1
            for (uint32_t j = 4 * pw; j < nc4; j += 64) {
                const uint32_t mine = lds32(list + j);
                int rank = 0;
#pragma unroll 1
                for (uint32_t i = 0; i < nc4; i += 128) rank += __popc(__ballot_sync(0xffffffffu, lds32(list + i + 4 * lane) > mine));
                if (rank < 8 && lane == 0) sts32(sb + 96 + 4 * rank, mine);
            }
            __syncthreads();
            if (tid < 8 * NTOP) st_gpu32(&p.sc->top[tid >> 3][tid & 7], lds32(sb + 96 + 4 * (tid & 7)) | (((tag + pass - 1) & 31) << 11));
            WSTAMP(3);
            if (!pass) RSTAMP(4);
        }
        WDUMP();
        return;
    }

    WSTAMP(0);
    if (pw < 8) {
        const int d = 8 * c + pw - MAIN_W0;
        if (lane == 0) asm volatile("cp.async.ca.shared.global [%0], [%1], 4;" :: "r"(sb + M_DSK + 4 * (pw - MAIN_W0)), "l"(p.Dskip + (d & ~1)) : "memory");
        asm volatile("barrier.cluster.arrive.relaxed.aligned;" ::: "memory");
        const int warp = pw - MAIN_W0;
        asm volatile("setmaxnreg.inc.sync.aligned.u32 168;");
        const int g = lane >> 2, t = lane & 3;
        const int mi = lane >> 3, r = lane & 7;
        const uint32_t TB = sb + OFF_TAB + warp * TAB_W;
        const uint32_t UB = sb + OFF_U + warp * U_CH;
        if (mi < 2) sts128(UB + mi * U_PL + r * 16, 0, 0, 0, 0);
#pragma unroll
        for (int i = 0; i < 6; i++) sts128(TB + 16 * (lane + 32 * i), 0, 0, 0, 0);
        if (lane < 8) sts128(TB + 16 * (lane + 192), 0, 0, 0, 0);
        sts128(sb + OFF_SCR + warp * 8192 + lane * 16, 0x3C00u, 0x3C00u, 0x3C00u, 0x3C00u);
        __syncwarp();

        uint32_t cfix;
        {
            KSTAMP(4, v_la.x ^ v_ai.x ^ v_cr.x ^ v_ci.x ^ ldt16);
            const float dt = bf_round(exp_acc(__uint_as_float(ldt16 << 16)));
            float l2[4], li[4];
            {
                const uint32_t la[2] = {v_la.x, v_la.y}, ai[2] = {v_ai.x, v_ai.y};
                const float dt2 = -1.4426950408889634f * dt;
#pragma unroll
                for (int i = 0; i < 4; i++) {
                    l2[i] = bf_round(ex2f(((i & 1) ? bf_hi(la[i >> 1]) : bf_lo(la[i >> 1])) * 1.4426950408889634f)) * dt2;
                    li[i] = ((i & 1) ? bf_hi(ai[i >> 1]) : bf_lo(ai[i >> 1])) * dt;
                }
            }
            const uint32_t SX = sb + OFF_SCR + warp * 8192;
            const uint32_t sw = SX + (lane << 4);
#define PUT(buf, row, v) sts128(((sw + (row) * 512) ^ ((row) << 4)) + (buf) * 4096, v[0], v[1], v[2], v[3])
#define EMIT(bufa, rowa, bufb, rowb, xr, xi, k, kp) do { uint32_t pk[4], pd[4]; \
                _Pragma("unroll") for (int i = 0; i < 4; i++) { pk[i] = pack_h(xr[i], xi[i]); pd[i] = hcmul(pk[i], k[i], kp[i]); } \
                PUT(bufa, rowa, pk); PUT(bufb, rowb, pd); } while (0)
#define CMUL4(orr, oi, ar, ai, br, bi) _Pragma("unroll") for (int i = 0; i < 4; i++) CMUL(orr[i], oi[i], ar[i], ai[i], br[i], bi[i])
#define CSQ4(orr, oi, ar, ai) _Pragma("unroll") for (int i = 0; i < 4; i++) CSQ(orr[i], oi[i], ar[i], ai[i])
            float z1r[4], z1i[4], z2r[4], z2i[4], z8r[4], z8i[4], z256r[4], z256i[4];
            uint32_t k128[4], k128p[4], k4[4], k4p[4];
            float z4r[4], z4i[4];
#pragma unroll
            for (int i = 0; i < 4; i++) cexp_pow(l2[i], li[i], 1.f, z1r[i], z1i[i]);
            CSQ4(z2r, z2i, z1r, z1i);
            CSQ4(z4r, z4i, z2r, z2i);
            CSQ4(z8r, z8i, z4r, z4i);
            KSTAMP(5, __float_as_uint(z8r[3]));
            uint32_t Ya[16][4];
            float cr[4], ci[4], inv;
            {
                float w1r[4], w1i[4], ar[4], ai[4], br[4], bi[4];
                uint32_t k8[4], k8p[4];
#pragma unroll
                for (int i = 0; i < 4; i++) {
                    k8[i] = pack_h(z8r[i], -z8i[i]); k8p[i] = pack_h(z8i[i], z8r[i]);
                    CSQ(w1r[i], w1i[i], z8r[i], z8i[i]); w1i[i] = -w1i[i];
                }
                PUT(1, 0, k8);
                EMIT(0, 1, 1, 1, w1r, w1i, k8, k8p);
                CSQ4(ar, ai, w1r, w1i);            EMIT(0, 2, 1, 2, ar, ai, k8, k8p);
                CMUL4(br, bi, ar, ai, w1r, w1i);   EMIT(0, 3, 1, 3, br, bi, k8, k8p);
                CSQ4(ar, ai, ar, ai);              EMIT(0, 4, 1, 4, ar, ai, k8, k8p);
                CMUL4(ar, ai, ar, ai, w1r, w1i);   EMIT(0, 5, 1, 5, ar, ai, k8, k8p);
                CSQ4(br, bi, br, bi);              EMIT(0, 6, 1, 6, br, bi, k8, k8p);
                CMUL4(br, bi, br, bi, w1r, w1i);   EMIT(0, 7, 1, 7, br, bi, k8, k8p);
                __syncwarp();
                KSTAMP(6, 0);
                const uint32_t ab = SX + (mi & 1) * 4096 + r * 512, ax = ((mi >> 1) ^ r) << 4;
                const uint32_t vr[2] = {v_cr.x, v_cr.y}, vi[2] = {v_ci.x, v_ci.y};
                const uint32_t m2 = __vmaxu2(__vmaxu2(vr[0] & 0x7fff7fffu, vr[1] & 0x7fff7fffu), __vmaxu2(vi[0] & 0x7fff7fffu, vi[1] & 0x7fff7fffu));
                const uint32_t mx = __reduce_max_sync(0xffffffffu, max(m2, m2 << 16));
                const uint32_t e = min(max(mx >> 23, 11u), 254u);
                const float sc = __uint_as_float((264u - e) << 23);
                inv = __uint_as_float((e - 10u) << 23) * (2.f * dt);
#pragma unroll
                for (int i = 0; i < 4; i++) {
#pragma unroll
                    for (int k = 0; k < 4; k++) ldsm4(ab + (ax ^ (i << 5)) + k * 128, Ya[4 * k + i][0], Ya[4 * k + i][1], Ya[4 * k + i][2], Ya[4 * k + i][3]);
                    float tr, ti;
                    cexp_pow(l2[i], li[i], 128.f, tr, ti);
                    k128[i] = pack_h(tr, ti); k128p[i] = pack_h(-ti, tr);
                    k4[i] = pack_h(z4r[i], z4i[i]); k4p[i] = pack_h(-z4i[i], z4r[i]);
                    CSQ(z256r[i], z256i[i], tr, ti);
                    cr[i] = ((i & 1) ? bf_hi(vr[i >> 1]) : bf_lo(vr[i >> 1])) * sc;
                    ci[i] = ((i & 1) ? bf_hi(vi[i >> 1]) : bf_lo(vi[i >> 1])) * sc;
                }
#pragma unroll
                for (int i = 0; i < 4; i++) { sts32(TB + i * T_PL + 16 + 4 * lane, k128[i]); sts32(TB + i * T_PL + 160 + 4 * lane, k128p[i]); }
                __syncwarp();
            }
            KSTAMP(7, Ya[15][0]);
            const uint32_t ld0 = SX + r * 512 + ((mi ^ r) << 4), ld1 = ld0 ^ 64;
            float R[5][4], xr[4], xi[4];
            {
                float yr[4], yi[4];
                EMIT(0, 0, 0, 1, cr, ci, k4, k4p);
                CMUL4(yr, yi, cr, ci, z1r, z1i);        EMIT(0, 2, 0, 3, yr, yi, k4, k4p);
                CMUL4(xr, xi, cr, ci, z256r, z256i);    EMIT(1, 0, 1, 1, xr, xi, k4, k4p);
                CMUL4(yr, yi, yr, yi, z1r, z1i);        EMIT(0, 4, 0, 5, yr, yi, k4, k4p);
                CMUL4(cr, ci, xr, xi, z2r, z2i);        EMIT(1, 2, 1, 3, cr, ci, k4, k4p);
                CMUL4(yr, yi, yr, yi, z1r, z1i);        EMIT(0, 6, 0, 7, yr, yi, k4, k4p);
                CMUL4(xr, xi, xr, xi, z256r, z256i);    EMIT(1, 4, 1, 5, xr, xi, k4, k4p);
                CMUL4(xr, xi, xr, xi, z256r, z256i);    EMIT(1, 6, 1, 7, xr, xi, k4, k4p);
            }
            __syncwarp();
            {
                KSTAMP(8, 0);
                uint32_t bd[2][4] = {{0, 0, 0, 0}, {0, 0, 0, 0}};
                const bool on = (g >> 1) == t;
#pragma unroll
                for (int i = 0; i < 4; i++) { R[i][0] = R[i][1] = R[i][2] = R[i][3] = 0.f; }
#pragma unroll
                for (int k2 = 0; k2 < 8; k2++) {
                    uint32_t x[4], y[4], a1[2][4];
                    lds128_if(on, TB + t * T_PL + 16 + (g & 1) * 144 + 16 * k2, bd[k2 & 1]);
                    ldsm4(((k2 & 1) ? ld1 : ld0) + (k2 >> 1) * 128, x[0], x[1], x[2], x[3]);
                    ldsm4(((k2 & 1) ? ld1 : ld0) + (k2 >> 1) * 128 + 4096, y[0], y[1], y[2], y[3]);
#pragma unroll
                    for (int u = 0; u < 2; u++) {
                        mma_hh_k8(a1[u][0], a1[u][1], Ya[2 * k2 + u][0], Ya[2 * k2 + u][1], bd[k2 & 1][2 * u]);
                        mma_hh_k8(a1[u][2], a1[u][3], Ya[2 * k2 + u][2], Ya[2 * k2 + u][3], bd[k2 & 1][2 * u + 1]);
                    }
#pragma unroll
                    for (int u = 0; u < 2; u++) {
                        const uint32_t(&a0)[4] = Ya[2 * k2 + u];
                        mma_h(R[0], a0[0], a0[1], a0[2], a0[3], x[2 * u], x[2 * u + 1]);
                        mma_h(R[2], a0[0], a0[1], a0[2], a0[3], y[2 * u], y[2 * u + 1]);
                        mma_h(R[1], a1[u][0], a1[u][1], a1[u][2], a1[u][3], x[2 * u], x[2 * u + 1]);
                        mma_h(R[3], a1[u][0], a1[u][1], a1[u][2], a1[u][3], y[2 * u], y[2 * u + 1]);
                    }
                }
            }
            __syncwarp();
            KSTAMP(9, __float_as_uint(R[3][0]));
            asm volatile("barrier.cluster.wait.acquire.aligned;" ::: "memory");
            CMUL4(xr, xi, xr, xi, z256r, z256i);
            float s1024 = (xr[0] + xr[1]) + (xr[2] + xr[3]);
            CMUL4(xr, xi, xr, xi, z8r, z8i);        EMIT(0, 0, 0, 1, xr, xi, k128, k128p);
            CMUL4(xr, xi, xr, xi, z256r, z256i);    EMIT(0, 2, 0, 3, xr, xi, k128, k128p);
            CMUL4(xr, xi, xr, xi, z256r, z256i);    EMIT(0, 4, 0, 5, xr, xi, k128, k128p);
            CMUL4(xr, xi, xr, xi, z256r, z256i);    EMIT(0, 6, 0, 7, xr, xi, k128, k128p);
            __syncwarp();
            {
                KSTAMP(10, 0);
                float a1[4] = {0.f, 0.f, 0.f, 0.f};
                R[4][0] = R[4][1] = R[4][2] = R[4][3] = 0.f;
#pragma unroll
                for (int k2 = 0; k2 < 8; k2++) {
                    uint32_t x[4];
                    ldsm4(((k2 & 1) ? ld1 : ld0) + (k2 >> 1) * 128, x[0], x[1], x[2], x[3]);
                    mma_h(R[4], Ya[2 * k2][0], Ya[2 * k2][1], Ya[2 * k2][2], Ya[2 * k2][3], x[0], x[1]);
                    mma_h(a1, Ya[2 * k2 + 1][0], Ya[2 * k2 + 1][1], Ya[2 * k2 + 1][2], Ya[2 * k2 + 1][3], x[2], x[3]);
                }
#pragma unroll
                for (int i = 0; i < 4; i++) R[4][i] += a1[i];
            }
            if (lane == 0) mbar_arrive(bars + 8 * B_KG + (__float_as_uint(R[4][0]) & p.zero));
            KSTAMP(11, __float_as_uint(R[4][0]));
#undef PUT
#undef EMIT
#pragma unroll
            for (int o = 16; o > 0; o >>= 1) s1024 += __shfl_xor_sync(0xffffffffu, s1024, o);
            uint32_t w[4][4], dsk = 0;
            cp_wait_all();
            asm volatile("{\n\t.reg .pred p;\n\tsetp.eq.u32 p, %2, 0;\n\t@p ld.shared.u16 %0, [%1];\n\t}" : "+r"(dsk) : "r"(sb + M_DSK + 4 * warp + 2 * (warp & 1)), "r"(lane) : "memory");
#pragma unroll
            for (int a = 0; a < 4; a++) {
                const float v0 = (a == 0) ? fmaf(R[0][0], inv, __uint_as_float(dsk << 16)) : R[a][0] * inv;
                const float v1 = R[a][1] * inv, v2 = R[a][2] * inv, v3 = R[a][3] * inv;
                w[a][0] = pack_bf(v0, 0.f); w[a][1] = pack_bf(v1, v0); w[a][2] = pack_bf(v2, v1); w[a][3] = pack_bf(v3, v2);
            }
            const uint32_t wb = TB + 16 + 16 * g, w1 = wb + t * T_PL, w2 = wb + 256 + 2 * t * T_PL;
            const uint32_t w3 = (t == 0) ? wb + 256 + 3 * T_PL : TB + T_A + 8 * (16 * t + g);
            const uint32_t w3s = (t == 0) ? 128 : 64, w3o = (t == 0) ? 8 : 12;
            const uint32_t k512 = __shfl_sync(0xffffffffu, w[2][1], 2);
#pragma unroll
            for (int a = 0; a < 2; a++) {
                sts128(w1 + 128 * a, w[a][0], w[a][1], w[a][2], w[a][3]);
                const uint32_t(&q)[4] = w[2 + a];
                if (t < 2) sts128(w2 + 128 * a, q[0], q[1], q[2], q[3]);
                if (t == 0) { sts128(w2 + T_PL + 128 * a, q[0], q[1], q[2], q[3]); sts32(w3 + 128 * a + 4, q[2]); }
                sts32_if(t != 1 && (a == 1 || lane != 2), w3 + w3s * a, q[1]);
                sts32_if(t != 1, w3 + w3s * a + w3o, q[3]);
            }
            sts128_if(lane < 4, w1 + 512, t == 3 ? k512 : k512 >> 16, t < 2 ? k512 : t == 2 ? k512 & 0xffff0000u : k512 << 16, t < 2 ? k512 << 16 : 0u, 0);
            __syncwarp();
#pragma unroll
            for (int a = 0; a < 2; a++) {
                sts16(w1 + 128 * a + 18, w[a][3]);
                const uint32_t(&q)[4] = w[2 + a];
                if (t < 2) sts16(w2 + 128 * a + 18, q[3]);
                if (t == 0) { sts16(w2 + T_PL + 128 * a + 18, q[3]); sts16(w3 + 128 * a + 14, q[3]); }
            }
            if (t == 0) sts16(w3 + 128 - 4, w[3][0]);
            if (lane == 2 || (t == 0 && g > 0)) sts16(lane == 2 ? TB + 16 + 3 * T_PL + 4 * 127 : w3 - 4, w[2][0]);
            {
                const uint32_t b0 = pack_bf(R[4][0] * inv, R[4][2] * inv), b1 = pack_bf(R[4][1] * inv, R[4][3] * inv);
                const uint32_t wq = TB + T_B + 8 * (65 + 16 * t + g);
                sts32(wq, b0); sts32(wq + 12, b0); sts32(wq + 64, b1); sts32(wq + 76, b1);
            }
            cfix = pack_bf(s1024 * inv, s1024 * inv);
            if (lane == 0) sts32(TB + T_A + 8 * 64, cfix);
            __syncwarp();
        }
        WSTAMP(1);

        mbar_wait(bars + 8 * B_U);
        WSTAMP(2);

        float D[16][4];
        {
            const int x5 = g - t + 5;
            const uint32_t tabD = TB + (x5 & 3) * T_PL + (x5 & 12) + 16;
            {
                const uint32_t a1 = lds32(tabD - 8), a0 = p.zero;
#pragma unroll
                for (int jq = 0; jq < 4; jq++) {
                    uint32_t b[4];
                    ldsm4(UB + (9 + lane) * 16 + jq * 512, b[0], b[1], b[2], b[3]);
#pragma unroll
                    for (int i = 0; i < 4; i++) mma_bf_k8z(D[4 * jq + i], a0, a1, b[i]);
                }
            }
            const uint32_t ua = UB + (mi & 1) * U_PL + (8 + 8 * (mi >> 1) + r) * 16;
#pragma unroll 1
            for (int k0 = 0; k0 < 8; k0++) {
                uint32_t Uf[16][2];
#pragma unroll
                for (int jp = 0; jp < 8; jp++) ldsm4(ua + jp * 256 - k0 * 16, Uf[2 * jp][0], Uf[2 * jp][1], Uf[2 * jp + 1][0], Uf[2 * jp + 1][1]);
#pragma unroll
                for (int k1 = 0; k1 < 4; k1++) {
                    const uint32_t ta = tabD + 16 * (8 * k1 + k0);
                    const uint32_t a0 = lds32(ta), a1 = lds32(ta + 8), a2 = lds32(ta - 8), a3 = a0 ^ p.zero;
#pragma unroll
                    for (int J = k1; J < 16; J++) mma_bf(D[J], a0, a1, a2, a3, Uf[J - k1][0], Uf[J - k1][1]);
                }
                if (k0 == 0) {
                    const uint32_t ta = tabD + 16 * 32;
                    const uint32_t a0 = lds32(ta), a1 = lds32(ta + 8), a2 = lds32(ta - 8), a3 = a0 ^ p.zero;
#pragma unroll
                    for (int J = 4; J < 16; J++) mma_bf(D[J], a0, a1, a2, a3, Uf[J - 4][0], Uf[J - 4][1]);
                    const uint32_t f0 = (cfix ^ 0x80008000u) & (g == t ? 0xffffu : g == t + 4 ? 0xffff0000u : 0u);
                    const uint32_t f1 = p.zero, f2 = p.zero + p.zero, f3 = f0 ^ p.zero;
#pragma unroll
                    for (int J = 8; J < 16; J++) mma_bf(D[J], f0, f1, f2, f3, Uf[J - 8][0], Uf[J - 8][1]);
                }
            }
        }
        WSTAMP(3);
        {
            const int ch = 8 * h + warp;
            const uint32_t yo = sb + ch * 512 + ((lane ^ (((ch >> 2) << 1) | (ch & 1))) << 4);
            const uint32_t yr = mapa(yo, h ^ 1), ybr = mapa(bars + 8 * B_Y, h ^ 1);
            auto ship = [&](const int Q) {
                uint4 y[2];
#pragma unroll
                for (int hh = 0; hh < 2; hh++) {
                    const int J = 4 * Q + 2 * hh;
                    y[hh] = make_uint4(pack_bf(D[J][0], D[J][1]), pack_bf(D[J][2], D[J][3]), pack_bf(D[J + 1][0], D[J + 1][1]), pack_bf(D[J + 1][2], D[J + 1][3]));
                }
                if (!(Q & 1)) mbar_wait(bars + 8 * (B_F + (Q >> 1)));
                asm volatile("{\n\t.reg .pred p;\n\tsetp.eq.u32 p, %11, 0;\n\t"
                             "@p st.async.weak.shared::cluster.mbarrier::complete_tx::bytes.v4.b32 [%9], {%4,%5,%6,%7}, [%10];\n\t"
                             "@!p st.async.weak.shared::cluster.mbarrier::complete_tx::bytes.v4.b32 [%9], {%0,%1,%2,%3}, [%10];\n\t"
                             "@p st.shared.v4.b32 [%8], {%0,%1,%2,%3};\n\t@!p st.shared.v4.b32 [%8], {%4,%5,%6,%7};\n\t}"
                             :: "r"(y[0].x), "r"(y[0].y), "r"(y[0].z), "r"(y[0].w), "r"(y[1].x), "r"(y[1].y), "r"(y[1].z), "r"(y[1].w),
                                "r"(yo + y_off(Q)), "r"(yr + y_off(Q)), "r"(ybr + 8 * Q), "r"(h) : "memory");
                __syncwarp();
                if (lane == 0) mbar_arrive(bars + 8 * (B_Y + Q));
            };
            ship(0);
            const uint4 bA = lds128(sb + OFF_BAND + (g - t + 3) * 48), bB = lds128(sb + OFF_BAND + (g - t + 3) * 48 + 16);
            const uint2 bC = lds64(sb + OFF_BAND + (g - t + 3) * 48 + 32);
            uint2 QA[5][2], QB[8];
            const uint32_t tq = TB + 8 * (1 + g - 2 * t);
#pragma unroll
            for (int dd = 0; dd < 5; dd++) { QA[dd][0] = lds64(tq + T_A + 64 * (dd + 4)); QA[dd][1] = lds64(tq + T_A + 64 * (dd + 4) - 8); }
#pragma unroll
            for (int dd = 0; dd < 8; dd++) QB[dd] = lds64(tq + T_B + 64 * (dd + 8));
            const uint32_t u1 = UB + (mi & 1) * U_PL + (7 + r + (mi >> 1)) * 16;
            const uint32_t u2 = UB + ((mi & 1) ^ 1) * U_PL + (7 + r + (mi & 1) + 8 * (mi >> 1)) * 16;
            uint32_t n[4];
#pragma unroll
            for (int j = 0; j < 12; j++) {
                uint32_t m[4];
                ldsm4(u1 + j * 128, m[0], m[1], m[2], m[3]);
                if (!(j & 1)) ldsm4(u2 + j * 128, n[0], n[1], n[2], n[3]);
                const uint32_t n0 = n[2 * (j & 1)], n1 = n[2 * (j & 1) + 1];
                float wa[4], wb[4], wc[4], g1[4], g2[4];
                mma_bf_z(wa, bA.x, bA.y, bA.z, bA.w, m[0], m[1]);
                mma_bf_z(wb, bA.x, bA.y, bA.z, bA.w, n0, n1);
                mma_bf_z(wc, bA.x, bA.y, bA.z, bA.w, m[2], m[3]);
                if (j < 8) {
                    mma_bf_z(g1, bB.x, bB.y, bB.z, bB.w, m[0], m[1]);
                    mma_bf_z(g2, bB.x, bB.y, bB.z, bB.w, n0, n1);
                    mma_bf_k8(g1, bC.x, bC.y, m[2]);
                    mma_bf_k8(g2, bC.x, bC.y, m[3]);
                }
#pragma unroll
                for (int e = 0; e < 2; e++) {
                    const uint32_t q0 = pack_bf(wa[e], wa[e + 2]), q1 = pack_bf(wb[e], wb[e + 2]), q2 = q1 ^ p.zero, q3 = pack_bf(wc[e], wc[e + 2]);
#pragma unroll
                    for (int dd = 0; dd < 5; dd++)
                        if (j + 4 + dd < 16) mma_bf(D[j + 4 + dd], q0, q1, q2, q3, QA[dd][e].x, QA[dd][e].y);
                }
                if (j < 8) {
                    const uint32_t q0 = pack_bf(g1[0], g1[2]), q1 = pack_bf(g2[0], g2[2]), q2 = pack_bf(g1[1], g1[3]), q3 = pack_bf(g2[1], g2[3]);
#pragma unroll
                    for (int dd = 7 - j; dd >= 0; dd--) mma_bf(D[j + 8 + dd], q0, q1, q2, q3, QB[dd].x, QB[dd].y);
                }
                if ((j & 3) == 3) {
                    WSTAMP(4 + 2 * (j >> 2));
                    if (j == 11 && LATE2) ship(2);
                    if (j != 7 || !LATE2) ship((j >> 2) + 1);
                }
            }
        }
        const int warpu = __reduce_max_sync(0xffffffffu, warp);
        mix_rows<1, BULKM>(p, &tm_out, sb, sb + OFF_U + warpu * U_CH + (warpu & 1) * 64, PQ, 4, warpu, h, pr, lane);
        if (BULKM) asm volatile("cp.async.bulk.commit_group;\n\tcp.async.bulk.wait_group.read 0;" ::: "memory");
        WSTAMP(10);
        WDUMP();
    } else if ((pw & 12) == AUX_W0) {
        asm volatile("setmaxnreg.inc.sync.aligned.u32 136;");
        const int v = __reduce_max_sync(0xffffffffu, pw & 3);
        const int at = tid & 127;
        const int g = lane >> 2, t = lane & 3;
        unsigned tag;
        const bool gu = c < NGU_CTA;
        {
            uint4 xa[16];
            const uint32_t xb = sb + (v < 2 ? OFF_XSEL : OFF_RING + 2 * 8192) + v * 8192;
            const uint32_t gws = sb + (gu ? M_DPIN : OFF_RING + 2 * 8192);
            const uint32_t row = 16 * c + 4 * v + (g >> 1);
            const unsigned epoch = *(volatile unsigned*)&p.sc->epoch;
#pragma unroll
            for (int i = 0; i < 4; i++)
                asm volatile("cp.async.ca.shared.global [%0], [%1], 4;" :: "r"(sb + OFF_GP + 512 * i + (tid & 124) * 4 + (tid & 1) * 8 + (tid & 2) * 2),
                             "l"(p.wr + 256 * i + (tid & 127) * 2) : "memory");
            cp16(gws + (tid & 127) * 16, p.gatew + (tid & 127) * 8);
            if ((tid & 127) < 33) cp16(sb + OFF_BAND + (tid & 127) * 16, p.band + (tid & 127));
            asm volatile("barrier.cluster.arrive.relaxed.aligned;" ::: "memory");
            tag = __reduce_max_sync(0xffffffffu, (epoch + 1) & 0xffffu);
            if (gu) st_gpu32((uint32_t*)&p.sc->h[(tag + 1) & 1][32 * c] + at, 0);
            if (v == 0) sts32(sb + M_BMAP + lane * 4, 0);
            cp_wait_all();
            bar_sync(1, 128);
            uint2 w[16];
#pragma unroll
            for (int kb = 0; kb < 16; kb++) w[kb] = lds64(sb + OFF_GP + 128 * kb + 32 * (g & 2) + 16 * t + 8 * (g & 1));
            asm volatile("barrier.cluster.wait.acquire.aligned;" ::: "memory");
            mbar_wait(bars + 8 * (B_X + v));
            WSTAMP(10);
#pragma unroll
            for (int kb = 0; kb < 16; kb++) xa[kb] = lds128(xb + (g >> 1) * 2048 + 128 * kb + 16 * (lane & 7));
            float dr[4][4];
#pragma unroll
            for (int kb = 0; kb < 16; kb++) {
                if (kb < 4) mma_bf_z(dr[kb], xa[kb].x, xa[kb].y, xa[kb].z, xa[kb].w, w[kb].x, w[kb].y);
                else mma_bf(dr[kb & 3], xa[kb].x, xa[kb].y, xa[kb].z, xa[kb].w, w[kb].x, w[kb].y);
            }
            float rs = ((dr[0][0] + dr[0][3]) + (dr[1][0] + dr[1][3])) + ((dr[2][0] + dr[2][3]) + (dr[3][0] + dr[3][3]));
            if (lane == 0) mbar_arrive(bars + 8 * (B_XE + v) + (__float_as_uint(rs) & p.zero));
            rs += __shfl_xor_sync(0xffffffffu, rs, 5);
            const uint32_t rb = pack_bf(0.f, rs);
            if (!(lane & 7)) st_gpu32((uint32_t*)&p.sc->r[(row >> 2) * RS] + (row & 3), ((rb ^ (((int)rb >> 31) | 0x80000000u)) & 0xffff0000u) | tag);
            WSTAMP(1);
            {
                const int n = 3 + (lane >> 3) + 4 * (lane & 1);
                const uint32_t so = (n & 7) * S_PL + ((lane & 6) + (n >> 3)) * 32;
                const uint32_t src[2] = {sb + OFF_S + v * S_Q + s_addr(so, h), sb + OFF_S + v * S_Q + s_addr(so + 32, h)};
                const uint32_t dst = sb + OFF_U + g * U_CH + (8 + 32 * v + 16 * h + t) * 16;
                const uint32_t rdst = mapa(dst, h ^ 1), rbar = mapa(bars + 8 * B_U, h ^ 1);
                mbar_wait(bars + 8 * (B_S + v));
                WSTAMP(9);
                uint4 a[8];
#pragma unroll
                for (int b = 0; b < 2; b++) {
#pragma unroll
                    for (int j = 0; j < 8; j++) ldsm4t((b ? src[j & 1] : src[j & 1] ^ 16) + (j >> 1) * 256, a[j].x, a[j].y, a[j].z, a[j].w);
#pragma unroll
                    for (int j = 0; j < 8; j++) {
                        if (b) sts128(dst + (j >> 1) * 64 + (j & 1) * U_PL, a[j].x, a[j].y, a[j].z, a[j].w);
                        else st_async16(rdst + (j >> 1) * 64 + (j & 1) * U_PL, a[j], rbar);
                    }
                }
                if (h && v == 3) {
                    ldsm4t((src[0] ^ 16) + 1024, a[0].x, a[0].y, a[0].z, a[0].w);
                    ldsm4t(src[0] + 1024, a[1].x, a[1].y, a[1].z, a[1].w);
                    if (t == 0) {
                        st_async16(rdst + 256, make_uint4(a[0].x, a[0].y & 0xffffu, a[0].z & 0xffffu, a[0].w & 0xffffu), rbar);
                        sts128(dst + 256, a[1].x, a[1].y & 0xffffu, a[1].z & 0xffffu, a[1].w & 0xffffu);
                    }
                }
                __syncwarp();
                if (lane == 0) mbar_arrive(bars + 8 * B_U);
            }
            const uint32_t one0 = 0x3F803F80u ^ p.zero, one1 = 0x3F803F80u + p.zero;
#pragma unroll
            for (int kb = 0; kb < 16; kb++) {
                const uint4 gw = lds128(gws + 128 * kb + 16 * (lane & 7));
                const uint32_t a0 = hmul2_bf(xa[kb].x, gw.x), a1 = hmul2_bf(xa[kb].y, gw.y), a2 = hmul2_bf(xa[kb].z, gw.z), a3 = hmul2_bf(xa[kb].w, gw.w);
                if (kb < 4) mma_bf_z(dr[kb], a0, a1, a2, a3, one0, one1);
                else mma_bf(dr[kb & 3], a0, a1, a2, a3, one0, one1);
            }
            float sg = ((dr[0][0] + dr[0][3]) + (dr[1][0] + dr[1][3])) + ((dr[2][0] + dr[2][3]) + (dr[3][0] + dr[3][3]));
            sg += __shfl_xor_sync(0xffffffffu, sg, 4);
            if (!(lane & 7)) st_gpu32((uint32_t*)p.sc->g + ((row & 256) << 2) + gate_pos(row), (pack_bf(sigmoid_f(bf_round(sg)), 0.f) & 0xffffu) | (tag << 16));
            WSTAMP(2);
        }
        if (at == 32) { sts32(sb + M_TAG, tag << 16); mbar_arrive(bars + 8 * B_F); }
        {
            const bool lane0 = pin(lane, lane) == 0;
            const uint32_t own = pin(sb + OFF_XSEL + (at ^ ((at >> 1) & 4)) * 16, lane);
            float acc[8][4];
#pragma unroll
            for (int i = 0; i < 8; i++) { acc[i][0] = acc[i][1] = acc[i][2] = acc[i][3] = 0.f; }
            const int krow = ((lane >> 1) & 8) + (lane & 7);
            const uint32_t tile0 = pin(sb + OFF_RING + krow * 64 + ((((lane >> 3) & 1) ^ ((krow >> 1) & 3)) << 4), lane);
            const uint32_t xo = pin(sb + OFF_XSEL + (lane & 7) * XS_ROW + 512 * v + 2 * (lane & 24), lane);
            const uint32_t po = pin(sb + OFF_XSEL + t * XS_ROW + (g & 3) * 128 + (g & 1) * 64 + v * 16 + (lane >> 4) * 8, lane);
            const uint32_t po1 = pin(po + 64 - (g & 1) * 128, lane);
            uint32_t* hdst = pin((uint32_t*)&p.sc->h[tag & 1][32 * c] + at, lane);
            auto signal = [&](const int k, const uint32_t dep) {
                if (lane < 2 && v < 2)
                    asm volatile("st.async.weak.shared::cluster.mbarrier::complete_tx::bytes.b32 [%0], %1, [%2];"
                                 :: "r"(mapa(sb + M_SINK, lane)), "r"(dep), "r"(mapa(bars + 8 * (B_F + k), lane)) : "memory");
            };
#pragma unroll 1
            for (int i = 0; i < 4; i++) {
                const int s = 4 * i + v;
                uint32_t a[16][4], b[2][4];
                if (gu) {
                    const uint32_t tile = tile0 + (s < 14 ? s : v) * 8192;
                    if (lane0 && i > 1) mbar_arrive(bars + 8 * (B_E + s - 4));
                    if (i == 2) signal(0, 0);
                    mbar_wait(bars + 8 * (B_W + s));
#pragma unroll
                    for (int q = 0; q < 16; q++) ldsm4t((tile ^ ((q & 1) << 5)) + ((q >> 1) & 1) * 4096 + (q >> 2) * 1024, a[q][0], a[q][1], a[q][2], a[q][3]);
                }
                if (i == 0) {
                    if (gu) {
                        uint32_t dep = p.zero;
#pragma unroll
                        for (int q = 0; q < 16; q += 2) dep &= a[q][0] & a[q + 1][0];
                        if (lane == 0) mbar_arrive(bars + 8 * (B_E + v) + dep);
                    }
                    WSTAMP(11);
                    uint32_t top;
#pragma unroll 1
                    for (int it = 0; it < (1 << 22); it++) {
                        asm volatile("ld.relaxed.gpu.global.u32 %0, [%1];" : "=r"(top) : "l"(&p.sc->top[c % NTOP][g]) : "memory");
                        if (__all_sync(0xffffffffu, ((top ^ (tag << 11)) & 0xf800u) == 0)) break;
                        if (TSLEEP) __nanosleep(TSLEEP);
                    }
                    WSTAMP(3);
                    if (gu) {
                        const uint32_t k = 4 * h + v, row = __reduce_max_sync(0xffffffffu, lane == 4 * k ? ~top & 2047 : 0);
                        asm volatile("{\n\t.reg .pred p;\n\telect.sync _|p, 0xffffffff;\n\t"
                                     "@p cp.async.bulk.shared::cluster.global.mbarrier::complete_tx::bytes.multicast::cluster [%0], [%1], 2048, [%2], %3;\n\t}"
                            :: "r"(sb + OFF_XSEL + k * XS_ROW), "l"(p.u + (size_t)row * D_), "r"(bars + 8 * B_G), "h"((unsigned short)3) : "memory");
                    }
                    if (v == 0) {
                        const uint32_t row = ~top & 2047;
                        if (t == 0 && ((row >> 8) & 1) == h)
                            asm volatile("red.shared.or.b32 [%0], %1;" :: "r"(sb + M_BMAP + (row & 7) * 16 + (row >> 9) * 4), "r"(1u << (gate_pos(row) & 31)) : "memory");
                        if (t == 0) sts32(sb + M_TOP + lane, top);
                        if (c == 0 && lane == 0) *(volatile unsigned*)&p.sc->epoch = tag;
                        __syncwarp();
                        if (lane0) mbar_arrive(bars + 8 * B_Y);
                    }
                    if (!gu) break;
                    mbar_wait(bars + 8 * B_G);
                    WSTAMP(4);
                }
                ldsm4(xo + 128 * i, b[0][0], b[0][1], b[0][2], b[0][3]);
                ldsm4(xo + 128 * i + 64, b[1][0], b[1][1], b[1][2], b[1][3]);
#pragma unroll
                for (int q = 0; q < 16; q++) mma_bf(acc[q & 7], a[q][0], a[q][1], a[q][2], a[q][3], b[q >> 3][(q >> 1) & 2], b[q >> 3][((q >> 1) & 2) + 1]);
            }
            if (gu) {
                WSTAMP(5);
                __syncwarp();
#pragma unroll
                for (int q = 0; q < 4; q++) {
                    const int ct = q >> 1, e = 2 * (q & 1);
                    sts128(own + q * XS_ROW,
                           __float_as_uint(acc[ct][e] + acc[4 + ct][e]), __float_as_uint(acc[2 + ct][e] + acc[6 + ct][e]),
                           __float_as_uint(acc[ct][e + 1] + acc[4 + ct][e + 1]), __float_as_uint(acc[2 + ct][e + 1] + acc[6 + ct][e + 1]));
                }
                bar_sync(1, 128);
                float sl[2], uv[2];
#pragma unroll
                for (int e = 0; e < 2; e++) {
                    uint2 q[4];
#pragma unroll
                    for (int i = 0; i < 4; i++) q[i] = lds64((e ? po1 : po) + 512 * i);
                    const float s0 = (__uint_as_float(q[0].x) + __uint_as_float(q[1].x)) + (__uint_as_float(q[2].x) + __uint_as_float(q[3].x));
                    const float s1 = (__uint_as_float(q[0].y) + __uint_as_float(q[1].y)) + (__uint_as_float(q[2].y) + __uint_as_float(q[3].y));
                    const float gv = bf_round(p.gu_swap ? s1 : s0);
                    uv[e] = p.gu_swap ? s0 : s1;
                    sl[e] = gv * sigmoid_f(gv);
                }
                const uint32_t hw = hmul2_bf(pack_bf(sl[0], sl[1]), pack_bf(uv[0], uv[1]));
                st_gpu32(hdst, hw ? hw : 0x80000000u);
                signal(1, hw);
            }
        }
        WSTAMP(6);
        asm volatile("setmaxnreg.dec.sync.aligned.u32 104;");
        {
            const uint32_t own = pin(sb + OFF_XSEL + at * 16, lane);
            const uint32_t hb = sb + (v < 2 ? OFF_XSEL + 7168 * v : OFF_RING + 8192 * v), hl = pin(hb + 16 * lane, lane);
            const int krow = ((lane >> 1) & 8) + (lane & 7);
            const uint32_t tile = pin(sb + OFF_RING + v * 8192 + krow * 32 + ((((lane >> 3) ^ (krow >> 2)) & 1) << 4), lane);
            float dd[4][4];
            bar_sync(1, 128);
            mbar_wait(bars + 8 * (B_W + HW));
            WSTAMP(12);
#pragma unroll 1
            for (int it = 0; it < (1 << 16); it++) {
                bulk_load(hb, &p.sc->h[tag & 1][32 * (56 * h + 14 * v)], 7168, bars + 8 * (B_X + v));
                uint32_t a[14][4], mn = 0xffffffffu;
                mbar_wait(bars + 8 * (B_W + 16 + v));
#pragma unroll
                for (int j = 0; j < 14; j++) ldsm4t(tile + (v & 2) * 16384 + j * 512, a[j][0], a[j][1], a[j][2], a[j][3]);
                mbar_wait(bars + 8 * (B_W + 20 + v));
                mbar_wait(bars + 8 * (B_X + v), ~it & 1);
                WSTAMP(7);
#pragma unroll
                for (int j = 0; j < 14; j++) {
                    const uint4 q = lds128(hl + 512 * j);
                    mn = min(mn, q.x);
#pragma unroll
                    for (int e = 0; e < 2; e++) {
                        uint32_t(&f)[4] = a[(2 * j + e) % 14];
                        if (j >= 7) ldsm4t(tile + 65536 + (2 * j + e - 14) * 512, f[0], f[1], f[2], f[3]);
                        if (j < 2) mma_bf_z(dd[2 * j + e], f[0], f[1], f[2], f[3], e ? q.z : q.x, e ? q.w : q.y);
                        else mma_bf(dd[(2 * j + e) & 3], f[0], f[1], f[2], f[3], e ? q.z : q.x, e ? q.w : q.y);
                    }
                }
                if (__all_sync(0xffffffffu, mn != 0)) break;
            }
            WSTAMP(8);
            uint4 part;
            part.x = __float_as_uint((dd[0][0] + dd[1][0]) + (dd[2][0] + dd[3][0])); part.y = __float_as_uint((dd[0][1] + dd[1][1]) + (dd[2][1] + dd[3][1]));
            part.z = __float_as_uint((dd[0][2] + dd[1][2]) + (dd[2][2] + dd[3][2])); part.w = __float_as_uint((dd[0][3] + dd[1][3]) + (dd[2][3] + dd[3][3]));
            st_async16(mapa(own + (M_DPIN - OFF_XSEL), h ^ 1), part, mapa(bars + 8 * B_DP, h ^ 1));
            sts128(own + 14336, part.x, part.y, part.z, part.w);
            __syncwarp();
            if (lane == 0) mbar_arrive(bars + 8 * B_DP);
        }
        WDUMP();
    } else {
        asm volatile("setmaxnreg.dec.sync.aligned.u32 40;");
        const int v = __reduce_max_sync(0xffffffffu, pw - PREP_W0);
        const bool gu = c < NGU_CTA;
        const uint32_t t0 = clock();
        const uint32_t bu = bars + 8 * v;
        if (lane == 0) {
            mbar_init(bu + 8 * B_X, 1);
            asm volatile("fence.mbarrier_init.release.cluster;" ::: "memory");
        }
        __syncwarp();
        if (DELAY_X > 0) __nanosleep(DELAY_X);
        bulk_load(sb + (v < 2 ? OFF_XSEL : OFF_RING + 2 * 8192) + v * 8192, p.u + (size_t)(16 * c + 4 * v) * D_, 8192, bu + 8 * B_X);
        if (lane == 0) {
#pragma unroll
            for (int i = 0; i < 10; i++) mbar_init(bu + 32 * i, 1);
            mbar_init(bu + 8 * B_XE, 1);
            mbar_init(bu + 8 * B_Y, v == 0 ? 11 : 9);
            mbar_init(bu + 8 * B_DP, (0x1855 >> (4 * v)) & 15);
            mbar_init(bu + 8 * B_F, v == 0 ? 2 : 1);
            mbar_init(bu + 8 * B_H, 1);
            asm volatile("fence.mbarrier_init.release.cluster;" ::: "memory");
            mbar_expect(bu + 8 * B_Y, 4096);
            if (v != 2) mbar_expect(bu + 8 * B_DP, v == 0 ? 2048 : (h || v == 3) ? 16384 : 16384 + 128);
            mbar_expect(bu + 8 * B_F, c < NGU_CTA ? 16 : 0);
        }
        __syncwarp();
        asm volatile("barrier.cluster.arrive.relaxed.aligned;" ::: "memory");
        tma3d(sb + OFF_S + v * S_Q, &tm_x, 16 * pr, 64 * v + 32 * h - 1, bars + 8 * (B_S + v), S_Q);
        WSTAMP(9);
        if (v < 3 && lane == 0) asm volatile("prefetch.tensormap [%0];" :: "l"(v == 0 ? &tm_gu : v == 1 ? &tm_down : &tm_out) : "memory");
        asm volatile("barrier.cluster.wait.acquire.aligned;" ::: "memory");
        if (v > 0) mbar_wait(bars + 8 * (B_H + v));
        {
            const int gap = v == 0 ? GAP : v == 1 ? GAP1 : v == 2 ? GAP2 : GAP3;
            uint32_t last = v ? clock() - SLACK : t0 + T0 - GAP + STAG * ((pr * 5) & 15) / 16;
#pragma unroll 1
            for (int s = 6 * v; s < 6 * v + 6; s++) {
                const int i = s >> 2, w = s & 3, slot = s < 14 ? s : (s | 1) == 17 ? s - 16 : s - 12;
                if (s >= 4) mbar_wait(bars + 8 * ((gu && s >= 14) ? B_E + slot : s < 6 ? B_XE + s - 2 : B_KG));
                uint32_t now;
#pragma unroll 1
                while ((int)((now = clock()) - last) < gap) __nanosleep(CSLEEP);
                last = max((int)(now - last) - SLACK, gap) + last;
                WSTAMP(3 + s - 6 * v);
                if (gu || s >= 16) tma3d(sb + OFF_RING + slot * 8192, i < 4 ? &tm_gu : &tm_down, i < 4 ? 32 * c : 16 * pr,
                      i < 4 ? 256 * w + 64 * i : 1792 * h + 448 * w + 224 * (i - 4), bars + 8 * (B_W + s), i < 4 ? 8192 : 7168);
            }
            if (lane == 0) mbar_arrive(bars + 8 * (B_H + ((v + 1) & 3)));
        }
        if (v == 0) {
            mbar_wait(bars + 8 * B_U);
            mbar_wait(bars + 8 * B_F);
            if (!gu) mbar_wait(bars + 8 * (B_H + 3));
            const uint32_t tag16 = lds32(sb + M_TAG);
#pragma unroll 1
            for (int k = 0; k < 2; k++) {
                uint4 q[4];
#pragma unroll 1
                for (int it = 0; it < (1 << 22); it++) {
                    uint32_t bad = 0;
#pragma unroll
                    for (int i = 0; i < 4; i++) q[i] = ld_gpu128(&p.sc->g[256 * h + 128 * k + 32 * i + lane]);
#pragma unroll
                    for (int i = 0; i < 4; i++) bad |= ((q[i].x ^ tag16) | (q[i].y ^ tag16)) | ((q[i].z ^ tag16) | (q[i].w ^ tag16));
                    if ((bad >> 16) == 0) break;
                    __nanosleep(200);
                }
#pragma unroll
                for (int i = 0; i < 4; i++)
                    asm volatile("st.shared.v2.u32 [%0], {%1, %2};" :: "r"(sb + OFF_GP + 1024 * k + 256 * i + lane * 8),
                                 "r"(__byte_perm(q[i].x, q[i].y, 0x5410)), "r"(__byte_perm(q[i].z, q[i].w, 0x5410)) : "memory");
            }
            __syncwarp();
            if (lane == 0) mbar_arrive(bars + 8 * B_Y);
        }
        {
            asm volatile("setmaxnreg.inc.sync.aligned.u32 72;");
            WSTAMP(1);
            mix_rows<2, true>(p, &tm_out, sb, sb + OFF_TAB + v * TAB_W, 0, PQ, v, h, pr, lane);
            WSTAMP(2);
            asm volatile("cp.async.bulk.commit_group;" ::: "memory");
            const uint32_t top = lds32(sb + M_TOP + 8 * v + 4 * (lane >> 4));
            const uint32_t row = ~top & 2047, ch = lane & 15, gp = gate_pos(row);
            const bool mine = ((row >> 8) & 1) == h;
            uint32_t gfin, x16, y16 = 0;
            asm volatile("ld.shared.u16 %0, [%1];" : "=r"(gfin) : "r"(sb + OFF_GP + gp * 2) : "memory");
            asm volatile("ld.shared.u16 %0, [%1];" : "=r"(x16) : "r"(sb + OFF_S + (row >> 9) * S_Q + s_addr((row & 7) * S_PL + 32 + (row & 248) * 4, ch >> 3) + 2 * (ch & 7)) : "memory");
            const float rsel = __uint_as_float(pin(__float_as_uint(bf_round(sigmoid_f(__uint_as_float((top ^ (((int)~top >> 31) | 0x80000000u)) & 0xffff0000u)))), lane));
            const uint32_t po = pin(sb + (4 * (ch & 7) + v) * 16 + (ch >> 3) * 8 + (lane >> 4) * 4, lane);
            bf16* op = pin(p.out + (size_t)row * D_ + 16 * pr + ch, lane);
            if (mine) {
                mbar_wait(bars + 8 * (B_Y + (row >> 9)));
                asm volatile("ld.shared.u16 %0, [%1];" : "=r"(y16)
                             : "r"(sb + y_off(row >> 9) + ch * 512 + (((4 * (row & 7) + ((row >> 5) & 3)) ^ (((ch >> 2) << 1) | (ch & 1))) << 4) + 2 * row_elem(row)) : "memory");
            }
            mbar_wait(bars + 8 * B_DP);
            float q[8];
#pragma unroll
            for (int i = 0; i < 4; i++) { q[i] = ldsf(po + M_DPIN + 512 * i); q[4 + i] = ldsf(po + OFF_XSEL + 14336 + 512 * i); }
            const float tot = ((q[0] + q[1]) + (q[2] + q[3])) + ((q[4] + q[5]) + (q[6] + q[7]));
            const float b = bf_round(__uint_as_float(x16 << 16) + bf_round(bf_round(tot) * rsel));
            if (mine) *op = __float2bfloat16_rn(fmaf(bf_lo(gfin), __uint_as_float(y16 << 16), bf_round(bf_round(1.f - bf_lo(gfin)) * b)));
        }
        asm volatile("cp.async.bulk.wait_group.read 0;" ::: "memory");
        WSTAMP(10);
        WDUMP();
    }
}

typedef CUresult (*EncodeFn)(CUtensorMap*, CUtensorMapDataType, cuuint32_t, void*, const cuuint64_t*, const cuuint64_t*,
                             const cuuint32_t*, const cuuint32_t*, CUtensorMapInterleave, CUtensorMapSwizzle,
                             CUtensorMapL2promotion, CUtensorMapFloatOOBfill);

void make_map(EncodeFn f, CUtensorMap* m, const void* ptr, uint64_t cols, uint64_t rows, uint64_t pitch, uint32_t bc, uint32_t br, CUtensorMapSwizzle sw, int prom,
              uint32_t planes = 1, uint64_t plane_stride = 0, uint32_t box_planes = 0) {
    cuuint64_t dims[3] = {cols, rows, planes};
    cuuint64_t str[2] = {pitch, planes > 1 ? plane_stride : pitch * rows};
    cuuint32_t box[3] = {bc, br, box_planes ? box_planes : planes};
    cuuint32_t es[3] = {1, 1, 1};
    f(m, CU_TENSOR_MAP_DATA_TYPE_BFLOAT16, 3, (void*)ptr, dims, str, box, es, CU_TENSOR_MAP_INTERLEAVE_NONE, sw,
      (CUtensorMapL2promotion)prom, CU_TENSOR_MAP_FLOAT_OOB_FILL_NONE);
}

}

extern "C" void kernel_launch(void* const* d_in, const int* in_sizes, int n_in, void* d_out, int out_size) {
    static EncodeFn enc = nullptr;
    static void *sc = nullptr, *band = nullptr;
    if (!enc) {
        void* fn = nullptr;
        cudaDriverEntryPointQueryResult qr;
        cudaGetDriverEntryPoint("cuTensorMapEncodeTiled", &fn, cudaEnableDefault, &qr);
        enc = (EncodeFn)fn;
        cudaGetSymbolAddress(&sc, g_scratch);
        cudaGetSymbolAddress(&band, g_band);
        cudaFuncSetAttribute(fused_kernel, cudaFuncAttributeMaxDynamicSharedMemorySize, SMEM_BYTES);
    }
    CUtensorMap tg, td, tx, to;
    const char *wg = (const char*)d_in[9], *wu = (const char*)d_in[10];
    const bool swap = wu < wg;
    make_map(enc, &tg, swap ? wu : wg, F_, D_, F_ * 2, 32, 64, CU_TENSOR_MAP_SWIZZLE_64B, PROMG, 2, swap ? wg - wu : wu - wg);
    make_map(enc, &td, d_in[11], D_, F_, D_ * 2, 16, 224, CU_TENSOR_MAP_SWIZZLE_32B, PROMD);
    make_map(enc, &tx, d_in[0], D_, L_ / 8, D_ * 16, 16, 33, CU_TENSOR_MAP_SWIZZLE_32B, PROMX, 8, D_ * 2);
    make_map(enc, &to, d_out, D_, L_ / 8, D_ * 16, 16, 32, CU_TENSOR_MAP_SWIZZLE_NONE, 0, 8, D_ * 2, 1);
    Params p;
    p.u = (const bf16*)d_in[0]; p.logA = (const bf16*)d_in[1]; p.Aim = (const bf16*)d_in[2];
    p.Cre = (const bf16*)d_in[3]; p.Cim = (const bf16*)d_in[4]; p.logdt = (const bf16*)d_in[5];
    p.Dskip = (const bf16*)d_in[6]; p.wr = (const bf16*)d_in[8]; p.gatew = (const bf16*)d_in[12];
    p.out = (bf16*)d_out;
    p.sc = (Scratch*)sc; p.band = (const uint4*)band;
    p.gu_swap = swap;
    p.zero = 0;
    fused_kernel<<<NCTA, NTHREADS, SMEM_BYTES>>>(p, tg, td, tx, to);
}
```

```cpp
#include <cuda_runtime.h>
#include <cuda_bf16.h>
#include <cuda_fp16.h>
#include <cuda.h>
#include <stdint.h>

typedef __nv_bfloat16 bf16;

namespace {

constexpr int L_ = 2048, D_ = 1024, F_ = 3584;
constexpr int NCTA = 130;
constexpr int NTHREADS = 512;
#define AUXW 12
constexpr int MAIN_W0 = 0, AUX_W0 = AUXW, PREP_W0 = 20 - AUXW;
#define T0 3500
#define GAP 590
#define GAP1 530
#define GAP2 530
#define GAP3 550
#define STAG GAP
#define CSLEEP 50
#define SLACK 300
#define DELAY_X 150
#define TSLEEP 40
#define RS 2
#define BULKM false
#define PQ 3
#define PROMG 2
#define PROMD 1
#define PROMX 0
#define LATE2 0
#define HW 21
constexpr int NGU_CTA = 112;

constexpr int OFF_RING = 0;
constexpr int OFF_SCR  = 6 * 8192;
constexpr int S_PL     = 1056;
constexpr int S_Q      = 8 * S_PL;
constexpr int OFF_S    = 114688;
constexpr int OFF_GP   = OFF_S + 4 * S_Q;
constexpr int U_PL     = 2240;
constexpr int U_CH     = 4416;
constexpr int OFF_U    = 151552;
constexpr int TAB_W    = 3200;
constexpr int T_PL     = 544;
constexpr int T_A      = 2192 - 26 * 8;
constexpr int T_B      = 2568 - 59 * 8;
constexpr int OFF_TAB  = 186880;
constexpr int OFF_XSEL = 212480;
constexpr int XS_ROW   = 2064;
constexpr int OFF_BAND = 228992;
constexpr int OFF_MISC = 229536;
constexpr int M_BARS   = OFF_MISC;
constexpr int M_DSK    = OFF_MISC + 2736;
constexpr int M_SINK   = OFF_MISC + 512;
constexpr int M_TAG    = OFF_MISC + 516;
constexpr int M_BMAP   = OFF_MISC + 528;
constexpr int M_DPIN   = OFF_MISC + 656;
constexpr int M_TOP    = OFF_MISC + 2704;
constexpr int SMEM_BYTES = OFF_MISC + 2768;
__device__ __forceinline__ uint32_t s_addr(uint32_t o, uint32_t half) { return o + (((half ^ (o >> 7)) & 1) << 4); }
__host__ __device__ constexpr uint32_t y_off(uint32_t q) { return OFF_RING + 32768 + (q & 1) * 8192 + (q >> 1) * 65536; }

constexpr int B_W = 0;
constexpr int B_E = 24;
constexpr int B_S = 36;
constexpr int B_Y = 40;
constexpr int B_DP = 44, B_U = 45, B_KG = 46, B_G = 47;
constexpr int B_F = 48;
constexpr int B_H = 60;
constexpr int B_X = 52, B_XE = 56;

struct BandTab { uint32_t w[11][12]; };
constexpr BandTab make_band() {
    BandTab b{};
    for (int cls = 0; cls < 11; cls++)
        for (int wd = 0; wd < 10; wd++) {
            const int tau = cls + 2 - 8 * ((wd < 4 ? wd : wd - 4) >> 1);
            const int lo = (wd < 4) ? ((wd & 1) ? -2 : 3) : ((wd & 1) ? -4 : -11), wid = (wd < 4 ? 3 : 7) + 2 * (wd & 1);
            b.w[cls][wd] = ((tau >= lo && tau < lo + wid) ? 0x3F80u : 0u) | ((tau - 4 >= lo && tau - 4 < lo + wid) ? 0x3F800000u : 0u);
        }
    return b;
}
constexpr int NTOP = 32;
struct Scratch {
    uint4 r[L_ / 4 * RS];
    uint4 g[L_ / 4];
    uint4 h[2][8 * F_ / 8];
    uint32_t top[NTOP][32];
    unsigned epoch;
};
__device__ __align__(128) Scratch g_scratch;
__device__ const __align__(16) BandTab g_band = make_band();

struct Params {
    const bf16 *u, *logA, *Aim, *Cre, *Cim, *logdt, *Dskip, *wr, *gatew;
    bf16* out;
    Scratch* sc;
    const uint4* band;
    uint32_t gu_swap;
    uint32_t zero;
};

#define WSTAMP(i) do {} while (0)
#define KSTAMP(i, dep) do {} while (0)
#define WDUMP() do {} while (0)
#define RSTAMP(i) do {} while (0)

__device__ __forceinline__ uint32_t smem_u32(const void* p) { return (uint32_t)__cvta_generic_to_shared(p); }
__device__ __forceinline__ void mbar_init(uint32_t b, uint32_t c) { asm volatile("mbarrier.init.shared::cta.b64 [%0], %1;" :: "r"(b), "r"(c) : "memory"); }
__device__ __forceinline__ void mbar_expect(uint32_t b, uint32_t tx) { asm volatile("mbarrier.arrive.expect_tx.shared::cta.b64 _, [%0], %1;" :: "r"(b), "r"(tx) : "memory"); }
__device__ __forceinline__ void mbar_arrive(uint32_t b) { asm volatile("mbarrier.arrive.shared::cta.b64 _, [%0];" :: "r"(b) : "memory"); }
__device__ __forceinline__ void mbar_wait(uint32_t b, uint32_t parity = 0) {
    asm volatile("{\n\t.reg .pred p;\nW%=:\n\tmbarrier.try_wait.parity.shared::cta.b64 p, [%0], %1, 20000;\n\t@!p bra W%=;\n\t}" :: "r"(b), "r"(parity) : "memory");
}
__device__ __forceinline__ uint32_t mapa(uint32_t addr, uint32_t rank) { uint32_t r; asm("mapa.shared::cluster.u32 %0, %1, %2;" : "=r"(r) : "r"(addr), "r"(rank)); return r; }
__device__ __forceinline__ void tma3d(uint32_t dst, const CUtensorMap* tm, int c0, int c1, uint32_t bar, uint32_t bytes) {
    asm volatile("{\n\t.reg .pred p;\n\telect.sync _|p, 0xffffffff;\n\t"
                 "@p mbarrier.arrive.expect_tx.shared::cta.b64 _, [%2], %5;\n\t"
                 "@p cp.async.bulk.tensor.3d.shared::cluster.global.mbarrier::complete_tx::bytes [%0], [%1, {%3, %4, 0}], [%2];\n\t}"
        :: "r"(dst), "l"(tm), "r"(bar), "r"(c0), "r"(c1), "r"(bytes) : "memory");
}
__device__ __forceinline__ void bulk_load(uint32_t dst, const void* src, uint32_t bytes, uint32_t bar) {
    asm volatile("{\n\t.reg .pred p;\n\telect.sync _|p, 0xffffffff;\n\t"
                 "@p mbarrier.arrive.expect_tx.shared::cta.b64 _, [%2], %3;\n\t"
                 "@p cp.async.bulk.shared::cluster.global.mbarrier::complete_tx::bytes [%0], [%1], %3, [%2];\n\t}"
        :: "r"(dst), "l"(src), "r"(bar), "r"(bytes) : "memory");
}
__device__ __forceinline__ void st_async16(uint32_t dst, const uint4& v, uint32_t bar) {
    asm volatile("st.async.weak.shared::cluster.mbarrier::complete_tx::bytes.v4.b32 [%0], {%1,%2,%3,%4}, [%5];"
                 :: "r"(dst), "r"(v.x), "r"(v.y), "r"(v.z), "r"(v.w), "r"(bar) : "memory");
}
__device__ __forceinline__ void bar_sync(int id, int n) { asm volatile("bar.sync %0, %1;" :: "r"(id), "r"(n) : "memory"); }
__device__ __forceinline__ void cp16(uint32_t dst, const void* src) { asm volatile("cp.async.cg.shared.global [%0], [%1], 16;" :: "r"(dst), "l"(src) : "memory"); }
__device__ __forceinline__ void cp_wait_all() { asm volatile("cp.async.wait_all;" ::: "memory"); }
__device__ __forceinline__ uint4 ld_gpu128(const void* p) { uint4 v; asm volatile("ld.relaxed.gpu.global.v4.u32 {%0,%1,%2,%3}, [%4];" : "=r"(v.x), "=r"(v.y), "=r"(v.z), "=r"(v.w) : "l"(p) : "memory"); return v; }
__device__ __forceinline__ void st_gpu32(void* p, uint32_t v) { asm volatile("st.relaxed.gpu.global.u32 [%0], %1;" :: "l"(p), "r"(v) : "memory"); }

__device__ __forceinline__ void ldsm4(uint32_t a, uint32_t& r0, uint32_t& r1, uint32_t& r2, uint32_t& r3) {
    asm volatile("ldmatrix.sync.aligned.m8n8.x4.shared.b16 {%0,%1,%2,%3}, [%4];" : "=r"(r0), "=r"(r1), "=r"(r2), "=r"(r3) : "r"(a) : "memory");
}
__device__ __forceinline__ void ldsm4t(uint32_t a, uint32_t& r0, uint32_t& r1, uint32_t& r2, uint32_t& r3) {
    asm volatile("ldmatrix.sync.aligned.m8n8.x4.trans.shared.b16 {%0,%1,%2,%3}, [%4];" : "=r"(r0), "=r"(r1), "=r"(r2), "=r"(r3) : "r"(a) : "memory");
}
__device__ __forceinline__ uint32_t lds32(uint32_t a) { uint32_t v; asm volatile("ld.shared.u32 %0, [%1];" : "=r"(v) : "r"(a) : "memory"); return v; }
__device__ __forceinline__ uint2 lds64(uint32_t a) { uint2 v; asm volatile("ld.shared.v2.u32 {%0,%1}, [%2];" : "=r"(v.x), "=r"(v.y) : "r"(a) : "memory"); return v; }
__device__ __forceinline__ uint4 lds128(uint32_t a) { uint4 v; asm volatile("ld.shared.v4.u32 {%0,%1,%2,%3}, [%4];" : "=r"(v.x), "=r"(v.y), "=r"(v.z), "=r"(v.w) : "r"(a) : "memory"); return v; }
__device__ __forceinline__ void sts32(uint32_t a, uint32_t v) { asm volatile("st.shared.u32 [%0], %1;" :: "r"(a), "r"(v) : "memory"); }
__device__ __forceinline__ void sts16(uint32_t a, uint32_t v) { asm volatile("st.shared.u16 [%0], %1;" :: "r"(a), "h"((unsigned short)v) : "memory"); }
__device__ __forceinline__ void sts128(uint32_t a, uint32_t x, uint32_t y, uint32_t z, uint32_t w) { asm volatile("st.shared.v4.u32 [%0], {%1,%2,%3,%4};" :: "r"(a), "r"(x), "r"(y), "r"(z), "r"(w) : "memory"); }
__device__ __forceinline__ float ldsf(uint32_t a) { float v; asm volatile("ld.shared.f32 %0, [%1];" : "=f"(v) : "r"(a) : "memory"); return v; }

__device__ __forceinline__ void mma_bf(float (&d)[4], uint32_t a0, uint32_t a1, uint32_t a2, uint32_t a3, uint32_t b0, uint32_t b1) {
    asm volatile("mma.sync.aligned.m16n8k16.row.col.f32.bf16.bf16.f32 {%0,%1,%2,%3}, {%4,%5,%6,%7}, {%8,%9}, {%0,%1,%2,%3};"
        : "+f"(d[0]), "+f"(d[1]), "+f"(d[2]), "+f"(d[3]) : "r"(a0), "r"(a1), "r"(a2), "r"(a3), "r"(b0), "r"(b1));
}
__device__ __forceinline__ void mma_bf_z(float (&d)[4], uint32_t a0, uint32_t a1, uint32_t a2, uint32_t a3, uint32_t b0, uint32_t b1) {
    asm volatile("mma.sync.aligned.m16n8k16.row.col.f32.bf16.bf16.f32 {%0,%1,%2,%3}, {%4,%5,%6,%7}, {%8,%9}, {%10,%10,%10,%10};"
        : "=f"(d[0]), "=f"(d[1]), "=f"(d[2]), "=f"(d[3]) : "r"(a0), "r"(a1), "r"(a2), "r"(a3), "r"(b0), "r"(b1), "f"(0.f));
}
__device__ __forceinline__ void mma_bf_k8(float (&d)[4], uint32_t a0, uint32_t a1, uint32_t b0) {
    asm volatile("mma.sync.aligned.m16n8k8.row.col.f32.bf16.bf16.f32 {%0,%1,%2,%3}, {%4,%5}, {%6}, {%0,%1,%2,%3};"
        : "+f"(d[0]), "+f"(d[1]), "+f"(d[2]), "+f"(d[3]) : "r"(a0), "r"(a1), "r"(b0));
}
__device__ __forceinline__ void mma_h(float (&d)[4], uint32_t a0, uint32_t a1, uint32_t a2, uint32_t a3, uint32_t b0, uint32_t b1) {
    asm volatile("mma.sync.aligned.m16n8k16.row.col.f32.f16.f16.f32 {%0,%1,%2,%3}, {%4,%5,%6,%7}, {%8,%9}, {%0,%1,%2,%3};"
        : "+f"(d[0]), "+f"(d[1]), "+f"(d[2]), "+f"(d[3]) : "r"(a0), "r"(a1), "r"(a2), "r"(a3), "r"(b0), "r"(b1));
}
__device__ __forceinline__ uint32_t pack_bf(float lo, float hi) { uint32_t r; asm("cvt.rn.bf16x2.f32 %0, %1, %2;" : "=r"(r) : "f"(hi), "f"(lo)); return r; }
__device__ __forceinline__ uint32_t pack_h(float lo, float hi) { uint32_t r; asm("cvt.rn.f16x2.f32 %0, %1, %2;" : "=r"(r) : "f"(hi), "f"(lo)); return r; }
__device__ __forceinline__ float bf_lo(uint32_t v) { return __uint_as_float(v << 16); }
__device__ __forceinline__ float bf_hi(uint32_t v) { return __uint_as_float(v & 0xffff0000u); }
__device__ __forceinline__ float bf_round(float x) { return __uint_as_float(pack_bf(0.f, x)); }
__device__ __forceinline__ uint32_t hmul2_bf(uint32_t a, uint32_t b) { uint32_t r; asm("mul.rn.bf16x2 %0, %1, %2;" : "=r"(r) : "r"(a), "r"(b)); return r; }
__device__ __forceinline__ float ex2f(float x) { float r; asm("ex2.approx.ftz.f32 %0, %1;" : "=f"(r) : "f"(x)); return r; }

__device__ __forceinline__ float exp_acc(float x) {
    const float t = x * 1.4426950216293335f;
    const float r = fmaf(x, 1.4426950216293335f, -t) + x * 1.9259629911266175e-8f;
    return ex2f(t) * fmaf(r, 0.6931471805599453f, 1.f);
}
__device__ __forceinline__ float sigmoid_f(float x) { return __fdividef(1.f, 1.f + ex2f(-x * 1.4426950408889634f)); }
__device__ __forceinline__ void cexp_pow(float l2, float li, float e, float& zr, float& zi) {
    const float mag = ex2f(l2 * e);
    zr = mag * __cosf(li * e);
    zi = mag * __sinf(li * e);
}
__device__ __forceinline__ uint32_t hcmul(uint32_t a, uint32_t k, uint32_t kp) {
    const __half2 A = *reinterpret_cast<const __half2*>(&a);
    const __half2 r = __hfma2(__high2half2(A), *reinterpret_cast<const __half2*>(&kp), __hmul2(__low2half2(A), *reinterpret_cast<const __half2*>(&k)));
    return *reinterpret_cast<const uint32_t*>(&r);
}
#define CMUL(orr, oi, ar, ai, br, bi) do { float _r = (ar) * (br) - (ai) * (bi); float _i = (ar) * (bi) + (ai) * (br); orr = _r; oi = _i; } while (0)
#define CSQ(orr, oi, ar, ai) do { float _r = (ar) * (ar) - (ai) * (ai); float _i = 2.f * (ar) * (ai); orr = _r; oi = _i; } while (0)

__device__ __forceinline__ void mma_bf_k8z(float (&d)[4], uint32_t a0, uint32_t a1, uint32_t b0) {
    asm volatile("mma.sync.aligned.m16n8k8.row.col.f32.bf16.bf16.f32 {%0,%1,%2,%3}, {%4,%5}, {%6}, {%7,%7,%7,%7};"
        : "=f"(d[0]), "=f"(d[1]), "=f"(d[2]), "=f"(d[3]) : "r"(a0), "r"(a1), "r"(b0), "f"(0.f));
}
__device__ __forceinline__ void mma_hh_k8(uint32_t& d0, uint32_t& d1, uint32_t a0, uint32_t a1, uint32_t b0) {
    asm volatile("mma.sync.aligned.m16n8k8.row.col.f16.f16.f16.f16 {%0,%1}, {%2,%3}, {%4}, {%5,%5};"
        : "=r"(d0), "=r"(d1) : "r"(a0), "r"(a1), "r"(b0), "r"(0));
}
__device__ __forceinline__ uint32_t pin(uint32_t x, int lane) { return __shfl_sync(0xffffffffu, x, lane); }
template <class T> __device__ __forceinline__ T* pin(T* x, int lane) { return (T*)__shfl_sync(0xffffffffu, (unsigned long long)x, lane); }
__device__ __forceinline__ void sts32_if(bool on, uint32_t a, uint32_t v) {
    asm volatile("{\n\t.reg .pred p;\n\tsetp.ne.u32 p, %2, 0;\n\t@p st.shared.u32 [%0], %1;\n\t}" :: "r"(a), "r"(v), "r"((uint32_t)on) : "memory");
}
__device__ __forceinline__ void sts128_if(bool on, uint32_t a, uint32_t x, uint32_t y, uint32_t z, uint32_t w) {
    asm volatile("{\n\t.reg .pred p;\n\tsetp.ne.u32 p, %5, 0;\n\t@p st.shared.v4.u32 [%0], {%1,%2,%3,%4};\n\t}" :: "r"(a), "r"(x), "r"(y), "r"(z), "r"(w), "r"((uint32_t)on) : "memory");
}
__device__ __forceinline__ void lds128_if(bool on, uint32_t a, uint32_t (&v)[4]) {
    asm volatile("{\n\t.reg .pred p;\n\tsetp.ne.u32 p, %5, 0;\n\t@p ld.shared.v4.u32 {%0,%1,%2,%3}, [%4];\n\t}"
        : "+r"(v[0]), "+r"(v[1]), "+r"(v[2]), "+r"(v[3]) : "r"(a), "r"((uint32_t)on) : "memory");
}
__device__ __forceinline__ uint32_t hfma2_bf(uint32_t a, uint32_t b, uint32_t c) { uint32_t r; asm("fma.rn.bf16x2 %0, %1, %2, %3;" : "=r"(r) : "r"(a), "r"(b), "r"(c)); return r; }
__device__ __forceinline__ uint32_t row_elem(uint32_t row) { return ((row >> 5) & 4) | ((row >> 2) & 2) | ((row >> 4) & 1); }
__device__ __forceinline__ uint32_t gate_pos(uint32_t row) { return ((row >> 9) << 8) | ((row & 7) << 5) | (row_elem(row) << 2) | ((row >> 5) & 3); }

template <int N, bool BULK>
__device__ __forceinline__ void mix_rows(const Params& p, const CUtensorMap* tm_out, uint32_t sb, uint32_t ob, int Q0, int Q1, int w, int h, int pr, int lane) {
    const int g = lane >> 2, t = lane & 3, mi = lane >> 3, r = lane & 7;
    const int m8 = 16 * (g >> 2) + ((g >> 1) & 1) + 2 * (g & 1);
    uint32_t yi = sb + (4 * (r >> 1) + 2 * (mi & 1) + (r & 1)) * 512 + (((4 * w + (mi >> 1)) ^ r) << 4);
    uint32_t xs = sb + OFF_S + s_addr(w * S_PL + 32 + m8 * 32, t >> 1) + ((t & 1) << 3);
    uint32_t gs = sb + OFF_GP + w * 64 + g * 8, os = ob + m8 * 32 + t * 8;
    if (N > 1) { yi = pin(yi, lane); xs = pin(xs, lane); gs = pin(gs, lane); os = pin(os, lane); }
    mbar_wait(sb + M_BARS + 8 * B_Y);
#pragma unroll 1
    for (int Q = Q0; Q < Q1; Q++) {
        uint2 xq[N][4];
        uint32_t gg[N][4], sw[N];
#pragma unroll
        for (int n = 0; n < N; n++) {
#pragma unroll
            for (int i = 0; i < 4; i++) xq[n][i] = lds64((xs ^ (((i ^ n) & 1) << 4)) + Q * S_Q + n * 4 * S_PL + i * 128);
            const uint2 gq = lds64(gs + Q * 512 + n * 256);
            sw[n] = lds32(sb + M_BMAP + w * 16 + n * 64 + Q * 4);
#pragma unroll
            for (int i = 0; i < 4; i++) {
                gg[n][i] = __byte_perm(i < 2 ? gq.x : gq.y, 0, (i & 1) ? 0x3232 : 0x1010);
                const uint32_t og = hfma2_bf(gg[n][i], 0xBF80BF80u, 0x3F803F80u);
                xq[n][i].x = hmul2_bf(og, xq[n][i].x); xq[n][i].y = hmul2_bf(og, xq[n][i].y);
            }
        }
        mbar_wait(sb + M_BARS + 8 * (B_Y + Q));
        __syncwarp();
#pragma unroll
        for (int n = 0; n < N; n++) {
#pragma unroll
            for (int x = 0; x < 2; x++) {
                uint32_t y[4];
                ldsm4t((yi ^ (x << 5)) + y_off(Q) + n * 256, y[0], y[1], y[2], y[3]);
#pragma unroll
                for (int e = 0; e < 2; e++) {
                    uint2& o = xq[n][2 * x + e];
                    o.x = hfma2_bf(gg[n][2 * x + e], y[2 * e], o.x); o.y = hfma2_bf(gg[n][2 * x + e], y[2 * e + 1], o.y);
                }
            }
        }
        if (BULK && (sw[0] | sw[N - 1]) == 0) {
#pragma unroll
            for (int n = 0; n < N; n++)
#pragma unroll
                for (int i = 0; i < 4; i++)
                    asm volatile("st.shared.v2.u32 [%0], {%1, %2};" :: "r"(os + Q * 1024 + n * 4 * TAB_W + i * 128), "r"(xq[n][i].x), "r"(xq[n][i].y) : "memory");
            asm volatile("fence.proxy.async.shared::cta;" ::: "memory");
            __syncwarp();
#pragma unroll
            for (int n = 0; n < N; n++)
                asm volatile("{\n\t.reg .pred p;\n\telect.sync _|p, 0xffffffff;\n\t"
                             "@p cp.async.bulk.tensor.3d.global.shared::cta.bulk_group [%1, {%2, %3, %4}], [%0];\n\t}"
                    :: "r"(ob + 4 * n * TAB_W + Q * 1024), "l"(tm_out), "r"(16 * pr), "r"(64 * Q + 32 * h), "r"(w + 4 * n) : "memory");
        } else {
            bf16* op = p.out + (size_t)(512 * Q + 256 * h + 8 * m8 + w) * D_ + 16 * pr + 4 * t;
#pragma unroll
            for (int n = 0; n < N; n++)
#pragma unroll
                for (int i = 0; i < 4; i++)
                    if (!((sw[n] >> (4 * g)) & (1u << i))) *(uint2*)(op + (size_t)(32 * i + 4 * n) * D_) = xq[n][i];
        }
    }
}

__global__ void __cluster_dims__(2, 1, 1) __launch_bounds__(NTHREADS, 1)
fused_kernel(const Params p, const __grid_constant__ CUtensorMap tm_gu, const __grid_constant__ CUtensorMap tm_down,
             const __grid_constant__ CUtensorMap tm_x, const __grid_constant__ CUtensorMap tm_out) {
    extern __shared__ __align__(1024) unsigned char smem[];
    const uint32_t sb = smem_u32(smem);
    int tid;
    asm volatile("mov.u32 %0, %%tid.x;" : "=r"(tid));
    const int pw = tid >> 5, lane = tid & 31;
    const int c = blockIdx.x, h = c & 1, pr = c >> 1;
    const uint32_t bars = sb + M_BARS;

    uint2 v_la, v_ai, v_cr, v_ci;
    uint32_t ldt16;
    {
        const uint32_t po = c * 256 + tid;
        asm volatile("{\n\t.reg .pred p;\n\t.reg .b64 a;\n\tsetp.ne.u32 p, %16, 0;\n\t"
                     "mad.wide.u32 a, %14, 8, %9;\n\t@p ld.global.nc.L1::no_allocate.v2.u32 {%0,%1}, [a];\n\t"
                     "mad.wide.u32 a, %15, 2, %13;\n\t@p ld.global.nc.u16 %8, [a];\n\t"
                     "mad.wide.u32 a, %14, 8, %10;\n\t@p ld.global.nc.L1::no_allocate.v2.u32 {%2,%3}, [a];\n\t"
                     "mad.wide.u32 a, %14, 8, %11;\n\t@p ld.global.nc.L1::no_allocate.v2.u32 {%4,%5}, [a];\n\t"
                     "mad.wide.u32 a, %14, 8, %12;\n\t@p ld.global.nc.L1::no_allocate.v2.u32 {%6,%7}, [a];\n\t}"
            : "=r"(v_la.x), "=r"(v_la.y), "=r"(v_ai.x), "=r"(v_ai.y), "=r"(v_cr.x), "=r"(v_cr.y), "=r"(v_ci.x), "=r"(v_ci.y), "=r"(ldt16)
            : "l"(p.logA), "l"(p.Aim), "l"(p.Cre), "l"(p.Cim), "l"(p.logdt), "r"(po), "r"(po >> 5), "r"((uint32_t)(tid < 256 && c < 128)));
    }

    if (c >= 128) {
        if (c != 128) return;
        RSTAMP(5);
        const unsigned tag = (*(volatile unsigned*)&p.sc->epoch + 1) & 0xffffu;
        const uint32_t list = sb + 128;
#pragma unroll 1
        for (int pass = 0; pass < 2; pass++) {
            sts128(list + 16 * tid, 0, 0, 0, 0);
            if (tid == 0) sts32(sb + 64, 0);
            uint32_t key[4];
            bool ok = false;
#pragma unroll 1
            for (int it = 0; it < (1 << 22); it++) {
                const uint4 a = ld_gpu128(&p.sc->r[tid * RS]);
                key[0] = a.x; key[1] = a.y; key[2] = a.z; key[3] = a.w;
                ok = (((a.x ^ tag) | (a.y ^ tag) | (a.z ^ tag) | (a.w ^ tag)) & 0xffffu) == 0;
                if (ok || !pass) break;
            }
            WSTAMP(0);
            uint32_t m = 0;
#pragma unroll
            for (int i = 0; i < 4; i++) {
                key[i] = ((pass ? key[i] : (lane + i) << 16) & 0xffff0000u) | (uint32_t)(2047 - (4 * tid + i));
                m = max(m, key[i]);
            }
            const uint32_t wm = __reduce_max_sync(0xffffffffu, m);
            if (lane == 0) sts32(sb + pw * 4, wm);
            __syncthreads();
            uint32_t thr = 0xffffffffu;
#pragma unroll
            for (int i = 0; i < 4; i++) { const uint4 q = lds128(sb + 16 * i); thr = min(thr, min(max(q.x, q.y), max(q.z, q.w))); }
            if (thr != 1) WSTAMP(1);
            if (m >= thr) {
                uint32_t pos;
                asm volatile("atom.shared.add.u32 %0, [%1], %2;" : "=r"(pos) : "r"(sb + 64), "r"(4 * ((key[0] >= thr) + (key[1] >= thr) + (key[2] >= thr) + (key[3] >= thr))) : "memory");
#pragma unroll
                for (int i = 0; i < 4; i++) if (key[i] >= thr) { sts32(list + pos, key[i]); pos += 4; }
            }
            __syncthreads();
            const uint32_t nc4 = lds32(sb + 64);
            if (nc4 != 1) WSTAMP(2);
#pragma unroll 1
            for (uint32_t j = 4 * pw; j < nc4; j += 64) {
                const uint32_t mine = lds32(list + j);
                int rank = 0;
#pragma unroll 1
                for (uint32_t i = 0; i < nc4; i += 128) rank += __popc(__ballot_sync(0xffffffffu, lds32(list + i + 4 * lane) > mine));
                if (rank < 8 && lane == 0) sts32(sb + 96 + 4 * rank, mine);
            }
            __syncthreads();
            if (tid < 8 * NTOP) st_gpu32(&p.sc->top[tid >> 3][tid & 7], lds32(sb + 96 + 4 * (tid & 7)) | (((tag + pass - 1) & 31) << 11));
            WSTAMP(3);
            if (!pass) RSTAMP(4);
        }
        WDUMP();
        return;
    }

    WSTAMP(0);
    if (pw < 8) {
        const int d = 8 * c + pw - MAIN_W0;
        if (lane == 0) asm volatile("cp.async.ca.shared.global [%0], [%1], 4;" :: "r"(sb + M_DSK + 4 * (pw - MAIN_W0)), "l"(p.Dskip + (d & ~1)) : "memory");
        asm volatile("barrier.cluster.arrive.relaxed.aligned;" ::: "memory");
        const int warp = pw - MAIN_W0;
        asm volatile("setmaxnreg.inc.sync.aligned.u32 168;");
        const int g = lane >> 2, t = lane & 3;
        const int mi = lane >> 3, r = lane & 7;
        const uint32_t TB = sb + OFF_TAB + warp * TAB_W;
        const uint32_t UB = sb + OFF_U + warp * U_CH;
        if (mi < 2) sts128(UB + mi * U_PL + r * 16, 0, 0, 0, 0);
        if (lane < 4) sts128(TB + lane * T_PL, 0, 0, 0, 0);
        sts128(sb + OFF_SCR + warp * 8192 + lane * 16, 0x3C00u, 0x3C00u, 0x3C00u, 0x3C00u);
        __syncwarp();

        uint32_t cfix;
        {
            KSTAMP(4, v_la.x ^ v_ai.x ^ v_cr.x ^ v_ci.x ^ ldt16);
            const float dt = bf_round(exp_acc(__uint_as_float(ldt16 << 16)));
            float l2[4], li[4];
            {
                const uint32_t la[2] = {v_la.x, v_la.y}, ai[2] = {v_ai.x, v_ai.y};
                const float dt2 = -1.4426950408889634f * dt;
#pragma unroll
                for (int i = 0; i < 4; i++) {
                    l2[i] = bf_round(ex2f(((i & 1) ? bf_hi(la[i >> 1]) : bf_lo(la[i >> 1])) * 1.4426950408889634f)) * dt2;
                    li[i] = ((i & 1) ? bf_hi(ai[i >> 1]) : bf_lo(ai[i >> 1])) * dt;
                }
            }
            const uint32_t SX = sb + OFF_SCR + warp * 8192;
            const uint32_t sw = SX + (lane << 4);
#define PUT(buf, row, v) sts128(((sw + (row) * 512) ^ ((row) << 4)) + (buf) * 4096, v[0], v[1], v[2], v[3])
#define EMIT(bufa, rowa, bufb, rowb, xr, xi, k, kp) do { uint32_t pk[4], pd[4]; \
                _Pragma("unroll") for (int i = 0; i < 4; i++) { pk[i] = pack_h(xr[i], xi[i]); pd[i] = hcmul(pk[i], k[i], kp[i]); } \
                PUT(bufa, rowa, pk); PUT(bufb, rowb, pd); } while (0)
#define CMUL4(orr, oi, ar, ai, br, bi) _Pragma("unroll") for (int i = 0; i < 4; i++) CMUL(orr[i], oi[i], ar[i], ai[i], br[i], bi[i])
#define CSQ4(orr, oi, ar, ai) _Pragma("unroll") for (int i = 0; i < 4; i++) CSQ(orr[i], oi[i], ar[i], ai[i])
            float z1r[4], z1i[4], z2r[4], z2i[4], z8r[4], z8i[4], z256r[4], z256i[4];
            uint32_t k4[4], k4p[4];
            float z4r[4], z4i[4];
#pragma unroll
            for (int i = 0; i < 4; i++) cexp_pow(l2[i], li[i], 1.f, z1r[i], z1i[i]);
            CSQ4(z2r, z2i, z1r, z1i);
            CSQ4(z4r, z4i, z2r, z2i);
            CSQ4(z8r, z8i, z4r, z4i);
            KSTAMP(5, __float_as_uint(z8r[3]));
            uint32_t Ya[16][4];
            float cr[4], ci[4], inv;
            {
                float w1r[4], w1i[4], ar[4], ai[4], br[4], bi[4];
                uint32_t k8[4], k8p[4];
#pragma unroll
                for (int i = 0; i < 4; i++) {
                    k8[i] = pack_h(z8r[i], -z8i[i]); k8p[i] = pack_h(z8i[i], z8r[i]);
                    CSQ(w1r[i], w1i[i], z8r[i], z8i[i]); w1i[i] = -w1i[i];
                }
                PUT(1, 0, k8);
                EMIT(0, 1, 1, 1, w1r, w1i, k8, k8p);
                CSQ4(ar, ai, w1r, w1i);            EMIT(0, 2, 1, 2, ar, ai, k8, k8p);
                CMUL4(br, bi, ar, ai, w1r, w1i);   EMIT(0, 3, 1, 3, br, bi, k8, k8p);
                CSQ4(ar, ai, ar, ai);              EMIT(0, 4, 1, 4, ar, ai, k8, k8p);
                CMUL4(ar, ai, ar, ai, w1r, w1i);   EMIT(0, 5, 1, 5, ar, ai, k8, k8p);
                CSQ4(br, bi, br, bi);              EMIT(0, 6, 1, 6, br, bi, k8, k8p);
                CMUL4(br, bi, br, bi, w1r, w1i);   EMIT(0, 7, 1, 7, br, bi, k8, k8p);
                __syncwarp();
                KSTAMP(6, 0);
                const uint32_t ab = SX + (mi & 1) * 4096 + r * 512, ax = ((mi >> 1) ^ r) << 4;
                const uint32_t vr[2] = {v_cr.x, v_cr.y}, vi[2] = {v_ci.x, v_ci.y};
                const uint32_t m2 = __vmaxu2(__vmaxu2(vr[0] & 0x7fff7fffu, vr[1] & 0x7fff7fffu), __vmaxu2(vi[0] & 0x7fff7fffu, vi[1] & 0x7fff7fffu));
                const uint32_t mx = __reduce_max_sync(0xffffffffu, max(m2, m2 << 16));
                const uint32_t e = min(max(mx >> 23, 11u), 254u);
                const float sc = __uint_as_float((264u - e) << 23);
                inv = __uint_as_float((e - 10u) << 23) * (2.f * dt);
#pragma unroll
                for (int i = 0; i < 4; i++) {
#pragma unroll
                    for (int k = 0; k < 4; k++) ldsm4(ab + (ax ^ (i << 5)) + k * 128, Ya[4 * k + i][0], Ya[4 * k + i][1], Ya[4 * k + i][2], Ya[4 * k + i][3]);
                    float tr, ti;
                    cexp_pow(l2[i], li[i], 128.f, tr, ti);
                    sts32(TB + 2176 + 256 * i + 4 * lane, pack_h(tr, ti));
                    sts32(TB + 2176 + 256 * i + 128 + 4 * (lane ^ 16), pack_h(-ti, tr));
                    k4[i] = pack_h(z4r[i], z4i[i]); k4p[i] = pack_h(-z4i[i], z4r[i]);
                    CSQ(z256r[i], z256i[i], tr, ti);
                    cr[i] = ((i & 1) ? bf_hi(vr[i >> 1]) : bf_lo(vr[i >> 1])) * sc;
                    ci[i] = ((i & 1) ? bf_hi(vi[i >> 1]) : bf_lo(vi[i >> 1])) * sc;
                }
                __syncwarp();
            }
            KSTAMP(7, Ya[15][0]);
            const uint32_t ld0 = SX + r * 512 + ((mi ^ r) << 4), ld1 = ld0 ^ 64;
            float R[6][4], s1024;
            {
                float xr[4], xi[4], yr[4], yi[4];
                EMIT(0, 0, 0, 1, cr, ci, k4, k4p);
                CMUL4(yr, yi, cr, ci, z1r, z1i);        EMIT(0, 2, 0, 3, yr, yi, k4, k4p);
                CMUL4(xr, xi, cr, ci, z256r, z256i);    EMIT(1, 0, 1, 1, xr, xi, k4, k4p);
                CMUL4(yr, yi, yr, yi, z1r, z1i);        EMIT(0, 4, 0, 5, yr, yi, k4, k4p);
                CMUL4(cr, ci, xr, xi, z2r, z2i);        EMIT(1, 2, 1, 3, cr, ci, k4, k4p);
                CMUL4(yr, yi, yr, yi, z1r, z1i);        EMIT(0, 6, 0, 7, yr, yi, k4, k4p);
                CMUL4(xr, xi, xr, xi, z256r, z256i);    EMIT(1, 4, 1, 5, xr, xi, k4, k4p);
                CMUL4(xr, xi, xr, xi, z256r, z256i);    EMIT(1, 6, 1, 7, xr, xi, k4, k4p);
                CMUL4(xr, xi, xr, xi, z256r, z256i);
                s1024 = (xr[0] + xr[1]) + (xr[2] + xr[3]);
#pragma unroll
                for (int m = 0; m < 4; m++) {
                    if (m == 0) { CMUL4(xr, xi, xr, xi, z8r, z8i); } else { CMUL4(xr, xi, xr, xi, z256r, z256i); }
                    sts128(TB + m * T_PL + 16 + 16 * lane, pack_h(xr[0], xi[0]), pack_h(xr[1], xi[1]), pack_h(xr[2], xi[2]), pack_h(xr[3], xi[3]));
                }
            }
            asm volatile("barrier.cluster.wait.acquire.aligned;" ::: "memory");
            __syncwarp();
            {
                KSTAMP(8, 0);
                uint32_t bd[2][4] = {{0, 0, 0, 0}, {0, 0, 0, 0}};
                const bool on = (g >> 1) == t;
#pragma unroll
                for (int i = 0; i < 6; i++) { R[i][0] = R[i][1] = R[i][2] = R[i][3] = 0.f; }
#pragma unroll
                for (int k2 = 0; k2 < 8; k2++) {
                    uint32_t x[4], y[4], z[4], a1[2][4];
                    lds128_if(on, TB + 2176 + g * 128 + (k2 < 4 ? 64 : -64) * (g & 1) + 16 * k2, bd[k2 & 1]);
                    ldsm4(TB + (r & 3) * T_PL + 16 + 16 * mi + 64 * k2, z[0], z[1], z[2], z[3]);
                    ldsm4(((k2 & 1) ? ld1 : ld0) + (k2 >> 1) * 128, x[0], x[1], x[2], x[3]);
                    ldsm4(((k2 & 1) ? ld1 : ld0) + (k2 >> 1) * 128 + 4096, y[0], y[1], y[2], y[3]);
#pragma unroll
                    for (int u = 0; u < 2; u++) {
                        mma_hh_k8(a1[u][0], a1[u][1], Ya[2 * k2 + u][0], Ya[2 * k2 + u][1], bd[k2 & 1][2 * u]);
                        mma_hh_k8(a1[u][2], a1[u][3], Ya[2 * k2 + u][2], Ya[2 * k2 + u][3], bd[k2 & 1][2 * u + 1]);
                    }
#pragma unroll
                    for (int u = 0; u < 2; u++) {
                        const uint32_t(&a0)[4] = Ya[2 * k2 + u];
                        mma_h(R[0], a0[0], a0[1], a0[2], a0[3], x[2 * u], x[2 * u + 1]);
                        mma_h(R[2], a0[0], a0[1], a0[2], a0[3], y[2 * u], y[2 * u + 1]);
                        mma_h(R[4], a0[0], a0[1], a0[2], a0[3], z[2 * u], z[2 * u + 1]);
                        mma_h(R[1], a1[u][0], a1[u][1], a1[u][2], a1[u][3], x[2 * u], x[2 * u + 1]);
                        mma_h(R[3], a1[u][0], a1[u][1], a1[u][2], a1[u][3], y[2 * u], y[2 * u + 1]);
                        mma_h(R[5], a1[u][0], a1[u][1], a1[u][2], a1[u][3], z[2 * u], z[2 * u + 1]);
                    }
                }
            }
            __syncwarp();
            KSTAMP(9, __float_as_uint(R[3][0]));
            if (lane == 0) mbar_arrive(bars + 8 * B_KG + (__float_as_uint(R[0][0]) & __float_as_uint(R[2][0]) & p.zero));
            sts128(TB + 2176 + 16 * lane, 0, 0, 0, 0);
            sts128(TB + 2688 + 16 * lane, 0, 0, 0, 0);
            __syncwarp();
#undef PUT
#undef EMIT
#pragma unroll
            for (int o = 16; o > 0; o >>= 1) s1024 += __shfl_xor_sync(0xffffffffu, s1024, o);
            uint32_t w[4][4], dsk = 0;
            cp_wait_all();
            asm volatile("{\n\t.reg .pred p;\n\tsetp.eq.u32 p, %2, 0;\n\t@p ld.shared.u16 %0, [%1];\n\t}" : "+r"(dsk) : "r"(sb + M_DSK + 4 * warp + 2 * (warp & 1)), "r"(lane) : "memory");
#pragma unroll
            for (int a = 0; a < 4; a++) {
                const float v0 = (a == 0) ? fmaf(R[0][0], inv, __uint_as_float(dsk << 16)) : R[a][0] * inv;
                const float v1 = R[a][1] * inv, v2 = R[a][2] * inv, v3 = R[a][3] * inv;
                w[a][0] = pack_bf(v0, 0.f); w[a][1] = pack_bf(v1, v0); w[a][2] = pack_bf(v2, v1); w[a][3] = pack_bf(v3, v2);
            }
            const uint32_t wb = TB + 16 + 16 * g, w1 = wb + t * T_PL, w2 = wb + 256 + 2 * t * T_PL;
            const uint32_t w3 = (t == 0) ? wb + 256 + 3 * T_PL : TB + T_A + 8 * (16 * t + g);
            const uint32_t w3s = (t == 0) ? 128 : 64, w3o = (t == 0) ? 8 : 12;
            const uint32_t k512 = __shfl_sync(0xffffffffu, w[2][1], 2);
#pragma unroll
            for (int a = 0; a < 2; a++) {
                sts128(w1 + 128 * a, w[a][0], w[a][1], w[a][2], w[a][3]);
                const uint32_t(&q)[4] = w[2 + a];
                if (t < 2) sts128(w2 + 128 * a, q[0], q[1], q[2], q[3]);
                if (t == 0) { sts128(w2 + T_PL + 128 * a, q[0], q[1], q[2], q[3]); sts32(w3 + 128 * a + 4, q[2]); }
                sts32_if(t != 1 && (a == 1 || lane != 2), w3 + w3s * a, q[1]);
                sts32_if(t != 1, w3 + w3s * a + w3o, q[3]);
            }
            sts128_if(lane < 4, w1 + 512, t == 3 ? k512 : k512 >> 16, t < 2 ? k512 : t == 2 ? k512 & 0xffff0000u : k512 << 16, t < 2 ? k512 << 16 : 0u, 0);
            __syncwarp();
#pragma unroll
            for (int a = 0; a < 2; a++) {
                sts16(w1 + 128 * a + 18, w[a][3]);
                const uint32_t(&q)[4] = w[2 + a];
                if (t < 2) sts16(w2 + 128 * a + 18, q[3]);
                if (t == 0) { sts16(w2 + T_PL + 128 * a + 18, q[3]); sts16(w3 + 128 * a + 14, q[3]); }
            }
            if (t == 0) sts16(w3 + 128 - 4, w[3][0]);
            if (lane == 2 || (t == 0 && g > 0)) sts16(lane == 2 ? TB + 16 + 3 * T_PL + 4 * 127 : w3 - 4, w[2][0]);
            {
                float q[4];
#pragma unroll
                for (int i = 0; i < 4; i++) q[i] = (t < 2 ? R[4][i] : R[5][i]) * inv;
                const uint32_t b0 = pack_bf(q[0], q[2]), b1 = pack_bf(q[1], q[3]);
                const uint32_t wq = TB + T_B + 8 * (65 + 32 * (t & 1) + 4 * (t & 2) + g);
                sts32(wq, b0); sts32(wq + 12, b0); sts32(wq + 128, b1); sts32(wq + 140, b1);
            }
            cfix = pack_bf(s1024 * inv, s1024 * inv);
            if (lane == 0) sts32(TB + T_A + 8 * 64, cfix);
            __syncwarp();
        }
        WSTAMP(1);

        mbar_wait(bars + 8 * B_U);
        WSTAMP(2);

        float D[16][4];
        {
            const int x5 = g - t + 5;
            const uint32_t tabD = TB + (x5 & 3) * T_PL + (x5 & 12) + 16;
            {
                const uint32_t a1 = lds32(tabD - 8), a0 = p.zero;
#pragma unroll
                for (int jq = 0; jq < 4; jq++) {
                    uint32_t b[4];
                    ldsm4(UB + (9 + lane) * 16 + jq * 512, b[0], b[1], b[2], b[3]);
#pragma unroll
                    for (int i = 0; i < 4; i++) mma_bf_k8z(D[4 * jq + i], a0, a1, b[i]);
                }
            }
            const uint32_t ua = UB + (mi & 1) * U_PL + (8 + 8 * (mi >> 1) + r) * 16;
#pragma unroll 1
            for (int k0 = 0; k0 < 8; k0++) {
                uint32_t Uf[16][2];
#pragma unroll
                for (int jp = 0; jp < 8; jp++) ldsm4(ua + jp * 256 - k0 * 16, Uf[2 * jp][0], Uf[2 * jp][1], Uf[2 * jp + 1][0], Uf[2 * jp + 1][1]);
#pragma unroll
                for (int k1 = 0; k1 < 4; k1++) {
                    const uint32_t ta = tabD + 16 * (8 * k1 + k0);
                    const uint32_t a0 = lds32(ta), a1 = lds32(ta + 8), a2 = lds32(ta - 8), a3 = a0 ^ p.zero;
#pragma unroll
                    for (int J = k1; J < 16; J++) mma_bf(D[J], a0, a1, a2, a3, Uf[J - k1][0], Uf[J - k1][1]);
                }
                if (k0 == 0) {
                    const uint32_t ta = tabD + 16 * 32;
                    const uint32_t a0 = lds32(ta), a1 = lds32(ta + 8), a2 = lds32(ta - 8), a3 = a0 ^ p.zero;
#pragma unroll
                    for (int J = 4; J < 16; J++) mma_bf(D[J], a0, a1, a2, a3, Uf[J - 4][0], Uf[J - 4][1]);
                    const uint32_t f0 = (cfix ^ 0x80008000u) & (g == t ? 0xffffu : g == t + 4 ? 0xffff0000u : 0u);
                    const uint32_t f1 = p.zero, f2 = p.zero + p.zero, f3 = f0 ^ p.zero;
#pragma unroll
                    for (int J = 8; J < 16; J++) mma_bf(D[J], f0, f1, f2, f3, Uf[J - 8][0], Uf[J - 8][1]);
                }
            }
        }
        WSTAMP(3);
        {
            const int ch = 8 * h + warp;
            const uint32_t yo = sb + ch * 512 + ((lane ^ (((ch >> 2) << 1) | (ch & 1))) << 4);
            const uint32_t yr = mapa(yo, h ^ 1), ybr = mapa(bars + 8 * B_Y, h ^ 1);
            auto ship = [&](const int Q) {
                uint4 y[2];
#pragma unroll
                for (int hh = 0; hh < 2; hh++) {
                    const int J = 4 * Q + 2 * hh;
                    y[hh] = make_uint4(pack_bf(D[J][0], D[J][1]), pack_bf(D[J][2], D[J][3]), pack_bf(D[J + 1][0], D[J + 1][1]), pack_bf(D[J + 1][2], D[J + 1][3]));
                }
                if (!(Q & 1)) mbar_wait(bars + 8 * (B_F + (Q >> 1)));
                asm volatile("{\n\t.reg .pred p;\n\tsetp.eq.u32 p, %11, 0;\n\t"
                             "@p st.async.weak.shared::cluster.mbarrier::complete_tx::bytes.v4.b32 [%9], {%4,%5,%6,%7}, [%10];\n\t"
                             "@!p st.async.weak.shared::cluster.mbarrier::complete_tx::bytes.v4.b32 [%9], {%0,%1,%2,%3}, [%10];\n\t"
                             "@p st.shared.v4.b32 [%8], {%0,%1,%2,%3};\n\t@!p st.shared.v4.b32 [%8], {%4,%5,%6,%7};\n\t}"
                             :: "r"(y[0].x), "r"(y[0].y), "r"(y[0].z), "r"(y[0].w), "r"(y[1].x), "r"(y[1].y), "r"(y[1].z), "r"(y[1].w),
                                "r"(yo + y_off(Q)), "r"(yr + y_off(Q)), "r"(ybr + 8 * Q), "r"(h) : "memory");
                __syncwarp();
                if (lane == 0) mbar_arrive(bars + 8 * (B_Y + Q));
            };
            ship(0);
            const uint4 bA = lds128(sb + OFF_BAND + (g - t + 3) * 48), bB = lds128(sb + OFF_BAND + (g - t + 3) * 48 + 16);
            const uint2 bC = lds64(sb + OFF_BAND + (g - t + 3) * 48 + 32);
            uint2 QA[5][2], QB[8];
            const uint32_t tq = TB + 8 * (1 + g - 2 * t);
#pragma unroll
            for (int dd = 0; dd < 5; dd++) { QA[dd][0] = lds64(tq + T_A + 64 * (dd + 4)); QA[dd][1] = lds64(tq + T_A + 64 * (dd + 4) - 8); }
#pragma unroll
            for (int dd = 0; dd < 8; dd++) QB[dd] = lds64(tq + T_B + 64 * (dd + 8));
            const uint32_t u1 = UB + (mi & 1) * U_PL + (7 + r + (mi >> 1)) * 16;
            const uint32_t u2 = UB + ((mi & 1) ^ 1) * U_PL + (7 + r + (mi & 1) + 8 * (mi >> 1)) * 16;
            uint32_t n[4];
#pragma unroll
            for (int j = 0; j < 12; j++) {
                uint32_t m[4];
                ldsm4(u1 + j * 128, m[0], m[1], m[2], m[3]);
                if (!(j & 1)) ldsm4(u2 + j * 128, n[0], n[1], n[2], n[3]);
                const uint32_t n0 = n[2 * (j & 1)], n1 = n[2 * (j & 1) + 1];
                float wa[4], wb[4], wc[4], g1[4], g2[4];
                mma_bf_z(wa, bA.x, bA.y, bA.z, bA.w, m[0], m[1]);
                mma_bf_z(wb, bA.x, bA.y, bA.z, bA.w, n0, n1);
                mma_bf_z(wc, bA.x, bA.y, bA.z, bA.w, m[2], m[3]);
                if (j < 8) {
                    mma_bf_z(g1, bB.x, bB.y, bB.z, bB.w, m[0], m[1]);
                    mma_bf_z(g2, bB.x, bB.y, bB.z, bB.w, n0, n1);
                    mma_bf_k8(g1, bC.x, bC.y, m[2]);
                    mma_bf_k8(g2, bC.x, bC.y, m[3]);
                }
#pragma unroll
                for (int e = 0; e < 2; e++) {
                    const uint32_t q0 = pack_bf(wa[e], wa[e + 2]), q1 = pack_bf(wb[e], wb[e + 2]), q2 = q1 ^ p.zero, q3 = pack_bf(wc[e], wc[e + 2]);
#pragma unroll
                    for (int dd = 0; dd < 5; dd++)
                        if (j + 4 + dd < 16) mma_bf(D[j + 4 + dd], q0, q1, q2, q3, QA[dd][e].x, QA[dd][e].y);
                }
                if (j < 8) {
                    const uint32_t q0 = pack_bf(g1[0], g1[2]), q1 = pack_bf(g2[0], g2[2]), q2 = pack_bf(g1[1], g1[3]), q3 = pack_bf(g2[1], g2[3]);
#pragma unroll
                    for (int dd = 7 - j; dd >= 0; dd--) mma_bf(D[j + 8 + dd], q0, q1, q2, q3, QB[dd].x, QB[dd].y);
                }
                if ((j & 3) == 3) {
                    WSTAMP(4 + 2 * (j >> 2));
                    if (j == 11 && LATE2) ship(2);
                    if (j != 7 || !LATE2) ship((j >> 2) + 1);
                }
            }
        }
        const int warpu = __reduce_max_sync(0xffffffffu, warp);
        mix_rows<1, BULKM>(p, &tm_out, sb, sb + OFF_U + warpu * U_CH + (warpu & 1) * 64, PQ, 4, warpu, h, pr, lane);
        if (BULKM) asm volatile("cp.async.bulk.commit_group;\n\tcp.async.bulk.wait_group.read 0;" ::: "memory");
        WSTAMP(10);
        WDUMP();
    } else if ((pw & 12) == AUX_W0) {
        asm volatile("setmaxnreg.inc.sync.aligned.u32 136;");
        const int v = __reduce_max_sync(0xffffffffu, pw & 3);
        const int at = tid & 127;
        const int g = lane >> 2, t = lane & 3;
        unsigned tag;
        const bool gu = c < NGU_CTA;
        {
            uint4 xa[16];
            const uint32_t xb = sb + (v < 2 ? OFF_XSEL : OFF_RING + 2 * 8192) + v * 8192;
            const uint32_t gws = sb + (gu ? M_DPIN : OFF_RING + 2 * 8192);
            const uint32_t row = 16 * c + 4 * v + (g >> 1);
            const unsigned epoch = *(volatile unsigned*)&p.sc->epoch;
#pragma unroll
            for (int i = 0; i < 4; i++)
                asm volatile("cp.async.ca.shared.global [%0], [%1], 4;" :: "r"(sb + OFF_GP + 512 * i + (tid & 124) * 4 + (tid & 1) * 8 + (tid & 2) * 2),
                             "l"(p.wr + 256 * i + (tid & 127) * 2) : "memory");
            cp16(gws + (tid & 127) * 16, p.gatew + (tid & 127) * 8);
            if ((tid & 127) < 33) cp16(sb + OFF_BAND + (tid & 127) * 16, p.band + (tid & 127));
            asm volatile("barrier.cluster.arrive.relaxed.aligned;" ::: "memory");
            tag = __reduce_max_sync(0xffffffffu, (epoch + 1) & 0xffffu);
            if (gu) st_gpu32((uint32_t*)&p.sc->h[(tag + 1) & 1][32 * c] + at, 0);
            if (v == 0) sts32(sb + M_BMAP + lane * 4, 0);
            cp_wait_all();
            bar_sync(1, 128);
            uint2 w[16];
#pragma unroll
            for (int kb = 0; kb < 16; kb++) w[kb] = lds64(sb + OFF_GP + 128 * kb + 32 * (g & 2) + 16 * t + 8 * (g & 1));
            asm volatile("barrier.cluster.wait.acquire.aligned;" ::: "memory");
            mbar_wait(bars + 8 * (B_X + v));
            WSTAMP(10);
#pragma unroll
            for (int kb = 0; kb < 16; kb++) xa[kb] = lds128(xb + (g >> 1) * 2048 + 128 * kb + 16 * (lane & 7));
            float dr[4][4];
#pragma unroll
            for (int kb = 0; kb < 16; kb++) {
                if (kb < 4) mma_bf_z(dr[kb], xa[kb].x, xa[kb].y, xa[kb].z, xa[kb].w, w[kb].x, w[kb].y);
                else mma_bf(dr[kb & 3], xa[kb].x, xa[kb].y, xa[kb].z, xa[kb].w, w[kb].x, w[kb].y);
            }
            float rs = ((dr[0][0] + dr[0][3]) + (dr[1][0] + dr[1][3])) + ((dr[2][0] + dr[2][3]) + (dr[3][0] + dr[3][3]));
            if (lane == 0) mbar_arrive(bars + 8 * (B_XE + v) + (__float_as_uint(rs) & p.zero));
            rs += __shfl_xor_sync(0xffffffffu, rs, 5);
            const uint32_t rb = pack_bf(0.f, rs);
            if (!(lane & 7)) st_gpu32((uint32_t*)&p.sc->r[(row >> 2) * RS] + (row & 3), ((rb ^ (((int)rb >> 31) | 0x80000000u)) & 0xffff0000u) | tag);
            WSTAMP(1);
            {
                const int n = 3 + (lane >> 3) + 4 * (lane & 1);
                const uint32_t so = (n & 7) * S_PL + ((lane & 6) + (n >> 3)) * 32;
                const uint32_t src[2] = {sb + OFF_S + v * S_Q + s_addr(so, h), sb + OFF_S + v * S_Q + s_addr(so + 32, h)};
                const uint32_t dst = sb + OFF_U + g * U_CH + (8 + 32 * v + 16 * h + t) * 16;
                const uint32_t rdst = mapa(dst, h ^ 1), rbar = mapa(bars + 8 * B_U, h ^ 1);
                mbar_wait(bars + 8 * (B_S + v));
                WSTAMP(9);
                uint4 a[8];
#pragma unroll
                for (int b = 0; b < 2; b++) {
#pragma unroll
                    for (int j = 0; j < 8; j++) ldsm4t((b ? src[j & 1] : src[j & 1] ^ 16) + (j >> 1) * 256, a[j].x, a[j].y, a[j].z, a[j].w);
#pragma unroll
                    for (int j = 0; j < 8; j++) {
                        if (b) sts128(dst + (j >> 1) * 64 + (j & 1) * U_PL, a[j].x, a[j].y, a[j].z, a[j].w);
                        else st_async16(rdst + (j >> 1) * 64 + (j & 1) * U_PL, a[j], rbar);
                    }
                }
                if (h && v == 3) {
                    ldsm4t((src[0] ^ 16) + 1024, a[0].x, a[0].y, a[0].z, a[0].w);
                    ldsm4t(src[0] + 1024, a[1].x, a[1].y, a[1].z, a[1].w);
                    if (t == 0) {
                        st_async16(rdst + 256, make_uint4(a[0].x, a[0].y & 0xffffu, a[0].z & 0xffffu, a[0].w & 0xffffu), rbar);
                        sts128(dst + 256, a[1].x, a[1].y & 0xffffu, a[1].z & 0xffffu, a[1].w & 0xffffu);
                    }
                }
                __syncwarp();
                if (lane == 0) mbar_arrive(bars + 8 * B_U);
            }
            const uint32_t one0 = 0x3F803F80u ^ p.zero, one1 = 0x3F803F80u + p.zero;
#pragma unroll
            for (int kb = 0; kb < 16; kb++) {
                const uint4 gw = lds128(gws + 128 * kb + 16 * (lane & 7));
                const uint32_t a0 = hmul2_bf(xa[kb].x, gw.x), a1 = hmul2_bf(xa[kb].y, gw.y), a2 = hmul2_bf(xa[kb].z, gw.z), a3 = hmul2_bf(xa[kb].w, gw.w);
                if (kb < 4) mma_bf_z(dr[kb], a0, a1, a2, a3, one0, one1);
                else mma_bf(dr[kb & 3], a0, a1, a2, a3, one0, one1);
            }
            float sg = ((dr[0][0] + dr[0][3]) + (dr[1][0] + dr[1][3])) + ((dr[2][0] + dr[2][3]) + (dr[3][0] + dr[3][3]));
            sg += __shfl_xor_sync(0xffffffffu, sg, 4);
            if (!(lane & 7)) st_gpu32((uint32_t*)p.sc->g + ((row & 256) << 2) + gate_pos(row), (pack_bf(sigmoid_f(bf_round(sg)), 0.f) & 0xffffu) | (tag << 16));
            WSTAMP(2);
        }
        if (at == 32) { sts32(sb + M_TAG, tag << 16); mbar_arrive(bars + 8 * B_F); }
        {
            const bool lane0 = pin(lane, lane) == 0;
            const uint32_t own = pin(sb + OFF_XSEL + (at ^ ((at >> 1) & 4)) * 16, lane);
            float acc[8][4];
#pragma unroll
            for (int i = 0; i < 8; i++) { acc[i][0] = acc[i][1] = acc[i][2] = acc[i][3] = 0.f; }
            const int krow = ((lane >> 1) & 8) + (lane & 7);
            const uint32_t tile0 = pin(sb + OFF_RING + krow * 64 + ((((lane >> 3) & 1) ^ ((krow >> 1) & 3)) << 4), lane);
            const uint32_t xo = pin(sb + OFF_XSEL + (lane & 7) * XS_ROW + 512 * v + 2 * (lane & 24), lane);
            const uint32_t po = pin(sb + OFF_XSEL + t * XS_ROW + (g & 3) * 128 + (g & 1) * 64 + v * 16 + (lane >> 4) * 8, lane);
            const uint32_t po1 = pin(po + 64 - (g & 1) * 128, lane);
            uint32_t* hdst = pin((uint32_t*)&p.sc->h[tag & 1][32 * c] + at, lane);
            auto signal = [&](const int k, const uint32_t dep) {
                if (lane < 2 && v < 2)
                    asm volatile("st.async.weak.shared::cluster.mbarrier::complete_tx::bytes.b32 [%0], %1, [%2];"
                                 :: "r"(mapa(sb + M_SINK, lane)), "r"(dep), "r"(mapa(bars + 8 * (B_F + k), lane)) : "memory");
            };
#pragma unroll 1
            for (int i = 0; i < 4; i++) {
                const int s = 4 * i + v;
                uint32_t a[16][4], b[2][4];
                if (gu) {
                    const uint32_t tile = tile0 + (s < 14 ? s : v) * 8192;
                    if (lane0 && i > 1) mbar_arrive(bars + 8 * (B_E + s - 4));
                    if (i == 2) signal(0, 0);
                    mbar_wait(bars + 8 * (B_W + s));
#pragma unroll
                    for (int q = 0; q < 16; q++) ldsm4t((tile ^ ((q & 1) << 5)) + ((q >> 1) & 1) * 4096 + (q >> 2) * 1024, a[q][0], a[q][1], a[q][2], a[q][3]);
                }
                if (i == 0) {
                    if (gu) {
                        uint32_t dep = p.zero;
#pragma unroll
                        for (int q = 0; q < 16; q += 2) dep &= a[q][0] & a[q + 1][0];
                        if (lane == 0) mbar_arrive(bars + 8 * (B_E + v) + dep);
                    }
                    WSTAMP(11);
                    uint32_t top;
#pragma unroll 1
                    for (int it = 0; it < (1 << 22); it++) {
                        asm volatile("ld.relaxed.gpu.global.u32 %0, [%1];" : "=r"(top) : "l"(&p.sc->top[c % NTOP][g]) : "memory");
                        if (__all_sync(0xffffffffu, ((top ^ (tag << 11)) & 0xf800u) == 0)) break;
                        if (TSLEEP) __nanosleep(TSLEEP);
                    }
                    WSTAMP(3);
                    if (gu) {
                        const uint32_t k = 4 * h + v, row = __reduce_max_sync(0xffffffffu, lane == 4 * k ? ~top & 2047 : 0);
                        asm volatile("{\n\t.reg .pred p;\n\telect.sync _|p, 0xffffffff;\n\t"
                                     "@p cp.async.bulk.shared::cluster.global.mbarrier::complete_tx::bytes.multicast::cluster [%0], [%1], 2048, [%2], %3;\n\t}"
                            :: "r"(sb + OFF_XSEL + k * XS_ROW), "l"(p.u + (size_t)row * D_), "r"(bars + 8 * B_G), "h"((unsigned short)3) : "memory");
                    }
                    if (v == 0) {
                        const uint32_t row = ~top & 2047;
                        if (t == 0 && ((row >> 8) & 1) == h)
                            asm volatile("red.shared.or.b32 [%0], %1;" :: "r"(sb + M_BMAP + (row & 7) * 16 + (row >> 9) * 4), "r"(1u << (gate_pos(row) & 31)) : "memory");
                        if (t == 0) sts32(sb + M_TOP + lane, top);
                        if (c == 0 && lane == 0) *(volatile unsigned*)&p.sc->epoch = tag;
                        __syncwarp();
                        if (lane0) mbar_arrive(bars + 8 * B_Y);
                    }
                    if (!gu) break;
                    mbar_wait(bars + 8 * B_G);
                    WSTAMP(4);
                }
                ldsm4(xo + 128 * i, b[0][0], b[0][1], b[0][2], b[0][3]);
                ldsm4(xo + 128 * i + 64, b[1][0], b[1][1], b[1][2], b[1][3]);
#pragma unroll
                for (int q = 0; q < 16; q++) mma_bf(acc[q & 7], a[q][0], a[q][1], a[q][2], a[q][3], b[q >> 3][(q >> 1) & 2], b[q >> 3][((q >> 1) & 2) + 1]);
            }
            if (gu) {
                WSTAMP(5);
                __syncwarp();
#pragma unroll
                for (int q = 0; q < 4; q++) {
                    const int ct = q >> 1, e = 2 * (q & 1);
                    sts128(own + q * XS_ROW,
                           __float_as_uint(acc[ct][e] + acc[4 + ct][e]), __float_as_uint(acc[2 + ct][e] + acc[6 + ct][e]),
                           __float_as_uint(acc[ct][e + 1] + acc[4 + ct][e + 1]), __float_as_uint(acc[2 + ct][e + 1] + acc[6 + ct][e + 1]));
                }
                bar_sync(1, 128);
                float sl[2], uv[2];
#pragma unroll
                for (int e = 0; e < 2; e++) {
                    uint2 q[4];
#pragma unroll
                    for (int i = 0; i < 4; i++) q[i] = lds64((e ? po1 : po) + 512 * i);
                    const float s0 = (__uint_as_float(q[0].x) + __uint_as_float(q[1].x)) + (__uint_as_float(q[2].x) + __uint_as_float(q[3].x));
                    const float s1 = (__uint_as_float(q[0].y) + __uint_as_float(q[1].y)) + (__uint_as_float(q[2].y) + __uint_as_float(q[3].y));
                    const float gv = bf_round(p.gu_swap ? s1 : s0);
                    uv[e] = p.gu_swap ? s0 : s1;
                    sl[e] = gv * sigmoid_f(gv);
                }
                const uint32_t hw = hmul2_bf(pack_bf(sl[0], sl[1]), pack_bf(uv[0], uv[1]));
                st_gpu32(hdst, hw ? hw : 0x80000000u);
                signal(1, hw);
            }
        }
        WSTAMP(6);
        asm volatile("setmaxnreg.dec.sync.aligned.u32 104;");
        {
            const uint32_t own = pin(sb + OFF_XSEL + at * 16, lane);
            const uint32_t hb = sb + (v < 2 ? OFF_XSEL + 7168 * v : OFF_RING + 8192 * v), hl = pin(hb + 16 * lane, lane);
            const int krow = ((lane >> 1) & 8) + (lane & 7);
            const uint32_t tile = pin(sb + OFF_RING + v * 8192 + krow * 32 + ((((lane >> 3) ^ (krow >> 2)) & 1) << 4), lane);
            float dd[4][4];
            bar_sync(1, 128);
            mbar_wait(bars + 8 * (B_W + HW));
            WSTAMP(12);
#pragma unroll 1
            for (int it = 0; it < (1 << 16); it++) {
                bulk_load(hb, &p.sc->h[tag & 1][32 * (56 * h + 14 * v)], 7168, bars + 8 * (B_X + v));
                uint32_t a[14][4], mn = 0xffffffffu;
                mbar_wait(bars + 8 * (B_W + 16 + v));
#pragma unroll
                for (int j = 0; j < 14; j++) ldsm4t(tile + (v & 2) * 16384 + j * 512, a[j][0], a[j][1], a[j][2], a[j][3]);
                mbar_wait(bars + 8 * (B_W + 20 + v));
                mbar_wait(bars + 8 * (B_X + v), ~it & 1);
                WSTAMP(7);
#pragma unroll
                for (int j = 0; j < 14; j++) {
                    const uint4 q = lds128(hl + 512 * j);
                    mn = min(mn, q.x);
#pragma unroll
                    for (int e = 0; e < 2; e++) {
                        uint32_t(&f)[4] = a[(2 * j + e) % 14];
                        if (j >= 7) ldsm4t(tile + 65536 + (2 * j + e - 14) * 512, f[0], f[1], f[2], f[3]);
                        if (j < 2) mma_bf_z(dd[2 * j + e], f[0], f[1], f[2], f[3], e ? q.z : q.x, e ? q.w : q.y);
                        else mma_bf(dd[(2 * j + e) & 3], f[0], f[1], f[2], f[3], e ? q.z : q.x, e ? q.w : q.y);
                    }
                }
                if (__all_sync(0xffffffffu, mn != 0)) break;
            }
            WSTAMP(8);
            uint4 part;
            part.x = __float_as_uint((dd[0][0] + dd[1][0]) + (dd[2][0] + dd[3][0])); part.y = __float_as_uint((dd[0][1] + dd[1][1]) + (dd[2][1] + dd[3][1]));
            part.z = __float_as_uint((dd[0][2] + dd[1][2]) + (dd[2][2] + dd[3][2])); part.w = __float_as_uint((dd[0][3] + dd[1][3]) + (dd[2][3] + dd[3][3]));
            st_async16(mapa(own + (M_DPIN - OFF_XSEL), h ^ 1), part, mapa(bars + 8 * B_DP, h ^ 1));
            sts128(own + 14336, part.x, part.y, part.z, part.w);
            __syncwarp();
            if (lane == 0) mbar_arrive(bars + 8 * B_DP);
        }
        WDUMP();
    } else {
        asm volatile("setmaxnreg.dec.sync.aligned.u32 40;");
        const int v = __reduce_max_sync(0xffffffffu, pw - PREP_W0);
        const bool gu = c < NGU_CTA;
        const uint32_t t0 = clock();
        const uint32_t bu = bars + 8 * v;
        if (lane == 0) {
            mbar_init(bu + 8 * B_X, 1);
            asm volatile("fence.mbarrier_init.release.cluster;" ::: "memory");
        }
        __syncwarp();
        if (DELAY_X > 0) __nanosleep(DELAY_X);
        bulk_load(sb + (v < 2 ? OFF_XSEL : OFF_RING + 2 * 8192) + v * 8192, p.u + (size_t)(16 * c + 4 * v) * D_, 8192, bu + 8 * B_X);
        if (lane == 0) {
#pragma unroll
            for (int i = 0; i < 10; i++) mbar_init(bu + 32 * i, 1);
            mbar_init(bu + 8 * B_XE, 1);
            mbar_init(bu + 8 * B_Y, v == 0 ? 11 : 9);
            mbar_init(bu + 8 * B_DP, (0x1855 >> (4 * v)) & 15);
            mbar_init(bu + 8 * B_F, v == 0 ? 2 : 1);
            mbar_init(bu + 8 * B_H, 1);
            asm volatile("fence.mbarrier_init.release.cluster;" ::: "memory");
            mbar_expect(bu + 8 * B_Y, 4096);
            if (v != 2) mbar_expect(bu + 8 * B_DP, v == 0 ? 2048 : (h || v == 3) ? 16384 : 16384 + 128);
            mbar_expect(bu + 8 * B_F, c < NGU_CTA ? 16 : 0);
        }
        __syncwarp();
        asm volatile("barrier.cluster.arrive.relaxed.aligned;" ::: "memory");
        tma3d(sb + OFF_S + v * S_Q, &tm_x, 16 * pr, 64 * v + 32 * h - 1, bars + 8 * (B_S + v), S_Q);
        WSTAMP(9);
        if (v < 3 && lane == 0) asm volatile("prefetch.tensormap [%0];" :: "l"(v == 0 ? &tm_gu : v == 1 ? &tm_down : &tm_out) : "memory");
        asm volatile("barrier.cluster.wait.acquire.aligned;" ::: "memory");
        if (v > 0) mbar_wait(bars + 8 * (B_H + v));
        {
            const int gap = v == 0 ? GAP : v == 1 ? GAP1 : v == 2 ? GAP2 : GAP3;
            uint32_t last = v ? clock() - SLACK : t0 + T0 - GAP + STAG * ((pr * 5) & 15) / 16;
#pragma unroll 1
            for (int s = 6 * v; s < 6 * v + 6; s++) {
                const int i = s >> 2, w = s & 3, slot = s < 14 ? s : (s | 1) == 17 ? s - 16 : s - 12;
                if (s >= 4) mbar_wait(bars + 8 * ((gu && s >= 14) ? B_E + slot : s < 6 ? B_XE + s - 2 : B_KG));
                uint32_t now;
#pragma unroll 1
                while ((int)((now = clock()) - last) < gap) __nanosleep(CSLEEP);
                last = max((int)(now - last) - SLACK, gap) + last;
                WSTAMP(3 + s - 6 * v);
                if (gu || s >= 16) tma3d(sb + OFF_RING + slot * 8192, i < 4 ? &tm_gu : &tm_down, i < 4 ? 32 * c : 16 * pr,
                      i < 4 ? 256 * w + 64 * i : 1792 * h + 448 * w + 224 * (i - 4), bars + 8 * (B_W + s), i < 4 ? 8192 : 7168);
            }
            if (lane == 0) mbar_arrive(bars + 8 * (B_H + ((v + 1) & 3)));
        }
        if (v == 0) {
            mbar_wait(bars + 8 * B_U);
            mbar_wait(bars + 8 * B_F);
            if (!gu) mbar_wait(bars + 8 * (B_H + 3));
            const uint32_t tag16 = lds32(sb + M_TAG);
#pragma unroll 1
            for (int k = 0; k < 2; k++) {
                uint4 q[4];
#pragma unroll 1
                for (int it = 0; it < (1 << 22); it++) {
                    uint32_t bad = 0;
#pragma unroll
                    for (int i = 0; i < 4; i++) q[i] = ld_gpu128(&p.sc->g[256 * h + 128 * k + 32 * i + lane]);
#pragma unroll
                    for (int i = 0; i < 4; i++) bad |= ((q[i].x ^ tag16) | (q[i].y ^ tag16)) | ((q[i].z ^ tag16) | (q[i].w ^ tag16));
                    if ((bad >> 16) == 0) break;
                    __nanosleep(200);
                }
#pragma unroll
                for (int i = 0; i < 4; i++)
                    asm volatile("st.shared.v2.u32 [%0], {%1, %2};" :: "r"(sb + OFF_GP + 1024 * k + 256 * i + lane * 8),
                                 "r"(__byte_perm(q[i].x, q[i].y, 0x5410)), "r"(__byte_perm(q[i].z, q[i].w, 0x5410)) : "memory");
            }
            __syncwarp();
            if (lane == 0) mbar_arrive(bars + 8 * B_Y);
        }
        {
            asm volatile("setmaxnreg.inc.sync.aligned.u32 72;");
            WSTAMP(1);
            mix_rows<2, true>(p, &tm_out, sb, sb + OFF_TAB + v * TAB_W, 0, PQ, v, h, pr, lane);
            WSTAMP(2);
            asm volatile("cp.async.bulk.commit_group;" ::: "memory");
            const uint32_t top = lds32(sb + M_TOP + 8 * v + 4 * (lane >> 4));
            const uint32_t row = ~top & 2047, ch = lane & 15, gp = gate_pos(row);
            const bool mine = ((row >> 8) & 1) == h;
            uint32_t gfin, x16, y16 = 0;
            asm volatile("ld.shared.u16 %0, [%1];" : "=r"(gfin) : "r"(sb + OFF_GP + gp * 2) : "memory");
            asm volatile("ld.shared.u16 %0, [%1];" : "=r"(x16) : "r"(sb + OFF_S + (row >> 9) * S_Q + s_addr((row & 7) * S_PL + 32 + (row & 248) * 4, ch >> 3) + 2 * (ch & 7)) : "memory");
            const float rsel = __uint_as_float(pin(__float_as_uint(bf_round(sigmoid_f(__uint_as_float((top ^ (((int)~top >> 31) | 0x80000000u)) & 0xffff0000u)))), lane));
            const uint32_t po = pin(sb + (4 * (ch & 7) + v) * 16 + (ch >> 3) * 8 + (lane >> 4) * 4, lane);
            bf16* op = pin(p.out + (size_t)row * D_ + 16 * pr + ch, lane);
            if (mine) {
                mbar_wait(bars + 8 * (B_Y + (row >> 9)));
                asm volatile("ld.shared.u16 %0, [%1];" : "=r"(y16)
                             : "r"(sb + y_off(row >> 9) + ch * 512 + (((4 * (row & 7) + ((row >> 5) & 3)) ^ (((ch >> 2) << 1) | (ch & 1))) << 4) + 2 * row_elem(row)) : "memory");
            }
            mbar_wait(bars + 8 * B_DP);
            float q[8];
#pragma unroll
            for (int i = 0; i < 4; i++) { q[i] = ldsf(po + M_DPIN + 512 * i); q[4 + i] = ldsf(po + OFF_XSEL + 14336 + 512 * i); }
            const float tot = ((q[0] + q[1]) + (q[2] + q[3])) + ((q[4] + q[5]) + (q[6] + q[7]));
            const float b = bf_round(__uint_as_float(x16 << 16) + bf_round(bf_round(tot) * rsel));
            if (mine) *op = __float2bfloat16_rn(fmaf(bf_lo(gfin), __uint_as_float(y16 << 16), bf_round(bf_round(1.f - bf_lo(gfin)) * b)));
        }
        asm volatile("cp.async.bulk.wait_group.read 0;" ::: "memory");
        WSTAMP(10);
        WDUMP();
    }
}

typedef CUresult (*EncodeFn)(CUtensorMap*, CUtensorMapDataType, cuuint32_t, void*, const cuuint64_t*, const cuuint64_t*,
                             const cuuint32_t*, const cuuint32_t*, CUtensorMapInterleave, CUtensorMapSwizzle,
                             CUtensorMapL2promotion, CUtensorMapFloatOOBfill);

void make_map(EncodeFn f, CUtensorMap* m, const void* ptr, uint64_t cols, uint64_t rows, uint64_t pitch, uint32_t bc, uint32_t br, CUtensorMapSwizzle sw, int prom,
              uint32_t planes = 1, uint64_t plane_stride = 0, uint32_t box_planes = 0) {
    cuuint64_t dims[3] = {cols, rows, planes};
    cuuint64_t str[2] = {pitch, planes > 1 ? plane_stride : pitch * rows};
    cuuint32_t box[3] = {bc, br, box_planes ? box_planes : planes};
    cuuint32_t es[3] = {1, 1, 1};
    f(m, CU_TENSOR_MAP_DATA_TYPE_BFLOAT16, 3, (void*)ptr, dims, str, box, es, CU_TENSOR_MAP_INTERLEAVE_NONE, sw,
      (CUtensorMapL2promotion)prom, CU_TENSOR_MAP_FLOAT_OOB_FILL_NONE);
}

}

extern "C" void kernel_launch(void* const* d_in, const int* in_sizes, int n_in, void* d_out, int out_size) {
    static EncodeFn enc = nullptr;
    static void *sc = nullptr, *band = nullptr;
    if (!enc) {
        void* fn = nullptr;
        cudaDriverEntryPointQueryResult qr;
        cudaGetDriverEntryPoint("cuTensorMapEncodeTiled", &fn, cudaEnableDefault, &qr);
        enc = (EncodeFn)fn;
        cudaGetSymbolAddress(&sc, g_scratch);
        cudaGetSymbolAddress(&band, g_band);
        cudaFuncSetAttribute(fused_kernel, cudaFuncAttributeMaxDynamicSharedMemorySize, SMEM_BYTES);
    }
    CUtensorMap tg, td, tx, to;
    const char *wg = (const char*)d_in[9], *wu = (const char*)d_in[10];
    const bool swap = wu < wg;
    make_map(enc, &tg, swap ? wu : wg, F_, D_, F_ * 2, 32, 64, CU_TENSOR_MAP_SWIZZLE_64B, PROMG, 2, swap ? wg - wu : wu - wg);
    make_map(enc, &td, d_in[11], D_, F_, D_ * 2, 16, 224, CU_TENSOR_MAP_SWIZZLE_32B, PROMD);
    make_map(enc, &tx, d_in[0], D_, L_ / 8, D_ * 16, 16, 33, CU_TENSOR_MAP_SWIZZLE_32B, PROMX, 8, D_ * 2);
    make_map(enc, &to, d_out, D_, L_ / 8, D_ * 16, 16, 32, CU_TENSOR_MAP_SWIZZLE_NONE, 0, 8, D_ * 2, 1);
    Params p;
    p.u = (const bf16*)d_in[0]; p.logA = (const bf16*)d_in[1]; p.Aim = (const bf16*)d_in[2];
    p.Cre = (const bf16*)d_in[3]; p.Cim = (const bf16*)d_in[4]; p.logdt = (const bf16*)d_in[5];
    p.Dskip = (const bf16*)d_in[6]; p.wr = (const bf16*)d_in[8]; p.gatew = (const bf16*)d_in[12];
    p.out = (bf16*)d_out;
    p.sc = (Scratch*)sc; p.band = (const uint4*)band;
    p.gu_swap = swap;
    p.zero = 0;
    fused_kernel<<<NCTA, NTHREADS, SMEM_BYTES>>>(p, tg, td, tx, to);
}
```

```cpp
#include <cuda_runtime.h>
#include <cuda_bf16.h>
#include <cuda_fp16.h>
#include <cuda.h>
#include <stdint.h>

typedef __nv_bfloat16 bf16;

namespace {

constexpr int L_ = 2048, D_ = 1024, F_ = 3584;
constexpr int NCTA = 130;
constexpr int NTHREADS = 512;
#define AUXW 12
constexpr int MAIN_W0 = 0, AUX_W0 = AUXW, PREP_W0 = 20 - AUXW;
#define T0 3500
#define GAP 590
#define GAP1 530
#define GAP2 530
#define GAP3 550
#define STAG GAP
#define CSLEEP 50
#define SLACK 300
#define DELAY_X 150
#define TSLEEP 40
#define RS 2
#define BULKM false
#define PW 19
#define PQ 3
#define PROMG 2
#define PROMD 1
#define PROMX 0
#define LATE2 0
#define HW 20
constexpr int NGU_CTA = 112;

constexpr int OFF_RING = 0;
constexpr int OFF_SCR  = 6 * 8192;
constexpr int S_PL     = 1056;
constexpr int S_Q      = 8 * S_PL;
constexpr int OFF_S    = 114688;
constexpr int OFF_GP   = OFF_S + 4 * S_Q;
constexpr int U_PL     = 2240;
constexpr int U_CH     = 4416;
constexpr int OFF_U    = 151552;
constexpr int TAB_W    = 3200;
constexpr int T_PL     = 544;
constexpr int T_A      = 2192 - 26 * 8;
constexpr int T_B      = 2568 - 59 * 8;
constexpr int OFF_TAB  = 186880;
constexpr int OFF_XSEL = 212480;
constexpr int XS_ROW   = 2064;
constexpr int OFF_BAND = 228992;
constexpr int OFF_MISC = 229536;
constexpr int M_BARS   = OFF_MISC;
constexpr int M_DSK    = OFF_MISC + 2736;
constexpr int M_SINK   = OFF_MISC + 512;
constexpr int M_TAG    = OFF_MISC + 516;
constexpr int M_BMAP   = OFF_MISC + 528;
constexpr int M_DPIN   = OFF_MISC + 656;
constexpr int M_TOP    = OFF_MISC + 2704;
constexpr int SMEM_BYTES = OFF_MISC + 2768;
__device__ __forceinline__ uint32_t s_addr(uint32_t o, uint32_t half) { return o + (((half ^ (o >> 7)) & 1) << 4); }
__host__ __device__ constexpr uint32_t y_off(uint32_t q) { return OFF_RING + 32768 + (q & 1) * 8192 + (q >> 1) * 65536; }

constexpr int B_W = 0;
constexpr int B_E = 24;
constexpr int B_S = 36;
constexpr int B_Y = 40;
constexpr int B_DP = 44, B_U = 45, B_KG = 46, B_G = 47;
constexpr int B_F = 48;
constexpr int B_H = 60;
constexpr int B_X = 52, B_XE = 56;

struct BandTab { uint32_t w[11][12]; };
constexpr BandTab make_band() {
    BandTab b{};
    for (int cls = 0; cls < 11; cls++)
        for (int wd = 0; wd < 10; wd++) {
            const int tau = cls + 2 - 8 * ((wd < 4 ? wd : wd - 4) >> 1);
            const int lo = (wd < 4) ? ((wd & 1) ? -2 : 3) : ((wd & 1) ? -4 : -11), wid = (wd < 4 ? 3 : 7) + 2 * (wd & 1);
            b.w[cls][wd] = ((tau >= lo && tau < lo + wid) ? 0x3F80u : 0u) | ((tau - 4 >= lo && tau - 4 < lo + wid) ? 0x3F800000u : 0u);
        }
    return b;
}
constexpr int NTOP = 32;
struct Scratch {
    uint4 r[L_ / 4 * RS];
    uint4 g[L_ / 4];
    uint4 h[2][8 * F_ / 8];
    uint32_t top[NTOP][32];
    unsigned epoch;
};
__device__ __align__(128) Scratch g_scratch;
__device__ const __align__(16) BandTab g_band = make_band();

struct Params {
    const bf16 *u, *logA, *Aim, *Cre, *Cim, *logdt, *Dskip, *wr, *gatew;
    bf16* out;
    Scratch* sc;
    const uint4* band;
    uint32_t gu_swap;
    uint32_t zero;
};

#define WSTAMP(i) do {} while (0)
#define KSTAMP(i, dep) do {} while (0)
#define WDUMP() do {} while (0)
#define RSTAMP(i) do {} while (0)

__device__ __forceinline__ uint32_t smem_u32(const void* p) { return (uint32_t)__cvta_generic_to_shared(p); }
__device__ __forceinline__ void mbar_init(uint32_t b, uint32_t c) { asm volatile("mbarrier.init.shared::cta.b64 [%0], %1;" :: "r"(b), "r"(c) : "memory"); }
__device__ __forceinline__ void mbar_expect(uint32_t b, uint32_t tx) { asm volatile("mbarrier.arrive.expect_tx.shared::cta.b64 _, [%0], %1;" :: "r"(b), "r"(tx) : "memory"); }
__device__ __forceinline__ void mbar_arrive(uint32_t b) { asm volatile("mbarrier.arrive.shared::cta.b64 _, [%0];" :: "r"(b) : "memory"); }
__device__ __forceinline__ void mbar_wait(uint32_t b, uint32_t parity = 0) {
    asm volatile("{\n\t.reg .pred p;\nW%=:\n\tmbarrier.try_wait.parity.shared::cta.b64 p, [%0], %1, 20000;\n\t@!p bra W%=;\n\t}" :: "r"(b), "r"(parity) : "memory");
}
__device__ __forceinline__ uint32_t mapa(uint32_t addr, uint32_t rank) { uint32_t r; asm("mapa.shared::cluster.u32 %0, %1, %2;" : "=r"(r) : "r"(addr), "r"(rank)); return r; }
__device__ __forceinline__ void tma3d(uint32_t dst, const CUtensorMap* tm, int c0, int c1, uint32_t bar, uint32_t bytes) {
    asm volatile("{\n\t.reg .pred p;\n\telect.sync _|p, 0xffffffff;\n\t"
                 "@p mbarrier.arrive.expect_tx.shared::cta.b64 _, [%2], %5;\n\t"
                 "@p cp.async.bulk.tensor.3d.shared::cluster.global.mbarrier::complete_tx::bytes [%0], [%1, {%3, %4, 0}], [%2];\n\t}"
        :: "r"(dst), "l"(tm), "r"(bar), "r"(c0), "r"(c1), "r"(bytes) : "memory");
}
__device__ __forceinline__ void bulk_load(uint32_t dst, const void* src, uint32_t bytes, uint32_t bar) {
    asm volatile("{\n\t.reg .pred p;\n\telect.sync _|p, 0xffffffff;\n\t"
                 "@p mbarrier.arrive.expect_tx.shared::cta.b64 _, [%2], %3;\n\t"
                 "@p cp.async.bulk.shared::cluster.global.mbarrier::complete_tx::bytes [%0], [%1], %3, [%2];\n\t}"
        :: "r"(dst), "l"(src), "r"(bar), "r"(bytes) : "memory");
}
__device__ __forceinline__ void st_async16(uint32_t dst, const uint4& v, uint32_t bar) {
    asm volatile("st.async.weak.shared::cluster.mbarrier::complete_tx::bytes.v4.b32 [%0], {%1,%2,%3,%4}, [%5];"
                 :: "r"(dst), "r"(v.x), "r"(v.y), "r"(v.z), "r"(v.w), "r"(bar) : "memory");
}
__device__ __forceinline__ void bar_sync(int id, int n) { asm volatile("bar.sync %0, %1;" :: "r"(id), "r"(n) : "memory"); }
__device__ __forceinline__ void cp16(uint32_t dst, const void* src) { asm volatile("cp.async.cg.shared.global [%0], [%1], 16;" :: "r"(dst), "l"(src) : "memory"); }
__device__ __forceinline__ void cp_wait_all() { asm volatile("cp.async.wait_all;" ::: "memory"); }
__device__ __forceinline__ uint4 ld_gpu128(const void* p) { uint4 v; asm volatile("ld.relaxed.gpu.global.v4.u32 {%0,%1,%2,%3}, [%4];" : "=r"(v.x), "=r"(v.y), "=r"(v.z), "=r"(v.w) : "l"(p) : "memory"); return v; }
__device__ __forceinline__ void st_gpu32(void* p, uint32_t v) { asm volatile("st.relaxed.gpu.global.u32 [%0], %1;" :: "l"(p), "r"(v) : "memory"); }

__device__ __forceinline__ void ldsm4(uint32_t a, uint32_t& r0, uint32_t& r1, uint32_t& r2, uint32_t& r3) {
    asm volatile("ldmatrix.sync.aligned.m8n8.x4.shared.b16 {%0,%1,%2,%3}, [%4];" : "=r"(r0), "=r"(r1), "=r"(r2), "=r"(r3) : "r"(a) : "memory");
}
__device__ __forceinline__ void ldsm4t(uint32_t a, uint32_t& r0, uint32_t& r1, uint32_t& r2, uint32_t& r3) {
    asm volatile("ldmatrix.sync.aligned.m8n8.x4.trans.shared.b16 {%0,%1,%2,%3}, [%4];" : "=r"(r0), "=r"(r1), "=r"(r2), "=r"(r3) : "r"(a) : "memory");
}
__device__ __forceinline__ uint32_t lds32(uint32_t a) { uint32_t v; asm volatile("ld.shared.u32 %0, [%1];" : "=r"(v) : "r"(a) : "memory"); return v; }
__device__ __forceinline__ uint2 lds64(uint32_t a) { uint2 v; asm volatile("ld.shared.v2.u32 {%0,%1}, [%2];" : "=r"(v.x), "=r"(v.y) : "r"(a) : "memory"); return v; }
__device__ __forceinline__ uint4 lds128(uint32_t a) { uint4 v; asm volatile("ld.shared.v4.u32 {%0,%1,%2,%3}, [%4];" : "=r"(v.x), "=r"(v.y), "=r"(v.z), "=r"(v.w) : "r"(a) : "memory"); return v; }
__device__ __forceinline__ void sts32(uint32_t a, uint32_t v) { asm volatile("st.shared.u32 [%0], %1;" :: "r"(a), "r"(v) : "memory"); }
__device__ __forceinline__ void sts16(uint32_t a, uint32_t v) { asm volatile("st.shared.u16 [%0], %1;" :: "r"(a), "h"((unsigned short)v) : "memory"); }
__device__ __forceinline__ void sts128(uint32_t a, uint32_t x, uint32_t y, uint32_t z, uint32_t w) { asm volatile("st.shared.v4.u32 [%0], {%1,%2,%3,%4};" :: "r"(a), "r"(x), "r"(y), "r"(z), "r"(w) : "memory"); }
__device__ __forceinline__ float ldsf(uint32_t a) { float v; asm volatile("ld.shared.f32 %0, [%1];" : "=f"(v) : "r"(a) : "memory"); return v; }

__device__ __forceinline__ void mma_bf(float (&d)[4], uint32_t a0, uint32_t a1, uint32_t a2, uint32_t a3, uint32_t b0, uint32_t b1) {
    asm volatile("mma.sync.aligned.m16n8k16.row.col.f32.bf16.bf16.f32 {%0,%1,%2,%3}, {%4,%5,%6,%7}, {%8,%9}, {%0,%1,%2,%3};"
        : "+f"(d[0]), "+f"(d[1]), "+f"(d[2]), "+f"(d[3]) : "r"(a0), "r"(a1), "r"(a2), "r"(a3), "r"(b0), "r"(b1));
}
__device__ __forceinline__ void mma_bf_z(float (&d)[4], uint32_t a0, uint32_t a1, uint32_t a2, uint32_t a3, uint32_t b0, uint32_t b1) {
    asm volatile("mma.sync.aligned.m16n8k16.row.col.f32.bf16.bf16.f32 {%0,%1,%2,%3}, {%4,%5,%6,%7}, {%8,%9}, {%10,%10,%10,%10};"
        : "=f"(d[0]), "=f"(d[1]), "=f"(d[2]), "=f"(d[3]) : "r"(a0), "r"(a1), "r"(a2), "r"(a3), "r"(b0), "r"(b1), "f"(0.f));
}
__device__ __forceinline__ void mma_bf_k8(float (&d)[4], uint32_t a0, uint32_t a1, uint32_t b0) {
    asm volatile("mma.sync.aligned.m16n8k8.row.col.f32.bf16.bf16.f32 {%0,%1,%2,%3}, {%4,%5}, {%6}, {%0,%1,%2,%3};"
        : "+f"(d[0]), "+f"(d[1]), "+f"(d[2]), "+f"(d[3]) : "r"(a0), "r"(a1), "r"(b0));
}
__device__ __forceinline__ void mma_h(float (&d)[4], uint32_t a0, uint32_t a1, uint32_t a2, uint32_t a3, uint32_t b0, uint32_t b1) {
    asm volatile("mma.sync.aligned.m16n8k16.row.col.f32.f16.f16.f32 {%0,%1,%2,%3}, {%4,%5,%6,%7}, {%8,%9}, {%0,%1,%2,%3};"
        : "+f"(d[0]), "+f"(d[1]), "+f"(d[2]), "+f"(d[3]) : "r"(a0), "r"(a1), "r"(a2), "r"(a3), "r"(b0), "r"(b1));
}
__device__ __forceinline__ uint32_t pack_bf(float lo, float hi) { uint32_t r; asm("cvt.rn.bf16x2.f32 %0, %1, %2;" : "=r"(r) : "f"(hi), "f"(lo)); return r; }
__device__ __forceinline__ uint32_t pack_h(float lo, float hi) { uint32_t r; asm("cvt.rn.f16x2.f32 %0, %1, %2;" : "=r"(r) : "f"(hi), "f"(lo)); return r; }
__device__ __forceinline__ float bf_lo(uint32_t v) { return __uint_as_float(v << 16); }
__device__ __forceinline__ float bf_hi(uint32_t v) { return __uint_as_float(v & 0xffff0000u); }
__device__ __forceinline__ float bf_round(float x) { return __uint_as_float(pack_bf(0.f, x)); }
__device__ __forceinline__ uint32_t hmul2_bf(uint32_t a, uint32_t b) { uint32_t r; asm("mul.rn.bf16x2 %0, %1, %2;" : "=r"(r) : "r"(a), "r"(b)); return r; }
__device__ __forceinline__ float ex2f(float x) { float r; asm("ex2.approx.ftz.f32 %0, %1;" : "=f"(r) : "f"(x)); return r; }

__device__ __forceinline__ float exp_acc(float x) {
    const float t = x * 1.4426950216293335f;
    const float r = fmaf(x, 1.4426950216293335f, -t) + x * 1.9259629911266175e-8f;
    return ex2f(t) * fmaf(r, 0.6931471805599453f, 1.f);
}
__device__ __forceinline__ float sigmoid_f(float x) { return __fdividef(1.f, 1.f + ex2f(-x * 1.4426950408889634f)); }
__device__ __forceinline__ void cexp_pow(float l2, float li, float e, float& zr, float& zi) {
    const float mag = ex2f(l2 * e);
    zr = mag * __cosf(li * e);
    zi = mag * __sinf(li * e);
}
__device__ __forceinline__ uint32_t hcmul(uint32_t a, uint32_t k, uint32_t kp) {
    const __half2 A = *reinterpret_cast<const __half2*>(&a);
    const __half2 r = __hfma2(__high2half2(A), *reinterpret_cast<const __half2*>(&kp), __hmul2(__low2half2(A), *reinterpret_cast<const __half2*>(&k)));
    return *reinterpret_cast<const uint32_t*>(&r);
}
#define CMUL(orr, oi, ar, ai, br, bi) do { float _r = (ar) * (br) - (ai) * (bi); float _i = (ar) * (bi) + (ai) * (br); orr = _r; oi = _i; } while (0)
#define CSQ(orr, oi, ar, ai) do { float _r = (ar) * (ar) - (ai) * (ai); float _i = 2.f * (ar) * (ai); orr = _r; oi = _i; } while (0)

__device__ __forceinline__ void mma_bf_k8z(float (&d)[4], uint32_t a0, uint32_t a1, uint32_t b0) {
    asm volatile("mma.sync.aligned.m16n8k8.row.col.f32.bf16.bf16.f32 {%0,%1,%2,%3}, {%4,%5}, {%6}, {%7,%7,%7,%7};"
        : "=f"(d[0]), "=f"(d[1]), "=f"(d[2]), "=f"(d[3]) : "r"(a0), "r"(a1), "r"(b0), "f"(0.f));
}
__device__ __forceinline__ void mma_hh_k8(uint32_t& d0, uint32_t& d1, uint32_t a0, uint32_t a1, uint32_t b0) {
    asm volatile("mma.sync.aligned.m16n8k8.row.col.f16.f16.f16.f16 {%0,%1}, {%2,%3}, {%4}, {%5,%5};"
        : "=r"(d0), "=r"(d1) : "r"(a0), "r"(a1), "r"(b0), "r"(0));
}
__device__ __forceinline__ uint32_t pin(uint32_t x, int lane) { return __shfl_sync(0xffffffffu, x, lane); }
template <class T> __device__ __forceinline__ T* pin(T* x, int lane) { return (T*)__shfl_sync(0xffffffffu, (unsigned long long)x, lane); }
__device__ __forceinline__ void sts32_if(bool on, uint32_t a, uint32_t v) {
    asm volatile("{\n\t.reg .pred p;\n\tsetp.ne.u32 p, %2, 0;\n\t@p st.shared.u32 [%0], %1;\n\t}" :: "r"(a), "r"(v), "r"((uint32_t)on) : "memory");
}
__device__ __forceinline__ void sts128_if(bool on, uint32_t a, uint32_t x, uint32_t y, uint32_t z, uint32_t w) {
    asm volatile("{\n\t.reg .pred p;\n\tsetp.ne.u32 p, %5, 0;\n\t@p st.shared.v4.u32 [%0], {%1,%2,%3,%4};\n\t}" :: "r"(a), "r"(x), "r"(y), "r"(z), "r"(w), "r"((uint32_t)on) : "memory");
}
__device__ __forceinline__ void lds128_if(bool on, uint32_t a, uint32_t (&v)[4]) {
    asm volatile("{\n\t.reg .pred p;\n\tsetp.ne.u32 p, %5, 0;\n\t@p ld.shared.v4.u32 {%0,%1,%2,%3}, [%4];\n\t}"
        : "+r"(v[0]), "+r"(v[1]), "+r"(v[2]), "+r"(v[3]) : "r"(a), "r"((uint32_t)on) : "memory");
}
__device__ __forceinline__ uint32_t hfma2_bf(uint32_t a, uint32_t b, uint32_t c) { uint32_t r; asm("fma.rn.bf16x2 %0, %1, %2, %3;" : "=r"(r) : "r"(a), "r"(b), "r"(c)); return r; }
__device__ __forceinline__ uint32_t row_elem(uint32_t row) { return ((row >> 5) & 4) | ((row >> 2) & 2) | ((row >> 4) & 1); }
__device__ __forceinline__ uint32_t gate_pos(uint32_t row) { return ((row >> 9) << 8) | ((row & 7) << 5) | (row_elem(row) << 2) | ((row >> 5) & 3); }

template <int N, bool BULK>
__device__ __forceinline__ void mix_rows(const Params& p, const CUtensorMap* tm_out, uint32_t sb, uint32_t ob, int Q0, int Q1, int w, int h, int pr, int lane) {
    const int g = lane >> 2, t = lane & 3, mi = lane >> 3, r = lane & 7;
    const int m8 = 16 * (g >> 2) + ((g >> 1) & 1) + 2 * (g & 1);
    uint32_t yi = sb + (4 * (r >> 1) + 2 * (mi & 1) + (r & 1)) * 512 + (((4 * w + (mi >> 1)) ^ r) << 4);
    uint32_t xs = sb + OFF_S + s_addr(w * S_PL + 32 + m8 * 32, t >> 1) + ((t & 1) << 3);
    uint32_t gs = sb + OFF_GP + w * 64 + g * 8, os = ob + m8 * 32 + t * 8;
    if (N > 1) { yi = pin(yi, lane); xs = pin(xs, lane); gs = pin(gs, lane); os = pin(os, lane); }
    mbar_wait(sb + M_BARS + 8 * B_Y);
#pragma unroll 1
    for (int Q = Q0; Q < Q1; Q++) {
        uint2 xq[N][4];
        uint32_t gg[N][4], sw[N];
#pragma unroll
        for (int n = 0; n < N; n++) {
#pragma unroll
            for (int i = 0; i < 4; i++) xq[n][i] = lds64((xs ^ (((i ^ n) & 1) << 4)) + Q * S_Q + n * 4 * S_PL + i * 128);
            const uint2 gq = lds64(gs + Q * 512 + n * 256);
            sw[n] = lds32(sb + M_BMAP + w * 16 + n * 64 + Q * 4);
#pragma unroll
            for (int i = 0; i < 4; i++) {
                gg[n][i] = __byte_perm(i < 2 ? gq.x : gq.y, 0, (i & 1) ? 0x3232 : 0x1010);
                const uint32_t og = hfma2_bf(gg[n][i], 0xBF80BF80u, 0x3F803F80u);
                xq[n][i].x = hmul2_bf(og, xq[n][i].x); xq[n][i].y = hmul2_bf(og, xq[n][i].y);
            }
        }
        mbar_wait(sb + M_BARS + 8 * (B_Y + Q));
        __syncwarp();
#pragma unroll
        for (int n = 0; n < N; n++) {
#pragma unroll
            for (int x = 0; x < 2; x++) {
                uint32_t y[4];
                ldsm4t((yi ^ (x << 5)) + y_off(Q) + n * 256, y[0], y[1], y[2], y[3]);
#pragma unroll
                for (int e = 0; e < 2; e++) {
                    uint2& o = xq[n][2 * x + e];
                    o.x = hfma2_bf(gg[n][2 * x + e], y[2 * e], o.x); o.y = hfma2_bf(gg[n][2 * x + e], y[2 * e + 1], o.y);
                }
            }
        }
        if (BULK && (sw[0] | sw[N - 1]) == 0) {
#pragma unroll
            for (int n = 0; n < N; n++)
#pragma unroll
                for (int i = 0; i < 4; i++)
                    asm volatile("st.shared.v2.u32 [%0], {%1, %2};" :: "r"(os + Q * 1024 + n * 4 * TAB_W + i * 128), "r"(xq[n][i].x), "r"(xq[n][i].y) : "memory");
            asm volatile("fence.proxy.async.shared::cta;" ::: "memory");
            __syncwarp();
#pragma unroll
            for (int n = 0; n < N; n++)
                asm volatile("{\n\t.reg .pred p;\n\telect.sync _|p, 0xffffffff;\n\t"
                             "@p cp.async.bulk.tensor.3d.global.shared::cta.bulk_group [%1, {%2, %3, %4}], [%0];\n\t}"
                    :: "r"(ob + 4 * n * TAB_W + Q * 1024), "l"(tm_out), "r"(16 * pr), "r"(64 * Q + 32 * h), "r"(w + 4 * n) : "memory");
        } else {
            bf16* op = p.out + (size_t)(512 * Q + 256 * h + 8 * m8 + w) * D_ + 16 * pr + 4 * t;
#pragma unroll
            for (int n = 0; n < N; n++)
#pragma unroll
                for (int i = 0; i < 4; i++)
                    if (!((sw[n] >> (4 * g)) & (1u << i))) *(uint2*)(op + (size_t)(32 * i + 4 * n) * D_) = xq[n][i];
        }
    }
}

__global__ void __cluster_dims__(2, 1, 1) __launch_bounds__(NTHREADS, 1)
fused_kernel(const Params p, const __grid_constant__ CUtensorMap tm_gu, const __grid_constant__ CUtensorMap tm_down,
             const __grid_constant__ CUtensorMap tm_x, const __grid_constant__ CUtensorMap tm_out) {
    extern __shared__ __align__(1024) unsigned char smem[];
    const uint32_t sb = smem_u32(smem);
    int tid;
    asm volatile("mov.u32 %0, %%tid.x;" : "=r"(tid));
    const int pw = tid >> 5, lane = tid & 31;
    const int c = blockIdx.x, h = c & 1, pr = c >> 1;
    const uint32_t bars = sb + M_BARS;

    uint2 v_la, v_ai, v_cr, v_ci;
    uint32_t ldt16;
    {
        const uint32_t po = c * 256 + tid;
        asm volatile("{\n\t.reg .pred p;\n\t.reg .b64 a;\n\tsetp.ne.u32 p, %16, 0;\n\t"
                     "mad.wide.u32 a, %14, 8, %9;\n\t@p ld.global.nc.L1::no_allocate.v2.u32 {%0,%1}, [a];\n\t"
                     "mad.wide.u32 a, %15, 2, %13;\n\t@p ld.global.nc.u16 %8, [a];\n\t"
                     "mad.wide.u32 a, %14, 8, %10;\n\t@p ld.global.nc.L1::no_allocate.v2.u32 {%2,%3}, [a];\n\t"
                     "mad.wide.u32 a, %14, 8, %11;\n\t@p ld.global.nc.L1::no_allocate.v2.u32 {%4,%5}, [a];\n\t"
                     "mad.wide.u32 a, %14, 8, %12;\n\t@p ld.global.nc.L1::no_allocate.v2.u32 {%6,%7}, [a];\n\t}"
            : "=r"(v_la.x), "=r"(v_la.y), "=r"(v_ai.x), "=r"(v_ai.y), "=r"(v_cr.x), "=r"(v_cr.y), "=r"(v_ci.x), "=r"(v_ci.y), "=r"(ldt16)
            : "l"(p.logA), "l"(p.Aim), "l"(p.Cre), "l"(p.Cim), "l"(p.logdt), "r"(po), "r"(po >> 5), "r"((uint32_t)(tid < 256 && c < 128)));
    }

    if (c >= 128) {
        if (c != 128) return;
        RSTAMP(5);
        const unsigned tag = (*(volatile unsigned*)&p.sc->epoch + 1) & 0xffffu;
        const uint32_t list = sb + 128;
#pragma unroll 1
        for (int pass = 0; pass < 2; pass++) {
            sts128(list + 16 * tid, 0, 0, 0, 0);
            if (tid == 0) sts32(sb + 64, 0);
            uint32_t key[4];
            bool ok = false;
#pragma unroll 1
            for (int it = 0; it < (1 << 22); it++) {
                const uint4 a = ld_gpu128(&p.sc->r[tid * RS]);
                key[0] = a.x; key[1] = a.y; key[2] = a.z; key[3] = a.w;
                ok = (((a.x ^ tag) | (a.y ^ tag) | (a.z ^ tag) | (a.w ^ tag)) & 0xffffu) == 0;
                if (ok || !pass) break;
            }
            WSTAMP(0);
            uint32_t m = 0;
#pragma unroll
            for (int i = 0; i < 4; i++) {
                key[i] = ((pass ? key[i] : (lane + i) << 16) & 0xffff0000u) | (uint32_t)(2047 - (4 * tid + i));
                m = max(m, key[i]);
            }
            const uint32_t wm = __reduce_max_sync(0xffffffffu, m);
            if (lane == 0) sts32(sb + pw * 4, wm);
            __syncthreads();
            uint32_t thr = 0xffffffffu;
#pragma unroll
            for (int i = 0; i < 4; i++) { const uint4 q = lds128(sb + 16 * i); thr = min(thr, min(max(q.x, q.y), max(q.z, q.w))); }
            if (thr != 1) WSTAMP(1);
            if (m >= thr) {
                uint32_t pos;
                asm volatile("atom.shared.add.u32 %0, [%1], %2;" : "=r"(pos) : "r"(sb + 64), "r"(4 * ((key[0] >= thr) + (key[1] >= thr) + (key[2] >= thr) + (key[3] >= thr))) : "memory");
#pragma unroll
                for (int i = 0; i < 4; i++) if (key[i] >= thr) { sts32(list + pos, key[i]); pos += 4; }
            }
            __syncthreads();
            const uint32_t nc4 = lds32(sb + 64);
            if (nc4 != 1) WSTAMP(2);
#pragma unroll 1
            for (uint32_t j = 4 * pw; j < nc4; j += 64) {
                const uint32_t mine = lds32(list + j);
                int rank = 0;
#pragma unroll 1
                for (uint32_t i = 0; i < nc4; i += 128) rank += __popc(__ballot_sync(0xffffffffu, lds32(list + i + 4 * lane) > mine));
                if (rank < 8 && lane == 0) sts32(sb + 96 + 4 * rank, mine);
            }
            __syncthreads();
            if (tid < 8 * NTOP) st_gpu32(&p.sc->top[tid >> 3][tid & 7], lds32(sb + 96 + 4 * (tid & 7)) | (((tag + pass - 1) & 31) << 11));
            WSTAMP(3);
            if (!pass) RSTAMP(4);
        }
        WDUMP();
        return;
    }

    WSTAMP(0);
    if (pw < 8) {
        const int d = 8 * c + pw - MAIN_W0;
        if (lane == 0) asm volatile("cp.async.ca.shared.global [%0], [%1], 4;" :: "r"(sb + M_DSK + 4 * (pw - MAIN_W0)), "l"(p.Dskip + (d & ~1)) : "memory");
        asm volatile("barrier.cluster.arrive.relaxed.aligned;" ::: "memory");
        const int warp = pw - MAIN_W0;
        asm volatile("setmaxnreg.inc.sync.aligned.u32 168;");
        const int g = lane >> 2, t = lane & 3;
        const int mi = lane >> 3, r = lane & 7;
        const uint32_t TB = sb + OFF_TAB + warp * TAB_W;
        const uint32_t UB = sb + OFF_U + warp * U_CH;
        if (mi < 2) sts128(UB + mi * U_PL + r * 16, 0, 0, 0, 0);
        if (lane < 4) sts128(TB + lane * T_PL, 0, 0, 0, 0);
        sts128(sb + OFF_SCR + warp * 8192 + lane * 16, 0x3C00u, 0x3C00u, 0x3C00u, 0x3C00u);
        __syncwarp();

        uint32_t cfix;
        {
            KSTAMP(4, v_la.x ^ v_ai.x ^ v_cr.x ^ v_ci.x ^ ldt16);
            const float dt = bf_round(exp_acc(__uint_as_float(ldt16 << 16)));
            float l2[4], li[4];
            {
                const uint32_t la[2] = {v_la.x, v_la.y}, ai[2] = {v_ai.x, v_ai.y};
                const float dt2 = -1.4426950408889634f * dt;
#pragma unroll
                for (int i = 0; i < 4; i++) {
                    l2[i] = bf_round(ex2f(((i & 1) ? bf_hi(la[i >> 1]) : bf_lo(la[i >> 1])) * 1.4426950408889634f)) * dt2;
                    li[i] = ((i & 1) ? bf_hi(ai[i >> 1]) : bf_lo(ai[i >> 1])) * dt;
                }
            }
            const uint32_t SX = sb + OFF_SCR + warp * 8192;
            const uint32_t sw = SX + (lane << 4);
#define PUT(buf, row, v) sts128(((sw + (row) * 512) ^ ((row) << 4)) + (buf) * 4096, v[0], v[1], v[2], v[3])
#define EMIT(bufa, rowa, bufb, rowb, xr, xi, k, kp) do { uint32_t pk[4], pd[4]; \
                _Pragma("unroll") for (int i = 0; i < 4; i++) { pk[i] = pack_h(xr[i], xi[i]); pd[i] = hcmul(pk[i], k[i], kp[i]); } \
                PUT(bufa, rowa, pk); PUT(bufb, rowb, pd); } while (0)
#define CMUL4(orr, oi, ar, ai, br, bi) _Pragma("unroll") for (int i = 0; i < 4; i++) CMUL(orr[i], oi[i], ar[i], ai[i], br[i], bi[i])
#define CSQ4(orr, oi, ar, ai) _Pragma("unroll") for (int i = 0; i < 4; i++) CSQ(orr[i], oi[i], ar[i], ai[i])
            float z1r[4], z1i[4], z2r[4], z2i[4], z8r[4], z8i[4], z256r[4], z256i[4];
            uint32_t k4[4], k4p[4];
            float z4r[4], z4i[4];
#pragma unroll
            for (int i = 0; i < 4; i++) cexp_pow(l2[i], li[i], 1.f, z1r[i], z1i[i]);
            CSQ4(z2r, z2i, z1r, z1i);
            CSQ4(z4r, z4i, z2r, z2i);
            CSQ4(z8r, z8i, z4r, z4i);
            KSTAMP(5, __float_as_uint(z8r[3]));
            uint32_t Ya[16][4];
            float cr[4], ci[4], inv;
            {
                float w1r[4], w1i[4], ar[4], ai[4], br[4], bi[4];
                uint32_t k8[4], k8p[4];
#pragma unroll
                for (int i = 0; i < 4; i++) {
                    k8[i] = pack_h(z8r[i], -z8i[i]); k8p[i] = pack_h(z8i[i], z8r[i]);
                    CSQ(w1r[i], w1i[i], z8r[i], z8i[i]); w1i[i] = -w1i[i];
                }
                PUT(1, 0, k8);
                EMIT(0, 1, 1, 1, w1r, w1i, k8, k8p);
                CSQ4(ar, ai, w1r, w1i);            EMIT(0, 2, 1, 2, ar, ai, k8, k8p);
                CMUL4(br, bi, ar, ai, w1r, w1i);   EMIT(0, 3, 1, 3, br, bi, k8, k8p);
                CSQ4(ar, ai, ar, ai);              EMIT(0, 4, 1, 4, ar, ai, k8, k8p);
                CMUL4(ar, ai, ar, ai, w1r, w1i);   EMIT(0, 5, 1, 5, ar, ai, k8, k8p);
                CSQ4(br, bi, br, bi);              EMIT(0, 6, 1, 6, br, bi, k8, k8p);
                CMUL4(br, bi, br, bi, w1r, w1i);   EMIT(0, 7, 1, 7, br, bi, k8, k8p);
                __syncwarp();
                KSTAMP(6, 0);
                const uint32_t ab = SX + (mi & 1) * 4096 + r * 512, ax = ((mi >> 1) ^ r) << 4;
                const uint32_t vr[2] = {v_cr.x, v_cr.y}, vi[2] = {v_ci.x, v_ci.y};
                const uint32_t m2 = __vmaxu2(__vmaxu2(vr[0] & 0x7fff7fffu, vr[1] & 0x7fff7fffu), __vmaxu2(vi[0] & 0x7fff7fffu, vi[1] & 0x7fff7fffu));
                const uint32_t mx = __reduce_max_sync(0xffffffffu, max(m2, m2 << 16));
                const uint32_t e = min(max(mx >> 23, 11u), 254u);
                const float sc = __uint_as_float((264u - e) << 23);
                inv = __uint_as_float((e - 10u) << 23) * (2.f * dt);
#pragma unroll
                for (int i = 0; i < 4; i++) {
#pragma unroll
                    for (int k = 0; k < 4; k++) ldsm4(ab + (ax ^ (i << 5)) + k * 128, Ya[4 * k + i][0], Ya[4 * k + i][1], Ya[4 * k + i][2], Ya[4 * k + i][3]);
                    float tr, ti;
                    cexp_pow(l2[i], li[i], 128.f, tr, ti);
                    sts32(TB + 2176 + 256 * i + 4 * lane, pack_h(tr, ti));
                    sts32(TB + 2176 + 256 * i + 128 + 4 * (lane ^ 16), pack_h(-ti, tr));
                    k4[i] = pack_h(z4r[i], z4i[i]); k4p[i] = pack_h(-z4i[i], z4r[i]);
                    CSQ(z256r[i], z256i[i], tr, ti);
                    cr[i] = ((i & 1) ? bf_hi(vr[i >> 1]) : bf_lo(vr[i >> 1])) * sc;
                    ci[i] = ((i & 1) ? bf_hi(vi[i >> 1]) : bf_lo(vi[i >> 1])) * sc;
                }
                __syncwarp();
            }
            KSTAMP(7, Ya[15][0]);
            const uint32_t ld0 = SX + r * 512 + ((mi ^ r) << 4), ld1 = ld0 ^ 64;
            float R[6][4], s1024;
            {
                float xr[4], xi[4], yr[4], yi[4];
                EMIT(0, 0, 0, 1, cr, ci, k4, k4p);
                CMUL4(yr, yi, cr, ci, z1r, z1i);        EMIT(0, 2, 0, 3, yr, yi, k4, k4p);
                CMUL4(xr, xi, cr, ci, z256r, z256i);    EMIT(1, 0, 1, 1, xr, xi, k4, k4p);
                CMUL4(yr, yi, yr, yi, z1r, z1i);        EMIT(0, 4, 0, 5, yr, yi, k4, k4p);
                CMUL4(cr, ci, xr, xi, z2r, z2i);        EMIT(1, 2, 1, 3, cr, ci, k4, k4p);
                CMUL4(yr, yi, yr, yi, z1r, z1i);        EMIT(0, 6, 0, 7, yr, yi, k4, k4p);
                CMUL4(xr, xi, xr, xi, z256r, z256i);    EMIT(1, 4, 1, 5, xr, xi, k4, k4p);
                CMUL4(xr, xi, xr, xi, z256r, z256i);    EMIT(1, 6, 1, 7, xr, xi, k4, k4p);
                CMUL4(xr, xi, xr, xi, z256r, z256i);
                s1024 = (xr[0] + xr[1]) + (xr[2] + xr[3]);
#pragma unroll
                for (int m = 0; m < 4; m++) {
                    if (m == 0) { CMUL4(xr, xi, xr, xi, z8r, z8i); } else { CMUL4(xr, xi, xr, xi, z256r, z256i); }
                    sts128(TB + m * T_PL + 16 + 16 * lane, pack_h(xr[0], xi[0]), pack_h(xr[1], xi[1]), pack_h(xr[2], xi[2]), pack_h(xr[3], xi[3]));
                }
            }
            asm volatile("barrier.cluster.wait.acquire.aligned;" ::: "memory");
            __syncwarp();
            {
                KSTAMP(8, 0);
                uint32_t bd[2][4] = {{0, 0, 0, 0}, {0, 0, 0, 0}};
                const bool on = (g >> 1) == t;
#pragma unroll
                for (int i = 0; i < 6; i++) { R[i][0] = R[i][1] = R[i][2] = R[i][3] = 0.f; }
#pragma unroll
                for (int k2 = 0; k2 < 8; k2++) {
                    uint32_t x[4], y[4], z[4], a1[2][4];
                    lds128_if(on, TB + 2176 + g * 128 + (k2 < 4 ? 64 : -64) * (g & 1) + 16 * k2, bd[k2 & 1]);
                    ldsm4(TB + (r & 3) * T_PL + 16 + 16 * mi + 64 * k2, z[0], z[1], z[2], z[3]);
                    ldsm4(((k2 & 1) ? ld1 : ld0) + (k2 >> 1) * 128, x[0], x[1], x[2], x[3]);
                    ldsm4(((k2 & 1) ? ld1 : ld0) + (k2 >> 1) * 128 + 4096, y[0], y[1], y[2], y[3]);
#pragma unroll
                    for (int u = 0; u < 2; u++) {
                        mma_hh_k8(a1[u][0], a1[u][1], Ya[2 * k2 + u][0], Ya[2 * k2 + u][1], bd[k2 & 1][2 * u]);
                        mma_hh_k8(a1[u][2], a1[u][3], Ya[2 * k2 + u][2], Ya[2 * k2 + u][3], bd[k2 & 1][2 * u + 1]);
                    }
#pragma unroll
                    for (int u = 0; u < 2; u++) {
                        const uint32_t(&a0)[4] = Ya[2 * k2 + u];
                        mma_h(R[0], a0[0], a0[1], a0[2], a0[3], x[2 * u], x[2 * u + 1]);
                        mma_h(R[2], a0[0], a0[1], a0[2], a0[3], y[2 * u], y[2 * u + 1]);
                        mma_h(R[4], a0[0], a0[1], a0[2], a0[3], z[2 * u], z[2 * u + 1]);
                        mma_h(R[1], a1[u][0], a1[u][1], a1[u][2], a1[u][3], x[2 * u], x[2 * u + 1]);
                        mma_h(R[3], a1[u][0], a1[u][1], a1[u][2], a1[u][3], y[2 * u], y[2 * u + 1]);
                        mma_h(R[5], a1[u][0], a1[u][1], a1[u][2], a1[u][3], z[2 * u], z[2 * u + 1]);
                    }
                }
            }
            __syncwarp();
            KSTAMP(9, __float_as_uint(R[3][0]));
            if (lane == 0) mbar_arrive(bars + 8 * B_KG + (__float_as_uint(R[0][0]) & __float_as_uint(R[2][0]) & p.zero));
            sts128(TB + 2176 + 16 * lane, 0, 0, 0, 0);
            sts128(TB + 2688 + 16 * lane, 0, 0, 0, 0);
            __syncwarp();
#undef PUT
#undef EMIT
#pragma unroll
            for (int o = 16; o > 0; o >>= 1) s1024 += __shfl_xor_sync(0xffffffffu, s1024, o);
            uint32_t w[4][4], dsk = 0;
            cp_wait_all();
            asm volatile("{\n\t.reg .pred p;\n\tsetp.eq.u32 p, %2, 0;\n\t@p ld.shared.u16 %0, [%1];\n\t}" : "+r"(dsk) : "r"(sb + M_DSK + 4 * warp + 2 * (warp & 1)), "r"(lane) : "memory");
#pragma unroll
            for (int a = 0; a < 4; a++) {
                const float v0 = (a == 0) ? fmaf(R[0][0], inv, __uint_as_float(dsk << 16)) : R[a][0] * inv;
                const float v1 = R[a][1] * inv, v2 = R[a][2] * inv, v3 = R[a][3] * inv;
                w[a][0] = pack_bf(v0, 0.f); w[a][1] = pack_bf(v1, v0); w[a][2] = pack_bf(v2, v1); w[a][3] = pack_bf(v3, v2);
            }
            const uint32_t wb = TB + 16 + 16 * g, w1 = wb + t * T_PL, w2 = wb + 256 + 2 * t * T_PL;
            const uint32_t w3 = (t == 0) ? wb + 256 + 3 * T_PL : TB + T_A + 8 * (16 * t + g);
            const uint32_t w3s = (t == 0) ? 128 : 64, w3o = (t == 0) ? 8 : 12;
            const uint32_t k512 = __shfl_sync(0xffffffffu, w[2][1], 2);
#pragma unroll
            for (int a = 0; a < 2; a++) {
                sts128(w1 + 128 * a, w[a][0], w[a][1], w[a][2], w[a][3]);
                const uint32_t(&q)[4] = w[2 + a];
                if (t < 2) sts128(w2 + 128 * a, q[0], q[1], q[2], q[3]);
                if (t == 0) { sts128(w2 + T_PL + 128 * a, q[0], q[1], q[2], q[3]); sts32(w3 + 128 * a + 4, q[2]); }
                sts32_if(t != 1 && (a == 1 || lane != 2), w3 + w3s * a, q[1]);
                sts32_if(t != 1, w3 + w3s * a + w3o, q[3]);
            }
            sts128_if(lane < 4, w1 + 512, t == 3 ? k512 : k512 >> 16, t < 2 ? k512 : t == 2 ? k512 & 0xffff0000u : k512 << 16, t < 2 ? k512 << 16 : 0u, 0);
            __syncwarp();
#pragma unroll
            for (int a = 0; a < 2; a++) {
                sts16(w1 + 128 * a + 18, w[a][3]);
                const uint32_t(&q)[4] = w[2 + a];
                if (t < 2) sts16(w2 + 128 * a + 18, q[3]);
                if (t == 0) { sts16(w2 + T_PL + 128 * a + 18, q[3]); sts16(w3 + 128 * a + 14, q[3]); }
            }
            if (t == 0) sts16(w3 + 128 - 4, w[3][0]);
            if (lane == 2 || (t == 0 && g > 0)) sts16(lane == 2 ? TB + 16 + 3 * T_PL + 4 * 127 : w3 - 4, w[2][0]);
            {
                float q[4];
#pragma unroll
                for (int i = 0; i < 4; i++) q[i] = (t < 2 ? R[4][i] : R[5][i]) * inv;
                const uint32_t b0 = pack_bf(q[0], q[2]), b1 = pack_bf(q[1], q[3]);
                const uint32_t wq = TB + T_B + 8 * (65 + 32 * (t & 1) + 4 * (t & 2) + g);
                sts32(wq, b0); sts32(wq + 12, b0); sts32(wq + 128, b1); sts32(wq + 140, b1);
            }
            cfix = pack_bf(s1024 * inv, s1024 * inv);
            if (lane == 0) sts32(TB + T_A + 8 * 64, cfix);
            __syncwarp();
        }
        WSTAMP(1);

        mbar_wait(bars + 8 * B_U);
        WSTAMP(2);

        float D[16][4];
        {
            const int x5 = g - t + 5;
            const uint32_t tabD = TB + (x5 & 3) * T_PL + (x5 & 12) + 16;
            {
                const uint32_t a1 = lds32(tabD - 8), a0 = p.zero;
#pragma unroll
                for (int jq = 0; jq < 4; jq++) {
                    uint32_t b[4];
                    ldsm4(UB + (9 + lane) * 16 + jq * 512, b[0], b[1], b[2], b[3]);
#pragma unroll
                    for (int i = 0; i < 4; i++) mma_bf_k8z(D[4 * jq + i], a0, a1, b[i]);
                }
            }
            const uint32_t ua = UB + (mi & 1) * U_PL + (8 + 8 * (mi >> 1) + r) * 16;
#pragma unroll 1
            for (int k0 = 0; k0 < 8; k0++) {
                uint32_t Uf[16][2];
#pragma unroll
                for (int jp = 0; jp < 8; jp++) ldsm4(ua + jp * 256 - k0 * 16, Uf[2 * jp][0], Uf[2 * jp][1], Uf[2 * jp + 1][0], Uf[2 * jp + 1][1]);
#pragma unroll
                for (int k1 = 0; k1 < 4; k1++) {
                    const uint32_t ta = tabD + 16 * (8 * k1 + k0);
                    const uint32_t a0 = lds32(ta), a1 = lds32(ta + 8), a2 = lds32(ta - 8), a3 = a0 ^ p.zero;
#pragma unroll
                    for (int J = k1; J < 16; J++) mma_bf(D[J], a0, a1, a2, a3, Uf[J - k1][0], Uf[J - k1][1]);
                }
                if (k0 == 0) {
                    const uint32_t ta = tabD + 16 * 32;
                    const uint32_t a0 = lds32(ta), a1 = lds32(ta + 8), a2 = lds32(ta - 8), a3 = a0 ^ p.zero;
#pragma unroll
                    for (int J = 4; J < 16; J++) mma_bf(D[J], a0, a1, a2, a3, Uf[J - 4][0], Uf[J - 4][1]);
                    const uint32_t f0 = (cfix ^ 0x80008000u) & (g == t ? 0xffffu : g == t + 4 ? 0xffff0000u : 0u);
                    const uint32_t f1 = p.zero, f2 = p.zero + p.zero, f3 = f0 ^ p.zero;
#pragma unroll
                    for (int J = 8; J < 16; J++) mma_bf(D[J], f0, f1, f2, f3, Uf[J - 8][0], Uf[J - 8][1]);
                }
            }
        }
        WSTAMP(3);
        {
            const int ch = 8 * h + warp;
            const uint32_t yo = sb + ch * 512 + ((lane ^ (((ch >> 2) << 1) | (ch & 1))) << 4);
            const uint32_t yr = mapa(yo, h ^ 1), ybr = mapa(bars + 8 * B_Y, h ^ 1);
            auto ship = [&](const int Q) {
                uint4 y[2];
#pragma unroll
                for (int hh = 0; hh < 2; hh++) {
                    const int J = 4 * Q + 2 * hh;
                    y[hh] = make_uint4(pack_bf(D[J][0], D[J][1]), pack_bf(D[J][2], D[J][3]), pack_bf(D[J + 1][0], D[J + 1][1]), pack_bf(D[J + 1][2], D[J + 1][3]));
                }
                if (!(Q & 1)) mbar_wait(bars + 8 * (B_F + (Q >> 1)));
                asm volatile("{\n\t.reg .pred p;\n\tsetp.eq.u32 p, %11, 0;\n\t"
                             "@p st.async.weak.shared::cluster.mbarrier::complete_tx::bytes.v4.b32 [%9], {%4,%5,%6,%7}, [%10];\n\t"
                             "@!p st.async.weak.shared::cluster.mbarrier::complete_tx::bytes.v4.b32 [%9], {%0,%1,%2,%3}, [%10];\n\t"
                             "@p st.shared.v4.b32 [%8], {%0,%1,%2,%3};\n\t@!p st.shared.v4.b32 [%8], {%4,%5,%6,%7};\n\t}"
                             :: "r"(y[0].x), "r"(y[0].y), "r"(y[0].z), "r"(y[0].w), "r"(y[1].x), "r"(y[1].y), "r"(y[1].z), "r"(y[1].w),
                                "r"(yo + y_off(Q)), "r"(yr + y_off(Q)), "r"(ybr + 8 * Q), "r"(h) : "memory");
                __syncwarp();
                if (lane == 0) mbar_arrive(bars + 8 * (B_Y + Q));
            };
            ship(0);
            const uint4 bA = lds128(sb + OFF_BAND + (g - t + 3) * 48), bB = lds128(sb + OFF_BAND + (g - t + 3) * 48 + 16);
            const uint2 bC = lds64(sb + OFF_BAND + (g - t + 3) * 48 + 32);
            uint2 QA[5][2], QB[8];
            const uint32_t tq = TB + 8 * (1 + g - 2 * t);
#pragma unroll
            for (int dd = 0; dd < 5; dd++) { QA[dd][0] = lds64(tq + T_A + 64 * (dd + 4)); QA[dd][1] = lds64(tq + T_A + 64 * (dd + 4) - 8); }
#pragma unroll
            for (int dd = 0; dd < 8; dd++) QB[dd] = lds64(tq + T_B + 64 * (dd + 8));
            const uint32_t u1 = UB + (mi & 1) * U_PL + (7 + r + (mi >> 1)) * 16;
            const uint32_t u2 = UB + ((mi & 1) ^ 1) * U_PL + (7 + r + (mi & 1) + 8 * (mi >> 1)) * 16;
            uint32_t n[4];
#pragma unroll
            for (int j = 0; j < 12; j++) {
                uint32_t m[4];
                ldsm4(u1 + j * 128, m[0], m[1], m[2], m[3]);
                if (!(j & 1)) ldsm4(u2 + j * 128, n[0], n[1], n[2], n[3]);
                const uint32_t n0 = n[2 * (j & 1)], n1 = n[2 * (j & 1) + 1];
                float wa[4], wb[4], wc[4], g1[4], g2[4];
                mma_bf_z(wa, bA.x, bA.y, bA.z, bA.w, m[0], m[1]);
                mma_bf_z(wb, bA.x, bA.y, bA.z, bA.w, n0, n1);
                mma_bf_z(wc, bA.x, bA.y, bA.z, bA.w, m[2], m[3]);
                if (j < 8) {
                    mma_bf_z(g1, bB.x, bB.y, bB.z, bB.w, m[0], m[1]);
                    mma_bf_z(g2, bB.x, bB.y, bB.z, bB.w, n0, n1);
                    mma_bf_k8(g1, bC.x, bC.y, m[2]);
                    mma_bf_k8(g2, bC.x, bC.y, m[3]);
                }
#pragma unroll
                for (int e = 0; e < 2; e++) {
                    const uint32_t q0 = pack_bf(wa[e], wa[e + 2]), q1 = pack_bf(wb[e], wb[e + 2]), q2 = q1 ^ p.zero, q3 = pack_bf(wc[e], wc[e + 2]);
#pragma unroll
                    for (int dd = 0; dd < 5; dd++)
                        if (j + 4 + dd < 16) mma_bf(D[j + 4 + dd], q0, q1, q2, q3, QA[dd][e].x, QA[dd][e].y);
                }
                if (j < 8) {
                    const uint32_t q0 = pack_bf(g1[0], g1[2]), q1 = pack_bf(g2[0], g2[2]), q2 = pack_bf(g1[1], g1[3]), q3 = pack_bf(g2[1], g2[3]);
#pragma unroll
                    for (int dd = 7 - j; dd >= 0; dd--) mma_bf(D[j + 8 + dd], q0, q1, q2, q3, QB[dd].x, QB[dd].y);
                }
                if ((j & 3) == 3) {
                    WSTAMP(4 + 2 * (j >> 2));
                    if (j == 11 && LATE2) ship(2);
                    if (j != 7 || !LATE2) ship((j >> 2) + 1);
                }
            }
        }
        const int warpu = __reduce_max_sync(0xffffffffu, warp);
        mix_rows<1, BULKM>(p, &tm_out, sb, sb + OFF_U + warpu * U_CH + (warpu & 1) * 64, PQ, 4, warpu, h, pr, lane);
        if (BULKM) asm volatile("cp.async.bulk.commit_group;\n\tcp.async.bulk.wait_group.read 0;" ::: "memory");
        WSTAMP(10);
        WDUMP();
    } else if ((pw & 12) == AUX_W0) {
        asm volatile("setmaxnreg.inc.sync.aligned.u32 136;");
        const int v = __reduce_max_sync(0xffffffffu, pw & 3);
        const int at = tid & 127;
        const int g = lane >> 2, t = lane & 3;
        unsigned tag;
        const bool gu = c < NGU_CTA;
        {
            uint4 xa[16];
            const uint32_t xb = sb + (v < 2 ? OFF_XSEL : OFF_RING + 2 * 8192) + v * 8192;
            const uint32_t gws = sb + (gu ? M_DPIN : OFF_RING + 2 * 8192);
            const uint32_t row = 16 * c + 4 * v + (g >> 1);
            const unsigned epoch = *(volatile unsigned*)&p.sc->epoch;
#pragma unroll
            for (int i = 0; i < 4; i++)
                asm volatile("cp.async.ca.shared.global [%0], [%1], 4;" :: "r"(sb + OFF_GP + 512 * i + (tid & 124) * 4 + (tid & 1) * 8 + (tid & 2) * 2),
                             "l"(p.wr + 256 * i + (tid & 127) * 2) : "memory");
            cp16(gws + (tid & 127) * 16, p.gatew + (tid & 127) * 8);
            if ((tid & 127) < 33) cp16(sb + OFF_BAND + (tid & 127) * 16, p.band + (tid & 127));
            asm volatile("barrier.cluster.arrive.relaxed.aligned;" ::: "memory");
            tag = __reduce_max_sync(0xffffffffu, (epoch + 1) & 0xffffu);
            if (gu) st_gpu32((uint32_t*)&p.sc->h[(tag + 1) & 1][32 * c] + at, 0);
            if (v == 0) sts32(sb + M_BMAP + lane * 4, 0);
            cp_wait_all();
            bar_sync(1, 128);
            uint2 w[16];
#pragma unroll
            for (int kb = 0; kb < 16; kb++) w[kb] = lds64(sb + OFF_GP + 128 * kb + 32 * (g & 2) + 16 * t + 8 * (g & 1));
            asm volatile("barrier.cluster.wait.acquire.aligned;" ::: "memory");
            mbar_wait(bars + 8 * (B_X + v));
            WSTAMP(10);
#pragma unroll
            for (int kb = 0; kb < 16; kb++) xa[kb] = lds128(xb + (g >> 1) * 2048 + 128 * kb + 16 * (lane & 7));
            float dr[4][4];
#pragma unroll
            for (int kb = 0; kb < 16; kb++) {
                if (kb < 4) mma_bf_z(dr[kb], xa[kb].x, xa[kb].y, xa[kb].z, xa[kb].w, w[kb].x, w[kb].y);
                else mma_bf(dr[kb & 3], xa[kb].x, xa[kb].y, xa[kb].z, xa[kb].w, w[kb].x, w[kb].y);
            }
            float rs = ((dr[0][0] + dr[0][3]) + (dr[1][0] + dr[1][3])) + ((dr[2][0] + dr[2][3]) + (dr[3][0] + dr[3][3]));
            if (lane == 0) mbar_arrive(bars + 8 * (B_XE + v) + (__float_as_uint(rs) & p.zero));
            rs += __shfl_xor_sync(0xffffffffu, rs, 5);
            const uint32_t rb = pack_bf(0.f, rs);
            if (!(lane & 7)) st_gpu32((uint32_t*)&p.sc->r[(row >> 2) * RS] + (row & 3), ((rb ^ (((int)rb >> 31) | 0x80000000u)) & 0xffff0000u) | tag);
            WSTAMP(1);
            {
                const int n = 3 + (lane >> 3) + 4 * (lane & 1);
                const uint32_t so = (n & 7) * S_PL + ((lane & 6) + (n >> 3)) * 32;
                const uint32_t src[2] = {sb + OFF_S + v * S_Q + s_addr(so, h), sb + OFF_S + v * S_Q + s_addr(so + 32, h)};
                const uint32_t dst = sb + OFF_U + g * U_CH + (8 + 32 * v + 16 * h + t) * 16;
                const uint32_t rdst = mapa(dst, h ^ 1), rbar = mapa(bars + 8 * B_U, h ^ 1);
                mbar_wait(bars + 8 * (B_S + v));
                WSTAMP(9);
                uint4 a[8];
#pragma unroll
                for (int b = 0; b < 2; b++) {
#pragma unroll
                    for (int j = 0; j < 8; j++) ldsm4t((b ? src[j & 1] : src[j & 1] ^ 16) + (j >> 1) * 256, a[j].x, a[j].y, a[j].z, a[j].w);
#pragma unroll
                    for (int j = 0; j < 8; j++) {
                        if (b) sts128(dst + (j >> 1) * 64 + (j & 1) * U_PL, a[j].x, a[j].y, a[j].z, a[j].w);
                        else st_async16(rdst + (j >> 1) * 64 + (j & 1) * U_PL, a[j], rbar);
                    }
                }
                if (h && v == 3) {
                    ldsm4t((src[0] ^ 16) + 1024, a[0].x, a[0].y, a[0].z, a[0].w);
                    ldsm4t(src[0] + 1024, a[1].x, a[1].y, a[1].z, a[1].w);
                    if (t == 0) {
                        st_async16(rdst + 256, make_uint4(a[0].x, a[0].y & 0xffffu, a[0].z & 0xffffu, a[0].w & 0xffffu), rbar);
                        sts128(dst + 256, a[1].x, a[1].y & 0xffffu, a[1].z & 0xffffu, a[1].w & 0xffffu);
                    }
                }
                __syncwarp();
                if (lane == 0) mbar_arrive(bars + 8 * B_U);
            }
            const uint32_t one0 = 0x3F803F80u ^ p.zero, one1 = 0x3F803F80u + p.zero;
#pragma unroll
            for (int kb = 0; kb < 16; kb++) {
                const uint4 gw = lds128(gws + 128 * kb + 16 * (lane & 7));
                const uint32_t a0 = hmul2_bf(xa[kb].x, gw.x), a1 = hmul2_bf(xa[kb].y, gw.y), a2 = hmul2_bf(xa[kb].z, gw.z), a3 = hmul2_bf(xa[kb].w, gw.w);
                if (kb < 4) mma_bf_z(dr[kb], a0, a1, a2, a3, one0, one1);
                else mma_bf(dr[kb & 3], a0, a1, a2, a3, one0, one1);
            }
            float sg = ((dr[0][0] + dr[0][3]) + (dr[1][0] + dr[1][3])) + ((dr[2][0] + dr[2][3]) + (dr[3][0] + dr[3][3]));
            sg += __shfl_xor_sync(0xffffffffu, sg, 4);
            if (!(lane & 7)) st_gpu32((uint32_t*)p.sc->g + ((row & 256) << 2) + gate_pos(row), (pack_bf(sigmoid_f(bf_round(sg)), 0.f) & 0xffffu) | (tag << 16));
            WSTAMP(2);
        }
        if (at == 32) { sts32(sb + M_TAG, tag << 16); mbar_arrive(bars + 8 * B_F); }
        {
            const bool lane0 = pin(lane, lane) == 0;
            const uint32_t own = pin(sb + OFF_XSEL + (at ^ ((at >> 1) & 4)) * 16, lane);
            float acc[8][4];
#pragma unroll
            for (int i = 0; i < 8; i++) { acc[i][0] = acc[i][1] = acc[i][2] = acc[i][3] = 0.f; }
            const int krow = ((lane >> 1) & 8) + (lane & 7);
            const uint32_t tile0 = pin(sb + OFF_RING + krow * 64 + ((((lane >> 3) & 1) ^ ((krow >> 1) & 3)) << 4), lane);
            const uint32_t xo = pin(sb + OFF_XSEL + (lane & 7) * XS_ROW + 512 * v + 2 * (lane & 24), lane);
            const uint32_t po = pin(sb + OFF_XSEL + t * XS_ROW + (g & 3) * 128 + (g & 1) * 64 + v * 16 + (lane >> 4) * 8, lane);
            const uint32_t po1 = pin(po + 64 - (g & 1) * 128, lane);
            uint32_t* hdst = pin((uint32_t*)&p.sc->h[tag & 1][32 * c] + at, lane);
            auto signal = [&](const int k, const uint32_t dep) {
                if (lane < 2 && v < 2)
                    asm volatile("st.async.weak.shared::cluster.mbarrier::complete_tx::bytes.b32 [%0], %1, [%2];"
                                 :: "r"(mapa(sb + M_SINK, lane)), "r"(dep), "r"(mapa(bars + 8 * (B_F + k), lane)) : "memory");
            };
#pragma unroll 1
            for (int i = 0; i < 4; i++) {
                const int s = 4 * i + v;
                uint32_t a[16][4], b[2][4];
                if (gu) {
                    const uint32_t tile = tile0 + (s < 14 ? s : v) * 8192;
                    if (lane0 && i > 1) mbar_arrive(bars + 8 * (B_E + s - 4));
                    if (i == 2) signal(0, 0);
                    mbar_wait(bars + 8 * (B_W + s));
#pragma unroll
                    for (int q = 0; q < 16; q++) ldsm4t((tile ^ ((q & 1) << 5)) + ((q >> 1) & 1) * 4096 + (q >> 2) * 1024, a[q][0], a[q][1], a[q][2], a[q][3]);
                }
                if (i == 0) {
                    if (gu) {
                        uint32_t dep = p.zero;
#pragma unroll
                        for (int q = 0; q < 16; q += 2) dep &= a[q][0] & a[q + 1][0];
                        if (lane == 0) mbar_arrive(bars + 8 * (B_E + v) + dep);
                    }
                    WSTAMP(11);
                    uint32_t top;
#pragma unroll 1
                    for (int it = 0; it < (1 << 22); it++) {
                        asm volatile("ld.relaxed.gpu.global.u32 %0, [%1];" : "=r"(top) : "l"(&p.sc->top[c % NTOP][g]) : "memory");
                        if (__all_sync(0xffffffffu, ((top ^ (tag << 11)) & 0xf800u) == 0)) break;
                        if (TSLEEP) __nanosleep(TSLEEP);
                    }
                    WSTAMP(3);
                    if (gu) {
                        const uint32_t k = 4 * h + v, row = __reduce_max_sync(0xffffffffu, lane == 4 * k ? ~top & 2047 : 0);
                        asm volatile("{\n\t.reg .pred p;\n\telect.sync _|p, 0xffffffff;\n\t"
                                     "@p cp.async.bulk.shared::cluster.global.mbarrier::complete_tx::bytes.multicast::cluster [%0], [%1], 2048, [%2], %3;\n\t}"
                            :: "r"(sb + OFF_XSEL + k * XS_ROW), "l"(p.u + (size_t)row * D_), "r"(bars + 8 * B_G), "h"((unsigned short)3) : "memory");
                    }
                    if (v == 0) {
                        const uint32_t row = ~top & 2047;
                        if (t == 0 && ((row >> 8) & 1) == h)
                            asm volatile("red.shared.or.b32 [%0], %1;" :: "r"(sb + M_BMAP + (row & 7) * 16 + (row >> 9) * 4), "r"(1u << (gate_pos(row) & 31)) : "memory");
                        if (t == 0) sts32(sb + M_TOP + lane, top);
                        if (c == 0 && lane == 0) *(volatile unsigned*)&p.sc->epoch = tag;
                        __syncwarp();
                        if (lane0) mbar_arrive(bars + 8 * B_Y);
                    }
                    if (!gu) break;
                    mbar_wait(bars + 8 * B_G);
                    WSTAMP(4);
                }
                ldsm4(xo + 128 * i, b[0][0], b[0][1], b[0][2], b[0][3]);
                ldsm4(xo + 128 * i + 64, b[1][0], b[1][1], b[1][2], b[1][3]);
#pragma unroll
                for (int q = 0; q < 16; q++) mma_bf(acc[q & 7], a[q][0], a[q][1], a[q][2], a[q][3], b[q >> 3][(q >> 1) & 2], b[q >> 3][((q >> 1) & 2) + 1]);
            }
            if (gu) {
                WSTAMP(5);
                __syncwarp();
#pragma unroll
                for (int q = 0; q < 4; q++) {
                    const int ct = q >> 1, e = 2 * (q & 1);
                    sts128(own + q * XS_ROW,
                           __float_as_uint(acc[ct][e] + acc[4 + ct][e]), __float_as_uint(acc[2 + ct][e] + acc[6 + ct][e]),
                           __float_as_uint(acc[ct][e + 1] + acc[4 + ct][e + 1]), __float_as_uint(acc[2 + ct][e + 1] + acc[6 + ct][e + 1]));
                }
                bar_sync(1, 128);
                float sl[2], uv[2];
#pragma unroll
                for (int e = 0; e < 2; e++) {
                    uint2 q[4];
#pragma unroll
                    for (int i = 0; i < 4; i++) q[i] = lds64((e ? po1 : po) + 512 * i);
                    const float s0 = (__uint_as_float(q[0].x) + __uint_as_float(q[1].x)) + (__uint_as_float(q[2].x) + __uint_as_float(q[3].x));
                    const float s1 = (__uint_as_float(q[0].y) + __uint_as_float(q[1].y)) + (__uint_as_float(q[2].y) + __uint_as_float(q[3].y));
                    const float gv = bf_round(p.gu_swap ? s1 : s0);
                    uv[e] = p.gu_swap ? s0 : s1;
                    sl[e] = gv * sigmoid_f(gv);
                }
                const uint32_t hw = hmul2_bf(pack_bf(sl[0], sl[1]), pack_bf(uv[0], uv[1]));
                st_gpu32(hdst, hw ? hw : 0x80000000u);
                signal(1, hw);
            }
        }
        WSTAMP(6);
        asm volatile("setmaxnreg.dec.sync.aligned.u32 104;");
        {
            const uint32_t own = pin(sb + OFF_XSEL + at * 16, lane);
            const uint32_t hb = sb + (v < 2 ? OFF_XSEL + 7168 * v : OFF_RING + 8192 * v), hl = pin(hb + 16 * lane, lane);
            const int krow = ((lane >> 1) & 8) + (lane & 7);
            const uint32_t tile = pin(sb + OFF_RING + v * 8192 + krow * 32 + ((((lane >> 3) ^ (krow >> 2)) & 1) << 4), lane);
            float dd[4][4];
            bar_sync(1, 128);
            mbar_wait(bars + 8 * (B_W + HW));
            WSTAMP(12);
            uint4 hq[7];
#pragma unroll 1
            for (int it = 0; it < (1 << 16); it++) {
                bulk_load(hb, &p.sc->h[tag & 1][32 * (56 * h + 14 * v)], 7168, bars + 8 * (B_X + v));
                uint32_t a[14][4], mn = 0xffffffffu;
                mbar_wait(bars + 8 * (B_W + 16 + v));
#pragma unroll
                for (int j = 0; j < 14; j++) ldsm4t(tile + (v & 2) * 16384 + j * 512, a[j][0], a[j][1], a[j][2], a[j][3]);
                mbar_wait(bars + 8 * (B_X + v), ~it & 1);
                WSTAMP(7);
#pragma unroll
                for (int j = 0; j < 7; j++) {
                    const uint4 q = lds128(hl + 512 * j);
                    mn = min(mn, q.x);
#pragma unroll
                    for (int e = 0; e < 2; e++) {
                        const uint32_t(&f)[4] = a[2 * j + e];
                        if (j < 2) mma_bf_z(dd[2 * j + e], f[0], f[1], f[2], f[3], e ? q.z : q.x, e ? q.w : q.y);
                        else mma_bf(dd[(2 * j + e) & 3], f[0], f[1], f[2], f[3], e ? q.z : q.x, e ? q.w : q.y);
                    }
                }
#pragma unroll
                for (int j = 0; j < 7; j++) { hq[j] = lds128(hl + 3584 + 512 * j); mn = min(mn, hq[j].x); }
                if (__all_sync(0xffffffffu, mn != 0)) break;
            }
            mbar_wait(bars + 8 * (B_W + 20 + v));
#pragma unroll
            for (int j = 0; j < 14; j++) {
                uint32_t f[4];
                ldsm4t(tile + 65536 + j * 512, f[0], f[1], f[2], f[3]);
                mma_bf(dd[(j + 2) & 3], f[0], f[1], f[2], f[3], (j & 1) ? hq[j >> 1].z : hq[j >> 1].x, (j & 1) ? hq[j >> 1].w : hq[j >> 1].y);
            }
            WSTAMP(8);
            uint4 part;
            part.x = __float_as_uint((dd[0][0] + dd[1][0]) + (dd[2][0] + dd[3][0])); part.y = __float_as_uint((dd[0][1] + dd[1][1]) + (dd[2][1] + dd[3][1]));
            part.z = __float_as_uint((dd[0][2] + dd[1][2]) + (dd[2][2] + dd[3][2])); part.w = __float_as_uint((dd[0][3] + dd[1][3]) + (dd[2][3] + dd[3][3]));
            st_async16(mapa(own + (M_DPIN - OFF_XSEL), h ^ 1), part, mapa(bars + 8 * B_DP, h ^ 1));
            sts128(own + 14336, part.x, part.y, part.z, part.w);
            __syncwarp();
            if (lane == 0) mbar_arrive(bars + 8 * B_DP);
        }
        WDUMP();
    } else {
        asm volatile("setmaxnreg.dec.sync.aligned.u32 40;");
        const int v = __reduce_max_sync(0xffffffffu, pw - PREP_W0);
        const bool gu = c < NGU_CTA;
        const uint32_t t0 = clock();
        const uint32_t bu = bars + 8 * v;
        if (lane == 0) {
            mbar_init(bu + 8 * B_X, 1);
            asm volatile("fence.mbarrier_init.release.cluster;" ::: "memory");
        }
        __syncwarp();
        if (DELAY_X > 0) __nanosleep(DELAY_X);
        bulk_load(sb + (v < 2 ? OFF_XSEL : OFF_RING + 2 * 8192) + v * 8192, p.u + (size_t)(16 * c + 4 * v) * D_, 8192, bu + 8 * B_X);
        if (lane == 0) {
#pragma unroll
            for (int i = 0; i < 10; i++) mbar_init(bu + 32 * i, 1);
            mbar_init(bu + 8 * B_XE, 1);
            mbar_init(bu + 8 * B_Y, v == 0 ? 11 : 9);
            mbar_init(bu + 8 * B_DP, (0x1855 >> (4 * v)) & 15);
            mbar_init(bu + 8 * B_F, v == 0 ? 2 : 1);
            mbar_init(bu + 8 * B_H, 1);
            asm volatile("fence.mbarrier_init.release.cluster;" ::: "memory");
            mbar_expect(bu + 8 * B_Y, 4096);
            if (v != 2) mbar_expect(bu + 8 * B_DP, v == 0 ? 2048 : (h || v == 3) ? 16384 : 16384 + 128);
            mbar_expect(bu + 8 * B_F, c < NGU_CTA ? 16 : 0);
        }
        __syncwarp();
        asm volatile("barrier.cluster.arrive.relaxed.aligned;" ::: "memory");
        tma3d(sb + OFF_S + v * S_Q, &tm_x, 16 * pr, 64 * v + 32 * h - 1, bars + 8 * (B_S + v), S_Q);
        WSTAMP(9);
        if (v < 3 && lane == 0) asm volatile("prefetch.tensormap [%0];" :: "l"(v == 0 ? &tm_gu : v == 1 ? &tm_down : &tm_out) : "memory");
        asm volatile("barrier.cluster.wait.acquire.aligned;" ::: "memory");
        if (v > 0) mbar_wait(bars + 8 * (B_H + v));
        {
            const int gap = v == 0 ? GAP : v == 1 ? GAP1 : v == 2 ? GAP2 : GAP3;
            uint32_t last = v ? clock() - SLACK : t0 + T0 - GAP + STAG * ((pr * 5) & 15) / 16;
#pragma unroll 1
            for (int s = 6 * v; s < 6 * v + 6; s++) {
                const int i = s >> 2, w = s & 3, slot = s < 14 ? s : (s | 1) == 17 ? s - 16 : s - 12;
                if (s >= 4) mbar_wait(bars + 8 * ((gu && s >= 14) ? B_E + slot : s < 6 ? B_XE + s - 2 : B_KG));
                uint32_t now;
#pragma unroll 1
                while ((int)((now = clock()) - last) < gap) __nanosleep(CSLEEP);
                last = max((int)(now - last) - SLACK, gap) + last;
                WSTAMP(3 + s - 6 * v);
                if (gu || s >= 16) tma3d(sb + OFF_RING + slot * 8192, i < 4 ? &tm_gu : &tm_down, i < 4 ? 32 * c : 16 * pr,
                      i < 4 ? 256 * w + 64 * i : 1792 * h + 448 * w + 224 * (i - 4), bars + 8 * (B_W + s), i < 4 ? 8192 : 7168);
            }
            if (lane == 0) mbar_arrive(bars + 8 * (B_H + ((v + 1) & 3)));
        }
        if (v == 0) {
            mbar_wait(bars + 8 * B_U);
            mbar_wait(bars + 8 * B_F);
            if (!gu) mbar_wait(bars + 8 * (B_H + 3));
            const uint32_t tag16 = lds32(sb + M_TAG);
#pragma unroll 1
            for (int k = 0; k < 2; k++) {
                uint4 q[4];
#pragma unroll 1
                for (int it = 0; it < (1 << 22); it++) {
                    uint32_t bad = 0;
#pragma unroll
                    for (int i = 0; i < 4; i++) q[i] = ld_gpu128(&p.sc->g[256 * h + 128 * k + 32 * i + lane]);
#pragma unroll
                    for (int i = 0; i < 4; i++) bad |= ((q[i].x ^ tag16) | (q[i].y ^ tag16)) | ((q[i].z ^ tag16) | (q[i].w ^ tag16));
                    if ((bad >> 16) == 0) break;
                    __nanosleep(200);
                }
#pragma unroll
                for (int i = 0; i < 4; i++)
                    asm volatile("st.shared.v2.u32 [%0], {%1, %2};" :: "r"(sb + OFF_GP + 1024 * k + 256 * i + lane * 8),
                                 "r"(__byte_perm(q[i].x, q[i].y, 0x5410)), "r"(__byte_perm(q[i].z, q[i].w, 0x5410)) : "memory");
            }
            __syncwarp();
            if (lane == 0) mbar_arrive(bars + 8 * B_Y);
        }
        {
            asm volatile("setmaxnreg.inc.sync.aligned.u32 72;");
            mbar_wait(bars + 8 * (B_W + PW));
            WSTAMP(1);
            mix_rows<2, true>(p, &tm_out, sb, sb + OFF_TAB + v * TAB_W, 0, PQ, v, h, pr, lane);
            WSTAMP(2);
            asm volatile("cp.async.bulk.commit_group;" ::: "memory");
            const uint32_t top = lds32(sb + M_TOP + 8 * v + 4 * (lane >> 4));
            const uint32_t row = ~top & 2047, ch = lane & 15, gp = gate_pos(row);
            const bool mine = ((row >> 8) & 1) == h;
            uint32_t gfin, x16, y16 = 0;
            asm volatile("ld.shared.u16 %0, [%1];" : "=r"(gfin) : "r"(sb + OFF_GP + gp * 2) : "memory");
            asm volatile("ld.shared.u16 %0, [%1];" : "=r"(x16) : "r"(sb + OFF_S + (row >> 9) * S_Q + s_addr((row & 7) * S_PL + 32 + (row & 248) * 4, ch >> 3) + 2 * (ch & 7)) : "memory");
            const float rsel = __uint_as_float(pin(__float_as_uint(bf_round(sigmoid_f(__uint_as_float((top ^ (((int)~top >> 31) | 0x80000000u)) & 0xffff0000u)))), lane));
            const uint32_t po = pin(sb + (4 * (ch & 7) + v) * 16 + (ch >> 3) * 8 + (lane >> 4) * 4, lane);
            bf16* op = pin(p.out + (size_t)row * D_ + 16 * pr + ch, lane);
            if (mine) {
                mbar_wait(bars + 8 * (B_Y + (row >> 9)));
                asm volatile("ld.shared.u16 %0, [%1];" : "=r"(y16)
                             : "r"(sb + y_off(row >> 9) + ch * 512 + (((4 * (row & 7) + ((row >> 5) & 3)) ^ (((ch >> 2) << 1) | (ch & 1))) << 4) + 2 * row_elem(row)) : "memory");
            }
            mbar_wait(bars + 8 * B_DP);
            float q[8];
#pragma unroll
            for (int i = 0; i < 4; i++) { q[i] = ldsf(po + M_DPIN + 512 * i); q[4 + i] = ldsf(po + OFF_XSEL + 14336 + 512 * i); }
            const float tot = ((q[0] + q[1]) + (q[2] + q[3])) + ((q[4] + q[5]) + (q[6] + q[7]));
            const float b = bf_round(__uint_as_float(x16 << 16) + bf_round(bf_round(tot) * rsel));
            if (mine) *op = __float2bfloat16_rn(fmaf(bf_lo(gfin), __uint_as_float(y16 << 16), bf_round(bf_round(1.f - bf_lo(gfin)) * b)));
        }
        asm volatile("cp.async.bulk.wait_group.read 0;" ::: "memory");
        WSTAMP(10);
        WDUMP();
    }
}

typedef CUresult (*EncodeFn)(CUtensorMap*, CUtensorMapDataType, cuuint32_t, void*, const cuuint64_t*, const cuuint64_t*,
                             const cuuint32_t*, const cuuint32_t*, CUtensorMapInterleave, CUtensorMapSwizzle,
                             CUtensorMapL2promotion, CUtensorMapFloatOOBfill);

void make_map(EncodeFn f, CUtensorMap* m, const void* ptr, uint64_t cols, uint64_t rows, uint64_t pitch, uint32_t bc, uint32_t br, CUtensorMapSwizzle sw, int prom,
              uint32_t planes = 1, uint64_t plane_stride = 0, uint32_t box_planes = 0) {
    cuuint64_t dims[3] = {cols, rows, planes};
    cuuint64_t str[2] = {pitch, planes > 1 ? plane_stride : pitch * rows};
    cuuint32_t box[3] = {bc, br, box_planes ? box_planes : planes};
    cuuint32_t es[3] = {1, 1, 1};
    f(m, CU_TENSOR_MAP_DATA_TYPE_BFLOAT16, 3, (void*)ptr, dims, str, box, es, CU_TENSOR_MAP_INTERLEAVE_NONE, sw,
      (CUtensorMapL2promotion)prom, CU_TENSOR_MAP_FLOAT_OOB_FILL_NONE);
}

}

extern "C" void kernel_launch(void* const* d_in, const int* in_sizes, int n_in, void* d_out, int out_size) {
    static EncodeFn enc = nullptr;
    static void *sc = nullptr, *band = nullptr;
    if (!enc) {
        void* fn = nullptr;
        cudaDriverEntryPointQueryResult qr;
        cudaGetDriverEntryPoint("cuTensorMapEncodeTiled", &fn, cudaEnableDefault, &qr);
        enc = (EncodeFn)fn;
        cudaGetSymbolAddress(&sc, g_scratch);
        cudaGetSymbolAddress(&band, g_band);
        cudaFuncSetAttribute(fused_kernel, cudaFuncAttributeMaxDynamicSharedMemorySize, SMEM_BYTES);
    }
    CUtensorMap tg, td, tx, to;
    const char *wg = (const char*)d_in[9], *wu = (const char*)d_in[10];
    const bool swap = wu < wg;
    make_map(enc, &tg, swap ? wu : wg, F_, D_, F_ * 2, 32, 64, CU_TENSOR_MAP_SWIZZLE_64B, PROMG, 2, swap ? wg - wu : wu - wg);
    make_map(enc, &td, d_in[11], D_, F_, D_ * 2, 16, 224, CU_TENSOR_MAP_SWIZZLE_32B, PROMD);
    make_map(enc, &tx, d_in[0], D_, L_ / 8, D_ * 16, 16, 33, CU_TENSOR_MAP_SWIZZLE_32B, PROMX, 8, D_ * 2);
    make_map(enc, &to, d_out, D_, L_ / 8, D_ * 16, 16, 32, CU_TENSOR_MAP_SWIZZLE_NONE, 0, 8, D_ * 2, 1);
    Params p;
    p.u = (const bf16*)d_in[0]; p.logA = (const bf16*)d_in[1]; p.Aim = (const bf16*)d_in[2];
    p.Cre = (const bf16*)d_in[3]; p.Cim = (const bf16*)d_in[4]; p.logdt = (const bf16*)d_in[5];
    p.Dskip = (const bf16*)d_in[6]; p.wr = (const bf16*)d_in[8]; p.gatew = (const bf16*)d_in[12];
    p.out = (bf16*)d_out;
    p.sc = (Scratch*)sc; p.band = (const uint4*)band;
    p.gu_swap = swap;
    p.zero = 0;
    fused_kernel<<<NCTA, NTHREADS, SMEM_BYTES>>>(p, tg, td, tx, to);
}
```

```cpp
#include <cuda_runtime.h>
#include <cuda_bf16.h>
#include <cuda_fp16.h>
#include <cuda.h>
#include <stdint.h>

typedef __nv_bfloat16 bf16;

namespace {

constexpr int L_ = 2048, D_ = 1024, F_ = 3584;
constexpr int NCTA = 130;
constexpr int NTHREADS = 512;
#define AUXW 12
constexpr int MAIN_W0 = 0, AUX_W0 = AUXW, PREP_W0 = 20 - AUXW;
#define T0 3500
#define GAP 590
#define GAP1 530
#define GAP2 530
#define GAP3 550
#define STAG GAP
#define CSLEEP 50
#define SLACK 300
#define DELAY_X 70
#define TSLEEP 40
#define RS 2
#define BULKM false
#define PW 19
#define PRESLEEP 64
#define PQ 3
#define PROMG 2
#define PROMD 1
#define PROMX 0
#define LATE2 0
#define HW 21
constexpr int NGU_CTA = 112;

constexpr int OFF_RING = 0;
constexpr int OFF_SCR  = 6 * 8192;
constexpr int S_PL     = 1056;
constexpr int S_Q      = 8 * S_PL;
constexpr int OFF_S    = 114688;
constexpr int OFF_GP   = OFF_S + 4 * S_Q;
constexpr int U_PL     = 2240;
constexpr int U_CH     = 4416;
constexpr int OFF_U    = 151552;
constexpr int TAB_W    = 3200;
constexpr int T_PL     = 544;
constexpr int T_A      = 2192 - 26 * 8;
constexpr int T_B      = 2568 - 59 * 8;
constexpr int OFF_TAB  = 186880;
constexpr int OFF_XSEL = 212480;
constexpr int XS_ROW   = 2064;
constexpr int OFF_BAND = 228992;
constexpr int OFF_MISC = 229536;
constexpr int M_BARS   = OFF_MISC;
constexpr int M_DSK    = OFF_MISC + 2736;
constexpr int M_SINK   = OFF_MISC + 512;
constexpr int M_TAG    = OFF_MISC + 516;
constexpr int M_BMAP   = OFF_MISC + 528;
constexpr int M_DPIN   = OFF_MISC + 656;
constexpr int M_TOP    = OFF_MISC + 2704;
constexpr int SMEM_BYTES = OFF_MISC + 2768;
__device__ __forceinline__ uint32_t s_addr(uint32_t o, uint32_t half) { return o + (((half ^ (o >> 7)) & 1) << 4); }
__host__ __device__ constexpr uint32_t y_off(uint32_t q) { return OFF_RING + 32768 + (q & 1) * 8192 + (q >> 1) * 65536; }

constexpr int B_W = 0;
constexpr int B_E = 24;
constexpr int B_S = 36;
constexpr int B_Y = 40;
constexpr int B_DP = 44, B_U = 45, B_KG = 46, B_G = 47;
constexpr int B_F = 48;
constexpr int B_H = 60;
constexpr int B_X = 52, B_XE = 56;

struct BandTab { uint32_t w[11][12]; };
constexpr BandTab make_band() {
    BandTab b{};
    for (int cls = 0; cls < 11; cls++)
        for (int wd = 0; wd < 10; wd++) {
            const int tau = cls + 2 - 8 * ((wd < 4 ? wd : wd - 4) >> 1);
            const int lo = (wd < 4) ? ((wd & 1) ? -2 : 3) : ((wd & 1) ? -4 : -11), wid = (wd < 4 ? 3 : 7) + 2 * (wd & 1);
            b.w[cls][wd] = ((tau >= lo && tau < lo + wid) ? 0x3F80u : 0u) | ((tau - 4 >= lo && tau - 4 < lo + wid) ? 0x3F800000u : 0u);
        }
    return b;
}
constexpr int NTOP = 32;
struct Scratch {
    uint4 r[L_ / 4 * RS];
    uint4 g[L_ / 4];
    uint4 h[2][8 * F_ / 8];
    uint32_t top[NTOP][32];
    unsigned epoch;
};
__device__ __align__(128) Scratch g_scratch;
__device__ const __align__(16) BandTab g_band = make_band();

struct Params {
    const bf16 *u, *logA, *Aim, *Cre, *Cim, *logdt, *Dskip, *wr, *gatew;
    bf16* out;
    Scratch* sc;
    const uint4* band;
    uint32_t gu_swap;
    uint32_t zero;
};

#define WSTAMP(i) do {} while (0)
#define KSTAMP(i, dep) do {} while (0)
#define WDUMP() do {} while (0)
#define RSTAMP(i) do {} while (0)

__device__ __forceinline__ uint32_t smem_u32(const void* p) { return (uint32_t)__cvta_generic_to_shared(p); }
__device__ __forceinline__ void mbar_init(uint32_t b, uint32_t c) { asm volatile("mbarrier.init.shared::cta.b64 [%0], %1;" :: "r"(b), "r"(c) : "memory"); }
__device__ __forceinline__ void mbar_expect(uint32_t b, uint32_t tx) { asm volatile("mbarrier.arrive.expect_tx.shared::cta.b64 _, [%0], %1;" :: "r"(b), "r"(tx) : "memory"); }
__device__ __forceinline__ void mbar_arrive(uint32_t b) { asm volatile("mbarrier.arrive.shared::cta.b64 _, [%0];" :: "r"(b) : "memory"); }
__device__ __forceinline__ void mbar_wait(uint32_t b, uint32_t parity = 0) {
    asm volatile("{\n\t.reg .pred p;\nW%=:\n\tmbarrier.try_wait.parity.shared::cta.b64 p, [%0], %1, 20000;\n\t@!p bra W%=;\n\t}" :: "r"(b), "r"(parity) : "memory");
}
__device__ __forceinline__ uint32_t mapa(uint32_t addr, uint32_t rank) { uint32_t r; asm("mapa.shared::cluster.u32 %0, %1, %2;" : "=r"(r) : "r"(addr), "r"(rank)); return r; }
__device__ __forceinline__ void tma3d(uint32_t dst, const CUtensorMap* tm, int c0, int c1, uint32_t bar, uint32_t bytes) {
    asm volatile("{\n\t.reg .pred p;\n\telect.sync _|p, 0xffffffff;\n\t"
                 "@p mbarrier.arrive.expect_tx.shared::cta.b64 _, [%2], %5;\n\t"
                 "@p cp.async.bulk.tensor.3d.shared::cluster.global.mbarrier::complete_tx::bytes [%0], [%1, {%3, %4, 0}], [%2];\n\t}"
        :: "r"(dst), "l"(tm), "r"(bar), "r"(c0), "r"(c1), "r"(bytes) : "memory");
}
__device__ __forceinline__ void bulk_load(uint32_t dst, const void* src, uint32_t bytes, uint32_t bar) {
    asm volatile("{\n\t.reg .pred p;\n\telect.sync _|p, 0xffffffff;\n\t"
                 "@p mbarrier.arrive.expect_tx.shared::cta.b64 _, [%2], %3;\n\t"
                 "@p cp.async.bulk.shared::cluster.global.mbarrier::complete_tx::bytes [%0], [%1], %3, [%2];\n\t}"
        :: "r"(dst), "l"(src), "r"(bar), "r"(bytes) : "memory");
}
__device__ __forceinline__ void st_async16(uint32_t dst, const uint4& v, uint32_t bar) {
    asm volatile("st.async.weak.shared::cluster.mbarrier::complete_tx::bytes.v4.b32 [%0], {%1,%2,%3,%4}, [%5];"
                 :: "r"(dst), "r"(v.x), "r"(v.y), "r"(v.z), "r"(v.w), "r"(bar) : "memory");
}
__device__ __forceinline__ void bar_sync(int id, int n) { asm volatile("bar.sync %0, %1;" :: "r"(id), "r"(n) : "memory"); }
__device__ __forceinline__ void cp16(uint32_t dst, const void* src) { asm volatile("cp.async.cg.shared.global [%0], [%1], 16;" :: "r"(dst), "l"(src) : "memory"); }
__device__ __forceinline__ void cp_wait_all() { asm volatile("cp.async.wait_all;" ::: "memory"); }
__device__ __forceinline__ uint4 ld_gpu128(const void* p) { uint4 v; asm volatile("ld.relaxed.gpu.global.v4.u32 {%0,%1,%2,%3}, [%4];" : "=r"(v.x), "=r"(v.y), "=r"(v.z), "=r"(v.w) : "l"(p) : "memory"); return v; }
__device__ __forceinline__ void st_gpu32(void* p, uint32_t v) { asm volatile("st.relaxed.gpu.global.u32 [%0], %1;" :: "l"(p), "r"(v) : "memory"); }

__device__ __forceinline__ void ldsm4(uint32_t a, uint32_t& r0, uint32_t& r1, uint32_t& r2, uint32_t& r3) {
    asm volatile("ldmatrix.sync.aligned.m8n8.x4.shared.b16 {%0,%1,%2,%3}, [%4];" : "=r"(r0), "=r"(r1), "=r"(r2), "=r"(r3) : "r"(a) : "memory");
}
__device__ __forceinline__ void ldsm4t(uint32_t a, uint32_t& r0, uint32_t& r1, uint32_t& r2, uint32_t& r3) {
    asm volatile("ldmatrix.sync.aligned.m8n8.x4.trans.shared.b16 {%0,%1,%2,%3}, [%4];" : "=r"(r0), "=r"(r1), "=r"(r2), "=r"(r3) : "r"(a) : "memory");
}
__device__ __forceinline__ uint32_t lds32(uint32_t a) { uint32_t v; asm volatile("ld.shared.u32 %0, [%1];" : "=r"(v) : "r"(a) : "memory"); return v; }
__device__ __forceinline__ uint2 lds64(uint32_t a) { uint2 v; asm volatile("ld.shared.v2.u32 {%0,%1}, [%2];" : "=r"(v.x), "=r"(v.y) : "r"(a) : "memory"); return v; }
__device__ __forceinline__ uint4 lds128(uint32_t a) { uint4 v; asm volatile("ld.shared.v4.u32 {%0,%1,%2,%3}, [%4];" : "=r"(v.x), "=r"(v.y), "=r"(v.z), "=r"(v.w) : "r"(a) : "memory"); return v; }
__device__ __forceinline__ void sts32(uint32_t a, uint32_t v) { asm volatile("st.shared.u32 [%0], %1;" :: "r"(a), "r"(v) : "memory"); }
__device__ __forceinline__ void sts16(uint32_t a, uint32_t v) { asm volatile("st.shared.u16 [%0], %1;" :: "r"(a), "h"((unsigned short)v) : "memory"); }
__device__ __forceinline__ void sts128(uint32_t a, uint32_t x, uint32_t y, uint32_t z, uint32_t w) { asm volatile("st.shared.v4.u32 [%0], {%1,%2,%3,%4};" :: "r"(a), "r"(x), "r"(y), "r"(z), "r"(w) : "memory"); }
__device__ __forceinline__ float ldsf(uint32_t a) { float v; asm volatile("ld.shared.f32 %0, [%1];" : "=f"(v) : "r"(a) : "memory"); return v; }

__device__ __forceinline__ void mma_bf(float (&d)[4], uint32_t a0, uint32_t a1, uint32_t a2, uint32_t a3, uint32_t b0, uint32_t b1) {
    asm volatile("mma.sync.aligned.m16n8k16.row.col.f32.bf16.bf16.f32 {%0,%1,%2,%3}, {%4,%5,%6,%7}, {%8,%9}, {%0,%1,%2,%3};"
        : "+f"(d[0]), "+f"(d[1]), "+f"(d[2]), "+f"(d[3]) : "r"(a0), "r"(a1), "r"(a2), "r"(a3), "r"(b0), "r"(b1));
}
__device__ __forceinline__ void mma_bf_z(float (&d)[4], uint32_t a0, uint32_t a1, uint32_t a2, uint32_t a3, uint32_t b0, uint32_t b1) {
    asm volatile("mma.sync.aligned.m16n8k16.row.col.f32.bf16.bf16.f32 {%0,%1,%2,%3}, {%4,%5,%6,%7}, {%8,%9}, {%10,%10,%10,%10};"
        : "=f"(d[0]), "=f"(d[1]), "=f"(d[2]), "=f"(d[3]) : "r"(a0), "r"(a1), "r"(a2), "r"(a3), "r"(b0), "r"(b1), "f"(0.f));
}
__device__ __forceinline__ void mma_bf_k8(float (&d)[4], uint32_t a0, uint32_t a1, uint32_t b0) {
    asm volatile("mma.sync.aligned.m16n8k8.row.col.f32.bf16.bf16.f32 {%0,%1,%2,%3}, {%4,%5}, {%6}, {%0,%1,%2,%3};"
        : "+f"(d[0]), "+f"(d[1]), "+f"(d[2]), "+f"(d[3]) : "r"(a0), "r"(a1), "r"(b0));
}
__device__ __forceinline__ void mma_h(float (&d)[4], uint32_t a0, uint32_t a1, uint32_t a2, uint32_t a3, uint32_t b0, uint32_t b1) {
    asm volatile("mma.sync.aligned.m16n8k16.row.col.f32.f16.f16.f32 {%0,%1,%2,%3}, {%4,%5,%6,%7}, {%8,%9}, {%0,%1,%2,%3};"
        : "+f"(d[0]), "+f"(d[1]), "+f"(d[2]), "+f"(d[3]) : "r"(a0), "r"(a1), "r"(a2), "r"(a3), "r"(b0), "r"(b1));
}
__device__ __forceinline__ uint32_t pack_bf(float lo, float hi) { uint32_t r; asm("cvt.rn.bf16x2.f32 %0, %1, %2;" : "=r"(r) : "f"(hi), "f"(lo)); return r; }
__device__ __forceinline__ uint32_t pack_h(float lo, float hi) { uint32_t r; asm("cvt.rn.f16x2.f32 %0, %1, %2;" : "=r"(r) : "f"(hi), "f"(lo)); return r; }
__device__ __forceinline__ float bf_lo(uint32_t v) { return __uint_as_float(v << 16); }
__device__ __forceinline__ float bf_hi(uint32_t v) { return __uint_as_float(v & 0xffff0000u); }
__device__ __forceinline__ float bf_round(float x) { return __uint_as_float(pack_bf(0.f, x)); }
__device__ __forceinline__ uint32_t hmul2_bf(uint32_t a, uint32_t b) { uint32_t r; asm("mul.rn.bf16x2 %0, %1, %2;" : "=r"(r) : "r"(a), "r"(b)); return r; }
__device__ __forceinline__ float ex2f(float x) { float r; asm("ex2.approx.ftz.f32 %0, %1;" : "=f"(r) : "f"(x)); return r; }

__device__ __forceinline__ float exp_acc(float x) {
    const float t = x * 1.4426950216293335f;
    const float r = fmaf(x, 1.4426950216293335f, -t) + x * 1.9259629911266175e-8f;
    return ex2f(t) * fmaf(r, 0.6931471805599453f, 1.f);
}
__device__ __forceinline__ float sigmoid_f(float x) { return __fdividef(1.f, 1.f + ex2f(-x * 1.4426950408889634f)); }
__device__ __forceinline__ void cexp_pow(float l2, float li, float e, float& zr, float& zi) {
    const float mag = ex2f(l2 * e);
    zr = mag * __cosf(li * e);
    zi = mag * __sinf(li * e);
}
__device__ __forceinline__ uint32_t hcmul(uint32_t a, uint32_t k, uint32_t kp) {
    const __half2 A = *reinterpret_cast<const __half2*>(&a);
    const __half2 r = __hfma2(__high2half2(A), *reinterpret_cast<const __half2*>(&kp), __hmul2(__low2half2(A), *reinterpret_cast<const __half2*>(&k)));
    return *reinterpret_cast<const uint32_t*>(&r);
}
#define CMUL(orr, oi, ar, ai, br, bi) do { float _r = (ar) * (br) - (ai) * (bi); float _i = (ar) * (bi) + (ai) * (br); orr = _r; oi = _i; } while (0)
#define CSQ(orr, oi, ar, ai) do { float _r = (ar) * (ar) - (ai) * (ai); float _i = 2.f * (ar) * (ai); orr = _r; oi = _i; } while (0)

__device__ __forceinline__ void mma_bf_k8z(float (&d)[4], uint32_t a0, uint32_t a1, uint32_t b0) {
    asm volatile("mma.sync.aligned.m16n8k8.row.col.f32.bf16.bf16.f32 {%0,%1,%2,%3}, {%4,%5}, {%6}, {%7,%7,%7,%7};"
        : "=f"(d[0]), "=f"(d[1]), "=f"(d[2]), "=f"(d[3]) : "r"(a0), "r"(a1), "r"(b0), "f"(0.f));
}
__device__ __forceinline__ void mma_hh_k8(uint32_t& d0, uint32_t& d1, uint32_t a0, uint32_t a1, uint32_t b0) {
    asm volatile("mma.sync.aligned.m16n8k8.row.col.f16.f16.f16.f16 {%0,%1}, {%2,%3}, {%4}, {%5,%5};"
        : "=r"(d0), "=r"(d1) : "r"(a0), "r"(a1), "r"(b0), "r"(0));
}
__device__ __forceinline__ uint32_t pin(uint32_t x, int lane) { return __shfl_sync(0xffffffffu, x, lane); }
template <class T> __device__ __forceinline__ T* pin(T* x, int lane) { return (T*)__shfl_sync(0xffffffffu, (unsigned long long)x, lane); }
__device__ __forceinline__ void sts32_if(bool on, uint32_t a, uint32_t v) {
    asm volatile("{\n\t.reg .pred p;\n\tsetp.ne.u32 p, %2, 0;\n\t@p st.shared.u32 [%0], %1;\n\t}" :: "r"(a), "r"(v), "r"((uint32_t)on) : "memory");
}
__device__ __forceinline__ void sts128_if(bool on, uint32_t a, uint32_t x, uint32_t y, uint32_t z, uint32_t w) {
    asm volatile("{\n\t.reg .pred p;\n\tsetp.ne.u32 p, %5, 0;\n\t@p st.shared.v4.u32 [%0], {%1,%2,%3,%4};\n\t}" :: "r"(a), "r"(x), "r"(y), "r"(z), "r"(w), "r"((uint32_t)on) : "memory");
}
__device__ __forceinline__ void lds128_if(bool on, uint32_t a, uint32_t (&v)[4]) {
    asm volatile("{\n\t.reg .pred p;\n\tsetp.ne.u32 p, %5, 0;\n\t@p ld.shared.v4.u32 {%0,%1,%2,%3}, [%4];\n\t}"
        : "+r"(v[0]), "+r"(v[1]), "+r"(v[2]), "+r"(v[3]) : "r"(a), "r"((uint32_t)on) : "memory");
}
__device__ __forceinline__ uint32_t hfma2_bf(uint32_t a, uint32_t b, uint32_t c) { uint32_t r; asm("fma.rn.bf16x2 %0, %1, %2, %3;" : "=r"(r) : "r"(a), "r"(b), "r"(c)); return r; }
__device__ __forceinline__ uint32_t row_elem(uint32_t row) { return ((row >> 5) & 4) | ((row >> 2) & 2) | ((row >> 4) & 1); }
__device__ __forceinline__ uint32_t gate_pos(uint32_t row) { return ((row >> 9) << 8) | ((row & 7) << 5) | (row_elem(row) << 2) | ((row >> 5) & 3); }

template <int N, bool BULK>
__device__ __forceinline__ void mix_rows(const Params& p, const CUtensorMap* tm_out, uint32_t sb, uint32_t ob, int Q0, int Q1, int w, int h, int pr, int lane) {
    const int g = lane >> 2, t = lane & 3, mi = lane >> 3, r = lane & 7;
    const int m8 = 16 * (g >> 2) + ((g >> 1) & 1) + 2 * (g & 1);
    uint32_t yi = sb + (4 * (r >> 1) + 2 * (mi & 1) + (r & 1)) * 512 + (((4 * w + (mi >> 1)) ^ r) << 4);
    uint32_t xs = sb + OFF_S + s_addr(w * S_PL + 32 + m8 * 32, t >> 1) + ((t & 1) << 3);
    uint32_t gs = sb + OFF_GP + w * 64 + g * 8, os = ob + m8 * 32 + t * 8;
    if (N > 1) { yi = pin(yi, lane); xs = pin(xs, lane); gs = pin(gs, lane); os = pin(os, lane); }
    mbar_wait(sb + M_BARS + 8 * B_Y);
#pragma unroll 1
    for (int Q = Q0; Q < Q1; Q++) {
        uint2 xq[N][4];
        uint32_t gg[N][4], sw[N];
#pragma unroll
        for (int n = 0; n < N; n++) {
#pragma unroll
            for (int i = 0; i < 4; i++) xq[n][i] = lds64((xs ^ (((i ^ n) & 1) << 4)) + Q * S_Q + n * 4 * S_PL + i * 128);
            const uint2 gq = lds64(gs + Q * 512 + n * 256);
            sw[n] = lds32(sb + M_BMAP + w * 16 + n * 64 + Q * 4);
#pragma unroll
            for (int i = 0; i < 4; i++) {
                gg[n][i] = __byte_perm(i < 2 ? gq.x : gq.y, 0, (i & 1) ? 0x3232 : 0x1010);
                const uint32_t og = hfma2_bf(gg[n][i], 0xBF80BF80u, 0x3F803F80u);
                xq[n][i].x = hmul2_bf(og, xq[n][i].x); xq[n][i].y = hmul2_bf(og, xq[n][i].y);
            }
        }
        mbar_wait(sb + M_BARS + 8 * (B_Y + Q));
        __syncwarp();
#pragma unroll
        for (int n = 0; n < N; n++) {
#pragma unroll
            for (int x = 0; x < 2; x++) {
                uint32_t y[4];
                ldsm4t((yi ^ (x << 5)) + y_off(Q) + n * 256, y[0], y[1], y[2], y[3]);
#pragma unroll
                for (int e = 0; e < 2; e++) {
                    uint2& o = xq[n][2 * x + e];
                    o.x = hfma2_bf(gg[n][2 * x + e], y[2 * e], o.x); o.y = hfma2_bf(gg[n][2 * x + e], y[2 * e + 1], o.y);
                }
            }
        }
        if (BULK && (sw[0] | sw[N - 1]) == 0) {
#pragma unroll
            for (int n = 0; n < N; n++)
#pragma unroll
                for (int i = 0; i < 4; i++)
                    asm volatile("st.shared.v2.u32 [%0], {%1, %2};" :: "r"(os + Q * 1024 + n * 4 * TAB_W + i * 128), "r"(xq[n][i].x), "r"(xq[n][i].y) : "memory");
            asm volatile("fence.proxy.async.shared::cta;" ::: "memory");
            __syncwarp();
#pragma unroll
            for (int n = 0; n < N; n++)
                asm volatile("{\n\t.reg .pred p;\n\telect.sync _|p, 0xffffffff;\n\t"
                             "@p cp.async.bulk.tensor.3d.global.shared::cta.bulk_group [%1, {%2, %3, %4}], [%0];\n\t}"
                    :: "r"(ob + 4 * n * TAB_W + Q * 1024), "l"(tm_out), "r"(16 * pr), "r"(64 * Q + 32 * h), "r"(w + 4 * n) : "memory");
        } else {
            bf16* op = p.out + (size_t)(512 * Q + 256 * h + 8 * m8 + w) * D_ + 16 * pr + 4 * t;
#pragma unroll
            for (int n = 0; n < N; n++)
#pragma unroll
                for (int i = 0; i < 4; i++)
                    if (!((sw[n] >> (4 * g)) & (1u << i))) *(uint2*)(op + (size_t)(32 * i + 4 * n) * D_) = xq[n][i];
        }
    }
}

__global__ void __cluster_dims__(2, 1, 1) __launch_bounds__(NTHREADS, 1)
fused_kernel(const Params p, const __grid_constant__ CUtensorMap tm_gu, const __grid_constant__ CUtensorMap tm_down,
             const __grid_constant__ CUtensorMap tm_x, const __grid_constant__ CUtensorMap tm_out) {
    extern __shared__ __align__(1024) unsigned char smem[];
    const uint32_t sb = smem_u32(smem);
    int tid;
    asm volatile("mov.u32 %0, %%tid.x;" : "=r"(tid));
    const int pw = tid >> 5, lane = tid & 31;
    const int c = blockIdx.x, h = c & 1, pr = c >> 1;
    const uint32_t bars = sb + M_BARS;

    uint2 v_la, v_ai, v_cr, v_ci;
    uint32_t ldt16;
    {
        const uint32_t po = c * 256 + tid;
        asm volatile("{\n\t.reg .pred p;\n\t.reg .b64 a;\n\tsetp.ne.u32 p, %16, 0;\n\t"
                     "mad.wide.u32 a, %14, 8, %9;\n\t@p ld.global.nc.L1::no_allocate.v2.u32 {%0,%1}, [a];\n\t"
                     "mad.wide.u32 a, %15, 2, %13;\n\t@p ld.global.nc.u16 %8, [a];\n\t"
                     "mad.wide.u32 a, %14, 8, %10;\n\t@p ld.global.nc.L1::no_allocate.v2.u32 {%2,%3}, [a];\n\t"
                     "mad.wide.u32 a, %14, 8, %11;\n\t@p ld.global.nc.L1::no_allocate.v2.u32 {%4,%5}, [a];\n\t"
                     "mad.wide.u32 a, %14, 8, %12;\n\t@p ld.global.nc.L1::no_allocate.v2.u32 {%6,%7}, [a];\n\t}"
            : "=r"(v_la.x), "=r"(v_la.y), "=r"(v_ai.x), "=r"(v_ai.y), "=r"(v_cr.x), "=r"(v_cr.y), "=r"(v_ci.x), "=r"(v_ci.y), "=r"(ldt16)
            : "l"(p.logA), "l"(p.Aim), "l"(p.Cre), "l"(p.Cim), "l"(p.logdt), "r"(po), "r"(po >> 5), "r"((uint32_t)(tid < 256 && c < 128)));
    }

    if (c >= 128) {
        if (c != 128) return;
        RSTAMP(5);
        const unsigned tag = (*(volatile unsigned*)&p.sc->epoch + 1) & 0xffffu;
        const uint32_t list = sb + 128;
#pragma unroll 1
        for (int pass = 0; pass < 2; pass++) {
            sts128(list + 16 * tid, 0, 0, 0, 0);
            if (tid == 0) sts32(sb + 64, 0);
            uint32_t key[4];
            bool ok = false;
#pragma unroll 1
            for (int it = 0; it < (1 << 22); it++) {
                const uint4 a = ld_gpu128(&p.sc->r[tid * RS]);
                key[0] = a.x; key[1] = a.y; key[2] = a.z; key[3] = a.w;
                ok = (((a.x ^ tag) | (a.y ^ tag) | (a.z ^ tag) | (a.w ^ tag)) & 0xffffu) == 0;
                if (ok || !pass) break;
            }
            WSTAMP(0);
            uint32_t m = 0;
#pragma unroll
            for (int i = 0; i < 4; i++) {
                key[i] = ((pass ? key[i] : (lane + i) << 16) & 0xffff0000u) | (uint32_t)(2047 - (4 * tid + i));
                m = max(m, key[i]);
            }
            const uint32_t wm = __reduce_max_sync(0xffffffffu, m);
            if (lane == 0) sts32(sb + pw * 4, wm);
            __syncthreads();
            uint32_t thr = 0xffffffffu;
#pragma unroll
            for (int i = 0; i < 4; i++) { const uint4 q = lds128(sb + 16 * i); thr = min(thr, min(max(q.x, q.y), max(q.z, q.w))); }
            if (thr != 1) WSTAMP(1);
            if (m >= thr) {
                uint32_t pos;
                asm volatile("atom.shared.add.u32 %0, [%1], %2;" : "=r"(pos) : "r"(sb + 64), "r"(4 * ((key[0] >= thr) + (key[1] >= thr) + (key[2] >= thr) + (key[3] >= thr))) : "memory");
#pragma unroll
                for (int i = 0; i < 4; i++) if (key[i] >= thr) { sts32(list + pos, key[i]); pos += 4; }
            }
            __syncthreads();
            const uint32_t nc4 = lds32(sb + 64);
            if (nc4 != 1) WSTAMP(2);
#pragma unroll 1
            for (uint32_t j = 4 * pw; j < nc4; j += 64) {
                const uint32_t mine = lds32(list + j);
                int rank = 0;
#pragma unroll 1
                for (uint32_t i = 0; i < nc4; i += 128) rank += __popc(__ballot_sync(0xffffffffu, lds32(list + i + 4 * lane) > mine));
                if (rank < 8 && lane == 0) sts32(sb + 96 + 4 * rank, mine);
            }
            __syncthreads();
            if (tid < 8 * NTOP) st_gpu32(&p.sc->top[tid >> 3][tid & 7], lds32(sb + 96 + 4 * (tid & 7)) | (((tag + pass - 1) & 31) << 11));
            WSTAMP(3);
            if (!pass) RSTAMP(4);
        }
        WDUMP();
        return;
    }

    WSTAMP(0);
    if (pw < 8) {
        const int d = 8 * c + pw - MAIN_W0;
        if (lane == 0) asm volatile("cp.async.ca.shared.global [%0], [%1], 4;" :: "r"(sb + M_DSK + 4 * (pw - MAIN_W0)), "l"(p.Dskip + (d & ~1)) : "memory");
        asm volatile("barrier.cluster.arrive.relaxed.aligned;" ::: "memory");
        const int warp = pw - MAIN_W0;
        asm volatile("setmaxnreg.inc.sync.aligned.u32 168;");
        const int g = lane >> 2, t = lane & 3;
        const int mi = lane >> 3, r = lane & 7;
        const uint32_t TB = sb + OFF_TAB + warp * TAB_W;
        const uint32_t UB = sb + OFF_U + warp * U_CH;
        if (mi < 2) sts128(UB + mi * U_PL + r * 16, 0, 0, 0, 0);
        if (lane < 4) sts128(TB + lane * T_PL, 0, 0, 0, 0);
        sts128(sb + OFF_SCR + warp * 8192 + lane * 16, 0x3C00u, 0x3C00u, 0x3C00u, 0x3C00u);
        __syncwarp();

        uint32_t cfix;
        {
            KSTAMP(4, v_la.x ^ v_ai.x ^ v_cr.x ^ v_ci.x ^ ldt16);
            const float dt = bf_round(exp_acc(__uint_as_float(ldt16 << 16)));
            float l2[4], li[4];
            {
                const uint32_t la[2] = {v_la.x, v_la.y}, ai[2] = {v_ai.x, v_ai.y};
                const float dt2 = -1.4426950408889634f * dt;
#pragma unroll
                for (int i = 0; i < 4; i++) {
                    l2[i] = bf_round(ex2f(((i & 1) ? bf_hi(la[i >> 1]) : bf_lo(la[i >> 1])) * 1.4426950408889634f)) * dt2;
                    li[i] = ((i & 1) ? bf_hi(ai[i >> 1]) : bf_lo(ai[i >> 1])) * dt;
                }
            }
            const uint32_t SX = sb + OFF_SCR + warp * 8192;
            const uint32_t sw = SX + (lane << 4);
#define PUT(buf, row, v) sts128(((sw + (row) * 512) ^ ((row) << 4)) + (buf) * 4096, v[0], v[1], v[2], v[3])
#define EMIT(bufa, rowa, bufb, rowb, xr, xi, k, kp) do { uint32_t pk[4], pd[4]; \
                _Pragma("unroll") for (int i = 0; i < 4; i++) { pk[i] = pack_h(xr[i], xi[i]); pd[i] = hcmul(pk[i], k[i], kp[i]); } \
                PUT(bufa, rowa, pk); PUT(bufb, rowb, pd); } while (0)
#define CMUL4(orr, oi, ar, ai, br, bi) _Pragma("unroll") for (int i = 0; i < 4; i++) CMUL(orr[i], oi[i], ar[i], ai[i], br[i], bi[i])
#define CSQ4(orr, oi, ar, ai) _Pragma("unroll") for (int i = 0; i < 4; i++) CSQ(orr[i], oi[i], ar[i], ai[i])
            float z1r[4], z1i[4], z2r[4], z2i[4], z8r[4], z8i[4], z256r[4], z256i[4];
            uint32_t k4[4], k4p[4];
            float z4r[4], z4i[4];
#pragma unroll
            for (int i = 0; i < 4; i++) cexp_pow(l2[i], li[i], 1.f, z1r[i], z1i[i]);
            CSQ4(z2r, z2i, z1r, z1i);
            CSQ4(z4r, z4i, z2r, z2i);
            CSQ4(z8r, z8i, z4r, z4i);
            KSTAMP(5, __float_as_uint(z8r[3]));
            uint32_t Ya[16][4];
            float cr[4], ci[4], inv;
            {
                float w1r[4], w1i[4], ar[4], ai[4], br[4], bi[4];
                uint32_t k8[4], k8p[4];
#pragma unroll
                for (int i = 0; i < 4; i++) {
                    k8[i] = pack_h(z8r[i], -z8i[i]); k8p[i] = pack_h(z8i[i], z8r[i]);
                    CSQ(w1r[i], w1i[i], z8r[i], z8i[i]); w1i[i] = -w1i[i];
                }
                PUT(1, 0, k8);
                EMIT(0, 1, 1, 1, w1r, w1i, k8, k8p);
                CSQ4(ar, ai, w1r, w1i);            EMIT(0, 2, 1, 2, ar, ai, k8, k8p);
                CMUL4(br, bi, ar, ai, w1r, w1i);   EMIT(0, 3, 1, 3, br, bi, k8, k8p);
                CSQ4(ar, ai, ar, ai);              EMIT(0, 4, 1, 4, ar, ai, k8, k8p);
                CMUL4(ar, ai, ar, ai, w1r, w1i);   EMIT(0, 5, 1, 5, ar, ai, k8, k8p);
                CSQ4(br, bi, br, bi);              EMIT(0, 6, 1, 6, br, bi, k8, k8p);
                CMUL4(br, bi, br, bi, w1r, w1i);   EMIT(0, 7, 1, 7, br, bi, k8, k8p);
                __syncwarp();
                KSTAMP(6, 0);
                const uint32_t ab = SX + (mi & 1) * 4096 + r * 512, ax = ((mi >> 1) ^ r) << 4;
                const uint32_t vr[2] = {v_cr.x, v_cr.y}, vi[2] = {v_ci.x, v_ci.y};
                const uint32_t m2 = __vmaxu2(__vmaxu2(vr[0] & 0x7fff7fffu, vr[1] & 0x7fff7fffu), __vmaxu2(vi[0] & 0x7fff7fffu, vi[1] & 0x7fff7fffu));
                const uint32_t mx = __reduce_max_sync(0xffffffffu, max(m2, m2 << 16));
                const uint32_t e = min(max(mx >> 23, 11u), 254u);
                const float sc = __uint_as_float((264u - e) << 23);
                inv = __uint_as_float((e - 10u) << 23) * (2.f * dt);
#pragma unroll
                for (int i = 0; i < 4; i++) {
#pragma unroll
                    for (int k = 0; k < 4; k++) ldsm4(ab + (ax ^ (i << 5)) + k * 128, Ya[4 * k + i][0], Ya[4 * k + i][1], Ya[4 * k + i][2], Ya[4 * k + i][3]);
                    float tr, ti;
                    cexp_pow(l2[i], li[i], 128.f, tr, ti);
                    sts32(TB + 2176 + 256 * i + 4 * lane, pack_h(tr, ti));
                    sts32(TB + 2176 + 256 * i + 128 + 4 * (lane ^ 16), pack_h(-ti, tr));
                    k4[i] = pack_h(z4r[i], z4i[i]); k4p[i] = pack_h(-z4i[i], z4r[i]);
                    CSQ(z256r[i], z256i[i], tr, ti);
                    cr[i] = ((i & 1) ? bf_hi(vr[i >> 1]) : bf_lo(vr[i >> 1])) * sc;
                    ci[i] = ((i & 1) ? bf_hi(vi[i >> 1]) : bf_lo(vi[i >> 1])) * sc;
                }
                __syncwarp();
            }
            KSTAMP(7, Ya[15][0]);
            const uint32_t ld0 = SX + r * 512 + ((mi ^ r) << 4), ld1 = ld0 ^ 64;
            float R[6][4], s1024;
            {
                float xr[4], xi[4], yr[4], yi[4];
                EMIT(0, 0, 0, 1, cr, ci, k4, k4p);
                CMUL4(yr, yi, cr, ci, z1r, z1i);        EMIT(0, 2, 0, 3, yr, yi, k4, k4p);
                CMUL4(xr, xi, cr, ci, z256r, z256i);    EMIT(1, 0, 1, 1, xr, xi, k4, k4p);
                CMUL4(yr, yi, yr, yi, z1r, z1i);        EMIT(0, 4, 0, 5, yr, yi, k4, k4p);
                CMUL4(cr, ci, xr, xi, z2r, z2i);        EMIT(1, 2, 1, 3, cr, ci, k4, k4p);
                CMUL4(yr, yi, yr, yi, z1r, z1i);        EMIT(0, 6, 0, 7, yr, yi, k4, k4p);
                CMUL4(xr, xi, xr, xi, z256r, z256i);    EMIT(1, 4, 1, 5, xr, xi, k4, k4p);
                CMUL4(xr, xi, xr, xi, z256r, z256i);    EMIT(1, 6, 1, 7, xr, xi, k4, k4p);
                CMUL4(xr, xi, xr, xi, z256r, z256i);
                s1024 = (xr[0] + xr[1]) + (xr[2] + xr[3]);
#pragma unroll
                for (int m = 0; m < 4; m++) {
                    if (m == 0) { CMUL4(xr, xi, xr, xi, z8r, z8i); } else { CMUL4(xr, xi, xr, xi, z256r, z256i); }
                    sts128(TB + m * T_PL + 16 + 16 * lane, pack_h(xr[0], xi[0]), pack_h(xr[1], xi[1]), pack_h(xr[2], xi[2]), pack_h(xr[3], xi[3]));
                }
            }
            asm volatile("barrier.cluster.wait.acquire.aligned;" ::: "memory");
            __syncwarp();
            {
                KSTAMP(8, 0);
                uint32_t bd[2][4] = {{0, 0, 0, 0}, {0, 0, 0, 0}};
                const bool on = (g >> 1) == t;
#pragma unroll
                for (int i = 0; i < 6; i++) { R[i][0] = R[i][1] = R[i][2] = R[i][3] = 0.f; }
#pragma unroll
                for (int k2 = 0; k2 < 8; k2++) {
                    uint32_t x[4], y[4], z[4], a1[2][4];
                    lds128_if(on, TB + 2176 + g * 128 + (k2 < 4 ? 64 : -64) * (g & 1) + 16 * k2, bd[k2 & 1]);
                    ldsm4(TB + (r & 3) * T_PL + 16 + 16 * mi + 64 * k2, z[0], z[1], z[2], z[3]);
                    ldsm4(((k2 & 1) ? ld1 : ld0) + (k2 >> 1) * 128, x[0], x[1], x[2], x[3]);
                    ldsm4(((k2 & 1) ? ld1 : ld0) + (k2 >> 1) * 128 + 4096, y[0], y[1], y[2], y[3]);
#pragma unroll
                    for (int u = 0; u < 2; u++) {
                        mma_hh_k8(a1[u][0], a1[u][1], Ya[2 * k2 + u][0], Ya[2 * k2 + u][1], bd[k2 & 1][2 * u]);
                        mma_hh_k8(a1[u][2], a1[u][3], Ya[2 * k2 + u][2], Ya[2 * k2 + u][3], bd[k2 & 1][2 * u + 1]);
                    }
#pragma unroll
                    for (int u = 0; u < 2; u++) {
                        const uint32_t(&a0)[4] = Ya[2 * k2 + u];
                        mma_h(R[0], a0[0], a0[1], a0[2], a0[3], x[2 * u], x[2 * u + 1]);
                        mma_h(R[2], a0[0], a0[1], a0[2], a0[3], y[2 * u], y[2 * u + 1]);
                        mma_h(R[4], a0[0], a0[1], a0[2], a0[3], z[2 * u], z[2 * u + 1]);
                        mma_h(R[1], a1[u][0], a1[u][1], a1[u][2], a1[u][3], x[2 * u], x[2 * u + 1]);
                        mma_h(R[3], a1[u][0], a1[u][1], a1[u][2], a1[u][3], y[2 * u], y[2 * u + 1]);
                        mma_h(R[5], a1[u][0], a1[u][1], a1[u][2], a1[u][3], z[2 * u], z[2 * u + 1]);
                    }
                }
            }
            __syncwarp();
            KSTAMP(9, __float_as_uint(R[3][0]));
            if (lane == 0) mbar_arrive(bars + 8 * B_KG + (__float_as_uint(R[0][0]) & __float_as_uint(R[2][0]) & p.zero));
            sts128(TB + 2176 + 16 * lane, 0, 0, 0, 0);
            sts128(TB + 2688 + 16 * lane, 0, 0, 0, 0);
            __syncwarp();
#undef PUT
#undef EMIT
#pragma unroll
            for (int o = 16; o > 0; o >>= 1) s1024 += __shfl_xor_sync(0xffffffffu, s1024, o);
            uint32_t w[4][4], dsk = 0;
            cp_wait_all();
            asm volatile("{\n\t.reg .pred p;\n\tsetp.eq.u32 p, %2, 0;\n\t@p ld.shared.u16 %0, [%1];\n\t}" : "+r"(dsk) : "r"(sb + M_DSK + 4 * warp + 2 * (warp & 1)), "r"(lane) : "memory");
#pragma unroll
            for (int a = 0; a < 4; a++) {
                const float v0 = (a == 0) ? fmaf(R[0][0], inv, __uint_as_float(dsk << 16)) : R[a][0] * inv;
                const float v1 = R[a][1] * inv, v2 = R[a][2] * inv, v3 = R[a][3] * inv;
                w[a][0] = pack_bf(v0, 0.f); w[a][1] = pack_bf(v1, v0); w[a][2] = pack_bf(v2, v1); w[a][3] = pack_bf(v3, v2);
            }
            const uint32_t wb = TB + 16 + 16 * g, w1 = wb + t * T_PL, w2 = wb + 256 + 2 * t * T_PL;
            const uint32_t w3 = (t == 0) ? wb + 256 + 3 * T_PL : TB + T_A + 8 * (16 * t + g);
            const uint32_t w3s = (t == 0) ? 128 : 64, w3o = (t == 0) ? 8 : 12;
            const uint32_t k512 = __shfl_sync(0xffffffffu, w[2][1], 2);
#pragma unroll
            for (int a = 0; a < 2; a++) {
                sts128(w1 + 128 * a, w[a][0], w[a][1], w[a][2], w[a][3]);
                const uint32_t(&q)[4] = w[2 + a];
                if (t < 2) sts128(w2 + 128 * a, q[0], q[1], q[2], q[3]);
                if (t == 0) { sts128(w2 + T_PL + 128 * a, q[0], q[1], q[2], q[3]); sts32(w3 + 128 * a + 4, q[2]); }
                sts32_if(t != 1 && (a == 1 || lane != 2), w3 + w3s * a, q[1]);
                sts32_if(t != 1, w3 + w3s * a + w3o, q[3]);
            }
            sts128_if(lane < 4, w1 + 512, t == 3 ? k512 : k512 >> 16, t < 2 ? k512 : t == 2 ? k512 & 0xffff0000u : k512 << 16, t < 2 ? k512 << 16 : 0u, 0);
            __syncwarp();
#pragma unroll
            for (int a = 0; a < 2; a++) {
                sts16(w1 + 128 * a + 18, w[a][3]);
                const uint32_t(&q)[4] = w[2 + a];
                if (t < 2) sts16(w2 + 128 * a + 18, q[3]);
                if (t == 0) { sts16(w2 + T_PL + 128 * a + 18, q[3]); sts16(w3 + 128 * a + 14, q[3]); }
            }
            if (t == 0) sts16(w3 + 128 - 4, w[3][0]);
            if (lane == 2 || (t == 0 && g > 0)) sts16(lane == 2 ? TB + 16 + 3 * T_PL + 4 * 127 : w3 - 4, w[2][0]);
            {
                float q[4];
#pragma unroll
                for (int i = 0; i < 4; i++) q[i] = (t < 2 ? R[4][i] : R[5][i]) * inv;
                const uint32_t b0 = pack_bf(q[0], q[2]), b1 = pack_bf(q[1], q[3]);
                const uint32_t wq = TB + T_B + 8 * (65 + 32 * (t & 1) + 4 * (t & 2) + g);
                sts32(wq, b0); sts32(wq + 12, b0); sts32(wq + 128, b1); sts32(wq + 140, b1);
            }
            cfix = pack_bf(s1024 * inv, s1024 * inv);
            if (lane == 0) sts32(TB + T_A + 8 * 64, cfix);
            __syncwarp();
        }
        WSTAMP(1);

        mbar_wait(bars + 8 * B_U);
        WSTAMP(2);

        float D[16][4];
        {
            const int x5 = g - t + 5;
            const uint32_t tabD = TB + (x5 & 3) * T_PL + (x5 & 12) + 16;
            {
                const uint32_t a1 = lds32(tabD - 8), a0 = p.zero;
#pragma unroll
                for (int jq = 0; jq < 4; jq++) {
                    uint32_t b[4];
                    ldsm4(UB + (9 + lane) * 16 + jq * 512, b[0], b[1], b[2], b[3]);
#pragma unroll
                    for (int i = 0; i < 4; i++) mma_bf_k8z(D[4 * jq + i], a0, a1, b[i]);
                }
            }
            const uint32_t ua = UB + (mi & 1) * U_PL + (8 + 8 * (mi >> 1) + r) * 16;
#pragma unroll 1
            for (int k0 = 0; k0 < 8; k0++) {
                uint32_t Uf[16][2];
#pragma unroll
                for (int jp = 0; jp < 8; jp++) ldsm4(ua + jp * 256 - k0 * 16, Uf[2 * jp][0], Uf[2 * jp][1], Uf[2 * jp + 1][0], Uf[2 * jp + 1][1]);
#pragma unroll
                for (int k1 = 0; k1 < 4; k1++) {
                    const uint32_t ta = tabD + 16 * (8 * k1 + k0);
                    const uint32_t a0 = lds32(ta), a1 = lds32(ta + 8), a2 = lds32(ta - 8), a3 = a0 ^ p.zero;
#pragma unroll
                    for (int J = k1; J < 16; J++) mma_bf(D[J], a0, a1, a2, a3, Uf[J - k1][0], Uf[J - k1][1]);
                }
                if (k0 == 0) {
                    const uint32_t ta = tabD + 16 * 32;
                    const uint32_t a0 = lds32(ta), a1 = lds32(ta + 8), a2 = lds32(ta - 8), a3 = a0 ^ p.zero;
#pragma unroll
                    for (int J = 4; J < 16; J++) mma_bf(D[J], a0, a1, a2, a3, Uf[J - 4][0], Uf[J - 4][1]);
                    const uint32_t f0 = (cfix ^ 0x80008000u) & (g == t ? 0xffffu : g == t + 4 ? 0xffff0000u : 0u);
                    const uint32_t f1 = p.zero, f2 = p.zero + p.zero, f3 = f0 ^ p.zero;
#pragma unroll
                    for (int J = 8; J < 16; J++) mma_bf(D[J], f0, f1, f2, f3, Uf[J - 8][0], Uf[J - 8][1]);
                }
            }
        }
        WSTAMP(3);
        {
            const int ch = 8 * h + warp;
            const uint32_t yo = sb + ch * 512 + ((lane ^ (((ch >> 2) << 1) | (ch & 1))) << 4);
            const uint32_t yr = mapa(yo, h ^ 1), ybr = mapa(bars + 8 * B_Y, h ^ 1);
            auto ship = [&](const int Q) {
                uint4 y[2];
#pragma unroll
                for (int hh = 0; hh < 2; hh++) {
                    const int J = 4 * Q + 2 * hh;
                    y[hh] = make_uint4(pack_bf(D[J][0], D[J][1]), pack_bf(D[J][2], D[J][3]), pack_bf(D[J + 1][0], D[J + 1][1]), pack_bf(D[J + 1][2], D[J + 1][3]));
                }
                if (!(Q & 1)) mbar_wait(bars + 8 * (B_F + (Q >> 1)));
                asm volatile("{\n\t.reg .pred p;\n\tsetp.eq.u32 p, %11, 0;\n\t"
                             "@p st.async.weak.shared::cluster.mbarrier::complete_tx::bytes.v4.b32 [%9], {%4,%5,%6,%7}, [%10];\n\t"
                             "@!p st.async.weak.shared::cluster.mbarrier::complete_tx::bytes.v4.b32 [%9], {%0,%1,%2,%3}, [%10];\n\t"
                             "@p st.shared.v4.b32 [%8], {%0,%1,%2,%3};\n\t@!p st.shared.v4.b32 [%8], {%4,%5,%6,%7};\n\t}"
                             :: "r"(y[0].x), "r"(y[0].y), "r"(y[0].z), "r"(y[0].w), "r"(y[1].x), "r"(y[1].y), "r"(y[1].z), "r"(y[1].w),
                                "r"(yo + y_off(Q)), "r"(yr + y_off(Q)), "r"(ybr + 8 * Q), "r"(h) : "memory");
                __syncwarp();
                if (lane == 0) mbar_arrive(bars + 8 * (B_Y + Q));
            };
            ship(0);
            const uint4 bA = lds128(sb + OFF_BAND + (g - t + 3) * 48), bB = lds128(sb + OFF_BAND + (g - t + 3) * 48 + 16);
            const uint2 bC = lds64(sb + OFF_BAND + (g - t + 3) * 48 + 32);
            uint2 QA[5][2], QB[8];
            const uint32_t tq = TB + 8 * (1 + g - 2 * t);
#pragma unroll
            for (int dd = 0; dd < 5; dd++) { QA[dd][0] = lds64(tq + T_A + 64 * (dd + 4)); QA[dd][1] = lds64(tq + T_A + 64 * (dd + 4) - 8); }
#pragma unroll
            for (int dd = 0; dd < 8; dd++) QB[dd] = lds64(tq + T_B + 64 * (dd + 8));
            const uint32_t u1 = UB + (mi & 1) * U_PL + (7 + r + (mi >> 1)) * 16;
            const uint32_t u2 = UB + ((mi & 1) ^ 1) * U_PL + (7 + r + (mi & 1) + 8 * (mi >> 1)) * 16;
            uint32_t n[4];
#pragma unroll
            for (int j = 0; j < 12; j++) {
                uint32_t m[4];
                ldsm4(u1 + j * 128, m[0], m[1], m[2], m[3]);
                if (!(j & 1)) ldsm4(u2 + j * 128, n[0], n[1], n[2], n[3]);
                const uint32_t n0 = n[2 * (j & 1)], n1 = n[2 * (j & 1) + 1];
                float wa[4], wb[4], wc[4], g1[4], g2[4];
                mma_bf_z(wa, bA.x, bA.y, bA.z, bA.w, m[0], m[1]);
                mma_bf_z(wb, bA.x, bA.y, bA.z, bA.w, n0, n1);
                mma_bf_z(wc, bA.x, bA.y, bA.z, bA.w, m[2], m[3]);
                if (j < 8) {
                    mma_bf_z(g1, bB.x, bB.y, bB.z, bB.w, m[0], m[1]);
                    mma_bf_z(g2, bB.x, bB.y, bB.z, bB.w, n0, n1);
                    mma_bf_k8(g1, bC.x, bC.y, m[2]);
                    mma_bf_k8(g2, bC.x, bC.y, m[3]);
                }
#pragma unroll
                for (int e = 0; e < 2; e++) {
                    const uint32_t q0 = pack_bf(wa[e], wa[e + 2]), q1 = pack_bf(wb[e], wb[e + 2]), q2 = q1 ^ p.zero, q3 = pack_bf(wc[e], wc[e + 2]);
#pragma unroll
                    for (int dd = 0; dd < 5; dd++)
                        if (j + 4 + dd < 16) mma_bf(D[j + 4 + dd], q0, q1, q2, q3, QA[dd][e].x, QA[dd][e].y);
                }
                if (j < 8) {
                    const uint32_t q0 = pack_bf(g1[0], g1[2]), q1 = pack_bf(g2[0], g2[2]), q2 = pack_bf(g1[1], g1[3]), q3 = pack_bf(g2[1], g2[3]);
#pragma unroll
                    for (int dd = 7 - j; dd >= 0; dd--) mma_bf(D[j + 8 + dd], q0, q1, q2, q3, QB[dd].x, QB[dd].y);
                }
                if ((j & 3) == 3) {
                    WSTAMP(4 + 2 * (j >> 2));
                    if (j == 11 && LATE2) ship(2);
                    if (j != 7 || !LATE2) ship((j >> 2) + 1);
                }
            }
        }
        const int warpu = __reduce_max_sync(0xffffffffu, warp);
        mix_rows<1, BULKM>(p, &tm_out, sb, sb + OFF_U + warpu * U_CH + (warpu & 1) * 64, PQ, 4, warpu, h, pr, lane);
        if (BULKM) asm volatile("cp.async.bulk.commit_group;\n\tcp.async.bulk.wait_group.read 0;" ::: "memory");
        WSTAMP(10);
        WDUMP();
    } else if ((pw & 12) == AUX_W0) {
        asm volatile("setmaxnreg.inc.sync.aligned.u32 136;");
        const int v = __reduce_max_sync(0xffffffffu, pw & 3);
        const int at = tid & 127;
        const int g = lane >> 2, t = lane & 3;
        unsigned tag;
        const bool gu = c < NGU_CTA;
        {
            uint4 xa[16];
            const uint32_t xb = sb + (v < 2 ? OFF_XSEL : OFF_RING + 2 * 8192) + v * 8192;
            const uint32_t gws = sb + (gu ? M_DPIN : OFF_RING + 2 * 8192);
            const uint32_t row = 16 * c + 4 * v + (g >> 1);
#pragma unroll
            for (int i = 0; i < 4; i++)
                asm volatile("cp.async.ca.shared.global [%0], [%1], 4;" :: "r"(sb + OFF_GP + 512 * i + (tid & 124) * 4 + (tid & 1) * 8 + (tid & 2) * 2),
                             "l"(p.wr + 256 * i + (tid & 127) * 2) : "memory");
            cp16(gws + (tid & 127) * 16, p.gatew + (tid & 127) * 8);
            if ((tid & 127) < 33) cp16(sb + OFF_BAND + (tid & 127) * 16, p.band + (tid & 127));
            asm volatile("barrier.cluster.arrive.relaxed.aligned;" ::: "memory");
            tag = __reduce_max_sync(0xffffffffu, (*(volatile unsigned*)&p.sc->epoch + 1) & 0xffffu);
            if (gu) st_gpu32((uint32_t*)&p.sc->h[(tag + 1) & 1][32 * c] + at, 0);
            if (v == 3) sts32(sb + M_BMAP + lane * 4, 0);
            if (at == 0) sts32(sb + M_TAG, tag << 16);
            cp_wait_all();
            bar_sync(1, 128);
            uint2 w[16];
#pragma unroll
            for (int kb = 0; kb < 16; kb++) w[kb] = lds64(sb + OFF_GP + 128 * kb + 32 * (g & 2) + 16 * t + 8 * (g & 1));
            asm volatile("barrier.cluster.wait.acquire.aligned;" ::: "memory");
            mbar_wait(bars + 8 * (B_X + v));
            WSTAMP(10);
#pragma unroll
            for (int kb = 0; kb < 16; kb++) xa[kb] = lds128(xb + (g >> 1) * 2048 + 128 * kb + 16 * (lane & 7));
            float dr[4][4];
#pragma unroll
            for (int kb = 0; kb < 16; kb++) {
                if (kb < 4) mma_bf_z(dr[kb], xa[kb].x, xa[kb].y, xa[kb].z, xa[kb].w, w[kb].x, w[kb].y);
                else mma_bf(dr[kb & 3], xa[kb].x, xa[kb].y, xa[kb].z, xa[kb].w, w[kb].x, w[kb].y);
            }
            float rs = ((dr[0][0] + dr[0][3]) + (dr[1][0] + dr[1][3])) + ((dr[2][0] + dr[2][3]) + (dr[3][0] + dr[3][3]));
            if (lane == 0) mbar_arrive(bars + 8 * (B_XE + v) + (__float_as_uint(rs) & p.zero));
            rs += __shfl_xor_sync(0xffffffffu, rs, 5);
            const uint32_t rb = pack_bf(0.f, rs);
            if (!(lane & 7)) st_gpu32((uint32_t*)&p.sc->r[(row >> 2) * RS] + (row & 3), ((rb ^ (((int)rb >> 31) | 0x80000000u)) & 0xffff0000u) | tag);
            WSTAMP(1);
            {
                const int n = 3 + (lane >> 3) + 4 * (lane & 1);
                const uint32_t so = (n & 7) * S_PL + ((lane & 6) + (n >> 3)) * 32;
                const uint32_t src[2] = {sb + OFF_S + v * S_Q + s_addr(so, h), sb + OFF_S + v * S_Q + s_addr(so + 32, h)};
                const uint32_t dst = sb + OFF_U + g * U_CH + (8 + 32 * v + 16 * h + t) * 16;
                const uint32_t rdst = mapa(dst, h ^ 1), rbar = mapa(bars + 8 * B_U, h ^ 1);
                mbar_wait(bars + 8 * (B_S + v));
                WSTAMP(9);
                uint4 a[8];
#pragma unroll
                for (int b = 0; b < 2; b++) {
#pragma unroll
                    for (int j = 0; j < 8; j++) ldsm4t((b ? src[j & 1] : src[j & 1] ^ 16) + (j >> 1) * 256, a[j].x, a[j].y, a[j].z, a[j].w);
#pragma unroll
                    for (int j = 0; j < 8; j++) {
                        if (b) sts128(dst + (j >> 1) * 64 + (j & 1) * U_PL, a[j].x, a[j].y, a[j].z, a[j].w);
                        else st_async16(rdst + (j >> 1) * 64 + (j & 1) * U_PL, a[j], rbar);
                    }
                }
                if (h && v == 3) {
                    ldsm4t((src[0] ^ 16) + 1024, a[0].x, a[0].y, a[0].z, a[0].w);
                    ldsm4t(src[0] + 1024, a[1].x, a[1].y, a[1].z, a[1].w);
                    if (t == 0) {
                        st_async16(rdst + 256, make_uint4(a[0].x, a[0].y & 0xffffu, a[0].z & 0xffffu, a[0].w & 0xffffu), rbar);
                        sts128(dst + 256, a[1].x, a[1].y & 0xffffu, a[1].z & 0xffffu, a[1].w & 0xffffu);
                    }
                }
                __syncwarp();
                if (lane == 0) mbar_arrive(bars + 8 * B_U);
            }
            const uint32_t one0 = 0x3F803F80u ^ p.zero, one1 = 0x3F803F80u + p.zero;
#pragma unroll
            for (int kb = 0; kb < 16; kb++) {
                const uint4 gw = lds128(gws + 128 * kb + 16 * (lane & 7));
                const uint32_t a0 = hmul2_bf(xa[kb].x, gw.x), a1 = hmul2_bf(xa[kb].y, gw.y), a2 = hmul2_bf(xa[kb].z, gw.z), a3 = hmul2_bf(xa[kb].w, gw.w);
                if (kb < 4) mma_bf_z(dr[kb], a0, a1, a2, a3, one0, one1);
                else mma_bf(dr[kb & 3], a0, a1, a2, a3, one0, one1);
            }
            float sg = ((dr[0][0] + dr[0][3]) + (dr[1][0] + dr[1][3])) + ((dr[2][0] + dr[2][3]) + (dr[3][0] + dr[3][3]));
            sg += __shfl_xor_sync(0xffffffffu, sg, 4);
            if (!(lane & 7)) st_gpu32((uint32_t*)p.sc->g + ((row & 256) << 2) + gate_pos(row), (pack_bf(sigmoid_f(bf_round(sg)), 0.f) & 0xffffu) | (tag << 16));
            WSTAMP(2);
        }
        {
            const bool lane0 = pin(lane, lane) == 0;
            const uint32_t own = pin(sb + OFF_XSEL + (at ^ ((at >> 1) & 4)) * 16, lane);
            float acc[8][4];
#pragma unroll
            for (int i = 0; i < 8; i++) { acc[i][0] = acc[i][1] = acc[i][2] = acc[i][3] = 0.f; }
            const int krow = ((lane >> 1) & 8) + (lane & 7);
            const uint32_t tile0 = pin(sb + OFF_RING + krow * 64 + ((((lane >> 3) & 1) ^ ((krow >> 1) & 3)) << 4), lane);
            const uint32_t xo = pin(sb + OFF_XSEL + (lane & 7) * XS_ROW + 512 * v + 2 * (lane & 24), lane);
            const uint32_t po = pin(sb + OFF_XSEL + t * XS_ROW + (g & 3) * 128 + (g & 1) * 64 + v * 16 + (lane >> 4) * 8, lane);
            const uint32_t po1 = pin(po + 64 - (g & 1) * 128, lane);
            uint32_t* hdst = pin((uint32_t*)&p.sc->h[tag & 1][32 * c] + at, lane);
            auto signal = [&](const int k, const uint32_t dep) {
                if (lane < 2 && v < 2)
                    asm volatile("st.async.weak.shared::cluster.mbarrier::complete_tx::bytes.b32 [%0], %1, [%2];"
                                 :: "r"(mapa(sb + M_SINK, lane)), "r"(dep), "r"(mapa(bars + 8 * (B_F + k), lane)) : "memory");
            };
#pragma unroll 1
            for (int i = 0; i < 4; i++) {
                const int s = 4 * i + v;
                uint32_t a[16][4], b[2][4];
                if (gu) {
                    const uint32_t tile = tile0 + (s < 14 ? s : v) * 8192;
                    if (lane0 && i > 1) mbar_arrive(bars + 8 * (B_E + s - 4));
                    if (i == 2) signal(0, 0);
                    mbar_wait(bars + 8 * (B_W + s));
#pragma unroll
                    for (int q = 0; q < 16; q++) ldsm4t((tile ^ ((q & 1) << 5)) + ((q >> 1) & 1) * 4096 + (q >> 2) * 1024, a[q][0], a[q][1], a[q][2], a[q][3]);
                }
                if (i == 0) {
                    if (gu) {
                        uint32_t dep = p.zero;
#pragma unroll
                        for (int q = 0; q < 16; q += 2) dep &= a[q][0] & a[q + 1][0];
                        if (lane == 0) mbar_arrive(bars + 8 * (B_E + v) + dep);
                    }
                    WSTAMP(11);
                    uint32_t top;
#pragma unroll 1
                    for (int it = 0; it < (1 << 22); it++) {
                        asm volatile("ld.relaxed.gpu.global.u32 %0, [%1];" : "=r"(top) : "l"(&p.sc->top[c % NTOP][g]) : "memory");
                        if (__all_sync(0xffffffffu, ((top ^ (tag << 11)) & 0xf800u) == 0)) break;
                        if (TSLEEP) __nanosleep(TSLEEP);
                    }
                    WSTAMP(3);
                    if (gu) {
                        const uint32_t k = 4 * h + v, row = __reduce_max_sync(0xffffffffu, lane == 4 * k ? ~top & 2047 : 0);
                        asm volatile("{\n\t.reg .pred p;\n\telect.sync _|p, 0xffffffff;\n\t"
                                     "@p cp.async.bulk.shared::cluster.global.mbarrier::complete_tx::bytes.multicast::cluster [%0], [%1], 2048, [%2], %3;\n\t}"
                            :: "r"(sb + OFF_XSEL + k * XS_ROW), "l"(p.u + (size_t)row * D_), "r"(bars + 8 * B_G), "h"((unsigned short)3) : "memory");
                    }
                    if (v == 3) {
                        const uint32_t row = ~top & 2047;
                        if (t == 0 && ((row >> 8) & 1) == h)
                            asm volatile("red.shared.or.b32 [%0], %1;" :: "r"(sb + M_BMAP + (row & 7) * 16 + (row >> 9) * 4), "r"(1u << (gate_pos(row) & 31)) : "memory");
                        if (t == 0) sts32(sb + M_TOP + lane, top);
                        if (c == 0 && lane == 0) *(volatile unsigned*)&p.sc->epoch = tag;
                        __syncwarp();
                        if (lane0) mbar_arrive(bars + 8 * B_Y);
                    }
                    if (!gu) break;
                    mbar_wait(bars + 8 * B_G);
                    WSTAMP(4);
                }
                ldsm4(xo + 128 * i, b[0][0], b[0][1], b[0][2], b[0][3]);
                ldsm4(xo + 128 * i + 64, b[1][0], b[1][1], b[1][2], b[1][3]);
#pragma unroll
                for (int q = 0; q < 16; q++) mma_bf(acc[q & 7], a[q][0], a[q][1], a[q][2], a[q][3], b[q >> 3][(q >> 1) & 2], b[q >> 3][((q >> 1) & 2) + 1]);
            }
            if (gu) {
                WSTAMP(5);
                __syncwarp();
#pragma unroll
                for (int q = 0; q < 4; q++) {
                    const int ct = q >> 1, e = 2 * (q & 1);
                    sts128(own + q * XS_ROW,
                           __float_as_uint(acc[ct][e] + acc[4 + ct][e]), __float_as_uint(acc[2 + ct][e] + acc[6 + ct][e]),
                           __float_as_uint(acc[ct][e + 1] + acc[4 + ct][e + 1]), __float_as_uint(acc[2 + ct][e + 1] + acc[6 + ct][e + 1]));
                }
                bar_sync(1, 128);
                float sl[2], uv[2];
#pragma unroll
                for (int e = 0; e < 2; e++) {
                    uint2 q[4];
#pragma unroll
                    for (int i = 0; i < 4; i++) q[i] = lds64((e ? po1 : po) + 512 * i);
                    const float s0 = (__uint_as_float(q[0].x) + __uint_as_float(q[1].x)) + (__uint_as_float(q[2].x) + __uint_as_float(q[3].x));
                    const float s1 = (__uint_as_float(q[0].y) + __uint_as_float(q[1].y)) + (__uint_as_float(q[2].y) + __uint_as_float(q[3].y));
                    const float gv = bf_round(p.gu_swap ? s1 : s0);
                    uv[e] = p.gu_swap ? s0 : s1;
                    sl[e] = gv * sigmoid_f(gv);
                }
                const uint32_t hw = hmul2_bf(pack_bf(sl[0], sl[1]), pack_bf(uv[0], uv[1]));
                st_gpu32(hdst, hw ? hw : 0x80000000u);
                signal(1, hw);
            }
        }
        WSTAMP(6);
        asm volatile("setmaxnreg.dec.sync.aligned.u32 104;");
        {
            const uint32_t own = pin(sb + OFF_XSEL + at * 16, lane);
            const uint32_t hb = sb + (v < 2 ? OFF_XSEL + 7168 * v : OFF_RING + 8192 * v), hl = pin(hb + 16 * lane, lane);
            const int krow = ((lane >> 1) & 8) + (lane & 7);
            const uint32_t tile = pin(sb + OFF_RING + v * 8192 + krow * 32 + ((((lane >> 3) ^ (krow >> 2)) & 1) << 4), lane);
            float dd[4][4];
            bar_sync(1, 128);
            mbar_wait(bars + 8 * (B_W + HW));
            WSTAMP(12);
            uint4 hq[7];
#pragma unroll 1
            for (int it = 0; it < (1 << 16); it++) {
                bulk_load(hb, &p.sc->h[tag & 1][32 * (56 * h + 14 * v)], 7168, bars + 8 * (B_X + v));
                uint32_t a[14][4], mn = 0xffffffffu;
                mbar_wait(bars + 8 * (B_W + 16 + v));
#pragma unroll
                for (int j = 0; j < 14; j++) ldsm4t(tile + (v & 2) * 16384 + j * 512, a[j][0], a[j][1], a[j][2], a[j][3]);
                mbar_wait(bars + 8 * (B_X + v), ~it & 1);
                WSTAMP(7);
#pragma unroll
                for (int j = 0; j < 7; j++) {
                    const uint4 q = lds128(hl + 512 * j);
                    mn = min(mn, q.x);
#pragma unroll
                    for (int e = 0; e < 2; e++) {
                        const uint32_t(&f)[4] = a[2 * j + e];
                        if (j < 2) mma_bf_z(dd[2 * j + e], f[0], f[1], f[2], f[3], e ? q.z : q.x, e ? q.w : q.y);
                        else mma_bf(dd[(2 * j + e) & 3], f[0], f[1], f[2], f[3], e ? q.z : q.x, e ? q.w : q.y);
                    }
                }
#pragma unroll
                for (int j = 0; j < 7; j++) { hq[j] = lds128(hl + 3584 + 512 * j); mn = min(mn, hq[j].x); }
                if (__all_sync(0xffffffffu, mn != 0)) break;
            }
            mbar_wait(bars + 8 * (B_W + 20 + v));
#pragma unroll
            for (int j = 0; j < 14; j++) {
                uint32_t f[4];
                ldsm4t(tile + 65536 + j * 512, f[0], f[1], f[2], f[3]);
                mma_bf(dd[(j + 2) & 3], f[0], f[1], f[2], f[3], (j & 1) ? hq[j >> 1].z : hq[j >> 1].x, (j & 1) ? hq[j >> 1].w : hq[j >> 1].y);
            }
            WSTAMP(8);
            uint4 part;
            part.x = __float_as_uint((dd[0][0] + dd[1][0]) + (dd[2][0] + dd[3][0])); part.y = __float_as_uint((dd[0][1] + dd[1][1]) + (dd[2][1] + dd[3][1]));
            part.z = __float_as_uint((dd[0][2] + dd[1][2]) + (dd[2][2] + dd[3][2])); part.w = __float_as_uint((dd[0][3] + dd[1][3]) + (dd[2][3] + dd[3][3]));
            st_async16(mapa(own + (M_DPIN - OFF_XSEL), h ^ 1), part, mapa(bars + 8 * B_DP, h ^ 1));
            sts128(own + 14336, part.x, part.y, part.z, part.w);
            __syncwarp();
            if (lane == 0) mbar_arrive(bars + 8 * B_DP);
        }
        WDUMP();
    } else {
        asm volatile("setmaxnreg.dec.sync.aligned.u32 40;");
        const int v = __reduce_max_sync(0xffffffffu, pw - PREP_W0);
        const bool gu = c < NGU_CTA;
        const uint32_t t0 = clock();
        const uint32_t bu = bars + 8 * v;
        if (lane == 0) {
            mbar_init(bu + 8 * B_X, 1);
            asm volatile("fence.mbarrier_init.release.cluster;" ::: "memory");
        }
        __syncwarp();
        if (DELAY_X > 0) __nanosleep(DELAY_X);
        bulk_load(sb + (v < 2 ? OFF_XSEL : OFF_RING + 2 * 8192) + v * 8192, p.u + (size_t)(16 * c + 4 * v) * D_, 8192, bu + 8 * B_X);
        if (lane == 0) {
#pragma unroll
            for (int i = 0; i < 10; i++) mbar_init(bu + 32 * i, 1);
            mbar_init(bu + 8 * B_XE, 1);
            mbar_init(bu + 8 * B_Y, v == 0 ? 12 : 9);
            mbar_init(bu + 8 * B_DP, (0x1855 >> (4 * v)) & 15);
            mbar_init(bu + 8 * B_F, 1);
            mbar_init(bu + 8 * B_H, 1);
            asm volatile("fence.mbarrier_init.release.cluster;" ::: "memory");
            mbar_expect(bu + 8 * B_Y, 4096);
            if (v != 2) mbar_expect(bu + 8 * B_DP, v == 0 ? 2048 : (h || v == 3) ? 16384 : 16384 + 128);
            mbar_expect(bu + 8 * B_F, c < NGU_CTA ? 16 : 0);
        }
        __syncwarp();
        asm volatile("barrier.cluster.arrive.relaxed.aligned;" ::: "memory");
        tma3d(sb + OFF_S + v * S_Q, &tm_x, 16 * pr, 64 * v + 32 * h - 1, bars + 8 * (B_S + v), S_Q);
        WSTAMP(9);
        if (v < 3 && lane == 0) asm volatile("prefetch.tensormap [%0];" :: "l"(v == 0 ? &tm_gu : v == 1 ? &tm_down : &tm_out) : "memory");
        asm volatile("barrier.cluster.wait.acquire.aligned;" ::: "memory");
        uint32_t desc;
        {
            const int s = 6 * v + lane, i = s >> 2, w = s & 3, slot = s < 14 ? s : (s | 1) == 17 ? s - 16 : s - 12;
            const int fb = s < 4 ? B_H : (gu && s >= 14) ? B_E + slot : s < 6 ? B_XE + s - 2 : B_KG;
            desc = slot | (fb << 4) | ((i < 4 ? 256 * w + 64 * i : 1792 * h + 448 * w + 224 * (i - 4)) << 10);
            if (lane < 6) mbar_expect(bars + 8 * (B_W + s), i < 4 ? 8192 : 7168);
            if (tid == 32 * PREP_W0) mbar_arrive(bars + 8 * B_H);
        }
        mbar_wait(bars + 8 * (B_H + v));
        {
            const int gap = v == 0 ? GAP : v == 1 ? GAP1 : v == 2 ? GAP2 : GAP3;
            uint32_t last = v ? clock() - SLACK : t0 + T0 - GAP + STAG * ((pr * 5) & 15) / 16;
#pragma unroll 1
            while ((int)(last - clock()) > 500) __nanosleep(256);
#pragma unroll 1
            for (int k = 0; k < 6; k++) {
                const uint32_t dk = __reduce_max_sync(0xffffffffu, lane == k ? desc : 0);
                const bool dn = 6 * v + k >= 16;
                mbar_wait(bars + ((dk >> 1) & 0x1f8));
                uint32_t now;
#pragma unroll 1
                while ((int)((now = clock()) - last) < gap) __nanosleep(CSLEEP);
                last = max((int)(now - last) - SLACK, gap) + last;
                WSTAMP(3 + k);
                if (gu || dn)
                    asm volatile("{\n\t.reg .pred p;\n\telect.sync _|p, 0xffffffff;\n\t"
                                 "@p cp.async.bulk.tensor.3d.shared::cluster.global.mbarrier::complete_tx::bytes [%0], [%1, {%3, %4, 0}], [%2];\n\t}"
                        :: "r"(sb + OFF_RING + (dk & 15) * 8192), "l"(dn ? &tm_down : &tm_gu), "r"(bars + 8 * (B_W + 6 * v + k)), "r"(dn ? 16 * pr : 32 * c), "r"(dk >> 10) : "memory");
                if (k < 5 && PRESLEEP) __nanosleep(PRESLEEP);
            }
            if (lane == 0 && v < 3) mbar_arrive(bars + 8 * (B_H + v + 1));
        }
        if (v < 2) {
            mbar_wait(bars + 8 * B_U);
            mbar_wait(bars + 8 * (gu ? B_G : B_H + 3));
            const uint32_t tag16 = lds32(sb + M_TAG);
            {
                const int k = v;
                uint4 q[4];
#pragma unroll 1
                for (int it = 0; it < (1 << 22); it++) {
                    uint32_t bad = 0;
#pragma unroll
                    for (int i = 0; i < 4; i++) q[i] = ld_gpu128(&p.sc->g[256 * h + 128 * k + 32 * i + lane]);
#pragma unroll
                    for (int i = 0; i < 4; i++) bad |= ((q[i].x ^ tag16) | (q[i].y ^ tag16)) | ((q[i].z ^ tag16) | (q[i].w ^ tag16));
                    if ((bad >> 16) == 0) break;
                    __nanosleep(200);
                }
#pragma unroll
                for (int i = 0; i < 4; i++)
                    asm volatile("st.shared.v2.u32 [%0], {%1, %2};" :: "r"(sb + OFF_GP + 1024 * k + 256 * i + lane * 8),
                                 "r"(__byte_perm(q[i].x, q[i].y, 0x5410)), "r"(__byte_perm(q[i].z, q[i].w, 0x5410)) : "memory");
            }
            __syncwarp();
            if (lane == 0) mbar_arrive(bars + 8 * B_Y);
        }
        {
            asm volatile("setmaxnreg.inc.sync.aligned.u32 72;");
            mbar_wait(bars + 8 * (B_W + PW));
            WSTAMP(1);
            mix_rows<2, true>(p, &tm_out, sb, sb + OFF_TAB + v * TAB_W, 0, PQ, v, h, pr, lane);
            WSTAMP(2);
            asm volatile("cp.async.bulk.commit_group;" ::: "memory");
            const uint32_t top = lds32(sb + M_TOP + 8 * v + 4 * (lane >> 4));
            const uint32_t row = ~top & 2047, ch = lane & 15, gp = gate_pos(row);
            const bool mine = ((row >> 8) & 1) == h;
            uint32_t gfin, x16, y16 = 0;
            asm volatile("ld.shared.u16 %0, [%1];" : "=r"(gfin) : "r"(sb + OFF_GP + gp * 2) : "memory");
            asm volatile("ld.shared.u16 %0, [%1];" : "=r"(x16) : "r"(sb + OFF_S + (row >> 9) * S_Q + s_addr((row & 7) * S_PL + 32 + (row & 248) * 4, ch >> 3) + 2 * (ch & 7)) : "memory");
            const float rsel = __uint_as_float(pin(__float_as_uint(bf_round(sigmoid_f(__uint_as_float((top ^ (((int)~top >> 31) | 0x80000000u)) & 0xffff0000u)))), lane));
            const uint32_t po = pin(sb + (4 * (ch & 7) + v) * 16 + (ch >> 3) * 8 + (lane >> 4) * 4, lane);
            bf16* op = pin(p.out + (size_t)row * D_ + 16 * pr + ch, lane);
            if (mine) {
                mbar_wait(bars + 8 * (B_Y + (row >> 9)));
                asm volatile("ld.shared.u16 %0, [%1];" : "=r"(y16)
                             : "r"(sb + y_off(row >> 9) + ch * 512 + (((4 * (row & 7) + ((row >> 5) & 3)) ^ (((ch >> 2) << 1) | (ch & 1))) << 4) + 2 * row_elem(row)) : "memory");
            }
            mbar_wait(bars + 8 * B_DP);
            float q[8];
#pragma unroll
            for (int i = 0; i < 4; i++) { q[i] = ldsf(po + M_DPIN + 512 * i); q[4 + i] = ldsf(po + OFF_XSEL + 14336 + 512 * i); }
            const float tot = ((q[0] + q[1]) + (q[2] + q[3])) + ((q[4] + q[5]) + (q[6] + q[7]));
            const float b = bf_round(__uint_as_float(x16 << 16) + bf_round(bf_round(tot) * rsel));
            if (mine) *op = __float2bfloat16_rn(fmaf(bf_lo(gfin), __uint_as_float(y16 << 16), bf_round(bf_round(1.f - bf_lo(gfin)) * b)));
        }
        asm volatile("cp.async.bulk.wait_group.read 0;" ::: "memory");
        WSTAMP(10);
        WDUMP();
    }
}

typedef CUresult (*EncodeFn)(CUtensorMap*, CUtensorMapDataType, cuuint32_t, void*, const cuuint64_t*, const cuuint64_t*,
                             const cuuint32_t*, const cuuint32_t*, CUtensorMapInterleave, CUtensorMapSwizzle,
                             CUtensorMapL2promotion, CUtensorMapFloatOOBfill);

void make_map(EncodeFn f, CUtensorMap* m, const void* ptr, uint64_t cols, uint64_t rows, uint64_t pitch, uint32_t bc, uint32_t br, CUtensorMapSwizzle sw, int prom,
              uint32_t planes = 1, uint64_t plane_stride = 0, uint32_t box_planes = 0) {
    cuuint64_t dims[3] = {cols, rows, planes};
    cuuint64_t str[2] = {pitch, planes > 1 ? plane_stride : pitch * rows};
    cuuint32_t box[3] = {bc, br, box_planes ? box_planes : planes};
    cuuint32_t es[3] = {1, 1, 1};
    f(m, CU_TENSOR_MAP_DATA_TYPE_BFLOAT16, 3, (void*)ptr, dims, str, box, es, CU_TENSOR_MAP_INTERLEAVE_NONE, sw,
      (CUtensorMapL2promotion)prom, CU_TENSOR_MAP_FLOAT_OOB_FILL_NONE);
}

}

extern "C" void kernel_launch(void* const* d_in, const int* in_sizes, int n_in, void* d_out, int out_size) {
    static EncodeFn enc = nullptr;
    static void *sc = nullptr, *band = nullptr;
    if (!enc) {
        void* fn = nullptr;
        cudaDriverEntryPointQueryResult qr;
        cudaGetDriverEntryPoint("cuTensorMapEncodeTiled", &fn, cudaEnableDefault, &qr);
        enc = (EncodeFn)fn;
        cudaGetSymbolAddress(&sc, g_scratch);
        cudaGetSymbolAddress(&band, g_band);
        cudaFuncSetAttribute(fused_kernel, cudaFuncAttributeMaxDynamicSharedMemorySize, SMEM_BYTES);
    }
    CUtensorMap tg, td, tx, to;
    const char *wg = (const char*)d_in[9], *wu = (const char*)d_in[10];
    const bool swap = wu < wg;
    make_map(enc, &tg, swap ? wu : wg, F_, D_, F_ * 2, 32, 64, CU_TENSOR_MAP_SWIZZLE_64B, PROMG, 2, swap ? wg - wu : wu - wg);
    make_map(enc, &td, d_in[11], D_, F_, D_ * 2, 16, 224, CU_TENSOR_MAP_SWIZZLE_32B, PROMD);
    make_map(enc, &tx, d_in[0], D_, L_ / 8, D_ * 16, 16, 33, CU_TENSOR_MAP_SWIZZLE_32B, PROMX, 8, D_ * 2);
    make_map(enc, &to, d_out, D_, L_ / 8, D_ * 16, 16, 32, CU_TENSOR_MAP_SWIZZLE_NONE, 0, 8, D_ * 2, 1);
    Params p;
    p.u = (const bf16*)d_in[0]; p.logA = (const bf16*)d_in[1]; p.Aim = (const bf16*)d_in[2];
    p.Cre = (const bf16*)d_in[3]; p.Cim = (const bf16*)d_in[4]; p.logdt = (const bf16*)d_in[5];
    p.Dskip = (const bf16*)d_in[6]; p.wr = (const bf16*)d_in[8]; p.gatew = (const bf16*)d_in[12];
    p.out = (bf16*)d_out;
    p.sc = (Scratch*)sc; p.band = (const uint4*)band;
    p.gu_swap = swap;
    p.zero = 0;
    fused_kernel<<<NCTA, NTHREADS, SMEM_BYTES>>>(p, tg, td, tx, to);
}
```

```cpp
#include <cuda_runtime.h>
#include <cuda_bf16.h>
#include <cuda_fp16.h>
#include <cuda.h>
#include <stdint.h>

typedef __nv_bfloat16 bf16;

namespace {

constexpr int L_ = 2048, D_ = 1024, F_ = 3584;
constexpr int NCTA = 130;
constexpr int NTHREADS = 512;
#define AUXW 12
constexpr int MAIN_W0 = 0, AUX_W0 = AUXW, PREP_W0 = 20 - AUXW;
#define T0 3500
#define GAP 590
#define GAP1 530
#define GAP2 530
#define GAP3 550
#define STAG GAP
#define CSLEEP 50
#define SLACK 300
#define DELAY_X 70
#define TSLEEP 40
#define RS 2
#define BULKM false
#define PW 19
#define PRESLEEP 64
#define PQ 3
#define PROMG 2
#define PROMD 1
#define PROMX 0
#define LATE2 0
#define HW 21
constexpr int NGU_CTA = 112;

constexpr int OFF_RING = 0;
constexpr int OFF_SCR  = 6 * 8192;
constexpr int S_PL     = 1056;
constexpr int S_Q      = 8 * S_PL;
constexpr int OFF_S    = 114688;
constexpr int OFF_GP   = OFF_S + 4 * S_Q;
constexpr int U_PL     = 2240;
constexpr int U_CH     = 4416;
constexpr int OFF_U    = 151552;
constexpr int TAB_W    = 3200;
constexpr int T_PL     = 544;
constexpr int T_A      = 2192 - 26 * 8;
constexpr int T_B      = 2568 - 59 * 8;
constexpr int OFF_TAB  = 186880;
constexpr int OFF_XSEL = 212480;
constexpr int XS_ROW   = 2064;
constexpr int OFF_BAND = 228992;
constexpr int OFF_MISC = 229536;
constexpr int M_BARS   = OFF_MISC;
constexpr int M_DSK    = OFF_MISC + 2736;
constexpr int M_SINK   = OFF_MISC + 512;
constexpr int M_TAG    = OFF_MISC + 516;
constexpr int M_BMAP   = OFF_MISC + 528;
constexpr int M_DPIN   = OFF_MISC + 656;
constexpr int M_TOP    = OFF_MISC + 2704;
constexpr int SMEM_BYTES = OFF_MISC + 2768;
__device__ __forceinline__ uint32_t s_addr(uint32_t o, uint32_t half) { return o + (((half ^ (o >> 7)) & 1) << 4); }
__host__ __device__ constexpr uint32_t y_off(uint32_t q) { return OFF_RING + 32768 + (q & 1) * 8192 + (q >> 1) * 65536; }

constexpr int B_W = 0;
constexpr int B_E = 24;
constexpr int B_S = 36;
constexpr int B_Y = 40;
constexpr int B_DP = 44, B_U = 45, B_KG = 46, B_G = 47;
constexpr int B_F = 48;
constexpr int B_H = 60;
constexpr int B_X = 52, B_XE = 56;

struct BandTab { uint32_t w[11][12]; };
constexpr BandTab make_band() {
    BandTab b{};
    for (int cls = 0; cls < 11; cls++)
        for (int wd = 0; wd < 10; wd++) {
            const int tau = cls + 2 - 8 * ((wd < 4 ? wd : wd - 4) >> 1);
            const int lo = (wd < 4) ? ((wd & 1) ? -2 : 3) : ((wd & 1) ? -4 : -11), wid = (wd < 4 ? 3 : 7) + 2 * (wd & 1);
            b.w[cls][wd] = ((tau >= lo && tau < lo + wid) ? 0x3F80u : 0u) | ((tau - 4 >= lo && tau - 4 < lo + wid) ? 0x3F800000u : 0u);
        }
    return b;
}
constexpr int NTOP = 32;
struct Scratch {
    uint4 r[L_ / 4 * RS];
    uint4 g[L_ / 4];
    uint4 h[2][8 * F_ / 8];
    uint32_t top[NTOP][32];
    unsigned epoch;
};
__device__ __align__(128) Scratch g_scratch;
__device__ const __align__(16) BandTab g_band = make_band();

struct Params {
    const bf16 *u, *logA, *Aim, *Cre, *Cim, *logdt, *Dskip, *wr, *gatew;
    bf16* out;
    Scratch* sc;
    const uint4* band;
    uint32_t gu_swap;
    uint32_t zero;
};

#define WSTAMP(i) do {} while (0)
#define KSTAMP(i, dep) do {} while (0)
#define WDUMP() do {} while (0)
#define RSTAMP(i) do {} while (0)

__device__ __forceinline__ uint32_t smem_u32(const void* p) { return (uint32_t)__cvta_generic_to_shared(p); }
__device__ __forceinline__ void mbar_init(uint32_t b, uint32_t c) { asm volatile("mbarrier.init.shared::cta.b64 [%0], %1;" :: "r"(b), "r"(c) : "memory"); }
__device__ __forceinline__ void mbar_expect(uint32_t b, uint32_t tx) { asm volatile("mbarrier.arrive.expect_tx.shared::cta.b64 _, [%0], %1;" :: "r"(b), "r"(tx) : "memory"); }
__device__ __forceinline__ void mbar_arrive(uint32_t b) { asm volatile("mbarrier.arrive.shared::cta.b64 _, [%0];" :: "r"(b) : "memory"); }
__device__ __forceinline__ void mbar_wait(uint32_t b, uint32_t parity = 0) {
    asm volatile("{\n\t.reg .pred p;\nW%=:\n\tmbarrier.try_wait.parity.shared::cta.b64 p, [%0], %1, 20000;\n\t@!p bra W%=;\n\t}" :: "r"(b), "r"(parity) : "memory");
}
__device__ __forceinline__ uint32_t mapa(uint32_t addr, uint32_t rank) { uint32_t r; asm("mapa.shared::cluster.u32 %0, %1, %2;" : "=r"(r) : "r"(addr), "r"(rank)); return r; }
__device__ __forceinline__ void tma3d(uint32_t dst, const CUtensorMap* tm, int c0, int c1, uint32_t bar, uint32_t bytes) {
    asm volatile("{\n\t.reg .pred p;\n\telect.sync _|p, 0xffffffff;\n\t"
                 "@p mbarrier.arrive.expect_tx.shared::cta.b64 _, [%2], %5;\n\t"
                 "@p cp.async.bulk.tensor.3d.shared::cluster.global.mbarrier::complete_tx::bytes [%0], [%1, {%3, %4, 0}], [%2];\n\t}"
        :: "r"(dst), "l"(tm), "r"(bar), "r"(c0), "r"(c1), "r"(bytes) : "memory");
}
__device__ __forceinline__ void bulk_load(uint32_t dst, const void* src, uint32_t bytes, uint32_t bar) {
    asm volatile("{\n\t.reg .pred p;\n\telect.sync _|p, 0xffffffff;\n\t"
                 "@p mbarrier.arrive.expect_tx.shared::cta.b64 _, [%2], %3;\n\t"
                 "@p cp.async.bulk.shared::cluster.global.mbarrier::complete_tx::bytes [%0], [%1], %3, [%2];\n\t}"
        :: "r"(dst), "l"(src), "r"(bar), "r"(bytes) : "memory");
}
__device__ __forceinline__ void st_async16(uint32_t dst, const uint4& v, uint32_t bar) {
    asm volatile("st.async.weak.shared::cluster.mbarrier::complete_tx::bytes.v4.b32 [%0], {%1,%2,%3,%4}, [%5];"
                 :: "r"(dst), "r"(v.x), "r"(v.y), "r"(v.z), "r"(v.w), "r"(bar) : "memory");
}
__device__ __forceinline__ void bar_sync(int id, int n) { asm volatile("bar.sync %0, %1;" :: "r"(id), "r"(n) : "memory"); }
__device__ __forceinline__ void cp16(uint32_t dst, const void* src) { asm volatile("cp.async.cg.shared.global [%0], [%1], 16;" :: "r"(dst), "l"(src) : "memory"); }
__device__ __forceinline__ void cp_wait_all() { asm volatile("cp.async.wait_all;" ::: "memory"); }
__device__ __forceinline__ uint4 ld_gpu128(const void* p) { uint4 v; asm volatile("ld.relaxed.gpu.global.v4.u32 {%0,%1,%2,%3}, [%4];" : "=r"(v.x), "=r"(v.y), "=r"(v.z), "=r"(v.w) : "l"(p) : "memory"); return v; }
__device__ __forceinline__ void st_gpu32(void* p, uint32_t v) { asm volatile("st.relaxed.gpu.global.u32 [%0], %1;" :: "l"(p), "r"(v) : "memory"); }

__device__ __forceinline__ void ldsm4(uint32_t a, uint32_t& r0, uint32_t& r1, uint32_t& r2, uint32_t& r3) {
    asm volatile("ldmatrix.sync.aligned.m8n8.x4.shared.b16 {%0,%1,%2,%3}, [%4];" : "=r"(r0), "=r"(r1), "=r"(r2), "=r"(r3) : "r"(a) : "memory");
}
__device__ __forceinline__ void ldsm4t(uint32_t a, uint32_t& r0, uint32_t& r1, uint32_t& r2, uint32_t& r3) {
    asm volatile("ldmatrix.sync.aligned.m8n8.x4.trans.shared.b16 {%0,%1,%2,%3}, [%4];" : "=r"(r0), "=r"(r1), "=r"(r2), "=r"(r3) : "r"(a) : "memory");
}
__device__ __forceinline__ uint32_t lds32(uint32_t a) { uint32_t v; asm volatile("ld.shared.u32 %0, [%1];" : "=r"(v) : "r"(a) : "memory"); return v; }
__device__ __forceinline__ uint2 lds64(uint32_t a) { uint2 v; asm volatile("ld.shared.v2.u32 {%0,%1}, [%2];" : "=r"(v.x), "=r"(v.y) : "r"(a) : "memory"); return v; }
__device__ __forceinline__ uint4 lds128(uint32_t a) { uint4 v; asm volatile("ld.shared.v4.u32 {%0,%1,%2,%3}, [%4];" : "=r"(v.x), "=r"(v.y), "=r"(v.z), "=r"(v.w) : "r"(a) : "memory"); return v; }
__device__ __forceinline__ void sts32(uint32_t a, uint32_t v) { asm volatile("st.shared.u32 [%0], %1;" :: "r"(a), "r"(v) : "memory"); }
__device__ __forceinline__ void sts16(uint32_t a, uint32_t v) { asm volatile("st.shared.u16 [%0], %1;" :: "r"(a), "h"((unsigned short)v) : "memory"); }
__device__ __forceinline__ void sts128(uint32_t a, uint32_t x, uint32_t y, uint32_t z, uint32_t w) { asm volatile("st.shared.v4.u32 [%0], {%1,%2,%3,%4};" :: "r"(a), "r"(x), "r"(y), "r"(z), "r"(w) : "memory"); }
__device__ __forceinline__ float ldsf(uint32_t a) { float v; asm volatile("ld.shared.f32 %0, [%1];" : "=f"(v) : "r"(a) : "memory"); return v; }

__device__ __forceinline__ void mma_bf(float (&d)[4], uint32_t a0, uint32_t a1, uint32_t a2, uint32_t a3, uint32_t b0, uint32_t b1) {
    asm volatile("mma.sync.aligned.m16n8k16.row.col.f32.bf16.bf16.f32 {%0,%1,%2,%3}, {%4,%5,%6,%7}, {%8,%9}, {%0,%1,%2,%3};"
        : "+f"(d[0]), "+f"(d[1]), "+f"(d[2]), "+f"(d[3]) : "r"(a0), "r"(a1), "r"(a2), "r"(a3), "r"(b0), "r"(b1));
}
__device__ __forceinline__ void mma_bf_z(float (&d)[4], uint32_t a0, uint32_t a1, uint32_t a2, uint32_t a3, uint32_t b0, uint32_t b1) {
    asm volatile("mma.sync.aligned.m16n8k16.row.col.f32.bf16.bf16.f32 {%0,%1,%2,%3}, {%4,%5,%6,%7}, {%8,%9}, {%10,%10,%10,%10};"
        : "=f"(d[0]), "=f"(d[1]), "=f"(d[2]), "=f"(d[3]) : "r"(a0), "r"(a1), "r"(a2), "r"(a3), "r"(b0), "r"(b1), "f"(0.f));
}
__device__ __forceinline__ void mma_bf_k8(float (&d)[4], uint32_t a0, uint32_t a1, uint32_t b0) {
    asm volatile("mma.sync.aligned.m16n8k8.row.col.f32.bf16.bf16.f32 {%0,%1,%2,%3}, {%4,%5}, {%6}, {%0,%1,%2,%3};"
        : "+f"(d[0]), "+f"(d[1]), "+f"(d[2]), "+f"(d[3]) : "r"(a0), "r"(a1), "r"(b0));
}
__device__ __forceinline__ void mma_h(float (&d)[4], uint32_t a0, uint32_t a1, uint32_t a2, uint32_t a3, uint32_t b0, uint32_t b1) {
    asm volatile("mma.sync.aligned.m16n8k16.row.col.f32.f16.f16.f32 {%0,%1,%2,%3}, {%4,%5,%6,%7}, {%8,%9}, {%0,%1,%2,%3};"
        : "+f"(d[0]), "+f"(d[1]), "+f"(d[2]), "+f"(d[3]) : "r"(a0), "r"(a1), "r"(a2), "r"(a3), "r"(b0), "r"(b1));
}
__device__ __forceinline__ uint32_t pack_bf(float lo, float hi) { uint32_t r; asm("cvt.rn.bf16x2.f32 %0, %1, %2;" : "=r"(r) : "f"(hi), "f"(lo)); return r; }
__device__ __forceinline__ uint32_t pack_h(float lo, float hi) { uint32_t r; asm("cvt.rn.f16x2.f32 %0, %1, %2;" : "=r"(r) : "f"(hi), "f"(lo)); return r; }
__device__ __forceinline__ float bf_lo(uint32_t v) { return __uint_as_float(v << 16); }
__device__ __forceinline__ float bf_hi(uint32_t v) { return __uint_as_float(v & 0xffff0000u); }
__device__ __forceinline__ float bf_round(float x) { return __uint_as_float(pack_bf(0.f, x)); }
__device__ __forceinline__ uint32_t hmul2_bf(uint32_t a, uint32_t b) { uint32_t r; asm("mul.rn.bf16x2 %0, %1, %2;" : "=r"(r) : "r"(a), "r"(b)); return r; }
__device__ __forceinline__ float ex2f(float x) { float r; asm("ex2.approx.ftz.f32 %0, %1;" : "=f"(r) : "f"(x)); return r; }

__device__ __forceinline__ float exp_acc(float x) {
    const float t = x * 1.4426950216293335f;
    const float r = fmaf(x, 1.4426950216293335f, -t) + x * 1.9259629911266175e-8f;
    return ex2f(t) * fmaf(r, 0.6931471805599453f, 1.f);
}
__device__ __forceinline__ float sigmoid_f(float x) { return __fdividef(1.f, 1.f + ex2f(-x * 1.4426950408889634f)); }
__device__ __forceinline__ void cexp_pow(float l2, float li, float e, float& zr, float& zi) {
    const float mag = ex2f(l2 * e);
    zr = mag * __cosf(li * e);
    zi = mag * __sinf(li * e);
}
__device__ __forceinline__ uint32_t hcmul(uint32_t a, uint32_t k, uint32_t kp) {
    const __half2 A = *reinterpret_cast<const __half2*>(&a);
    const __half2 r = __hfma2(__high2half2(A), *reinterpret_cast<const __half2*>(&kp), __hmul2(__low2half2(A), *reinterpret_cast<const __half2*>(&k)));
    return *reinterpret_cast<const uint32_t*>(&r);
}
#define CMUL(orr, oi, ar, ai, br, bi) do { float _r = (ar) * (br) - (ai) * (bi); float _i = (ar) * (bi) + (ai) * (br); orr = _r; oi = _i; } while (0)
#define CSQ(orr, oi, ar, ai) do { float _r = (ar) * (ar) - (ai) * (ai); float _i = 2.f * (ar) * (ai); orr = _r; oi = _i; } while (0)

__device__ __forceinline__ void mma_bf_k8z(float (&d)[4], uint32_t a0, uint32_t a1, uint32_t b0) {
    asm volatile("mma.sync.aligned.m16n8k8.row.col.f32.bf16.bf16.f32 {%0,%1,%2,%3}, {%4,%5}, {%6}, {%7,%7,%7,%7};"
        : "=f"(d[0]), "=f"(d[1]), "=f"(d[2]), "=f"(d[3]) : "r"(a0), "r"(a1), "r"(b0), "f"(0.f));
}
__device__ __forceinline__ void mma_hh_k8(uint32_t& d0, uint32_t& d1, uint32_t a0, uint32_t a1, uint32_t b0) {
    asm volatile("mma.sync.aligned.m16n8k8.row.col.f16.f16.f16.f16 {%0,%1}, {%2,%3}, {%4}, {%5,%5};"
        : "=r"(d0), "=r"(d1) : "r"(a0), "r"(a1), "r"(b0), "r"(0));
}
__device__ __forceinline__ uint32_t pin(uint32_t x, int lane) { return __shfl_sync(0xffffffffu, x, lane); }
template <class T> __device__ __forceinline__ T* pin(T* x, int lane) { return (T*)__shfl_sync(0xffffffffu, (unsigned long long)x, lane); }
__device__ __forceinline__ void sts32_if(bool on, uint32_t a, uint32_t v) {
    asm volatile("{\n\t.reg .pred p;\n\tsetp.ne.u32 p, %2, 0;\n\t@p st.shared.u32 [%0], %1;\n\t}" :: "r"(a), "r"(v), "r"((uint32_t)on) : "memory");
}
__device__ __forceinline__ void sts128_if(bool on, uint32_t a, uint32_t x, uint32_t y, uint32_t z, uint32_t w) {
    asm volatile("{\n\t.reg .pred p;\n\tsetp.ne.u32 p, %5, 0;\n\t@p st.shared.v4.u32 [%0], {%1,%2,%3,%4};\n\t}" :: "r"(a), "r"(x), "r"(y), "r"(z), "r"(w), "r"((uint32_t)on) : "memory");
}
__device__ __forceinline__ void lds128_if(bool on, uint32_t a, uint32_t (&v)[4]) {
    asm volatile("{\n\t.reg .pred p;\n\tsetp.ne.u32 p, %5, 0;\n\t@p ld.shared.v4.u32 {%0,%1,%2,%3}, [%4];\n\t}"
        : "+r"(v[0]), "+r"(v[1]), "+r"(v[2]), "+r"(v[3]) : "r"(a), "r"((uint32_t)on) : "memory");
}
__device__ __forceinline__ uint32_t hfma2_bf(uint32_t a, uint32_t b, uint32_t c) { uint32_t r; asm("fma.rn.bf16x2 %0, %1, %2, %3;" : "=r"(r) : "r"(a), "r"(b), "r"(c)); return r; }
__device__ __forceinline__ uint32_t row_elem(uint32_t row) { return ((row >> 5) & 4) | ((row >> 2) & 2) | ((row >> 4) & 1); }
__device__ __forceinline__ uint32_t gate_pos(uint32_t row) { return ((row >> 9) << 8) | ((row & 7) << 5) | (row_elem(row) << 2) | ((row >> 5) & 3); }

template <int N, bool BULK>
__device__ __forceinline__ void mix_rows(const Params& p, const CUtensorMap* tm_out, uint32_t sb, uint32_t ob, int Q0, int Q1, int w, int h, int pr, int lane) {
    const int g = lane >> 2, t = lane & 3, mi = lane >> 3, r = lane & 7;
    const int m8 = 16 * (g >> 2) + ((g >> 1) & 1) + 2 * (g & 1);
    uint32_t yi = sb + (4 * (r >> 1) + 2 * (mi & 1) + (r & 1)) * 512 + (((4 * w + (mi >> 1)) ^ r) << 4);
    uint32_t xs = sb + OFF_S + s_addr(w * S_PL + 32 + m8 * 32, t >> 1) + ((t & 1) << 3);
    uint32_t gs = sb + OFF_GP + w * 64 + g * 8, os = ob + m8 * 32 + t * 8;
    if (N > 1) { yi = pin(yi, lane); xs = pin(xs, lane); gs = pin(gs, lane); os = pin(os, lane); }
    mbar_wait(sb + M_BARS + 8 * B_Y);
#pragma unroll 1
    for (int Q = Q0; Q < Q1; Q++) {
        uint2 xq[N][4];
        uint32_t gg[N][4], sw[N];
#pragma unroll
        for (int n = 0; n < N; n++) {
#pragma unroll
            for (int i = 0; i < 4; i++) xq[n][i] = lds64((xs ^ (((i ^ n) & 1) << 4)) + Q * S_Q + n * 4 * S_PL + i * 128);
            const uint2 gq = lds64(gs + Q * 512 + n * 256);
            sw[n] = lds32(sb + M_BMAP + w * 16 + n * 64 + Q * 4);
#pragma unroll
            for (int i = 0; i < 4; i++) {
                gg[n][i] = __byte_perm(i < 2 ? gq.x : gq.y, 0, (i & 1) ? 0x3232 : 0x1010);
                const uint32_t og = hfma2_bf(gg[n][i], 0xBF80BF80u, 0x3F803F80u);
                xq[n][i].x = hmul2_bf(og, xq[n][i].x); xq[n][i].y = hmul2_bf(og, xq[n][i].y);
            }
        }
        mbar_wait(sb + M_BARS + 8 * (B_Y + Q));
        __syncwarp();
#pragma unroll
        for (int n = 0; n < N; n++) {
#pragma unroll
            for (int x = 0; x < 2; x++) {
                uint32_t y[4];
                ldsm4t((yi ^ (x << 5)) + y_off(Q) + n * 256, y[0], y[1], y[2], y[3]);
#pragma unroll
                for (int e = 0; e < 2; e++) {
                    uint2& o = xq[n][2 * x + e];
                    o.x = hfma2_bf(gg[n][2 * x + e], y[2 * e], o.x); o.y = hfma2_bf(gg[n][2 * x + e], y[2 * e + 1], o.y);
                }
            }
        }
        if (BULK && (sw[0] | sw[N - 1]) == 0) {
#pragma unroll
            for (int n = 0; n < N; n++)
#pragma unroll
                for (int i = 0; i < 4; i++)
                    asm volatile("st.shared.v2.u32 [%0], {%1, %2};" :: "r"(os + Q * 1024 + n * 4 * TAB_W + i * 128), "r"(xq[n][i].x), "r"(xq[n][i].y) : "memory");
            asm volatile("fence.proxy.async.shared::cta;" ::: "memory");
            __syncwarp();
#pragma unroll
            for (int n = 0; n < N; n++)
                asm volatile("{\n\t.reg .pred p;\n\telect.sync _|p, 0xffffffff;\n\t"
                             "@p cp.async.bulk.tensor.3d.global.shared::cta.bulk_group [%1, {%2, %3, %4}], [%0];\n\t}"
                    :: "r"(ob + 4 * n * TAB_W + Q * 1024), "l"(tm_out), "r"(16 * pr), "r"(64 * Q + 32 * h), "r"(w + 4 * n) : "memory");
        } else {
            bf16* op = p.out + (size_t)(512 * Q + 256 * h + 8 * m8 + w) * D_ + 16 * pr + 4 * t;
#pragma unroll
            for (int n = 0; n < N; n++)
#pragma unroll
                for (int i = 0; i < 4; i++)
                    if (!((sw[n] >> (4 * g)) & (1u << i))) *(uint2*)(op + (size_t)(32 * i + 4 * n) * D_) = xq[n][i];
        }
    }
}

__global__ void __cluster_dims__(2, 1, 1) __launch_bounds__(NTHREADS, 1)
fused_kernel(const Params p, const __grid_constant__ CUtensorMap tm_gu, const __grid_constant__ CUtensorMap tm_down,
             const __grid_constant__ CUtensorMap tm_x, const __grid_constant__ CUtensorMap tm_out) {
    extern __shared__ __align__(1024) unsigned char smem[];
    const uint32_t sb = smem_u32(smem);
    int tid;
    asm volatile("mov.u32 %0, %%tid.x;" : "=r"(tid));
    const int pw = tid >> 5, lane = tid & 31;
    const int c = blockIdx.x, h = c & 1, pr = c >> 1;
    const uint32_t bars = sb + M_BARS;

    uint2 v_la, v_ai, v_cr, v_ci;
    uint32_t ldt16;
    {
        const uint32_t po = c * 256 + tid;
        asm volatile("{\n\t.reg .pred p;\n\t.reg .b64 a;\n\tsetp.ne.u32 p, %16, 0;\n\t"
                     "mad.wide.u32 a, %14, 8, %9;\n\t@p ld.global.nc.L1::no_allocate.v2.u32 {%0,%1}, [a];\n\t"
                     "mad.wide.u32 a, %15, 2, %13;\n\t@p ld.global.nc.u16 %8, [a];\n\t"
                     "mad.wide.u32 a, %14, 8, %10;\n\t@p ld.global.nc.L1::no_allocate.v2.u32 {%2,%3}, [a];\n\t"
                     "mad.wide.u32 a, %14, 8, %11;\n\t@p ld.global.nc.L1::no_allocate.v2.u32 {%4,%5}, [a];\n\t"
                     "mad.wide.u32 a, %14, 8, %12;\n\t@p ld.global.nc.L1::no_allocate.v2.u32 {%6,%7}, [a];\n\t}"
            : "=r"(v_la.x), "=r"(v_la.y), "=r"(v_ai.x), "=r"(v_ai.y), "=r"(v_cr.x), "=r"(v_cr.y), "=r"(v_ci.x), "=r"(v_ci.y), "=r"(ldt16)
            : "l"(p.logA), "l"(p.Aim), "l"(p.Cre), "l"(p.Cim), "l"(p.logdt), "r"(po), "r"(po >> 5), "r"((uint32_t)(tid < 256 && c < 128)));
    }

    if (c >= 128) {
        if (c != 128) return;
        RSTAMP(5);
        const unsigned tag = (*(volatile unsigned*)&p.sc->epoch + 1) & 0xffffu;
        const uint32_t list = sb + 128;
#pragma unroll 1
        for (int pass = 0; pass < 2; pass++) {
            sts128(list + 16 * tid, 0, 0, 0, 0);
            if (tid == 0) sts32(sb + 64, 0);
            uint32_t key[4];
            bool ok = false;
#pragma unroll 1
            for (int it = 0; it < (1 << 22); it++) {
                const uint4 a = ld_gpu128(&p.sc->r[tid * RS]);
                key[0] = a.x; key[1] = a.y; key[2] = a.z; key[3] = a.w;
                ok = (((a.x ^ tag) | (a.y ^ tag) | (a.z ^ tag) | (a.w ^ tag)) & 0xffffu) == 0;
                if (ok || !pass) break;
            }
            WSTAMP(0);
            uint32_t m = 0;
#pragma unroll
            for (int i = 0; i < 4; i++) {
                key[i] = ((pass ? key[i] : (lane + i) << 16) & 0xffff0000u) | (uint32_t)(2047 - (4 * tid + i));
                m = max(m, key[i]);
            }
            const uint32_t wm = __reduce_max_sync(0xffffffffu, m);
            if (lane == 0) sts32(sb + pw * 4, wm);
            __syncthreads();
            uint32_t thr = 0xffffffffu;
#pragma unroll
            for (int i = 0; i < 4; i++) { const uint4 q = lds128(sb + 16 * i); thr = min(thr, min(max(q.x, q.y), max(q.z, q.w))); }
            if (thr != 1) WSTAMP(1);
            if (m >= thr) {
                uint32_t pos;
                asm volatile("atom.shared.add.u32 %0, [%1], %2;" : "=r"(pos) : "r"(sb + 64), "r"(4 * ((key[0] >= thr) + (key[1] >= thr) + (key[2] >= thr) + (key[3] >= thr))) : "memory");
#pragma unroll
                for (int i = 0; i < 4; i++) if (key[i] >= thr) { sts32(list + pos, key[i]); pos += 4; }
            }
            __syncthreads();
            const uint32_t nc4 = lds32(sb + 64);
            if (nc4 != 1) WSTAMP(2);
#pragma unroll 1
            for (uint32_t j = 4 * pw; j < nc4; j += 64) {
                const uint32_t mine = lds32(list + j);
                int rank = 0;
#pragma unroll 1
                for (uint32_t i = 0; i < nc4; i += 128) rank += __popc(__ballot_sync(0xffffffffu, lds32(list + i + 4 * lane) > mine));
                if (rank < 8 && lane == 0) sts32(sb + 96 + 4 * rank, mine);
            }
            __syncthreads();
            if (tid < 8 * NTOP) st_gpu32(&p.sc->top[tid >> 3][tid & 7], lds32(sb + 96 + 4 * (tid & 7)) | (((tag + pass - 1) & 31) << 11));
            WSTAMP(3);
            if (!pass) RSTAMP(4);
        }
        WDUMP();
        return;
    }

    WSTAMP(0);
    if (pw < 8) {
        const int d = 8 * c + pw - MAIN_W0;
        if (lane == 0) asm volatile("cp.async.ca.shared.global [%0], [%1], 4;" :: "r"(sb + M_DSK + 4 * (pw - MAIN_W0)), "l"(p.Dskip + (d & ~1)) : "memory");
        asm volatile("barrier.cluster.arrive.relaxed.aligned;" ::: "memory");
        const int warp = pw - MAIN_W0;
        asm volatile("setmaxnreg.inc.sync.aligned.u32 168;");
        const int g = lane >> 2, t = lane & 3;
        const int mi = lane >> 3, r = lane & 7;
        const uint32_t TB = sb + OFF_TAB + warp * TAB_W;
        const uint32_t UB = sb + OFF_U + warp * U_CH;
        if (mi < 2) sts128(UB + mi * U_PL + r * 16, 0, 0, 0, 0);
        if (lane < 4) sts128(TB + lane * T_PL, 0, 0, 0, 0);
        sts128(sb + OFF_SCR + warp * 8192 + lane * 16, 0x3C00u, 0x3C00u, 0x3C00u, 0x3C00u);
        __syncwarp();

        uint32_t cfix;
        {
            KSTAMP(4, v_la.x ^ v_ai.x ^ v_cr.x ^ v_ci.x ^ ldt16);
            const float dt = bf_round(exp_acc(__uint_as_float(ldt16 << 16)));
            float l2[4], li[4];
            {
                const uint32_t la[2] = {v_la.x, v_la.y}, ai[2] = {v_ai.x, v_ai.y};
                const float dt2 = -1.4426950408889634f * dt;
#pragma unroll
                for (int i = 0; i < 4; i++) {
                    l2[i] = bf_round(ex2f(((i & 1) ? bf_hi(la[i >> 1]) : bf_lo(la[i >> 1])) * 1.4426950408889634f)) * dt2;
                    li[i] = ((i & 1) ? bf_hi(ai[i >> 1]) : bf_lo(ai[i >> 1])) * dt;
                }
            }
            const uint32_t SX = sb + OFF_SCR + warp * 8192;
            const uint32_t sw = SX + (lane << 4);
#define PUT(buf, row, v) sts128(((sw + (row) * 512) ^ ((row) << 4)) + (buf) * 4096, v[0], v[1], v[2], v[3])
#define EMIT(bufa, rowa, bufb, rowb, xr, xi, k, kp) do { uint32_t pk[4], pd[4]; \
                _Pragma("unroll") for (int i = 0; i < 4; i++) { pk[i] = pack_h(xr[i], xi[i]); pd[i] = hcmul(pk[i], k[i], kp[i]); } \
                PUT(bufa, rowa, pk); PUT(bufb, rowb, pd); } while (0)
#define CMUL4(orr, oi, ar, ai, br, bi) _Pragma("unroll") for (int i = 0; i < 4; i++) CMUL(orr[i], oi[i], ar[i], ai[i], br[i], bi[i])
#define CSQ4(orr, oi, ar, ai) _Pragma("unroll") for (int i = 0; i < 4; i++) CSQ(orr[i], oi[i], ar[i], ai[i])
            float z1r[4], z1i[4], z2r[4], z2i[4], z8r[4], z8i[4], z256r[4], z256i[4];
            uint32_t k4[4], k4p[4];
            float z4r[4], z4i[4];
#pragma unroll
            for (int i = 0; i < 4; i++) cexp_pow(l2[i], li[i], 1.f, z1r[i], z1i[i]);
            CSQ4(z2r, z2i, z1r, z1i);
            CSQ4(z4r, z4i, z2r, z2i);
            CSQ4(z8r, z8i, z4r, z4i);
            KSTAMP(5, __float_as_uint(z8r[3]));
            uint32_t Ya[16][4];
            float cr[4], ci[4], inv;
            {
                float w1r[4], w1i[4], ar[4], ai[4], br[4], bi[4];
                uint32_t k8[4], k8p[4];
#pragma unroll
                for (int i = 0; i < 4; i++) {
                    k8[i] = pack_h(z8r[i], -z8i[i]); k8p[i] = pack_h(z8i[i], z8r[i]);
                    CSQ(w1r[i], w1i[i], z8r[i], z8i[i]); w1i[i] = -w1i[i];
                }
                PUT(1, 0, k8);
                EMIT(0, 1, 1, 1, w1r, w1i, k8, k8p);
                CSQ4(ar, ai, w1r, w1i);            EMIT(0, 2, 1, 2, ar, ai, k8, k8p);
                CMUL4(br, bi, ar, ai, w1r, w1i);   EMIT(0, 3, 1, 3, br, bi, k8, k8p);
                CSQ4(ar, ai, ar, ai);              EMIT(0, 4, 1, 4, ar, ai, k8, k8p);
                CMUL4(ar, ai, ar, ai, w1r, w1i);   EMIT(0, 5, 1, 5, ar, ai, k8, k8p);
                CSQ4(br, bi, br, bi);              EMIT(0, 6, 1, 6, br, bi, k8, k8p);
                CMUL4(br, bi, br, bi, w1r, w1i);   EMIT(0, 7, 1, 7, br, bi, k8, k8p);
                __syncwarp();
                KSTAMP(6, 0);
                const uint32_t ab = SX + (mi & 1) * 4096 + r * 512, ax = ((mi >> 1) ^ r) << 4;
                const uint32_t vr[2] = {v_cr.x, v_cr.y}, vi[2] = {v_ci.x, v_ci.y};
                const uint32_t m2 = __vmaxu2(__vmaxu2(vr[0] & 0x7fff7fffu, vr[1] & 0x7fff7fffu), __vmaxu2(vi[0] & 0x7fff7fffu, vi[1] & 0x7fff7fffu));
                const uint32_t mx = __reduce_max_sync(0xffffffffu, max(m2, m2 << 16));
                const uint32_t e = min(max(mx >> 23, 11u), 254u);
                const float sc = __uint_as_float((264u - e) << 23);
                inv = __uint_as_float((e - 10u) << 23) * (2.f * dt);
#pragma unroll
                for (int i = 0; i < 4; i++) {
#pragma unroll
                    for (int k = 0; k < 4; k++) ldsm4(ab + (ax ^ (i << 5)) + k * 128, Ya[4 * k + i][0], Ya[4 * k + i][1], Ya[4 * k + i][2], Ya[4 * k + i][3]);
                    float tr, ti;
                    cexp_pow(l2[i], li[i], 128.f, tr, ti);
                    sts32(TB + 2176 + 256 * i + 4 * lane, pack_h(tr, ti));
                    sts32(TB + 2176 + 256 * i + 128 + 4 * (lane ^ 16), pack_h(-ti, tr));
                    k4[i] = pack_h(z4r[i], z4i[i]); k4p[i] = pack_h(-z4i[i], z4r[i]);
                    CSQ(z256r[i], z256i[i], tr, ti);
                    cr[i] = ((i & 1) ? bf_hi(vr[i >> 1]) : bf_lo(vr[i >> 1])) * sc;
                    ci[i] = ((i & 1) ? bf_hi(vi[i >> 1]) : bf_lo(vi[i >> 1])) * sc;
                }
                __syncwarp();
            }
            KSTAMP(7, Ya[15][0]);
            const uint32_t ld0 = SX + r * 512 + ((mi ^ r) << 4), ld1 = ld0 ^ 64;
            float R[6][4], s1024;
            {
                float xr[4], xi[4], yr[4], yi[4];
                EMIT(0, 0, 0, 1, cr, ci, k4, k4p);
                CMUL4(yr, yi, cr, ci, z1r, z1i);        EMIT(0, 2, 0, 3, yr, yi, k4, k4p);
                CMUL4(xr, xi, cr, ci, z256r, z256i);    EMIT(1, 0, 1, 1, xr, xi, k4, k4p);
                CMUL4(yr, yi, yr, yi, z1r, z1i);        EMIT(0, 4, 0, 5, yr, yi, k4, k4p);
                CMUL4(cr, ci, xr, xi, z2r, z2i);        EMIT(1, 2, 1, 3, cr, ci, k4, k4p);
                CMUL4(yr, yi, yr, yi, z1r, z1i);        EMIT(0, 6, 0, 7, yr, yi, k4, k4p);
                CMUL4(xr, xi, xr, xi, z256r, z256i);    EMIT(1, 4, 1, 5, xr, xi, k4, k4p);
                CMUL4(xr, xi, xr, xi, z256r, z256i);    EMIT(1, 6, 1, 7, xr, xi, k4, k4p);
                CMUL4(xr, xi, xr, xi, z256r, z256i);
                s1024 = (xr[0] + xr[1]) + (xr[2] + xr[3]);
#pragma unroll
                for (int m = 0; m < 4; m++) {
                    if (m == 0) { CMUL4(xr, xi, xr, xi, z8r, z8i); } else { CMUL4(xr, xi, xr, xi, z256r, z256i); }
                    sts128(TB + m * T_PL + 16 + 16 * lane, pack_h(xr[0], xi[0]), pack_h(xr[1], xi[1]), pack_h(xr[2], xi[2]), pack_h(xr[3], xi[3]));
                }
            }
            asm volatile("barrier.cluster.wait.acquire.aligned;" ::: "memory");
            __syncwarp();
            {
                KSTAMP(8, 0);
                uint32_t bd[2][4] = {{0, 0, 0, 0}, {0, 0, 0, 0}};
                const bool on = (g >> 1) == t;
#pragma unroll
                for (int i = 0; i < 6; i++) { R[i][0] = R[i][1] = R[i][2] = R[i][3] = 0.f; }
#pragma unroll
                for (int k2 = 0; k2 < 8; k2++) {
                    uint32_t x[4], y[4], z[4], a1[2][4];
                    lds128_if(on, TB + 2176 + g * 128 + (k2 < 4 ? 64 : -64) * (g & 1) + 16 * k2, bd[k2 & 1]);
                    ldsm4(TB + (r & 3) * T_PL + 16 + 16 * mi + 64 * k2, z[0], z[1], z[2], z[3]);
                    ldsm4(((k2 & 1) ? ld1 : ld0) + (k2 >> 1) * 128, x[0], x[1], x[2], x[3]);
                    ldsm4(((k2 & 1) ? ld1 : ld0) + (k2 >> 1) * 128 + 4096, y[0], y[1], y[2], y[3]);
#pragma unroll
                    for (int u = 0; u < 2; u++) {
                        mma_hh_k8(a1[u][0], a1[u][1], Ya[2 * k2 + u][0], Ya[2 * k2 + u][1], bd[k2 & 1][2 * u]);
                        mma_hh_k8(a1[u][2], a1[u][3], Ya[2 * k2 + u][2], Ya[2 * k2 + u][3], bd[k2 & 1][2 * u + 1]);
                    }
#pragma unroll
                    for (int u = 0; u < 2; u++) {
                        const uint32_t(&a0)[4] = Ya[2 * k2 + u];
                        mma_h(R[0], a0[0], a0[1], a0[2], a0[3], x[2 * u], x[2 * u + 1]);
                        mma_h(R[2], a0[0], a0[1], a0[2], a0[3], y[2 * u], y[2 * u + 1]);
                        mma_h(R[4], a0[0], a0[1], a0[2], a0[3], z[2 * u], z[2 * u + 1]);
                        mma_h(R[1], a1[u][0], a1[u][1], a1[u][2], a1[u][3], x[2 * u], x[2 * u + 1]);
                        mma_h(R[3], a1[u][0], a1[u][1], a1[u][2], a1[u][3], y[2 * u], y[2 * u + 1]);
                        mma_h(R[5], a1[u][0], a1[u][1], a1[u][2], a1[u][3], z[2 * u], z[2 * u + 1]);
                    }
                }
            }
            __syncwarp();
            KSTAMP(9, __float_as_uint(R[3][0]));
            if (lane == 0) mbar_arrive(bars + 8 * B_KG + (__float_as_uint(R[0][0]) & __float_as_uint(R[2][0]) & p.zero));
            sts128(TB + 2176 + 16 * lane, 0, 0, 0, 0);
            sts128(TB + 2688 + 16 * lane, 0, 0, 0, 0);
            __syncwarp();
#undef PUT
#undef EMIT
#pragma unroll
            for (int o = 16; o > 0; o >>= 1) s1024 += __shfl_xor_sync(0xffffffffu, s1024, o);
            uint32_t w[4][4], dsk = 0;
            cp_wait_all();
            asm volatile("{\n\t.reg .pred p;\n\tsetp.eq.u32 p, %2, 0;\n\t@p ld.shared.u16 %0, [%1];\n\t}" : "+r"(dsk) : "r"(sb + M_DSK + 4 * warp + 2 * (warp & 1)), "r"(lane) : "memory");
#pragma unroll
            for (int a = 0; a < 4; a++) {
                const float v0 = (a == 0) ? fmaf(R[0][0], inv, __uint_as_float(dsk << 16)) : R[a][0] * inv;
                const float v1 = R[a][1] * inv, v2 = R[a][2] * inv, v3 = R[a][3] * inv;
                w[a][0] = pack_bf(v0, 0.f); w[a][1] = pack_bf(v1, v0); w[a][2] = pack_bf(v2, v1); w[a][3] = pack_bf(v3, v2);
            }
            const uint32_t wb = TB + 16 + 16 * g, w1 = wb + t * T_PL, w2 = wb + 256 + 2 * t * T_PL;
            const uint32_t w3 = (t == 0) ? wb + 256 + 3 * T_PL : TB + T_A + 8 * (16 * t + g);
            const uint32_t w3s = (t == 0) ? 128 : 64, w3o = (t == 0) ? 8 : 12;
            const uint32_t k512 = __shfl_sync(0xffffffffu, w[2][1], 2);
#pragma unroll
            for (int a = 0; a < 2; a++) {
                sts128(w1 + 128 * a, w[a][0], w[a][1], w[a][2], w[a][3]);
                const uint32_t(&q)[4] = w[2 + a];
                if (t < 2) sts128(w2 + 128 * a, q[0], q[1], q[2], q[3]);
                if (t == 0) { sts128(w2 + T_PL + 128 * a, q[0], q[1], q[2], q[3]); sts32(w3 + 128 * a + 4, q[2]); }
                sts32_if(t != 1 && (a == 1 || lane != 2), w3 + w3s * a, q[1]);
                sts32_if(t != 1, w3 + w3s * a + w3o, q[3]);
            }
            sts128_if(lane < 4, w1 + 512, t == 3 ? k512 : k512 >> 16, t < 2 ? k512 : t == 2 ? k512 & 0xffff0000u : k512 << 16, t < 2 ? k512 << 16 : 0u, 0);
            __syncwarp();
#pragma unroll
            for (int a = 0; a < 2; a++) {
                sts16(w1 + 128 * a + 18, w[a][3]);
                const uint32_t(&q)[4] = w[2 + a];
                if (t < 2) sts16(w2 + 128 * a + 18, q[3]);
                if (t == 0) { sts16(w2 + T_PL + 128 * a + 18, q[3]); sts16(w3 + 128 * a + 14, q[3]); }
            }
            if (t == 0) sts16(w3 + 128 - 4, w[3][0]);
            if (lane == 2 || (t == 0 && g > 0)) sts16(lane == 2 ? TB + 16 + 3 * T_PL + 4 * 127 : w3 - 4, w[2][0]);
            {
                float q[4];
#pragma unroll
                for (int i = 0; i < 4; i++) q[i] = (t < 2 ? R[4][i] : R[5][i]) * inv;
                const uint32_t b0 = pack_bf(q[0], q[2]), b1 = pack_bf(q[1], q[3]);
                const uint32_t wq = TB + T_B + 8 * (65 + 32 * (t & 1) + 4 * (t & 2) + g);
                sts32(wq, b0); sts32(wq + 12, b0); sts32(wq + 128, b1); sts32(wq + 140, b1);
            }
            cfix = pack_bf(s1024 * inv, s1024 * inv);
            if (lane == 0) sts32(TB + T_A + 8 * 64, cfix);
            __syncwarp();
        }
        WSTAMP(1);

        mbar_wait(bars + 8 * B_U);
        WSTAMP(2);

        float D[16][4];
        {
            const int x5 = g - t + 5;
            const uint32_t tabD = TB + (x5 & 3) * T_PL + (x5 & 12) + 16;
            {
                const uint32_t a1 = lds32(tabD - 8), a0 = p.zero;
#pragma unroll
                for (int jq = 0; jq < 4; jq++) {
                    uint32_t b[4];
                    ldsm4(UB + (9 + lane) * 16 + jq * 512, b[0], b[1], b[2], b[3]);
#pragma unroll
                    for (int i = 0; i < 4; i++) mma_bf_k8z(D[4 * jq + i], a0, a1, b[i]);
                }
            }
            const uint32_t ua = UB + (mi & 1) * U_PL + (8 + 8 * (mi >> 1) + r) * 16;
#pragma unroll 1
            for (int k0 = 0; k0 < 8; k0++) {
                uint32_t Uf[16][2];
#pragma unroll
                for (int jp = 0; jp < 8; jp++) ldsm4(ua + jp * 256 - k0 * 16, Uf[2 * jp][0], Uf[2 * jp][1], Uf[2 * jp + 1][0], Uf[2 * jp + 1][1]);
#pragma unroll
                for (int k1 = 0; k1 < 4; k1++) {
                    const uint32_t ta = tabD + 16 * (8 * k1 + k0);
                    const uint32_t a0 = lds32(ta), a1 = lds32(ta + 8), a2 = lds32(ta - 8), a3 = a0 ^ p.zero;
#pragma unroll
                    for (int J = k1; J < 16; J++) mma_bf(D[J], a0, a1, a2, a3, Uf[J - k1][0], Uf[J - k1][1]);
                }
                if (k0 == 0) {
                    const uint32_t ta = tabD + 16 * 32;
                    const uint32_t a0 = lds32(ta), a1 = lds32(ta + 8), a2 = lds32(ta - 8), a3 = a0 ^ p.zero;
#pragma unroll
                    for (int J = 4; J < 16; J++) mma_bf(D[J], a0, a1, a2, a3, Uf[J - 4][0], Uf[J - 4][1]);
                    const uint32_t f0 = (cfix ^ 0x80008000u) & (g == t ? 0xffffu : g == t + 4 ? 0xffff0000u : 0u);
                    const uint32_t f1 = p.zero, f2 = p.zero + p.zero, f3 = f0 ^ p.zero;
#pragma unroll
                    for (int J = 8; J < 16; J++) mma_bf(D[J], f0, f1, f2, f3, Uf[J - 8][0], Uf[J - 8][1]);
                }
            }
        }
        WSTAMP(3);
        {
            const int ch = 8 * h + warp;
            const uint32_t yo = sb + ch * 512 + ((lane ^ (((ch >> 2) << 1) | (ch & 1))) << 4);
            const uint32_t yr = mapa(yo, h ^ 1), ybr = mapa(bars + 8 * B_Y, h ^ 1);
            auto ship = [&](const int Q) {
                uint4 y[2];
#pragma unroll
                for (int hh = 0; hh < 2; hh++) {
                    const int J = 4 * Q + 2 * hh;
                    y[hh] = make_uint4(pack_bf(D[J][0], D[J][1]), pack_bf(D[J][2], D[J][3]), pack_bf(D[J + 1][0], D[J + 1][1]), pack_bf(D[J + 1][2], D[J + 1][3]));
                }
                if (!(Q & 1)) mbar_wait(bars + 8 * (B_F + (Q >> 1)));
                asm volatile("{\n\t.reg .pred p;\n\tsetp.eq.u32 p, %11, 0;\n\t"
                             "@p st.async.weak.shared::cluster.mbarrier::complete_tx::bytes.v4.b32 [%9], {%4,%5,%6,%7}, [%10];\n\t"
                             "@!p st.async.weak.shared::cluster.mbarrier::complete_tx::bytes.v4.b32 [%9], {%0,%1,%2,%3}, [%10];\n\t"
                             "@p st.shared.v4.b32 [%8], {%0,%1,%2,%3};\n\t@!p st.shared.v4.b32 [%8], {%4,%5,%6,%7};\n\t}"
                             :: "r"(y[0].x), "r"(y[0].y), "r"(y[0].z), "r"(y[0].w), "r"(y[1].x), "r"(y[1].y), "r"(y[1].z), "r"(y[1].w),
                                "r"(yo + y_off(Q)), "r"(yr + y_off(Q)), "r"(ybr + 8 * Q), "r"(h) : "memory");
                __syncwarp();
                if (lane == 0) mbar_arrive(bars + 8 * (B_Y + Q));
            };
            ship(0);
            const uint4 bA = lds128(sb + OFF_BAND + (g - t + 3) * 48), bB = lds128(sb + OFF_BAND + (g - t + 3) * 48 + 16);
            const uint2 bC = lds64(sb + OFF_BAND + (g - t + 3) * 48 + 32);
            uint2 QA[5][2], QB[8];
            const uint32_t tq = TB + 8 * (1 + g - 2 * t);
#pragma unroll
            for (int dd = 0; dd < 5; dd++) { QA[dd][0] = lds64(tq + T_A + 64 * (dd + 4)); QA[dd][1] = lds64(tq + T_A + 64 * (dd + 4) - 8); }
#pragma unroll
            for (int dd = 0; dd < 8; dd++) QB[dd] = lds64(tq + T_B + 64 * (dd + 8));
            const uint32_t u1 = UB + (mi & 1) * U_PL + (7 + r + (mi >> 1)) * 16;
            const uint32_t u2 = UB + ((mi & 1) ^ 1) * U_PL + (7 + r + (mi & 1) + 8 * (mi >> 1)) * 16;
            uint32_t n[4];
#pragma unroll
            for (int j = 0; j < 12; j++) {
                uint32_t m[4];
                ldsm4(u1 + j * 128, m[0], m[1], m[2], m[3]);
                if (!(j & 1)) ldsm4(u2 + j * 128, n[0], n[1], n[2], n[3]);
                const uint32_t n0 = n[2 * (j & 1)], n1 = n[2 * (j & 1) + 1];
                float wa[4], wb[4], wc[4], g1[4], g2[4];
                mma_bf_z(wa, bA.x, bA.y, bA.z, bA.w, m[0], m[1]);
                mma_bf_z(wb, bA.x, bA.y, bA.z, bA.w, n0, n1);
                mma_bf_z(wc, bA.x, bA.y, bA.z, bA.w, m[2], m[3]);
                if (j < 8) {
                    mma_bf_z(g1, bB.x, bB.y, bB.z, bB.w, m[0], m[1]);
                    mma_bf_z(g2, bB.x, bB.y, bB.z, bB.w, n0, n1);
                    mma_bf_k8(g1, bC.x, bC.y, m[2]);
                    mma_bf_k8(g2, bC.x, bC.y, m[3]);
                }
#pragma unroll
                for (int e = 0; e < 2; e++) {
                    const uint32_t q0 = pack_bf(wa[e], wa[e + 2]), q1 = pack_bf(wb[e], wb[e + 2]), q2 = q1 ^ p.zero, q3 = pack_bf(wc[e], wc[e + 2]);
#pragma unroll
                    for (int dd = 0; dd < 5; dd++)
                        if (j + 4 + dd < 16) mma_bf(D[j + 4 + dd], q0, q1, q2, q3, QA[dd][e].x, QA[dd][e].y);
                }
                if (j < 8) {
                    const uint32_t q0 = pack_bf(g1[0], g1[2]), q1 = pack_bf(g2[0], g2[2]), q2 = pack_bf(g1[1], g1[3]), q3 = pack_bf(g2[1], g2[3]);
#pragma unroll
                    for (int dd = 7 - j; dd >= 0; dd--) mma_bf(D[j + 8 + dd], q0, q1, q2, q3, QB[dd].x, QB[dd].y);
                }
                if ((j & 3) == 3) {
                    WSTAMP(4 + 2 * (j >> 2));
                    if (j == 11 && LATE2) ship(2);
                    if (j != 7 || !LATE2) ship((j >> 2) + 1);
                }
            }
        }
        const int warpu = __reduce_max_sync(0xffffffffu, warp);
        mix_rows<1, BULKM>(p, &tm_out, sb, sb + OFF_U + warpu * U_CH + (warpu & 1) * 64, PQ, 4, warpu, h, pr, lane);
        if (BULKM) asm volatile("cp.async.bulk.commit_group;\n\tcp.async.bulk.wait_group.read 0;" ::: "memory");
        WSTAMP(10);
        WDUMP();
    } else if ((pw & 12) == AUX_W0) {
        asm volatile("setmaxnreg.inc.sync.aligned.u32 136;");
        const int v = __reduce_max_sync(0xffffffffu, pw & 3);
        const int at = tid & 127;
        const int g = lane >> 2, t = lane & 3;
        unsigned tag;
        const bool gu = c < NGU_CTA;
        {
            const uint32_t xb = sb + (v < 2 ? OFF_XSEL : OFF_RING + 2 * 8192) + v * 8192;
            const uint32_t gws = sb + M_DPIN;
            const uint32_t row = 16 * c + 4 * v + (g >> 1);
#pragma unroll
            for (int i = 0; i < 8; i++)
                asm volatile("cp.async.ca.shared.global [%0], [%1], 4;" :: "r"((i < 4 ? sb + OFF_GP : gws) + 512 * (i & 3) + (tid & 124) * 4 + (tid & 1) * 8 + (tid & 2) * 2),
                             "l"((i < 4 ? p.wr : p.gatew) + 256 * (i & 3) + (tid & 127) * 2) : "memory");
            if ((tid & 127) < 33) cp16(sb + OFF_BAND + (tid & 127) * 16, p.band + (tid & 127));
            asm volatile("barrier.cluster.arrive.relaxed.aligned;" ::: "memory");
            tag = __reduce_max_sync(0xffffffffu, (*(volatile unsigned*)&p.sc->epoch + 1) & 0xffffu);
            if (gu) st_gpu32((uint32_t*)&p.sc->h[(tag + 1) & 1][32 * c] + at, 0);
            if (v == 3) sts32(sb + M_BMAP + lane * 4, 0);
            if (at == 0) sts32(sb + M_TAG, tag << 16);
            cp_wait_all();
            bar_sync(1, 128);
            uint2 w[16];
#pragma unroll
            for (int kb = 0; kb < 16; kb++) w[kb] = lds64((g < 4 ? sb + OFF_GP : gws) + 128 * kb + 32 * (g & 2) + 16 * t + 8 * (g & 1));
            asm volatile("barrier.cluster.wait.acquire.aligned;" ::: "memory");
            mbar_wait(bars + 8 * (B_X + v));
            WSTAMP(10);
            float dr[4][4];
#pragma unroll
            for (int kb = 0; kb < 16; kb++) {
                const uint4 x = lds128(xb + (g >> 1) * 2048 + 128 * kb + 16 * (lane & 7));
                if (kb < 4) mma_bf_z(dr[kb], x.x, x.y, x.z, x.w, w[kb].x, w[kb].y);
                else mma_bf(dr[kb & 3], x.x, x.y, x.z, x.w, w[kb].x, w[kb].y);
            }
            float rs = ((dr[0][0] + dr[0][3]) + (dr[1][0] + dr[1][3])) + ((dr[2][0] + dr[2][3]) + (dr[3][0] + dr[3][3]));
            if (lane == 0) mbar_arrive(bars + 8 * (B_XE + v) + (__float_as_uint(rs) & p.zero));
            rs += __shfl_xor_sync(0xffffffffu, rs, 5);
            const uint32_t rb = pack_bf(0.f, rs);
            if (!(lane & 7)) st_gpu32((uint32_t*)&p.sc->r[(row >> 2) * RS] + (row & 3), ((rb ^ (((int)rb >> 31) | 0x80000000u)) & 0xffff0000u) | tag);
            WSTAMP(1);
            {
                const int n = 3 + (lane >> 3) + 4 * (lane & 1);
                const uint32_t so = (n & 7) * S_PL + ((lane & 6) + (n >> 3)) * 32;
                const uint32_t src[2] = {sb + OFF_S + v * S_Q + s_addr(so, h), sb + OFF_S + v * S_Q + s_addr(so + 32, h)};
                const uint32_t dst = sb + OFF_U + g * U_CH + (8 + 32 * v + 16 * h + t) * 16;
                const uint32_t rdst = mapa(dst, h ^ 1), rbar = mapa(bars + 8 * B_U, h ^ 1);
                mbar_wait(bars + 8 * (B_S + v));
                WSTAMP(9);
                uint4 a[8];
#pragma unroll
                for (int b = 0; b < 2; b++) {
#pragma unroll
                    for (int j = 0; j < 8; j++) ldsm4t((b ? src[j & 1] : src[j & 1] ^ 16) + (j >> 1) * 256, a[j].x, a[j].y, a[j].z, a[j].w);
#pragma unroll
                    for (int j = 0; j < 8; j++) {
                        if (b) sts128(dst + (j >> 1) * 64 + (j & 1) * U_PL, a[j].x, a[j].y, a[j].z, a[j].w);
                        else st_async16(rdst + (j >> 1) * 64 + (j & 1) * U_PL, a[j], rbar);
                    }
                }
                if (h && v == 3) {
                    ldsm4t((src[0] ^ 16) + 1024, a[0].x, a[0].y, a[0].z, a[0].w);
                    ldsm4t(src[0] + 1024, a[1].x, a[1].y, a[1].z, a[1].w);
                    if (t == 0) {
                        st_async16(rdst + 256, make_uint4(a[0].x, a[0].y & 0xffffu, a[0].z & 0xffffu, a[0].w & 0xffffu), rbar);
                        sts128(dst + 256, a[1].x, a[1].y & 0xffffu, a[1].z & 0xffffu, a[1].w & 0xffffu);
                    }
                }
                __syncwarp();
                if (lane == 0) mbar_arrive(bars + 8 * B_U);
            }
            if ((lane & 7) == 2) st_gpu32((uint32_t*)p.sc->g + ((row & 256) << 2) + gate_pos(row), pack_bf(sigmoid_f(__uint_as_float(rb)), 0.f) | (tag << 16));
            WSTAMP(2);
        }
        {
            const bool lane0 = pin(lane, lane) == 0;
            const uint32_t own = pin(sb + OFF_XSEL + (at ^ ((at >> 1) & 4)) * 16, lane);
            float acc[8][4];
#pragma unroll
            for (int i = 0; i < 8; i++) { acc[i][0] = acc[i][1] = acc[i][2] = acc[i][3] = 0.f; }
            const int krow = ((lane >> 1) & 8) + (lane & 7);
            const uint32_t tile0 = pin(sb + OFF_RING + krow * 64 + ((((lane >> 3) & 1) ^ ((krow >> 1) & 3)) << 4), lane);
            const uint32_t xo = pin(sb + OFF_XSEL + (lane & 7) * XS_ROW + 512 * v + 2 * (lane & 24), lane);
            const uint32_t po = pin(sb + OFF_XSEL + t * XS_ROW + (g & 3) * 128 + (g & 1) * 64 + v * 16 + (lane >> 4) * 8, lane);
            const uint32_t po1 = pin(po + 64 - (g & 1) * 128, lane);
            uint32_t* hdst = pin((uint32_t*)&p.sc->h[tag & 1][32 * c] + at, lane);
            auto signal = [&](const int k, const uint32_t dep) {
                if (lane < 2 && v < 2)
                    asm volatile("st.async.weak.shared::cluster.mbarrier::complete_tx::bytes.b32 [%0], %1, [%2];"
                                 :: "r"(mapa(sb + M_SINK, lane)), "r"(dep), "r"(mapa(bars + 8 * (B_F + k), lane)) : "memory");
            };
#pragma unroll 1
            for (int i = 0; i < 4; i++) {
                const int s = 4 * i + v;
                uint32_t a[16][4], b[2][4];
                if (gu) {
                    const uint32_t tile = tile0 + (s < 14 ? s : v) * 8192;
                    if (lane0 && i > 1) mbar_arrive(bars + 8 * (B_E + s - 4));
                    if (i == 2) signal(0, 0);
                    mbar_wait(bars + 8 * (B_W + s));
#pragma unroll
                    for (int q = 0; q < 16; q++) ldsm4t((tile ^ ((q & 1) << 5)) + ((q >> 1) & 1) * 4096 + (q >> 2) * 1024, a[q][0], a[q][1], a[q][2], a[q][3]);
                }
                if (i == 0) {
                    if (gu) {
                        uint32_t dep = p.zero;
#pragma unroll
                        for (int q = 0; q < 16; q += 2) dep &= a[q][0] & a[q + 1][0];
                        if (lane == 0) mbar_arrive(bars + 8 * (B_E + v) + dep);
                    }
                    WSTAMP(11);
                    uint32_t top;
#pragma unroll 1
                    for (int it = 0; it < (1 << 22); it++) {
                        asm volatile("ld.relaxed.gpu.global.u32 %0, [%1];" : "=r"(top) : "l"(&p.sc->top[c % NTOP][g]) : "memory");
                        if (__all_sync(0xffffffffu, ((top ^ (tag << 11)) & 0xf800u) == 0)) break;
                        if (TSLEEP) __nanosleep(TSLEEP);
                    }
                    WSTAMP(3);
                    if (gu) {
                        const uint32_t k = 4 * h + v, row = __reduce_max_sync(0xffffffffu, lane == 4 * k ? ~top & 2047 : 0);
                        asm volatile("{\n\t.reg .pred p;\n\telect.sync _|p, 0xffffffff;\n\t"
                                     "@p cp.async.bulk.shared::cluster.global.mbarrier::complete_tx::bytes.multicast::cluster [%0], [%1], 2048, [%2], %3;\n\t}"
                            :: "r"(sb + OFF_XSEL + k * XS_ROW), "l"(p.u + (size_t)row * D_), "r"(bars + 8 * B_G), "h"((unsigned short)3) : "memory");
                    }
                    if (v == 3) {
                        const uint32_t row = ~top & 2047;
                        if (t == 0 && ((row >> 8) & 1) == h)
                            asm volatile("red.shared.or.b32 [%0], %1;" :: "r"(sb + M_BMAP + (row & 7) * 16 + (row >> 9) * 4), "r"(1u << (gate_pos(row) & 31)) : "memory");
                        if (t == 0) sts32(sb + M_TOP + lane, top);
                        if (c == 0 && lane == 0) *(volatile unsigned*)&p.sc->epoch = tag;
                        __syncwarp();
                        if (lane0) mbar_arrive(bars + 8 * B_Y);
                    }
                    if (!gu) break;
                    mbar_wait(bars + 8 * B_G);
                    WSTAMP(4);
                }
                ldsm4(xo + 128 * i, b[0][0], b[0][1], b[0][2], b[0][3]);
                ldsm4(xo + 128 * i + 64, b[1][0], b[1][1], b[1][2], b[1][3]);
#pragma unroll
                for (int q = 0; q < 16; q++) mma_bf(acc[q & 7], a[q][0], a[q][1], a[q][2], a[q][3], b[q >> 3][(q >> 1) & 2], b[q >> 3][((q >> 1) & 2) + 1]);
            }
            if (gu) {
                WSTAMP(5);
                __syncwarp();
#pragma unroll
                for (int q = 0; q < 4; q++) {
                    const int ct = q >> 1, e = 2 * (q & 1);
                    sts128(own + q * XS_ROW,
                           __float_as_uint(acc[ct][e] + acc[4 + ct][e]), __float_as_uint(acc[2 + ct][e] + acc[6 + ct][e]),
                           __float_as_uint(acc[ct][e + 1] + acc[4 + ct][e + 1]), __float_as_uint(acc[2 + ct][e + 1] + acc[6 + ct][e + 1]));
                }
                bar_sync(1, 128);
                float sl[2], uv[2];
#pragma unroll
                for (int e = 0; e < 2; e++) {
                    uint2 q[4];
#pragma unroll
                    for (int i = 0; i < 4; i++) q[i] = lds64((e ? po1 : po) + 512 * i);
                    const float s0 = (__uint_as_float(q[0].x) + __uint_as_float(q[1].x)) + (__uint_as_float(q[2].x) + __uint_as_float(q[3].x));
                    const float s1 = (__uint_as_float(q[0].y) + __uint_as_float(q[1].y)) + (__uint_as_float(q[2].y) + __uint_as_float(q[3].y));
                    const float gv = bf_round(p.gu_swap ? s1 : s0);
                    uv[e] = p.gu_swap ? s0 : s1;
                    sl[e] = gv * sigmoid_f(gv);
                }
                const uint32_t hw = hmul2_bf(pack_bf(sl[0], sl[1]), pack_bf(uv[0], uv[1]));
                st_gpu32(hdst, hw ? hw : 0x80000000u);
                signal(1, hw);
            }
        }
        WSTAMP(6);
        asm volatile("setmaxnreg.dec.sync.aligned.u32 104;");
        {
            const uint32_t own = pin(sb + OFF_XSEL + at * 16, lane);
            const uint32_t hb = sb + (v < 2 ? OFF_XSEL + 7168 * v : OFF_RING + 8192 * v), hl = pin(hb + 16 * lane, lane);
            const int krow = ((lane >> 1) & 8) + (lane & 7);
            const uint32_t tile = pin(sb + OFF_RING + v * 8192 + krow * 32 + ((((lane >> 3) ^ (krow >> 2)) & 1) << 4), lane);
            float dd[4][4];
            bar_sync(1, 128);
            mbar_wait(bars + 8 * (B_W + HW));
            WSTAMP(12);
            uint4 hq[7];
#pragma unroll 1
            for (int it = 0; it < (1 << 16); it++) {
                bulk_load(hb, &p.sc->h[tag & 1][32 * (56 * h + 14 * v)], 7168, bars + 8 * (B_X + v));
                uint32_t a[14][4], mn = 0xffffffffu;
                mbar_wait(bars + 8 * (B_W + 16 + v));
#pragma unroll
                for (int j = 0; j < 14; j++) ldsm4t(tile + (v & 2) * 16384 + j * 512, a[j][0], a[j][1], a[j][2], a[j][3]);
                mbar_wait(bars + 8 * (B_X + v), ~it & 1);
                WSTAMP(7);
#pragma unroll
                for (int j = 0; j < 7; j++) {
                    const uint4 q = lds128(hl + 512 * j);
                    mn = min(mn, q.x);
#pragma unroll
                    for (int e = 0; e < 2; e++) {
                        const uint32_t(&f)[4] = a[2 * j + e];
                        if (j < 2) mma_bf_z(dd[2 * j + e], f[0], f[1], f[2], f[3], e ? q.z : q.x, e ? q.w : q.y);
                        else mma_bf(dd[(2 * j + e) & 3], f[0], f[1], f[2], f[3], e ? q.z : q.x, e ? q.w : q.y);
                    }
                }
#pragma unroll
                for (int j = 0; j < 7; j++) { hq[j] = lds128(hl + 3584 + 512 * j); mn = min(mn, hq[j].x); }
                if (__all_sync(0xffffffffu, mn != 0)) break;
            }
            mbar_wait(bars + 8 * (B_W + 20 + v));
#pragma unroll
            for (int j = 0; j < 14; j++) {
                uint32_t f[4];
                ldsm4t(tile + 65536 + j * 512, f[0], f[1], f[2], f[3]);
                mma_bf(dd[(j + 2) & 3], f[0], f[1], f[2], f[3], (j & 1) ? hq[j >> 1].z : hq[j >> 1].x, (j & 1) ? hq[j >> 1].w : hq[j >> 1].y);
            }
            WSTAMP(8);
            uint4 part;
            part.x = __float_as_uint((dd[0][0] + dd[1][0]) + (dd[2][0] + dd[3][0])); part.y = __float_as_uint((dd[0][1] + dd[1][1]) + (dd[2][1] + dd[3][1]));
            part.z = __float_as_uint((dd[0][2] + dd[1][2]) + (dd[2][2] + dd[3][2])); part.w = __float_as_uint((dd[0][3] + dd[1][3]) + (dd[2][3] + dd[3][3]));
            st_async16(mapa(own + (M_DPIN - OFF_XSEL), h ^ 1), part, mapa(bars + 8 * B_DP, h ^ 1));
            sts128(own + 14336, part.x, part.y, part.z, part.w);
            __syncwarp();
            if (lane == 0) mbar_arrive(bars + 8 * B_DP);
        }
        WDUMP();
    } else {
        asm volatile("setmaxnreg.dec.sync.aligned.u32 40;");
        const int v = __reduce_max_sync(0xffffffffu, pw - PREP_W0);
        const bool gu = c < NGU_CTA;
        const uint32_t t0 = clock();
        const uint32_t bu = bars + 8 * v;
        if (lane == 0) {
            mbar_init(bu + 8 * B_X, 1);
            asm volatile("fence.mbarrier_init.release.cluster;" ::: "memory");
        }
        __syncwarp();
        if (DELAY_X > 0) __nanosleep(DELAY_X);
        bulk_load(sb + (v < 2 ? OFF_XSEL : OFF_RING + 2 * 8192) + v * 8192, p.u + (size_t)(16 * c + 4 * v) * D_, 8192, bu + 8 * B_X);
        if (lane == 0) {
#pragma unroll
            for (int i = 0; i < 10; i++) mbar_init(bu + 32 * i, 1);
            mbar_init(bu + 8 * B_XE, 1);
            mbar_init(bu + 8 * B_Y, v == 0 ? 12 : 9);
            mbar_init(bu + 8 * B_DP, (0x1855 >> (4 * v)) & 15);
            mbar_init(bu + 8 * B_F, 1);
            mbar_init(bu + 8 * B_H, 1);
            asm volatile("fence.mbarrier_init.release.cluster;" ::: "memory");
            mbar_expect(bu + 8 * B_Y, 4096);
            if (v != 2) mbar_expect(bu + 8 * B_DP, v == 0 ? 2048 : (h || v == 3) ? 16384 : 16384 + 128);
            mbar_expect(bu + 8 * B_F, c < NGU_CTA ? 16 : 0);
        }
        __syncwarp();
        asm volatile("barrier.cluster.arrive.relaxed.aligned;" ::: "memory");
        tma3d(sb + OFF_S + v * S_Q, &tm_x, 16 * pr, 64 * v + 32 * h - 1, bars + 8 * (B_S + v), S_Q);
        WSTAMP(9);
        if (v < 3 && lane == 0) asm volatile("prefetch.tensormap [%0];" :: "l"(v == 0 ? &tm_gu : v == 1 ? &tm_down : &tm_out) : "memory");
        asm volatile("barrier.cluster.wait.acquire.aligned;" ::: "memory");
        uint32_t desc;
        {
            const int s = 6 * v + lane, i = s >> 2, w = s & 3, slot = s < 14 ? s : (s | 1) == 17 ? s - 16 : s - 12;
            const int fb = s < 4 ? B_H : (gu && s >= 14) ? B_E + slot : s < 6 ? B_XE + s - 2 : B_KG;
            desc = slot | (fb << 4) | ((i < 4 ? 256 * w + 64 * i : 1792 * h + 448 * w + 224 * (i - 4)) << 10);
            if (lane < 6) mbar_expect(bars + 8 * (B_W + s), i < 4 ? 8192 : 7168);
            if (tid == 32 * PREP_W0) mbar_arrive(bars + 8 * B_H);
        }
        mbar_wait(bars + 8 * (B_H + v));
        {
            const int gap = v == 0 ? GAP : v == 1 ? GAP1 : v == 2 ? GAP2 : GAP3;
            uint32_t last = v ? clock() - SLACK : t0 + T0 - GAP + STAG * ((pr * 5) & 15) / 16;
#pragma unroll 1
            while ((int)(last - clock()) > 500) __nanosleep(256);
#pragma unroll 1
            for (int k = 0; k < 6; k++) {
                const uint32_t dk = __reduce_max_sync(0xffffffffu, lane == k ? desc : 0);
                const bool dn = 6 * v + k >= 16;
                mbar_wait(bars + ((dk >> 1) & 0x1f8));
                uint32_t now;
#pragma unroll 1
                while ((int)((now = clock()) - last) < gap) __nanosleep(CSLEEP);
                last = max((int)(now - last) - SLACK, gap) + last;
                WSTAMP(3 + k);
                if (gu || dn)
                    asm volatile("{\n\t.reg .pred p;\n\telect.sync _|p, 0xffffffff;\n\t"
                                 "@p cp.async.bulk.tensor.3d.shared::cluster.global.mbarrier::complete_tx::bytes [%0], [%1, {%3, %4, 0}], [%2];\n\t}"
                        :: "r"(sb + OFF_RING + (dk & 15) * 8192), "l"(dn ? &tm_down : &tm_gu), "r"(bars + 8 * (B_W + 6 * v + k)), "r"(dn ? 16 * pr : 32 * c), "r"(dk >> 10) : "memory");
                if (k < 5 && PRESLEEP) __nanosleep(PRESLEEP);
            }
            if (lane == 0 && v < 3) mbar_arrive(bars + 8 * (B_H + v + 1));
        }
        if (v < 2) {
            mbar_wait(bars + 8 * B_U);
            mbar_wait(bars + 8 * (gu ? B_G : B_H + 3));
            const uint32_t tag16 = lds32(sb + M_TAG);
            {
                const int k = v;
                uint4 q[4];
#pragma unroll 1
                for (int it = 0; it < (1 << 22); it++) {
                    uint32_t bad = 0;
#pragma unroll
                    for (int i = 0; i < 4; i++) q[i] = ld_gpu128(&p.sc->g[256 * h + 128 * k + 32 * i + lane]);
#pragma unroll
                    for (int i = 0; i < 4; i++) bad |= ((q[i].x ^ tag16) | (q[i].y ^ tag16)) | ((q[i].z ^ tag16) | (q[i].w ^ tag16));
                    if ((bad >> 16) == 0) break;
                    __nanosleep(200);
                }
#pragma unroll
                for (int i = 0; i < 4; i++)
                    asm volatile("st.shared.v2.u32 [%0], {%1, %2};" :: "r"(sb + OFF_GP + 1024 * k + 256 * i + lane * 8),
                                 "r"(__byte_perm(q[i].x, q[i].y, 0x5410)), "r"(__byte_perm(q[i].z, q[i].w, 0x5410)) : "memory");
            }
            __syncwarp();
            if (lane == 0) mbar_arrive(bars + 8 * B_Y);
        }
        {
            asm volatile("setmaxnreg.inc.sync.aligned.u32 72;");
            mbar_wait(bars + 8 * (B_W + PW));
            WSTAMP(1);
            mix_rows<2, true>(p, &tm_out, sb, sb + OFF_TAB + v * TAB_W, 0, PQ, v, h, pr, lane);
            WSTAMP(2);
            asm volatile("cp.async.bulk.commit_group;" ::: "memory");
            const uint32_t top = lds32(sb + M_TOP + 8 * v + 4 * (lane >> 4));
            const uint32_t row = ~top & 2047, ch = lane & 15, gp = gate_pos(row);
            const bool mine = ((row >> 8) & 1) == h;
            uint32_t gfin, x16, y16 = 0;
            asm volatile("ld.shared.u16 %0, [%1];" : "=r"(gfin) : "r"(sb + OFF_GP + gp * 2) : "memory");
            asm volatile("ld.shared.u16 %0, [%1];" : "=r"(x16) : "r"(sb + OFF_S + (row >> 9) * S_Q + s_addr((row & 7) * S_PL + 32 + (row & 248) * 4, ch >> 3) + 2 * (ch & 7)) : "memory");
            const float rsel = __uint_as_float(pin(__float_as_uint(bf_round(sigmoid_f(__uint_as_float((top ^ (((int)~top >> 31) | 0x80000000u)) & 0xffff0000u)))), lane));
            const uint32_t po = pin(sb + (4 * (ch & 7) + v) * 16 + (ch >> 3) * 8 + (lane >> 4) * 4, lane);
            bf16* op = pin(p.out + (size_t)row * D_ + 16 * pr + ch, lane);
            if (mine) {
                mbar_wait(bars + 8 * (B_Y + (row >> 9)));
                asm volatile("ld.shared.u16 %0, [%1];" : "=r"(y16)
                             : "r"(sb + y_off(row >> 9) + ch * 512 + (((4 * (row & 7) + ((row >> 5) & 3)) ^ (((ch >> 2) << 1) | (ch & 1))) << 4) + 2 * row_elem(row)) : "memory");
            }
            mbar_wait(bars + 8 * B_DP);
            float q[8];
#pragma unroll
            for (int i = 0; i < 4; i++) { q[i] = ldsf(po + M_DPIN + 512 * i); q[4 + i] = ldsf(po + OFF_XSEL + 14336 + 512 * i); }
            const float tot = ((q[0] + q[1]) + (q[2] + q[3])) + ((q[4] + q[5]) + (q[6] + q[7]));
            const float b = bf_round(__uint_as_float(x16 << 16) + bf_round(bf_round(tot) * rsel));
            if (mine) *op = __float2bfloat16_rn(fmaf(bf_lo(gfin), __uint_as_float(y16 << 16), bf_round(bf_round(1.f - bf_lo(gfin)) * b)));
        }
        asm volatile("cp.async.bulk.wait_group.read 0;" ::: "memory");
        WSTAMP(10);
        WDUMP();
    }
}

typedef CUresult (*EncodeFn)(CUtensorMap*, CUtensorMapDataType, cuuint32_t, void*, const cuuint64_t*, const cuuint64_t*,
                             const cuuint32_t*, const cuuint32_t*, CUtensorMapInterleave, CUtensorMapSwizzle,
                             CUtensorMapL2promotion, CUtensorMapFloatOOBfill);

void make_map(EncodeFn f, CUtensorMap* m, const void* ptr, uint64_t cols, uint64_t rows, uint64_t pitch, uint32_t bc, uint32_t br, CUtensorMapSwizzle sw, int prom,
              uint32_t planes = 1, uint64_t plane_stride = 0, uint32_t box_planes = 0) {
    cuuint64_t dims[3] = {cols, rows, planes};
    cuuint64_t str[2] = {pitch, planes > 1 ? plane_stride : pitch * rows};
    cuuint32_t box[3] = {bc, br, box_planes ? box_planes : planes};
    cuuint32_t es[3] = {1, 1, 1};
    f(m, CU_TENSOR_MAP_DATA_TYPE_BFLOAT16, 3, (void*)ptr, dims, str, box, es, CU_TENSOR_MAP_INTERLEAVE_NONE, sw,
      (CUtensorMapL2promotion)prom, CU_TENSOR_MAP_FLOAT_OOB_FILL_NONE);
}

}

extern "C" void kernel_launch(void* const* d_in, const int* in_sizes, int n_in, void* d_out, int out_size) {
    static EncodeFn enc = nullptr;
    static void *sc = nullptr, *band = nullptr;
    if (!enc) {
        void* fn = nullptr;
        cudaDriverEntryPointQueryResult qr;
        cudaGetDriverEntryPoint("cuTensorMapEncodeTiled", &fn, cudaEnableDefault, &qr);
        enc = (EncodeFn)fn;
        cudaGetSymbolAddress(&sc, g_scratch);
        cudaGetSymbolAddress(&band, g_band);
        cudaFuncSetAttribute(fused_kernel, cudaFuncAttributeMaxDynamicSharedMemorySize, SMEM_BYTES);
    }
    CUtensorMap tg, td, tx, to;
    const char *wg = (const char*)d_in[9], *wu = (const char*)d_in[10];
    const bool swap = wu < wg;
    make_map(enc, &tg, swap ? wu : wg, F_, D_, F_ * 2, 32, 64, CU_TENSOR_MAP_SWIZZLE_64B, PROMG, 2, swap ? wg - wu : wu - wg);
    make_map(enc, &td, d_in[11], D_, F_, D_ * 2, 16, 224, CU_TENSOR_MAP_SWIZZLE_32B, PROMD);
    make_map(enc, &tx, d_in[0], D_, L_ / 8, D_ * 16, 16, 33, CU_TENSOR_MAP_SWIZZLE_32B, PROMX, 8, D_ * 2);
    make_map(enc, &to, d_out, D_, L_ / 8, D_ * 16, 16, 32, CU_TENSOR_MAP_SWIZZLE_NONE, 0, 8, D_ * 2, 1);
    Params p;
    p.u = (const bf16*)d_in[0]; p.logA = (const bf16*)d_in[1]; p.Aim = (const bf16*)d_in[2];
    p.Cre = (const bf16*)d_in[3]; p.Cim = (const bf16*)d_in[4]; p.logdt = (const bf16*)d_in[5];
    p.Dskip = (const bf16*)d_in[6]; p.wr = (const bf16*)d_in[8]; p.gatew = (const bf16*)d_in[12];
    p.out = (bf16*)d_out;
    p.sc = (Scratch*)sc; p.band = (const uint4*)band;
    p.gu_swap = swap;
    p.zero = 0;
    fused_kernel<<<NCTA, NTHREADS, SMEM_BYTES>>>(p, tg, td, tx, to);
}
```

```cpp
#include <cuda_runtime.h>
#include <cuda_bf16.h>
#include <cuda_fp16.h>
#include <cuda.h>
#include <stdint.h>

typedef __nv_bfloat16 bf16;

namespace {

constexpr int L_ = 2048, D_ = 1024, F_ = 3584;
constexpr int NCTA = 130;
constexpr int NTHREADS = 512;
#define AUXW 12
constexpr int MAIN_W0 = 0, AUX_W0 = AUXW, PREP_W0 = 20 - AUXW;
#define T0 3400
#define GAP 540
#define GAP1 530
#define GAP2 530
#define GAP3 550
#define STAG GAP
#define CSLEEP 50
#define SLACK 300
#define DELAY_X 70
#define TSLEEP 40
#define RS 2
#define BULKM false
#define PW 19
#define PRESLEEP 64
#define PWQ 1
#define PQ 3
#define PROMG 2
#define PROMD 1
#define PROMX 0
#define LATE2 0
#define HW 21
constexpr int NGU_CTA = 112;

constexpr int OFF_RING = 0;
constexpr int OFF_SCR  = 6 * 8192;
constexpr int S_PL     = 1056;
constexpr int S_Q      = 8 * S_PL;
constexpr int OFF_S    = 114688;
constexpr int OFF_GP   = OFF_S + 4 * S_Q;
constexpr int U_PL     = 2240;
constexpr int U_CH     = 4416;
constexpr int OFF_U    = 151552;
constexpr int TAB_W    = 3200;
constexpr int T_PL     = 544;
constexpr int T_A      = 2192 - 26 * 8;
constexpr int T_B      = 2568 - 59 * 8;
constexpr int OFF_TAB  = 186880;
constexpr int OFF_XSEL = 212480;
constexpr int XS_ROW   = 2064;
constexpr int OFF_BAND = 228992;
constexpr int OFF_MISC = 229536;
constexpr int M_BARS   = OFF_MISC;
constexpr int M_DSK    = OFF_MISC + 2736;
constexpr int M_SINK   = OFF_MISC + 512;
constexpr int M_TAG    = OFF_MISC + 516;
constexpr int M_BMAP   = OFF_MISC + 528;
constexpr int M_DPIN   = OFF_MISC + 656;
constexpr int M_TOP    = OFF_MISC + 2704;
constexpr int SMEM_BYTES = OFF_MISC + 2768;
__device__ __forceinline__ uint32_t s_addr(uint32_t o, uint32_t half) { return o + (((half ^ (o >> 7)) & 1) << 4); }
__host__ __device__ constexpr uint32_t y_off(uint32_t q) { return OFF_RING + 32768 + (q & 1) * 8192 + (q >> 1) * 65536; }

constexpr int B_W = 0;
constexpr int B_E = 24;
constexpr int B_S = 36;
constexpr int B_Y = 40;
constexpr int B_DP = 44, B_U = 45, B_KG = 46, B_G = 47;
constexpr int B_F = 48;
constexpr int B_H = 60;
constexpr int B_X = 52, B_XE = 56;

struct BandTab { uint32_t w[11][12]; };
constexpr BandTab make_band() {
    BandTab b{};
    for (int cls = 0; cls < 11; cls++)
        for (int wd = 0; wd < 10; wd++) {
            const int tau = cls + 2 - 8 * ((wd < 4 ? wd : wd - 4) >> 1);
            const int lo = (wd < 4) ? ((wd & 1) ? -2 : 3) : ((wd & 1) ? -4 : -11), wid = (wd < 4 ? 3 : 7) + 2 * (wd & 1);
            b.w[cls][wd] = ((tau >= lo && tau < lo + wid) ? 0x3F80u : 0u) | ((tau - 4 >= lo && tau - 4 < lo + wid) ? 0x3F800000u : 0u);
        }
    return b;
}
constexpr int NTOP = 32;
struct Scratch {
    uint4 r[L_ / 4 * RS];
    uint4 g[L_ / 4];
    uint4 h[2][8 * F_ / 8];
    uint32_t top[NTOP][32];
    unsigned epoch;
};
__device__ __align__(128) Scratch g_scratch;
__device__ const __align__(16) BandTab g_band = make_band();

struct Params {
    const bf16 *u, *logA, *Aim, *Cre, *Cim, *logdt, *Dskip, *wr, *gatew;
    bf16* out;
    Scratch* sc;
    const uint4* band;
    uint32_t gu_swap;
    uint32_t zero;
};

#define WSTAMP(i) do {} while (0)
#define KSTAMP(i, dep) do {} while (0)
#define WDUMP() do {} while (0)
#define RSTAMP(i) do {} while (0)

__device__ __forceinline__ uint32_t smem_u32(const void* p) { return (uint32_t)__cvta_generic_to_shared(p); }
__device__ __forceinline__ void mbar_init(uint32_t b, uint32_t c) { asm volatile("mbarrier.init.shared::cta.b64 [%0], %1;" :: "r"(b), "r"(c) : "memory"); }
__device__ __forceinline__ void mbar_expect(uint32_t b, uint32_t tx) { asm volatile("mbarrier.arrive.expect_tx.shared::cta.b64 _, [%0], %1;" :: "r"(b), "r"(tx) : "memory"); }
__device__ __forceinline__ void mbar_arrive(uint32_t b) { asm volatile("mbarrier.arrive.shared::cta.b64 _, [%0];" :: "r"(b) : "memory"); }
__device__ __forceinline__ void mbar_wait(uint32_t b, uint32_t parity = 0) {
    asm volatile("{\n\t.reg .pred p;\nW%=:\n\tmbarrier.try_wait.parity.shared::cta.b64 p, [%0], %1, 20000;\n\t@!p bra W%=;\n\t}" :: "r"(b), "r"(parity) : "memory");
}
__device__ __forceinline__ uint32_t mapa(uint32_t addr, uint32_t rank) { uint32_t r; asm("mapa.shared::cluster.u32 %0, %1, %2;" : "=r"(r) : "r"(addr), "r"(rank)); return r; }
__device__ __forceinline__ void tma3d(uint32_t dst, const CUtensorMap* tm, int c0, int c1, uint32_t bar, uint32_t bytes) {
    asm volatile("{\n\t.reg .pred p;\n\telect.sync _|p, 0xffffffff;\n\t"
                 "@p mbarrier.arrive.expect_tx.shared::cta.b64 _, [%2], %5;\n\t"
                 "@p cp.async.bulk.tensor.3d.shared::cluster.global.mbarrier::complete_tx::bytes [%0], [%1, {%3, %4, 0}], [%2];\n\t}"
        :: "r"(dst), "l"(tm), "r"(bar), "r"(c0), "r"(c1), "r"(bytes) : "memory");
}
__device__ __forceinline__ void bulk_load(uint32_t dst, const void* src, uint32_t bytes, uint32_t bar) {
    asm volatile("{\n\t.reg .pred p;\n\telect.sync _|p, 0xffffffff;\n\t"
                 "@p mbarrier.arrive.expect_tx.shared::cta.b64 _, [%2], %3;\n\t"
                 "@p cp.async.bulk.shared::cluster.global.mbarrier::complete_tx::bytes [%0], [%1], %3, [%2];\n\t}"
        :: "r"(dst), "l"(src), "r"(bar), "r"(bytes) : "memory");
}
__device__ __forceinline__ void st_async16(uint32_t dst, const uint4& v, uint32_t bar) {
    asm volatile("st.async.weak.shared::cluster.mbarrier::complete_tx::bytes.v4.b32 [%0], {%1,%2,%3,%4}, [%5];"
                 :: "r"(dst), "r"(v.x), "r"(v.y), "r"(v.z), "r"(v.w), "r"(bar) : "memory");
}
__device__ __forceinline__ void bar_sync(int id, int n) { asm volatile("bar.sync %0, %1;" :: "r"(id), "r"(n) : "memory"); }
__device__ __forceinline__ void cp16(uint32_t dst, const void* src) { asm volatile("cp.async.cg.shared.global [%0], [%1], 16;" :: "r"(dst), "l"(src) : "memory"); }
__device__ __forceinline__ void cp_wait_all() { asm volatile("cp.async.wait_all;" ::: "memory"); }
__device__ __forceinline__ uint4 ld_gpu128(const void* p) { uint4 v; asm volatile("ld.relaxed.gpu.global.v4.u32 {%0,%1,%2,%3}, [%4];" : "=r"(v.x), "=r"(v.y), "=r"(v.z), "=r"(v.w) : "l"(p) : "memory"); return v; }
__device__ __forceinline__ void st_gpu32(void* p, uint32_t v) { asm volatile("st.relaxed.gpu.global.u32 [%0], %1;" :: "l"(p), "r"(v) : "memory"); }

__device__ __forceinline__ void ldsm4(uint32_t a, uint32_t& r0, uint32_t& r1, uint32_t& r2, uint32_t& r3) {
    asm volatile("ldmatrix.sync.aligned.m8n8.x4.shared.b16 {%0,%1,%2,%3}, [%4];" : "=r"(r0), "=r"(r1), "=r"(r2), "=r"(r3) : "r"(a) : "memory");
}
__device__ __forceinline__ void ldsm4t(uint32_t a, uint32_t& r0, uint32_t& r1, uint32_t& r2, uint32_t& r3) {
    asm volatile("ldmatrix.sync.aligned.m8n8.x4.trans.shared.b16 {%0,%1,%2,%3}, [%4];" : "=r"(r0), "=r"(r1), "=r"(r2), "=r"(r3) : "r"(a) : "memory");
}
__device__ __forceinline__ uint32_t lds32(uint32_t a) { uint32_t v; asm volatile("ld.shared.u32 %0, [%1];" : "=r"(v) : "r"(a) : "memory"); return v; }
__device__ __forceinline__ uint2 lds64(uint32_t a) { uint2 v; asm volatile("ld.shared.v2.u32 {%0,%1}, [%2];" : "=r"(v.x), "=r"(v.y) : "r"(a) : "memory"); return v; }
__device__ __forceinline__ uint4 lds128(uint32_t a) { uint4 v; asm volatile("ld.shared.v4.u32 {%0,%1,%2,%3}, [%4];" : "=r"(v.x), "=r"(v.y), "=r"(v.z), "=r"(v.w) : "r"(a) : "memory"); return v; }
__device__ __forceinline__ void sts32(uint32_t a, uint32_t v) { asm volatile("st.shared.u32 [%0], %1;" :: "r"(a), "r"(v) : "memory"); }
__device__ __forceinline__ void sts16(uint32_t a, uint32_t v) { asm volatile("st.shared.u16 [%0], %1;" :: "r"(a), "h"((unsigned short)v) : "memory"); }
__device__ __forceinline__ void sts128(uint32_t a, uint32_t x, uint32_t y, uint32_t z, uint32_t w) { asm volatile("st.shared.v4.u32 [%0], {%1,%2,%3,%4};" :: "r"(a), "r"(x), "r"(y), "r"(z), "r"(w) : "memory"); }
__device__ __forceinline__ float ldsf(uint32_t a) { float v; asm volatile("ld.shared.f32 %0, [%1];" : "=f"(v) : "r"(a) : "memory"); return v; }

__device__ __forceinline__ void mma_bf(float (&d)[4], uint32_t a0, uint32_t a1, uint32_t a2, uint32_t a3, uint32_t b0, uint32_t b1) {
    asm volatile("mma.sync.aligned.m16n8k16.row.col.f32.bf16.bf16.f32 {%0,%1,%2,%3}, {%4,%5,%6,%7}, {%8,%9}, {%0,%1,%2,%3};"
        : "+f"(d[0]), "+f"(d[1]), "+f"(d[2]), "+f"(d[3]) : "r"(a0), "r"(a1), "r"(a2), "r"(a3), "r"(b0), "r"(b1));
}
__device__ __forceinline__ void mma_bf_z(float (&d)[4], uint32_t a0, uint32_t a1, uint32_t a2, uint32_t a3, uint32_t b0, uint32_t b1) {
    asm volatile("mma.sync.aligned.m16n8k16.row.col.f32.bf16.bf16.f32 {%0,%1,%2,%3}, {%4,%5,%6,%7}, {%8,%9}, {%10,%10,%10,%10};"
        : "=f"(d[0]), "=f"(d[1]), "=f"(d[2]), "=f"(d[3]) : "r"(a0), "r"(a1), "r"(a2), "r"(a3), "r"(b0), "r"(b1), "f"(0.f));
}
__device__ __forceinline__ void mma_bf_k8(float (&d)[4], uint32_t a0, uint32_t a1, uint32_t b0) {
    asm volatile("mma.sync.aligned.m16n8k8.row.col.f32.bf16.bf16.f32 {%0,%1,%2,%3}, {%4,%5}, {%6}, {%0,%1,%2,%3};"
        : "+f"(d[0]), "+f"(d[1]), "+f"(d[2]), "+f"(d[3]) : "r"(a0), "r"(a1), "r"(b0));
}
__device__ __forceinline__ void mma_h(float (&d)[4], uint32_t a0, uint32_t a1, uint32_t a2, uint32_t a3, uint32_t b0, uint32_t b1) {
    asm volatile("mma.sync.aligned.m16n8k16.row.col.f32.f16.f16.f32 {%0,%1,%2,%3}, {%4,%5,%6,%7}, {%8,%9}, {%0,%1,%2,%3};"
        : "+f"(d[0]), "+f"(d[1]), "+f"(d[2]), "+f"(d[3]) : "r"(a0), "r"(a1), "r"(a2), "r"(a3), "r"(b0), "r"(b1));
}
__device__ __forceinline__ uint32_t pack_bf(float lo, float hi) { uint32_t r; asm("cvt.rn.bf16x2.f32 %0, %1, %2;" : "=r"(r) : "f"(hi), "f"(lo)); return r; }
__device__ __forceinline__ uint32_t pack_h(float lo, float hi) { uint32_t r; asm("cvt.rn.f16x2.f32 %0, %1, %2;" : "=r"(r) : "f"(hi), "f"(lo)); return r; }
__device__ __forceinline__ float bf_lo(uint32_t v) { return __uint_as_float(v << 16); }
__device__ __forceinline__ float bf_hi(uint32_t v) { return __uint_as_float(v & 0xffff0000u); }
__device__ __forceinline__ float bf_round(float x) { return __uint_as_float(pack_bf(0.f, x)); }
__device__ __forceinline__ uint32_t hmul2_bf(uint32_t a, uint32_t b) { uint32_t r; asm("mul.rn.bf16x2 %0, %1, %2;" : "=r"(r) : "r"(a), "r"(b)); return r; }
__device__ __forceinline__ float ex2f(float x) { float r; asm("ex2.approx.ftz.f32 %0, %1;" : "=f"(r) : "f"(x)); return r; }

__device__ __forceinline__ float exp_acc(float x) {
    const float t = x * 1.4426950216293335f;
    const float r = fmaf(x, 1.4426950216293335f, -t) + x * 1.9259629911266175e-8f;
    return ex2f(t) * fmaf(r, 0.6931471805599453f, 1.f);
}
__device__ __forceinline__ float sigmoid_f(float x) { return __fdividef(1.f, 1.f + ex2f(-x * 1.4426950408889634f)); }
__device__ __forceinline__ void cexp_pow(float l2, float li, float e, float& zr, float& zi) {
    const float mag = ex2f(l2 * e);
    zr = mag * __cosf(li * e);
    zi = mag * __sinf(li * e);
}
__device__ __forceinline__ uint32_t hcmul(uint32_t a, uint32_t k, uint32_t kp) {
    const __half2 A = *reinterpret_cast<const __half2*>(&a);
    const __half2 r = __hfma2(__high2half2(A), *reinterpret_cast<const __half2*>(&kp), __hmul2(__low2half2(A), *reinterpret_cast<const __half2*>(&k)));
    return *reinterpret_cast<const uint32_t*>(&r);
}
#define CMUL(orr, oi, ar, ai, br, bi) do { float _r = (ar) * (br) - (ai) * (bi); float _i = (ar) * (bi) + (ai) * (br); orr = _r; oi = _i; } while (0)
#define CSQ(orr, oi, ar, ai) do { float _r = (ar) * (ar) - (ai) * (ai); float _i = 2.f * (ar) * (ai); orr = _r; oi = _i; } while (0)

__device__ __forceinline__ void mma_bf_k8z(float (&d)[4], uint32_t a0, uint32_t a1, uint32_t b0) {
    asm volatile("mma.sync.aligned.m16n8k8.row.col.f32.bf16.bf16.f32 {%0,%1,%2,%3}, {%4,%5}, {%6}, {%7,%7,%7,%7};"
        : "=f"(d[0]), "=f"(d[1]), "=f"(d[2]), "=f"(d[3]) : "r"(a0), "r"(a1), "r"(b0), "f"(0.f));
}
__device__ __forceinline__ void mma_hh_k8(uint32_t& d0, uint32_t& d1, uint32_t a0, uint32_t a1, uint32_t b0) {
    asm volatile("mma.sync.aligned.m16n8k8.row.col.f16.f16.f16.f16 {%0,%1}, {%2,%3}, {%4}, {%5,%5};"
        : "=r"(d0), "=r"(d1) : "r"(a0), "r"(a1), "r"(b0), "r"(0));
}
__device__ __forceinline__ uint32_t pin(uint32_t x, int lane) { return __shfl_sync(0xffffffffu, x, lane); }
template <class T> __device__ __forceinline__ T* pin(T* x, int lane) { return (T*)__shfl_sync(0xffffffffu, (unsigned long long)x, lane); }
__device__ __forceinline__ void sts32_if(bool on, uint32_t a, uint32_t v) {
    asm volatile("{\n\t.reg .pred p;\n\tsetp.ne.u32 p, %2, 0;\n\t@p st.shared.u32 [%0], %1;\n\t}" :: "r"(a), "r"(v), "r"((uint32_t)on) : "memory");
}
__device__ __forceinline__ void sts128_if(bool on, uint32_t a, uint32_t x, uint32_t y, uint32_t z, uint32_t w) {
    asm volatile("{\n\t.reg .pred p;\n\tsetp.ne.u32 p, %5, 0;\n\t@p st.shared.v4.u32 [%0], {%1,%2,%3,%4};\n\t}" :: "r"(a), "r"(x), "r"(y), "r"(z), "r"(w), "r"((uint32_t)on) : "memory");
}
__device__ __forceinline__ void lds128_if(bool on, uint32_t a, uint32_t (&v)[4]) {
    asm volatile("{\n\t.reg .pred p;\n\tsetp.ne.u32 p, %5, 0;\n\t@p ld.shared.v4.u32 {%0,%1,%2,%3}, [%4];\n\t}"
        : "+r"(v[0]), "+r"(v[1]), "+r"(v[2]), "+r"(v[3]) : "r"(a), "r"((uint32_t)on) : "memory");
}
__device__ __forceinline__ uint32_t hfma2_bf(uint32_t a, uint32_t b, uint32_t c) { uint32_t r; asm("fma.rn.bf16x2 %0, %1, %2, %3;" : "=r"(r) : "r"(a), "r"(b), "r"(c)); return r; }
__device__ __forceinline__ uint32_t row_elem(uint32_t row) { return ((row >> 5) & 4) | ((row >> 2) & 2) | ((row >> 4) & 1); }
__device__ __forceinline__ uint32_t gate_pos(uint32_t row) { return ((row >> 9) << 8) | ((row & 7) << 5) | (row_elem(row) << 2) | ((row >> 5) & 3); }

template <int N, bool BULK>
__device__ __forceinline__ void mix_rows(const Params& p, const CUtensorMap* tm_out, uint32_t sb, uint32_t ob, int Q0, int Q1, int w, int h, int pr, int lane) {
    const int g = lane >> 2, t = lane & 3, mi = lane >> 3, r = lane & 7;
    const int m8 = 16 * (g >> 2) + ((g >> 1) & 1) + 2 * (g & 1);
    uint32_t yi = sb + (4 * (r >> 1) + 2 * (mi & 1) + (r & 1)) * 512 + (((4 * w + (mi >> 1)) ^ r) << 4);
    uint32_t xs = sb + OFF_S + s_addr(w * S_PL + 32 + m8 * 32, t >> 1) + ((t & 1) << 3);
    uint32_t gs = sb + OFF_GP + w * 64 + g * 8, os = ob + m8 * 32 + t * 8;
    if (N > 1) { yi = pin(yi, lane); xs = pin(xs, lane); gs = pin(gs, lane); os = pin(os, lane); }
    mbar_wait(sb + M_BARS + 8 * B_Y);
#pragma unroll 1
    for (int Q = Q0; Q < Q1; Q++) {
        uint2 xq[N][4];
        uint32_t gg[N][4], sw[N];
#pragma unroll
        for (int n = 0; n < N; n++) {
#pragma unroll
            for (int i = 0; i < 4; i++) xq[n][i] = lds64((xs ^ (((i ^ n) & 1) << 4)) + Q * S_Q + n * 4 * S_PL + i * 128);
            const uint2 gq = lds64(gs + Q * 512 + n * 256);
            sw[n] = lds32(sb + M_BMAP + w * 16 + n * 64 + Q * 4);
#pragma unroll
            for (int i = 0; i < 4; i++) {
                gg[n][i] = __byte_perm(i < 2 ? gq.x : gq.y, 0, (i & 1) ? 0x3232 : 0x1010);
                const uint32_t og = hfma2_bf(gg[n][i], 0xBF80BF80u, 0x3F803F80u);
                xq[n][i].x = hmul2_bf(og, xq[n][i].x); xq[n][i].y = hmul2_bf(og, xq[n][i].y);
            }
        }
        if (N > 1 && Q == PWQ) mbar_wait(sb + M_BARS + 8 * (B_W + PW));
        mbar_wait(sb + M_BARS + 8 * (B_Y + Q));
        __syncwarp();
#pragma unroll
        for (int n = 0; n < N; n++) {
#pragma unroll
            for (int x = 0; x < 2; x++) {
                uint32_t y[4];
                ldsm4t((yi ^ (x << 5)) + y_off(Q) + n * 256, y[0], y[1], y[2], y[3]);
#pragma unroll
                for (int e = 0; e < 2; e++) {
                    uint2& o = xq[n][2 * x + e];
                    o.x = hfma2_bf(gg[n][2 * x + e], y[2 * e], o.x); o.y = hfma2_bf(gg[n][2 * x + e], y[2 * e + 1], o.y);
                }
            }
        }
        if (BULK && (sw[0] | sw[N - 1]) == 0) {
#pragma unroll
            for (int n = 0; n < N; n++)
#pragma unroll
                for (int i = 0; i < 4; i++)
                    asm volatile("st.shared.v2.u32 [%0], {%1, %2};" :: "r"(os + Q * 1024 + n * 4 * TAB_W + i * 128), "r"(xq[n][i].x), "r"(xq[n][i].y) : "memory");
            asm volatile("fence.proxy.async.shared::cta;" ::: "memory");
            __syncwarp();
#pragma unroll
            for (int n = 0; n < N; n++)
                asm volatile("{\n\t.reg .pred p;\n\telect.sync _|p, 0xffffffff;\n\t"
                             "@p cp.async.bulk.tensor.3d.global.shared::cta.bulk_group [%1, {%2, %3, %4}], [%0];\n\t}"
                    :: "r"(ob + 4 * n * TAB_W + Q * 1024), "l"(tm_out), "r"(16 * pr), "r"(64 * Q + 32 * h), "r"(w + 4 * n) : "memory");
        } else {
            bf16* op = p.out + (size_t)(512 * Q + 256 * h + 8 * m8 + w) * D_ + 16 * pr + 4 * t;
#pragma unroll
            for (int n = 0; n < N; n++)
#pragma unroll
                for (int i = 0; i < 4; i++)
                    if (!((sw[n] >> (4 * g)) & (1u << i))) *(uint2*)(op + (size_t)(32 * i + 4 * n) * D_) = xq[n][i];
        }
    }
}

__global__ void __cluster_dims__(2, 1, 1) __launch_bounds__(NTHREADS, 1)
fused_kernel(const Params p, const __grid_constant__ CUtensorMap tm_gu, const __grid_constant__ CUtensorMap tm_down,
             const __grid_constant__ CUtensorMap tm_x, const __grid_constant__ CUtensorMap tm_out) {
    extern __shared__ __align__(1024) unsigned char smem[];
    const uint32_t sb = smem_u32(smem);
    int tid;
    asm volatile("mov.u32 %0, %%tid.x;" : "=r"(tid));
    const int pw = tid >> 5, lane = tid & 31;
    const int c = blockIdx.x, h = c & 1, pr = c >> 1;
    const uint32_t bars = sb + M_BARS;

    uint2 v_la, v_ai, v_cr, v_ci;
    uint32_t ldt16;
    {
        const uint32_t po = c * 256 + tid;
        asm volatile("{\n\t.reg .pred p;\n\t.reg .b64 a;\n\tsetp.ne.u32 p, %16, 0;\n\t"
                     "mad.wide.u32 a, %14, 8, %9;\n\t@p ld.global.nc.L1::no_allocate.v2.u32 {%0,%1}, [a];\n\t"
                     "mad.wide.u32 a, %15, 2, %13;\n\t@p ld.global.nc.u16 %8, [a];\n\t"
                     "mad.wide.u32 a, %14, 8, %10;\n\t@p ld.global.nc.L1::no_allocate.v2.u32 {%2,%3}, [a];\n\t"
                     "mad.wide.u32 a, %14, 8, %11;\n\t@p ld.global.nc.L1::no_allocate.v2.u32 {%4,%5}, [a];\n\t"
                     "mad.wide.u32 a, %14, 8, %12;\n\t@p ld.global.nc.L1::no_allocate.v2.u32 {%6,%7}, [a];\n\t}"
            : "=r"(v_la.x), "=r"(v_la.y), "=r"(v_ai.x), "=r"(v_ai.y), "=r"(v_cr.x), "=r"(v_cr.y), "=r"(v_ci.x), "=r"(v_ci.y), "=r"(ldt16)
            : "l"(p.logA), "l"(p.Aim), "l"(p.Cre), "l"(p.Cim), "l"(p.logdt), "r"(po), "r"(po >> 5), "r"((uint32_t)(tid < 256 && c < 128)));
    }

    if (c >= 128) {
        if (c != 128) return;
        RSTAMP(5);
        const unsigned tag = (*(volatile unsigned*)&p.sc->epoch + 1) & 0xffffu;
        const uint32_t list = sb + 128;
#pragma unroll 1
        for (int pass = 0; pass < 2; pass++) {
            sts128(list + 16 * tid, 0, 0, 0, 0);
            if (tid == 0) sts32(sb + 64, 0);
            uint32_t key[4];
            bool ok = false;
#pragma unroll 1
            for (int it = 0; it < (1 << 22); it++) {
                const uint4 a = ld_gpu128(&p.sc->r[tid * RS]);
                key[0] = a.x; key[1] = a.y; key[2] = a.z; key[3] = a.w;
                ok = (((a.x ^ tag) | (a.y ^ tag) | (a.z ^ tag) | (a.w ^ tag)) & 0xffffu) == 0;
                if (ok || !pass) break;
            }
            WSTAMP(0);
            uint32_t m = 0;
#pragma unroll
            for (int i = 0; i < 4; i++) {
                key[i] = ((pass ? key[i] : (lane + i) << 16) & 0xffff0000u) | (uint32_t)(2047 - (4 * tid + i));
                m = max(m, key[i]);
            }
            const uint32_t wm = __reduce_max_sync(0xffffffffu, m);
            if (lane == 0) sts32(sb + pw * 4, wm);
            __syncthreads();
            uint32_t thr = 0xffffffffu;
#pragma unroll
            for (int i = 0; i < 4; i++) { const uint4 q = lds128(sb + 16 * i); thr = min(thr, min(max(q.x, q.y), max(q.z, q.w))); }
            if (thr != 1) WSTAMP(1);
            if (m >= thr) {
                uint32_t pos;
                asm volatile("atom.shared.add.u32 %0, [%1], %2;" : "=r"(pos) : "r"(sb + 64), "r"(4 * ((key[0] >= thr) + (key[1] >= thr) + (key[2] >= thr) + (key[3] >= thr))) : "memory");
#pragma unroll
                for (int i = 0; i < 4; i++) if (key[i] >= thr) { sts32(list + pos, key[i]); pos += 4; }
            }
            __syncthreads();
            const uint32_t nc4 = lds32(sb + 64);
            if (nc4 != 1) WSTAMP(2);
#pragma unroll 1
            for (uint32_t j = 4 * pw; j < nc4; j += 64) {
                const uint32_t mine = lds32(list + j);
                int rank = 0;
#pragma unroll 1
                for (uint32_t i = 0; i < nc4; i += 128) rank += __popc(__ballot_sync(0xffffffffu, lds32(list + i + 4 * lane) > mine));
                if (rank < 8 && lane == 0) sts32(sb + 96 + 4 * rank, mine);
            }
            __syncthreads();
            if (tid < 8 * NTOP) st_gpu32(&p.sc->top[tid >> 3][tid & 7], lds32(sb + 96 + 4 * (tid & 7)) | (((tag + pass - 1) & 31) << 11));
            WSTAMP(3);
            if (!pass) RSTAMP(4);
        }
        WDUMP();
        return;
    }

    WSTAMP(0);
    if (pw < 8) {
        const int d = 8 * c + pw - MAIN_W0;
        if (lane == 0) asm volatile("cp.async.ca.shared.global [%0], [%1], 4;" :: "r"(sb + M_DSK + 4 * (pw - MAIN_W0)), "l"(p.Dskip + (d & ~1)) : "memory");
        asm volatile("barrier.cluster.arrive.relaxed.aligned;" ::: "memory");
        const int warp = pw - MAIN_W0;
        asm volatile("setmaxnreg.inc.sync.aligned.u32 160;");
        const int g = lane >> 2, t = lane & 3;
        const int mi = lane >> 3, r = lane & 7;
        const uint32_t TB = sb + OFF_TAB + warp * TAB_W;
        const uint32_t UB = sb + OFF_U + warp * U_CH;
        if (mi < 2) sts128(UB + mi * U_PL + r * 16, 0, 0, 0, 0);
        if (lane < 4) sts128(TB + lane * T_PL, 0, 0, 0, 0);
        sts128(sb + OFF_SCR + warp * 8192 + lane * 16, 0x3C00u, 0x3C00u, 0x3C00u, 0x3C00u);
        __syncwarp();

        uint32_t cfix;
        {
            KSTAMP(4, v_la.x ^ v_ai.x ^ v_cr.x ^ v_ci.x ^ ldt16);
            const float dt = bf_round(exp_acc(__uint_as_float(ldt16 << 16)));
            float l2[4], li[4];
            {
                const uint32_t la[2] = {v_la.x, v_la.y}, ai[2] = {v_ai.x, v_ai.y};
                const float dt2 = -1.4426950408889634f * dt;
#pragma unroll
                for (int i = 0; i < 4; i++) {
                    l2[i] = bf_round(ex2f(((i & 1) ? bf_hi(la[i >> 1]) : bf_lo(la[i >> 1])) * 1.4426950408889634f)) * dt2;
                    li[i] = ((i & 1) ? bf_hi(ai[i >> 1]) : bf_lo(ai[i >> 1])) * dt;
                }
            }
            const uint32_t SX = sb + OFF_SCR + warp * 8192;
            const uint32_t sw = SX + (lane << 4);
#define PUT(buf, row, v) sts128(((sw + (row) * 512) ^ ((row) << 4)) + (buf) * 4096, v[0], v[1], v[2], v[3])
#define EMIT(bufa, rowa, bufb, rowb, xr, xi, k, kp) do { uint32_t pk[4], pd[4]; \
                _Pragma("unroll") for (int i = 0; i < 4; i++) { pk[i] = pack_h(xr[i], xi[i]); pd[i] = hcmul(pk[i], k[i], kp[i]); } \
                PUT(bufa, rowa, pk); PUT(bufb, rowb, pd); } while (0)
#define CMUL4(orr, oi, ar, ai, br, bi) _Pragma("unroll") for (int i = 0; i < 4; i++) CMUL(orr[i], oi[i], ar[i], ai[i], br[i], bi[i])
#define CSQ4(orr, oi, ar, ai) _Pragma("unroll") for (int i = 0; i < 4; i++) CSQ(orr[i], oi[i], ar[i], ai[i])
            float z1r[4], z1i[4], z2r[4], z2i[4], z8r[4], z8i[4], z256r[4], z256i[4];
            uint32_t k4[4], k4p[4];
            float z4r[4], z4i[4];
#pragma unroll
            for (int i = 0; i < 4; i++) cexp_pow(l2[i], li[i], 1.f, z1r[i], z1i[i]);
            CSQ4(z2r, z2i, z1r, z1i);
            CSQ4(z4r, z4i, z2r, z2i);
            CSQ4(z8r, z8i, z4r, z4i);
            KSTAMP(5, __float_as_uint(z8r[3]));
            uint32_t Ya[16][4];
            float cr[4], ci[4], inv;
            {
                float w1r[4], w1i[4], ar[4], ai[4], br[4], bi[4];
                uint32_t k8[4], k8p[4];
#pragma unroll
                for (int i = 0; i < 4; i++) {
                    k8[i] = pack_h(z8r[i], -z8i[i]); k8p[i] = pack_h(z8i[i], z8r[i]);
                    CSQ(w1r[i], w1i[i], z8r[i], z8i[i]); w1i[i] = -w1i[i];
                }
                PUT(1, 0, k8);
                EMIT(0, 1, 1, 1, w1r, w1i, k8, k8p);
                CSQ4(ar, ai, w1r, w1i);            EMIT(0, 2, 1, 2, ar, ai, k8, k8p);
                CMUL4(br, bi, ar, ai, w1r, w1i);   EMIT(0, 3, 1, 3, br, bi, k8, k8p);
                CSQ4(ar, ai, ar, ai);              EMIT(0, 4, 1, 4, ar, ai, k8, k8p);
                CMUL4(ar, ai, ar, ai, w1r, w1i);   EMIT(0, 5, 1, 5, ar, ai, k8, k8p);
                CSQ4(br, bi, br, bi);              EMIT(0, 6, 1, 6, br, bi, k8, k8p);
                CMUL4(br, bi, br, bi, w1r, w1i);   EMIT(0, 7, 1, 7, br, bi, k8, k8p);
                __syncwarp();
                KSTAMP(6, 0);
                const uint32_t ab = SX + (mi & 1) * 4096 + r * 512, ax = ((mi >> 1) ^ r) << 4;
                const uint32_t vr[2] = {v_cr.x, v_cr.y}, vi[2] = {v_ci.x, v_ci.y};
                const uint32_t m2 = __vmaxu2(__vmaxu2(vr[0] & 0x7fff7fffu, vr[1] & 0x7fff7fffu), __vmaxu2(vi[0] & 0x7fff7fffu, vi[1] & 0x7fff7fffu));
                const uint32_t mx = __reduce_max_sync(0xffffffffu, max(m2, m2 << 16));
                const uint32_t e = min(max(mx >> 23, 11u), 254u);
                const float sc = __uint_as_float((264u - e) << 23);
                inv = __uint_as_float((e - 10u) << 23) * (2.f * dt);
#pragma unroll
                for (int i = 0; i < 4; i++) {
#pragma unroll
                    for (int k = 0; k < 4; k++) ldsm4(ab + (ax ^ (i << 5)) + k * 128, Ya[4 * k + i][0], Ya[4 * k + i][1], Ya[4 * k + i][2], Ya[4 * k + i][3]);
                    float tr, ti;
                    cexp_pow(l2[i], li[i], 128.f, tr, ti);
                    sts32(TB + 2176 + 256 * i + 4 * lane, pack_h(tr, ti));
                    sts32(TB + 2176 + 256 * i + 128 + 4 * (lane ^ 16), pack_h(-ti, tr));
                    k4[i] = pack_h(z4r[i], z4i[i]); k4p[i] = pack_h(-z4i[i], z4r[i]);
                    CSQ(z256r[i], z256i[i], tr, ti);
                    cr[i] = ((i & 1) ? bf_hi(vr[i >> 1]) : bf_lo(vr[i >> 1])) * sc;
                    ci[i] = ((i & 1) ? bf_hi(vi[i >> 1]) : bf_lo(vi[i >> 1])) * sc;
                }
                __syncwarp();
            }
            KSTAMP(7, Ya[15][0]);
            const uint32_t ld0 = SX + r * 512 + ((mi ^ r) << 4), ld1 = ld0 ^ 64;
            float R[6][4], s1024;
            {
                float xr[4], xi[4], yr[4], yi[4];
                EMIT(0, 0, 0, 1, cr, ci, k4, k4p);
                CMUL4(yr, yi, cr, ci, z1r, z1i);        EMIT(0, 2, 0, 3, yr, yi, k4, k4p);
                CMUL4(xr, xi, cr, ci, z256r, z256i);    EMIT(1, 0, 1, 1, xr, xi, k4, k4p);
                CMUL4(yr, yi, yr, yi, z1r, z1i);        EMIT(0, 4, 0, 5, yr, yi, k4, k4p);
                CMUL4(cr, ci, xr, xi, z2r, z2i);        EMIT(1, 2, 1, 3, cr, ci, k4, k4p);
                CMUL4(yr, yi, yr, yi, z1r, z1i);        EMIT(0, 6, 0, 7, yr, yi, k4, k4p);
                CMUL4(xr, xi, xr, xi, z256r, z256i);    EMIT(1, 4, 1, 5, xr, xi, k4, k4p);
                CMUL4(xr, xi, xr, xi, z256r, z256i);    EMIT(1, 6, 1, 7, xr, xi, k4, k4p);
                CMUL4(xr, xi, xr, xi, z256r, z256i);
                s1024 = (xr[0] + xr[1]) + (xr[2] + xr[3]);
#pragma unroll
                for (int m = 0; m < 4; m++) {
                    if (m == 0) { CMUL4(xr, xi, xr, xi, z8r, z8i); } else { CMUL4(xr, xi, xr, xi, z256r, z256i); }
                    sts128(TB + m * T_PL + 16 + 16 * lane, pack_h(xr[0], xi[0]), pack_h(xr[1], xi[1]), pack_h(xr[2], xi[2]), pack_h(xr[3], xi[3]));
                }
            }
            asm volatile("barrier.cluster.wait.acquire.aligned;" ::: "memory");
            __syncwarp();
            {
                KSTAMP(8, 0);
                uint32_t bd[2][4] = {{0, 0, 0, 0}, {0, 0, 0, 0}};
                const bool on = (g >> 1) == t;
#pragma unroll
                for (int i = 0; i < 6; i++) { R[i][0] = R[i][1] = R[i][2] = R[i][3] = 0.f; }
#pragma unroll
                for (int k2 = 0; k2 < 8; k2++) {
                    uint32_t x[4], y[4], z[4], a1[2][4];
                    lds128_if(on, TB + 2176 + g * 128 + (k2 < 4 ? 64 : -64) * (g & 1) + 16 * k2, bd[k2 & 1]);
                    ldsm4(TB + (r & 3) * T_PL + 16 + 16 * mi + 64 * k2, z[0], z[1], z[2], z[3]);
                    ldsm4(((k2 & 1) ? ld1 : ld0) + (k2 >> 1) * 128, x[0], x[1], x[2], x[3]);
                    ldsm4(((k2 & 1) ? ld1 : ld0) + (k2 >> 1) * 128 + 4096, y[0], y[1], y[2], y[3]);
#pragma unroll
                    for (int u = 0; u < 2; u++) {
                        mma_hh_k8(a1[u][0], a1[u][1], Ya[2 * k2 + u][0], Ya[2 * k2 + u][1], bd[k2 & 1][2 * u]);
                        mma_hh_k8(a1[u][2], a1[u][3], Ya[2 * k2 + u][2], Ya[2 * k2 + u][3], bd[k2 & 1][2 * u + 1]);
                    }
#pragma unroll
                    for (int u = 0; u < 2; u++) {
                        const uint32_t(&a0)[4] = Ya[2 * k2 + u];
                        mma_h(R[0], a0[0], a0[1], a0[2], a0[3], x[2 * u], x[2 * u + 1]);
                        mma_h(R[2], a0[0], a0[1], a0[2], a0[3], y[2 * u], y[2 * u + 1]);
                        mma_h(R[4], a0[0], a0[1], a0[2], a0[3], z[2 * u], z[2 * u + 1]);
                        mma_h(R[1], a1[u][0], a1[u][1], a1[u][2], a1[u][3], x[2 * u], x[2 * u + 1]);
                        mma_h(R[3], a1[u][0], a1[u][1], a1[u][2], a1[u][3], y[2 * u], y[2 * u + 1]);
                        mma_h(R[5], a1[u][0], a1[u][1], a1[u][2], a1[u][3], z[2 * u], z[2 * u + 1]);
                    }
                }
            }
            __syncwarp();
            KSTAMP(9, __float_as_uint(R[3][0]));
            if (lane == 0) mbar_arrive(bars + 8 * B_KG + (__float_as_uint(R[0][0]) & __float_as_uint(R[2][0]) & p.zero));
            sts128(TB + 2176 + 16 * lane, 0, 0, 0, 0);
            sts128(TB + 2688 + 16 * lane, 0, 0, 0, 0);
            __syncwarp();
#undef PUT
#undef EMIT
#pragma unroll
            for (int o = 16; o > 0; o >>= 1) s1024 += __shfl_xor_sync(0xffffffffu, s1024, o);
            uint32_t w[4][4], dsk = 0;
            cp_wait_all();
            asm volatile("{\n\t.reg .pred p;\n\tsetp.eq.u32 p, %2, 0;\n\t@p ld.shared.u16 %0, [%1];\n\t}" : "+r"(dsk) : "r"(sb + M_DSK + 4 * warp + 2 * (warp & 1)), "r"(lane) : "memory");
#pragma unroll
            for (int a = 0; a < 4; a++) {
                const float v0 = (a == 0) ? fmaf(R[0][0], inv, __uint_as_float(dsk << 16)) : R[a][0] * inv;
                const float v1 = R[a][1] * inv, v2 = R[a][2] * inv, v3 = R[a][3] * inv;
                w[a][0] = pack_bf(v0, 0.f); w[a][1] = pack_bf(v1, v0); w[a][2] = pack_bf(v2, v1); w[a][3] = pack_bf(v3, v2);
            }
            const uint32_t wb = TB + 16 + 16 * g, w1 = wb + t * T_PL, w2 = wb + 256 + 2 * t * T_PL;
            const uint32_t w3 = (t == 0) ? wb + 256 + 3 * T_PL : TB + T_A + 8 * (16 * t + g);
            const uint32_t w3s = (t == 0) ? 128 : 64, w3o = (t == 0) ? 8 : 12;
            const uint32_t k512 = __shfl_sync(0xffffffffu, w[2][1], 2);
#pragma unroll
            for (int a = 0; a < 2; a++) {
                sts128(w1 + 128 * a, w[a][0], w[a][1], w[a][2], w[a][3]);
                const uint32_t(&q)[4] = w[2 + a];
                if (t < 2) sts128(w2 + 128 * a, q[0], q[1], q[2], q[3]);
                if (t == 0) { sts128(w2 + T_PL + 128 * a, q[0], q[1], q[2], q[3]); sts32(w3 + 128 * a + 4, q[2]); }
                sts32_if(t != 1 && (a == 1 || lane != 2), w3 + w3s * a, q[1]);
                sts32_if(t != 1, w3 + w3s * a + w3o, q[3]);
            }
            sts128_if(lane < 4, w1 + 512, t == 3 ? k512 : k512 >> 16, t < 2 ? k512 : t == 2 ? k512 & 0xffff0000u : k512 << 16, t < 2 ? k512 << 16 : 0u, 0);
            __syncwarp();
#pragma unroll
            for (int a = 0; a < 2; a++) {
                sts16(w1 + 128 * a + 18, w[a][3]);
                const uint32_t(&q)[4] = w[2 + a];
                if (t < 2) sts16(w2 + 128 * a + 18, q[3]);
                if (t == 0) { sts16(w2 + T_PL + 128 * a + 18, q[3]); sts16(w3 + 128 * a + 14, q[3]); }
            }
            if (t == 0) sts16(w3 + 128 - 4, w[3][0]);
            if (lane == 2 || (t == 0 && g > 0)) sts16(lane == 2 ? TB + 16 + 3 * T_PL + 4 * 127 : w3 - 4, w[2][0]);
            {
                float q[4];
#pragma unroll
                for (int i = 0; i < 4; i++) q[i] = (t < 2 ? R[4][i] : R[5][i]) * inv;
                const uint32_t b0 = pack_bf(q[0], q[2]), b1 = pack_bf(q[1], q[3]);
                const uint32_t wq = TB + T_B + 8 * (65 + 32 * (t & 1) + 4 * (t & 2) + g);
                sts32(wq, b0); sts32(wq + 12, b0); sts32(wq + 128, b1); sts32(wq + 140, b1);
            }
            cfix = pack_bf(s1024 * inv, s1024 * inv);
            if (lane == 0) sts32(TB + T_A + 8 * 64, cfix);
            __syncwarp();
        }
        WSTAMP(1);

        mbar_wait(bars + 8 * B_U);
        WSTAMP(2);

        float D[16][4];
        {
            const int x5 = g - t + 5;
            const uint32_t tabD = TB + (x5 & 3) * T_PL + (x5 & 12) + 16;
            {
                const uint32_t a1 = lds32(tabD - 8), a0 = p.zero;
#pragma unroll
                for (int jq = 0; jq < 4; jq++) {
                    uint32_t b[4];
                    ldsm4(UB + (9 + lane) * 16 + jq * 512, b[0], b[1], b[2], b[3]);
#pragma unroll
                    for (int i = 0; i < 4; i++) mma_bf_k8z(D[4 * jq + i], a0, a1, b[i]);
                }
            }
            const uint32_t ua = UB + (mi & 1) * U_PL + (8 + 8 * (mi >> 1) + r) * 16;
#pragma unroll 1
            for (int k0 = 0; k0 < 8; k0++) {
                uint32_t Uf[16][2];
#pragma unroll
                for (int jp = 0; jp < 8; jp++) ldsm4(ua + jp * 256 - k0 * 16, Uf[2 * jp][0], Uf[2 * jp][1], Uf[2 * jp + 1][0], Uf[2 * jp + 1][1]);
#pragma unroll
                for (int k1 = 0; k1 < 4; k1++) {
                    const uint32_t ta = tabD + 16 * (8 * k1 + k0);
                    const uint32_t a0 = lds32(ta), a1 = lds32(ta + 8), a2 = lds32(ta - 8), a3 = a0 ^ p.zero;
#pragma unroll
                    for (int J = k1; J < 16; J++) mma_bf(D[J], a0, a1, a2, a3, Uf[J - k1][0], Uf[J - k1][1]);
                }
                if (k0 == 0) {
                    const uint32_t ta = tabD + 16 * 32;
                    const uint32_t a0 = lds32(ta), a1 = lds32(ta + 8), a2 = lds32(ta - 8), a3 = a0 ^ p.zero;
#pragma unroll
                    for (int J = 4; J < 16; J++) mma_bf(D[J], a0, a1, a2, a3, Uf[J - 4][0], Uf[J - 4][1]);
                    const uint32_t f0 = (cfix ^ 0x80008000u) & (g == t ? 0xffffu : g == t + 4 ? 0xffff0000u : 0u);
                    const uint32_t f1 = p.zero, f2 = p.zero + p.zero, f3 = f0 ^ p.zero;
#pragma unroll
                    for (int J = 8; J < 16; J++) mma_bf(D[J], f0, f1, f2, f3, Uf[J - 8][0], Uf[J - 8][1]);
                }
            }
        }
        WSTAMP(3);
        {
            const int ch = 8 * h + warp;
            const uint32_t yo = sb + ch * 512 + ((lane ^ (((ch >> 2) << 1) | (ch & 1))) << 4);
            const uint32_t yr = mapa(yo, h ^ 1), ybr = mapa(bars + 8 * B_Y, h ^ 1);
            auto ship = [&](const int Q) {
                uint4 y[2];
#pragma unroll
                for (int hh = 0; hh < 2; hh++) {
                    const int J = 4 * Q + 2 * hh;
                    y[hh] = make_uint4(pack_bf(D[J][0], D[J][1]), pack_bf(D[J][2], D[J][3]), pack_bf(D[J + 1][0], D[J + 1][1]), pack_bf(D[J + 1][2], D[J + 1][3]));
                }
                if (!(Q & 1)) mbar_wait(bars + 8 * (B_F + (Q >> 1)));
                asm volatile("{\n\t.reg .pred p;\n\tsetp.eq.u32 p, %11, 0;\n\t"
                             "@p st.async.weak.shared::cluster.mbarrier::complete_tx::bytes.v4.b32 [%9], {%4,%5,%6,%7}, [%10];\n\t"
                             "@!p st.async.weak.shared::cluster.mbarrier::complete_tx::bytes.v4.b32 [%9], {%0,%1,%2,%3}, [%10];\n\t"
                             "@p st.shared.v4.b32 [%8], {%0,%1,%2,%3};\n\t@!p st.shared.v4.b32 [%8], {%4,%5,%6,%7};\n\t}"
                             :: "r"(y[0].x), "r"(y[0].y), "r"(y[0].z), "r"(y[0].w), "r"(y[1].x), "r"(y[1].y), "r"(y[1].z), "r"(y[1].w),
                                "r"(yo + y_off(Q)), "r"(yr + y_off(Q)), "r"(ybr + 8 * Q), "r"(h) : "memory");
                __syncwarp();
                if (lane == 0) mbar_arrive(bars + 8 * (B_Y + Q));
            };
            ship(0);
            const uint4 bA = lds128(sb + OFF_BAND + (g - t + 3) * 48), bB = lds128(sb + OFF_BAND + (g - t + 3) * 48 + 16);
            const uint2 bC = lds64(sb + OFF_BAND + (g - t + 3) * 48 + 32);
            uint2 QA[5][2], QB[8];
            const uint32_t tq = TB + 8 * (1 + g - 2 * t);
#pragma unroll
            for (int dd = 0; dd < 5; dd++) { QA[dd][0] = lds64(tq + T_A + 64 * (dd + 4)); QA[dd][1] = lds64(tq + T_A + 64 * (dd + 4) - 8); }
#pragma unroll
            for (int dd = 0; dd < 8; dd++) QB[dd] = lds64(tq + T_B + 64 * (dd + 8));
            const uint32_t u1 = UB + (mi & 1) * U_PL + (7 + r + (mi >> 1)) * 16;
            const uint32_t u2 = UB + ((mi & 1) ^ 1) * U_PL + (7 + r + (mi & 1) + 8 * (mi >> 1)) * 16;
            uint32_t n[4];
#pragma unroll
            for (int j = 0; j < 12; j++) {
                uint32_t m[4];
                ldsm4(u1 + j * 128, m[0], m[1], m[2], m[3]);
                if (!(j & 1)) ldsm4(u2 + j * 128, n[0], n[1], n[2], n[3]);
                const uint32_t n0 = n[2 * (j & 1)], n1 = n[2 * (j & 1) + 1];
                float wa[4], wb[4], wc[4], g1[4], g2[4];
                mma_bf_z(wa, bA.x, bA.y, bA.z, bA.w, m[0], m[1]);
                mma_bf_z(wb, bA.x, bA.y, bA.z, bA.w, n0, n1);
                mma_bf_z(wc, bA.x, bA.y, bA.z, bA.w, m[2], m[3]);
                if (j < 8) {
                    mma_bf_z(g1, bB.x, bB.y, bB.z, bB.w, m[0], m[1]);
                    mma_bf_z(g2, bB.x, bB.y, bB.z, bB.w, n0, n1);
                    mma_bf_k8(g1, bC.x, bC.y, m[2]);
                    mma_bf_k8(g2, bC.x, bC.y, m[3]);
                }
#pragma unroll
                for (int e = 0; e < 2; e++) {
                    const uint32_t q0 = pack_bf(wa[e], wa[e + 2]), q1 = pack_bf(wb[e], wb[e + 2]), q2 = q1 ^ p.zero, q3 = pack_bf(wc[e], wc[e + 2]);
#pragma unroll
                    for (int dd = 0; dd < 5; dd++)
                        if (j + 4 + dd < 16) mma_bf(D[j + 4 + dd], q0, q1, q2, q3, QA[dd][e].x, QA[dd][e].y);
                }
                if (j < 8) {
                    const uint32_t q0 = pack_bf(g1[0], g1[2]), q1 = pack_bf(g2[0], g2[2]), q2 = pack_bf(g1[1], g1[3]), q3 = pack_bf(g2[1], g2[3]);
#pragma unroll
                    for (int dd = 7 - j; dd >= 0; dd--) mma_bf(D[j + 8 + dd], q0, q1, q2, q3, QB[dd].x, QB[dd].y);
                }
                if ((j & 3) == 3) {
                    WSTAMP(4 + 2 * (j >> 2));
                    if (j == 11 && LATE2) ship(2);
                    if (j != 7 || !LATE2) ship((j >> 2) + 1);
                }
            }
        }
        const int warpu = __reduce_max_sync(0xffffffffu, warp);
        mix_rows<1, BULKM>(p, &tm_out, sb, sb + OFF_U + warpu * U_CH + (warpu & 1) * 64, PQ, 4, warpu, h, pr, lane);
        if (BULKM) asm volatile("cp.async.bulk.commit_group;\n\tcp.async.bulk.wait_group.read 0;" ::: "memory");
        WSTAMP(10);
        WDUMP();
    } else if ((pw & 12) == AUX_W0) {
        const int v = __reduce_max_sync(0xffffffffu, pw & 3);
        const int at = tid & 127;
        const int g = lane >> 2, t = lane & 3;
        unsigned tag;
        const bool gu = c < NGU_CTA;
        {
            const uint32_t xb = sb + (v < 2 ? OFF_XSEL : OFF_RING + 2 * 8192) + v * 8192;
            const uint32_t gws = sb + M_DPIN;
            const uint32_t row = 16 * c + 4 * v + (g >> 1);
#pragma unroll
            for (int i = 0; i < 8; i++)
                asm volatile("cp.async.ca.shared.global [%0], [%1], 4;" :: "r"((i < 4 ? sb + OFF_GP : gws) + 512 * (i & 3) + (tid & 124) * 4 + (tid & 1) * 8 + (tid & 2) * 2),
                             "l"((i < 4 ? p.wr : p.gatew) + 256 * (i & 3) + (tid & 127) * 2) : "memory");
            if ((tid & 127) < 33) cp16(sb + OFF_BAND + (tid & 127) * 16, p.band + (tid & 127));
            asm volatile("barrier.cluster.arrive.relaxed.aligned;" ::: "memory");
            tag = __reduce_max_sync(0xffffffffu, (*(volatile unsigned*)&p.sc->epoch + 1) & 0xffffu);
            if (gu) st_gpu32((uint32_t*)&p.sc->h[(tag + 1) & 1][32 * c] + at, 0);
            if (v == 3) sts32(sb + M_BMAP + lane * 4, 0);
            if (at == 0) sts32(sb + M_TAG, tag << 16);
            cp_wait_all();
            bar_sync(1, 128);
            uint2 w[16];
#pragma unroll
            for (int kb = 0; kb < 16; kb++) w[kb] = lds64((g < 4 ? sb + OFF_GP : gws) + 128 * kb + 32 * (g & 2) + 16 * t + 8 * (g & 1));
            asm volatile("barrier.cluster.wait.acquire.aligned;" ::: "memory");
            mbar_wait(bars + 8 * (B_X + v));
            WSTAMP(10);
            float dr[4][4];
#pragma unroll
            for (int kb = 0; kb < 16; kb++) {
                const uint4 x = lds128(xb + (g >> 1) * 2048 + 128 * kb + 16 * (lane & 7));
                if (kb < 4) mma_bf_z(dr[kb], x.x, x.y, x.z, x.w, w[kb].x, w[kb].y);
                else mma_bf(dr[kb & 3], x.x, x.y, x.z, x.w, w[kb].x, w[kb].y);
            }
            float rs = ((dr[0][0] + dr[0][3]) + (dr[1][0] + dr[1][3])) + ((dr[2][0] + dr[2][3]) + (dr[3][0] + dr[3][3]));
            if (lane == 0) mbar_arrive(bars + 8 * (B_XE + v) + (__float_as_uint(rs) & p.zero));
            rs += __shfl_xor_sync(0xffffffffu, rs, 5);
            const uint32_t rb = pack_bf(0.f, rs);
            if (!(lane & 7)) st_gpu32((uint32_t*)&p.sc->r[(row >> 2) * RS] + (row & 3), ((rb ^ (((int)rb >> 31) | 0x80000000u)) & 0xffff0000u) | tag);
            WSTAMP(1);
            {
                const int n = 3 + (lane >> 3) + 4 * (lane & 1);
                const uint32_t so = (n & 7) * S_PL + ((lane & 6) + (n >> 3)) * 32;
                const uint32_t src[2] = {sb + OFF_S + v * S_Q + s_addr(so, h), sb + OFF_S + v * S_Q + s_addr(so + 32, h)};
                const uint32_t dst = sb + OFF_U + g * U_CH + (8 + 32 * v + 16 * h + t) * 16;
                const uint32_t rdst = mapa(dst, h ^ 1), rbar = mapa(bars + 8 * B_U, h ^ 1);
                mbar_wait(bars + 8 * (B_S + v));
                WSTAMP(9);
                uint4 a[8];
#pragma unroll
                for (int b = 0; b < 2; b++) {
#pragma unroll
                    for (int j = 0; j < 8; j++) ldsm4t((b ? src[j & 1] : src[j & 1] ^ 16) + (j >> 1) * 256, a[j].x, a[j].y, a[j].z, a[j].w);
#pragma unroll
                    for (int j = 0; j < 8; j++) {
                        if (b) sts128(dst + (j >> 1) * 64 + (j & 1) * U_PL, a[j].x, a[j].y, a[j].z, a[j].w);
                        else st_async16(rdst + (j >> 1) * 64 + (j & 1) * U_PL, a[j], rbar);
                    }
                }
                if (h && v == 3) {
                    ldsm4t((src[0] ^ 16) + 1024, a[0].x, a[0].y, a[0].z, a[0].w);
                    ldsm4t(src[0] + 1024, a[1].x, a[1].y, a[1].z, a[1].w);
                    if (t == 0) {
                        st_async16(rdst + 256, make_uint4(a[0].x, a[0].y & 0xffffu, a[0].z & 0xffffu, a[0].w & 0xffffu), rbar);
                        sts128(dst + 256, a[1].x, a[1].y & 0xffffu, a[1].z & 0xffffu, a[1].w & 0xffffu);
                    }
                }
                __syncwarp();
                if (lane == 0) mbar_arrive(bars + 8 * B_U);
            }
            if ((lane & 7) == 2) st_gpu32((uint32_t*)p.sc->g + ((row & 256) << 2) + gate_pos(row), pack_bf(sigmoid_f(__uint_as_float(rb)), 0.f) | (tag << 16));
            WSTAMP(2);
        }
        {
            const bool lane0 = pin(lane, lane) == 0;
            const uint32_t own = pin(sb + OFF_XSEL + (at ^ ((at >> 1) & 4)) * 16, lane);
            float acc[8][4];
#pragma unroll
            for (int i = 0; i < 8; i++) { acc[i][0] = acc[i][1] = acc[i][2] = acc[i][3] = 0.f; }
            const int krow = ((lane >> 1) & 8) + (lane & 7);
            const uint32_t tile0 = pin(sb + OFF_RING + krow * 64 + ((((lane >> 3) & 1) ^ ((krow >> 1) & 3)) << 4), lane);
            const uint32_t xo = pin(sb + OFF_XSEL + (lane & 7) * XS_ROW + 512 * v + 2 * (lane & 24), lane);
            const uint32_t po = pin(sb + OFF_XSEL + t * XS_ROW + (g & 3) * 128 + (g & 1) * 64 + v * 16 + (lane >> 4) * 8, lane);
            const uint32_t po1 = pin(po + 64 - (g & 1) * 128, lane);
            uint32_t* hdst = pin((uint32_t*)&p.sc->h[tag & 1][32 * c] + at, lane);
            auto signal = [&](const int k, const uint32_t dep) {
                if (lane < 2 && v < 2)
                    asm volatile("st.async.weak.shared::cluster.mbarrier::complete_tx::bytes.b32 [%0], %1, [%2];"
                                 :: "r"(mapa(sb + M_SINK, lane)), "r"(dep), "r"(mapa(bars + 8 * (B_F + k), lane)) : "memory");
            };
#pragma unroll 1
            for (int i = 0; i < 4; i++) {
                const int s = 4 * i + v;
                uint32_t a[16][4], b[2][4];
                if (gu) {
                    const uint32_t tile = tile0 + (s < 14 ? s : v) * 8192;
                    if (lane0 && i > 1) mbar_arrive(bars + 8 * (B_E + s - 4));
                    if (i == 2) signal(0, 0);
                    mbar_wait(bars + 8 * (B_W + s));
#pragma unroll
                    for (int q = 0; q < 16; q++) ldsm4t((tile ^ ((q & 1) << 5)) + ((q >> 1) & 1) * 4096 + (q >> 2) * 1024, a[q][0], a[q][1], a[q][2], a[q][3]);
                }
                if (i == 0) {
                    if (gu) {
                        uint32_t dep = p.zero;
#pragma unroll
                        for (int q = 0; q < 16; q += 2) dep &= a[q][0] & a[q + 1][0];
                        if (lane == 0) mbar_arrive(bars + 8 * (B_E + v) + dep);
                    }
                    WSTAMP(11);
                    uint32_t top;
#pragma unroll 1
                    for (int it = 0; it < (1 << 22); it++) {
                        asm volatile("ld.relaxed.gpu.global.u32 %0, [%1];" : "=r"(top) : "l"(&p.sc->top[c % NTOP][g]) : "memory");
                        if (__all_sync(0xffffffffu, ((top ^ (tag << 11)) & 0xf800u) == 0)) break;
                        if (TSLEEP) __nanosleep(TSLEEP);
                    }
                    WSTAMP(3);
                    if (gu) {
                        const uint32_t k = 4 * h + v, row = __reduce_max_sync(0xffffffffu, lane == 4 * k ? ~top & 2047 : 0);
                        asm volatile("{\n\t.reg .pred p;\n\telect.sync _|p, 0xffffffff;\n\t"
                                     "@p cp.async.bulk.shared::cluster.global.mbarrier::complete_tx::bytes.multicast::cluster [%0], [%1], 2048, [%2], %3;\n\t}"
                            :: "r"(sb + OFF_XSEL + k * XS_ROW), "l"(p.u + (size_t)row * D_), "r"(bars + 8 * B_G), "h"((unsigned short)3) : "memory");
                    }
                    if (v == 3) {
                        const uint32_t row = ~top & 2047;
                        if (t == 0 && ((row >> 8) & 1) == h)
                            asm volatile("red.shared.or.b32 [%0], %1;" :: "r"(sb + M_BMAP + (row & 7) * 16 + (row >> 9) * 4), "r"(1u << (gate_pos(row) & 31)) : "memory");
                        if (t == 0) sts32(sb + M_TOP + lane, top);
                        if (c == 0 && lane == 0) *(volatile unsigned*)&p.sc->epoch = tag;
                        __syncwarp();
                        if (lane0) mbar_arrive(bars + 8 * B_Y);
                    }
                    if (!gu) break;
                    mbar_wait(bars + 8 * B_G);
                    WSTAMP(4);
                }
                ldsm4(xo + 128 * i, b[0][0], b[0][1], b[0][2], b[0][3]);
                ldsm4(xo + 128 * i + 64, b[1][0], b[1][1], b[1][2], b[1][3]);
#pragma unroll
                for (int q = 0; q < 16; q++) mma_bf(acc[q & 7], a[q][0], a[q][1], a[q][2], a[q][3], b[q >> 3][(q >> 1) & 2], b[q >> 3][((q >> 1) & 2) + 1]);
            }
            if (gu) {
                WSTAMP(5);
                __syncwarp();
#pragma unroll
                for (int q = 0; q < 4; q++) {
                    const int ct = q >> 1, e = 2 * (q & 1);
                    sts128(own + q * XS_ROW,
                           __float_as_uint(acc[ct][e] + acc[4 + ct][e]), __float_as_uint(acc[2 + ct][e] + acc[6 + ct][e]),
                           __float_as_uint(acc[ct][e + 1] + acc[4 + ct][e + 1]), __float_as_uint(acc[2 + ct][e + 1] + acc[6 + ct][e + 1]));
                }
                bar_sync(1, 128);
                float sl[2], uv[2];
#pragma unroll
                for (int e = 0; e < 2; e++) {
                    uint2 q[4];
#pragma unroll
                    for (int i = 0; i < 4; i++) q[i] = lds64((e ? po1 : po) + 512 * i);
                    const float s0 = (__uint_as_float(q[0].x) + __uint_as_float(q[1].x)) + (__uint_as_float(q[2].x) + __uint_as_float(q[3].x));
                    const float s1 = (__uint_as_float(q[0].y) + __uint_as_float(q[1].y)) + (__uint_as_float(q[2].y) + __uint_as_float(q[3].y));
                    const float gv = bf_round(p.gu_swap ? s1 : s0);
                    uv[e] = p.gu_swap ? s0 : s1;
                    sl[e] = gv * sigmoid_f(gv);
                }
                const uint32_t hw = hmul2_bf(pack_bf(sl[0], sl[1]), pack_bf(uv[0], uv[1]));
                st_gpu32(hdst, hw ? hw : 0x80000000u);
                signal(1, hw);
            }
        }
        WSTAMP(6);
        {
            const uint32_t own = pin(sb + OFF_XSEL + at * 16, lane);
            const uint32_t hb = sb + (v < 2 ? OFF_XSEL + 7168 * v : OFF_RING + 8192 * v), hl = pin(hb + 16 * lane, lane);
            const int krow = ((lane >> 1) & 8) + (lane & 7);
            const uint32_t tile = pin(sb + OFF_RING + v * 8192 + krow * 32 + ((((lane >> 3) ^ (krow >> 2)) & 1) << 4), lane);
            float dd[4][4];
            bar_sync(1, 128);
            mbar_wait(bars + 8 * (B_W + HW));
            WSTAMP(12);
            uint4 hq[7];
#pragma unroll 1
            for (int it = 0; it < (1 << 16); it++) {
                bulk_load(hb, &p.sc->h[tag & 1][32 * (56 * h + 14 * v)], 7168, bars + 8 * (B_X + v));
                uint32_t a[14][4], mn = 0xffffffffu;
                mbar_wait(bars + 8 * (B_W + 16 + v));
#pragma unroll
                for (int j = 0; j < 14; j++) ldsm4t(tile + (v & 2) * 16384 + j * 512, a[j][0], a[j][1], a[j][2], a[j][3]);
                mbar_wait(bars + 8 * (B_X + v), ~it & 1);
                WSTAMP(7);
#pragma unroll
                for (int j = 0; j < 7; j++) {
                    const uint4 q = lds128(hl + 512 * j);
                    mn = min(mn, q.x);
#pragma unroll
                    for (int e = 0; e < 2; e++) {
                        const uint32_t(&f)[4] = a[2 * j + e];
                        if (j < 2) mma_bf_z(dd[2 * j + e], f[0], f[1], f[2], f[3], e ? q.z : q.x, e ? q.w : q.y);
                        else mma_bf(dd[(2 * j + e) & 3], f[0], f[1], f[2], f[3], e ? q.z : q.x, e ? q.w : q.y);
                    }
                }
#pragma unroll
                for (int j = 0; j < 7; j++) { hq[j] = lds128(hl + 3584 + 512 * j); mn = min(mn, hq[j].x); }
                if (__all_sync(0xffffffffu, mn != 0)) break;
            }
            mbar_wait(bars + 8 * (B_W + 20 + v));
#pragma unroll
            for (int j = 0; j < 14; j++) {
                uint32_t f[4];
                ldsm4t(tile + 65536 + j * 512, f[0], f[1], f[2], f[3]);
                mma_bf(dd[(j + 2) & 3], f[0], f[1], f[2], f[3], (j & 1) ? hq[j >> 1].z : hq[j >> 1].x, (j & 1) ? hq[j >> 1].w : hq[j >> 1].y);
            }
            WSTAMP(8);
            uint4 part;
            part.x = __float_as_uint((dd[0][0] + dd[1][0]) + (dd[2][0] + dd[3][0])); part.y = __float_as_uint((dd[0][1] + dd[1][1]) + (dd[2][1] + dd[3][1]));
            part.z = __float_as_uint((dd[0][2] + dd[1][2]) + (dd[2][2] + dd[3][2])); part.w = __float_as_uint((dd[0][3] + dd[1][3]) + (dd[2][3] + dd[3][3]));
            st_async16(mapa(own + (M_DPIN - OFF_XSEL), h ^ 1), part, mapa(bars + 8 * B_DP, h ^ 1));
            sts128(own + 14336, part.x, part.y, part.z, part.w);
            __syncwarp();
            if (lane == 0) mbar_arrive(bars + 8 * B_DP);
        }
        WDUMP();
    } else {
        asm volatile("setmaxnreg.dec.sync.aligned.u32 64;");
        const int v = __reduce_max_sync(0xffffffffu, pw - PREP_W0);
        const bool gu = c < NGU_CTA;
        const uint32_t t0 = clock();
        const uint32_t bu = bars + 8 * v;
        if (lane == 0) {
            mbar_init(bu + 8 * B_X, 1);
            asm volatile("fence.mbarrier_init.release.cluster;" ::: "memory");
        }
        __syncwarp();
        if (DELAY_X > 0) __nanosleep(DELAY_X);
        bulk_load(sb + (v < 2 ? OFF_XSEL : OFF_RING + 2 * 8192) + v * 8192, p.u + (size_t)(16 * c + 4 * v) * D_, 8192, bu + 8 * B_X);
        if (lane == 0) {
#pragma unroll
            for (int i = 0; i < 10; i++) mbar_init(bu + 32 * i, 1);
            mbar_init(bu + 8 * B_XE, 1);
            mbar_init(bu + 8 * B_Y, v == 0 ? 12 : 9);
            mbar_init(bu + 8 * B_DP, (0x1855 >> (4 * v)) & 15);
            mbar_init(bu + 8 * B_F, 1);
            mbar_init(bu + 8 * B_H, 1);
            asm volatile("fence.mbarrier_init.release.cluster;" ::: "memory");
            mbar_expect(bu + 8 * B_Y, 4096);
            if (v != 2) mbar_expect(bu + 8 * B_DP, v == 0 ? 2048 : (h || v == 3) ? 16384 : 16384 + 128);
            mbar_expect(bu + 8 * B_F, c < NGU_CTA ? 16 : 0);
        }
        __syncwarp();
        asm volatile("barrier.cluster.arrive.relaxed.aligned;" ::: "memory");
        tma3d(sb + OFF_S + v * S_Q, &tm_x, 16 * pr, 64 * v + 32 * h - 1, bars + 8 * (B_S + v), S_Q);
        WSTAMP(9);
        if (v < 3 && lane == 0) asm volatile("prefetch.tensormap [%0];" :: "l"(v == 0 ? &tm_gu : v == 1 ? &tm_down : &tm_out) : "memory");
        asm volatile("barrier.cluster.wait.acquire.aligned;" ::: "memory");
        uint32_t desc;
        {
            const int s = 6 * v + lane, i = s >> 2, w = s & 3, slot = s < 14 ? s : (s | 1) == 17 ? s - 16 : s - 12;
            const int fb = s < 4 ? B_H : (gu && s >= 14) ? B_E + slot : s < 6 ? B_XE + s - 2 : B_KG;
            desc = slot | (fb << 4) | ((i < 4 ? 256 * w + 64 * i : 1792 * h + 448 * w + 224 * (i - 4)) << 10);
            if (lane < 6) mbar_expect(bars + 8 * (B_W + s), i < 4 ? 8192 : 7168);
            if (tid == 32 * PREP_W0) mbar_arrive(bars + 8 * B_H);
        }
        mbar_wait(bars + 8 * (B_H + v));
        {
            const int gap = v == 0 ? GAP : v == 1 ? GAP1 : v == 2 ? GAP2 : GAP3;
            uint32_t last = v ? clock() - SLACK : t0 + T0 - GAP + STAG * ((pr * 5) & 15) / 16;
#pragma unroll 1
            while ((int)(last - clock()) > 500) __nanosleep(256);
#pragma unroll 1
            for (int k = 0; k < 6; k++) {
                const uint32_t dk = __reduce_max_sync(0xffffffffu, lane == k ? desc : 0);
                const bool dn = 6 * v + k >= 16;
                mbar_wait(bars + ((dk >> 1) & 0x1f8));
                uint32_t now;
#pragma unroll 1
                while ((int)((now = clock()) - last) < gap) __nanosleep(CSLEEP);
                last = max((int)(now - last) - SLACK, gap) + last;
                WSTAMP(3 + k);
                if (gu || dn)
                    asm volatile("{\n\t.reg .pred p;\n\telect.sync _|p, 0xffffffff;\n\t"
                                 "@p cp.async.bulk.tensor.3d.shared::cluster.global.mbarrier::complete_tx::bytes [%0], [%1, {%3, %4, 0}], [%2];\n\t}"
                        :: "r"(sb + OFF_RING + (dk & 15) * 8192), "l"(dn ? &tm_down : &tm_gu), "r"(bars + 8 * (B_W + 6 * v + k)), "r"(dn ? 16 * pr : 32 * c), "r"(dk >> 10) : "memory");
                if (k < 5 && PRESLEEP) __nanosleep(PRESLEEP);
            }
            if (lane == 0 && v < 3) mbar_arrive(bars + 8 * (B_H + v + 1));
        }
        if (v < 2) {
            mbar_wait(bars + 8 * B_U);
            mbar_wait(bars + 8 * (gu ? B_G : B_H + 3));
            const uint32_t tag16 = lds32(sb + M_TAG);
            {
                const int k = v;
                uint4 q[4];
#pragma unroll 1
                for (int it = 0; it < (1 << 22); it++) {
                    uint32_t bad = 0;
#pragma unroll
                    for (int i = 0; i < 4; i++) q[i] = ld_gpu128(&p.sc->g[256 * h + 128 * k + 32 * i + lane]);
#pragma unroll
                    for (int i = 0; i < 4; i++) bad |= ((q[i].x ^ tag16) | (q[i].y ^ tag16)) | ((q[i].z ^ tag16) | (q[i].w ^ tag16));
                    if ((bad >> 16) == 0) break;
                    __nanosleep(200);
                }
#pragma unroll
                for (int i = 0; i < 4; i++)
                    asm volatile("st.shared.v2.u32 [%0], {%1, %2};" :: "r"(sb + OFF_GP + 1024 * k + 256 * i + lane * 8),
                                 "r"(__byte_perm(q[i].x, q[i].y, 0x5410)), "r"(__byte_perm(q[i].z, q[i].w, 0x5410)) : "memory");
            }
            __syncwarp();
            if (lane == 0) mbar_arrive(bars + 8 * B_Y);
        }
        {
            WSTAMP(1);
            mix_rows<2, true>(p, &tm_out, sb, sb + OFF_TAB + v * TAB_W, 0, PQ, v, h, pr, lane);
            WSTAMP(2);
            asm volatile("cp.async.bulk.commit_group;" ::: "memory");
            const uint32_t top = lds32(sb + M_TOP + 8 * v + 4 * (lane >> 4));
            const uint32_t row = ~top & 2047, ch = lane & 15, gp = gate_pos(row);
            const bool mine = ((row >> 8) & 1) == h;
            uint32_t gfin, x16, y16 = 0;
            asm volatile("ld.shared.u16 %0, [%1];" : "=r"(gfin) : "r"(sb + OFF_GP + gp * 2) : "memory");
            asm volatile("ld.shared.u16 %0, [%1];" : "=r"(x16) : "r"(sb + OFF_S + (row >> 9) * S_Q + s_addr((row & 7) * S_PL + 32 + (row & 248) * 4, ch >> 3) + 2 * (ch & 7)) : "memory");
            const float rsel = __uint_as_float(pin(__float_as_uint(bf_round(sigmoid_f(__uint_as_float((top ^ (((int)~top >> 31) | 0x80000000u)) & 0xffff0000u)))), lane));
            const uint32_t po = pin(sb + (4 * (ch & 7) + v) * 16 + (ch >> 3) * 8 + (lane >> 4) * 4, lane);
            bf16* op = pin(p.out + (size_t)row * D_ + 16 * pr + ch, lane);
            if (mine) {
                mbar_wait(bars + 8 * (B_Y + (row >> 9)));
                asm volatile("ld.shared.u16 %0, [%1];" : "=r"(y16)
                             : "r"(sb + y_off(row >> 9) + ch * 512 + (((4 * (row & 7) + ((row >> 5) & 3)) ^ (((ch >> 2) << 1) | (ch & 1))) << 4) + 2 * row_elem(row)) : "memory");
            }
            mbar_wait(bars + 8 * B_DP);
            float q[8];
#pragma unroll
            for (int i = 0; i < 4; i++) { q[i] = ldsf(po + M_DPIN + 512 * i); q[4 + i] = ldsf(po + OFF_XSEL + 14336 + 512 * i); }
            const float tot = ((q[0] + q[1]) + (q[2] + q[3])) + ((q[4] + q[5]) + (q[6] + q[7]));
            const float b = bf_round(__uint_as_float(x16 << 16) + bf_round(bf_round(tot) * rsel));
            if (mine) *op = __float2bfloat16_rn(fmaf(bf_lo(gfin), __uint_as_float(y16 << 16), bf_round(bf_round(1.f - bf_lo(gfin)) * b)));
        }
        asm volatile("cp.async.bulk.wait_group.read 0;" ::: "memory");
        WSTAMP(10);
        WDUMP();
    }
}

typedef CUresult (*EncodeFn)(CUtensorMap*, CUtensorMapDataType, cuuint32_t, void*, const cuuint64_t*, const cuuint64_t*,
                             const cuuint32_t*, const cuuint32_t*, CUtensorMapInterleave, CUtensorMapSwizzle,
                             CUtensorMapL2promotion, CUtensorMapFloatOOBfill);

void make_map(EncodeFn f, CUtensorMap* m, const void* ptr, uint64_t cols, uint64_t rows, uint64_t pitch, uint32_t bc, uint32_t br, CUtensorMapSwizzle sw, int prom,
              uint32_t planes = 1, uint64_t plane_stride = 0, uint32_t box_planes = 0) {
    cuuint64_t dims[3] = {cols, rows, planes};
    cuuint64_t str[2] = {pitch, planes > 1 ? plane_stride : pitch * rows};
    cuuint32_t box[3] = {bc, br, box_planes ? box_planes : planes};
    cuuint32_t es[3] = {1, 1, 1};
    f(m, CU_TENSOR_MAP_DATA_TYPE_BFLOAT16, 3, (void*)ptr, dims, str, box, es, CU_TENSOR_MAP_INTERLEAVE_NONE, sw,
      (CUtensorMapL2promotion)prom, CU_TENSOR_MAP_FLOAT_OOB_FILL_NONE);
}

}

extern "C" void kernel_launch(void* const* d_in, const int* in_sizes, int n_in, void* d_out, int out_size) {
    static EncodeFn enc = nullptr;
    static void *sc = nullptr, *band = nullptr;
    if (!enc) {
        void* fn = nullptr;
        cudaDriverEntryPointQueryResult qr;
        cudaGetDriverEntryPoint("cuTensorMapEncodeTiled", &fn, cudaEnableDefault, &qr);
        enc = (EncodeFn)fn;
        cudaGetSymbolAddress(&sc, g_scratch);
        cudaGetSymbolAddress(&band, g_band);
        cudaFuncSetAttribute(fused_kernel, cudaFuncAttributeMaxDynamicSharedMemorySize, SMEM_BYTES);
    }
    CUtensorMap tg, td, tx, to;
    const char *wg = (const char*)d_in[9], *wu = (const char*)d_in[10];
    const bool swap = wu < wg;
    make_map(enc, &tg, swap ? wu : wg, F_, D_, F_ * 2, 32, 64, CU_TENSOR_MAP_SWIZZLE_64B, PROMG, 2, swap ? wg - wu : wu - wg);
    make_map(enc, &td, d_in[11], D_, F_, D_ * 2, 16, 224, CU_TENSOR_MAP_SWIZZLE_32B, PROMD);
    make_map(enc, &tx, d_in[0], D_, L_ / 8, D_ * 16, 16, 33, CU_TENSOR_MAP_SWIZZLE_32B, PROMX, 8, D_ * 2);
    make_map(enc, &to, d_out, D_, L_ / 8, D_ * 16, 16, 32, CU_TENSOR_MAP_SWIZZLE_NONE, 0, 8, D_ * 2, 1);
    Params p;
    p.u = (const bf16*)d_in[0]; p.logA = (const bf16*)d_in[1]; p.Aim = (const bf16*)d_in[2];
    p.Cre = (const bf16*)d_in[3]; p.Cim = (const bf16*)d_in[4]; p.logdt = (const bf16*)d_in[5];
    p.Dskip = (const bf16*)d_in[6]; p.wr = (const bf16*)d_in[8]; p.gatew = (const bf16*)d_in[12];
    p.out = (bf16*)d_out;
    p.sc = (Scratch*)sc; p.band = (const uint4*)band;
    p.gu_swap = swap;
    p.zero = 0;
    fused_kernel<<<NCTA, NTHREADS, SMEM_BYTES>>>(p, tg, td, tx, to);
}
```

```cpp
#include <cuda_runtime.h>
#include <cuda_bf16.h>
#include <cuda_fp16.h>
#include <cuda.h>
#include <stdint.h>

typedef __nv_bfloat16 bf16;

namespace {

constexpr int L_ = 2048, D_ = 1024, F_ = 3584;
constexpr int NCTA = 130;
constexpr int NTHREADS = 512;
#define AUXW 12
constexpr int MAIN_W0 = 0, AUX_W0 = AUXW, PREP_W0 = 20 - AUXW;
#define T0 3400
#define GAP 540
#define GAP1 530
#define GAP2 530
#define GAP3 550
#define STAG GAP
#define CSLEEP 50
#define SLACK 300
#define DELAY_X 70
#define TSLEEP 40
#define BULKM false
#define PW 19
#define PRESLEEP 64
#define PWQ 1
#define PQ 3
#define PROMG 2
#define PROMD 1
#define PROMX 0
#define LATE2 0
#define HW 21
constexpr int NGU_CTA = 112;

constexpr int OFF_RING = 0;
constexpr int OFF_SCR  = 6 * 8192;
constexpr int S_PL     = 1056;
constexpr int S_Q      = 8 * S_PL;
constexpr int OFF_S    = 114688;
constexpr int OFF_GP   = OFF_S + 4 * S_Q;
constexpr int U_PL     = 2240;
constexpr int U_CH     = 4416;
constexpr int OFF_U    = 151552;
constexpr int TAB_W    = 3200;
constexpr int T_PL     = 544;
constexpr int T_A      = 2192 - 26 * 8;
constexpr int T_B      = 2568 - 59 * 8;
constexpr int OFF_TAB  = 186880;
constexpr int OFF_XSEL = 212480;
constexpr int XS_ROW   = 2064;
constexpr int OFF_BAND = 228992;
constexpr int OFF_MISC = 229536;
constexpr int M_BARS   = OFF_MISC;
constexpr int M_DSK    = OFF_MISC + 2736;
constexpr int M_SINK   = OFF_MISC + 512;
constexpr int M_TAG    = OFF_MISC + 516;
constexpr int M_BMAP   = OFF_MISC + 528;
constexpr int M_DPIN   = OFF_MISC + 656;
constexpr int M_TOP    = OFF_MISC + 2704;
constexpr int SMEM_BYTES = OFF_MISC + 2768;
__device__ __forceinline__ uint32_t s_addr(uint32_t o, uint32_t half) { return o + (((half ^ (o >> 7)) & 1) << 4); }
__host__ __device__ constexpr uint32_t y_off(uint32_t q) { return OFF_RING + 32768 + (q & 1) * 8192 + (q >> 1) * 65536; }

constexpr int B_W = 0;
constexpr int B_E = 24;
constexpr int B_S = 36;
constexpr int B_Y = 40;
constexpr int B_DP = 44, B_U = 45, B_KG = 46, B_G = 47;
constexpr int B_F = 48;
constexpr int B_H = 60;
constexpr int B_X = 52, B_XE = 56;

struct BandTab { uint32_t w[11][12]; };
constexpr BandTab make_band() {
    BandTab b{};
    for (int cls = 0; cls < 11; cls++)
        for (int wd = 0; wd < 10; wd++) {
            const int tau = cls + 2 - 8 * ((wd < 4 ? wd : wd - 4) >> 1);
            const int lo = (wd < 4) ? ((wd & 1) ? -2 : 3) : ((wd & 1) ? -4 : -11), wid = (wd < 4 ? 3 : 7) + 2 * (wd & 1);
            b.w[cls][wd] = ((tau >= lo && tau < lo + wid) ? 0x3F80u : 0u) | ((tau - 4 >= lo && tau - 4 < lo + wid) ? 0x3F800000u : 0u);
        }
    return b;
}
constexpr int NTOP = 32;
struct Scratch {
    uint4 r[L_ / 4];
    uint4 g[L_ / 4];
    uint4 h[2][8 * F_ / 8];
    uint32_t top[NTOP][32];
    unsigned epoch;
};
__device__ __align__(128) Scratch g_scratch;
__device__ const __align__(16) BandTab g_band = make_band();

struct Params {
    const bf16 *u, *logA, *Aim, *Cre, *Cim, *logdt, *Dskip, *wr, *gatew;
    bf16* out;
    Scratch* sc;
    const uint4* band;
    uint32_t gu_swap;
    uint32_t zero;
};

#define WSTAMP(i) do {} while (0)
#define KSTAMP(i, dep) do {} while (0)
#define WDUMP() do {} while (0)
#define RSTAMP(i) do {} while (0)

__device__ __forceinline__ uint32_t smem_u32(const void* p) { return (uint32_t)__cvta_generic_to_shared(p); }
__device__ __forceinline__ void mbar_init(uint32_t b, uint32_t c) { asm volatile("mbarrier.init.shared::cta.b64 [%0], %1;" :: "r"(b), "r"(c) : "memory"); }
__device__ __forceinline__ void mbar_expect(uint32_t b, uint32_t tx) { asm volatile("mbarrier.arrive.expect_tx.shared::cta.b64 _, [%0], %1;" :: "r"(b), "r"(tx) : "memory"); }
__device__ __forceinline__ void mbar_arrive(uint32_t b) { asm volatile("mbarrier.arrive.shared::cta.b64 _, [%0];" :: "r"(b) : "memory"); }
__device__ __forceinline__ void mbar_wait(uint32_t b, uint32_t parity = 0) {
    asm volatile("{\n\t.reg .pred p;\nW%=:\n\tmbarrier.try_wait.parity.shared::cta.b64 p, [%0], %1, 20000;\n\t@!p bra W%=;\n\t}" :: "r"(b), "r"(parity) : "memory");
}
__device__ __forceinline__ uint32_t mapa(uint32_t addr, uint32_t rank) { uint32_t r; asm("mapa.shared::cluster.u32 %0, %1, %2;" : "=r"(r) : "r"(addr), "r"(rank)); return r; }
__device__ __forceinline__ void tma3d(uint32_t dst, const CUtensorMap* tm, int c0, int c1, uint32_t bar, uint32_t bytes) {
    asm volatile("{\n\t.reg .pred p;\n\telect.sync _|p, 0xffffffff;\n\t"
                 "@p mbarrier.arrive.expect_tx.shared::cta.b64 _, [%2], %5;\n\t"
                 "@p cp.async.bulk.tensor.3d.shared::cluster.global.mbarrier::complete_tx::bytes [%0], [%1, {%3, %4, 0}], [%2];\n\t}"
        :: "r"(dst), "l"(tm), "r"(bar), "r"(c0), "r"(c1), "r"(bytes) : "memory");
}
__device__ __forceinline__ void bulk_load(uint32_t dst, const void* src, uint32_t bytes, uint32_t bar) {
    asm volatile("{\n\t.reg .pred p;\n\telect.sync _|p, 0xffffffff;\n\t"
                 "@p mbarrier.arrive.expect_tx.shared::cta.b64 _, [%2], %3;\n\t"
                 "@p cp.async.bulk.shared::cluster.global.mbarrier::complete_tx::bytes [%0], [%1], %3, [%2];\n\t}"
        :: "r"(dst), "l"(src), "r"(bar), "r"(bytes) : "memory");
}
__device__ __forceinline__ void st_async16(uint32_t dst, const uint4& v, uint32_t bar) {
    asm volatile("st.async.weak.shared::cluster.mbarrier::complete_tx::bytes.v4.b32 [%0], {%1,%2,%3,%4}, [%5];"
                 :: "r"(dst), "r"(v.x), "r"(v.y), "r"(v.z), "r"(v.w), "r"(bar) : "memory");
}
__device__ __forceinline__ void bar_sync(int id, int n) { asm volatile("bar.sync %0, %1;" :: "r"(id), "r"(n) : "memory"); }
__device__ __forceinline__ void cp16(uint32_t dst, const void* src) { asm volatile("cp.async.cg.shared.global [%0], [%1], 16;" :: "r"(dst), "l"(src) : "memory"); }
__device__ __forceinline__ void cp_wait_all() { asm volatile("cp.async.wait_all;" ::: "memory"); }
__device__ __forceinline__ uint4 ld_gpu128(const void* p) { uint4 v; asm volatile("ld.relaxed.gpu.global.v4.u32 {%0,%1,%2,%3}, [%4];" : "=r"(v.x), "=r"(v.y), "=r"(v.z), "=r"(v.w) : "l"(p) : "memory"); return v; }
__device__ __forceinline__ void st_gpu32(void* p, uint32_t v) { asm volatile("st.relaxed.gpu.global.u32 [%0], %1;" :: "l"(p), "r"(v) : "memory"); }

__device__ __forceinline__ void ldsm4(uint32_t a, uint32_t& r0, uint32_t& r1, uint32_t& r2, uint32_t& r3) {
    asm volatile("ldmatrix.sync.aligned.m8n8.x4.shared.b16 {%0,%1,%2,%3}, [%4];" : "=r"(r0), "=r"(r1), "=r"(r2), "=r"(r3) : "r"(a) : "memory");
}
__device__ __forceinline__ void ldsm4t(uint32_t a, uint32_t& r0, uint32_t& r1, uint32_t& r2, uint32_t& r3) {
    asm volatile("ldmatrix.sync.aligned.m8n8.x4.trans.shared.b16 {%0,%1,%2,%3}, [%4];" : "=r"(r0), "=r"(r1), "=r"(r2), "=r"(r3) : "r"(a) : "memory");
}
__device__ __forceinline__ uint32_t lds32(uint32_t a) { uint32_t v; asm volatile("ld.shared.u32 %0, [%1];" : "=r"(v) : "r"(a) : "memory"); return v; }
__device__ __forceinline__ uint2 lds64(uint32_t a) { uint2 v; asm volatile("ld.shared.v2.u32 {%0,%1}, [%2];" : "=r"(v.x), "=r"(v.y) : "r"(a) : "memory"); return v; }
__device__ __forceinline__ uint4 lds128(uint32_t a) { uint4 v; asm volatile("ld.shared.v4.u32 {%0,%1,%2,%3}, [%4];" : "=r"(v.x), "=r"(v.y), "=r"(v.z), "=r"(v.w) : "r"(a) : "memory"); return v; }
__device__ __forceinline__ void sts32(uint32_t a, uint32_t v) { asm volatile("st.shared.u32 [%0], %1;" :: "r"(a), "r"(v) : "memory"); }
__device__ __forceinline__ void sts16(uint32_t a, uint32_t v) { asm volatile("st.shared.u16 [%0], %1;" :: "r"(a), "h"((unsigned short)v) : "memory"); }
__device__ __forceinline__ void sts128(uint32_t a, uint32_t x, uint32_t y, uint32_t z, uint32_t w) { asm volatile("st.shared.v4.u32 [%0], {%1,%2,%3,%4};" :: "r"(a), "r"(x), "r"(y), "r"(z), "r"(w) : "memory"); }
__device__ __forceinline__ float ldsf(uint32_t a) { float v; asm volatile("ld.shared.f32 %0, [%1];" : "=f"(v) : "r"(a) : "memory"); return v; }

__device__ __forceinline__ void mma_bf(float (&d)[4], uint32_t a0, uint32_t a1, uint32_t a2, uint32_t a3, uint32_t b0, uint32_t b1) {
    asm volatile("mma.sync.aligned.m16n8k16.row.col.f32.bf16.bf16.f32 {%0,%1,%2,%3}, {%4,%5,%6,%7}, {%8,%9}, {%0,%1,%2,%3};"
        : "+f"(d[0]), "+f"(d[1]), "+f"(d[2]), "+f"(d[3]) : "r"(a0), "r"(a1), "r"(a2), "r"(a3), "r"(b0), "r"(b1));
}
__device__ __forceinline__ void mma_bf_z(float (&d)[4], uint32_t a0, uint32_t a1, uint32_t a2, uint32_t a3, uint32_t b0, uint32_t b1) {
    asm volatile("mma.sync.aligned.m16n8k16.row.col.f32.bf16.bf16.f32 {%0,%1,%2,%3}, {%4,%5,%6,%7}, {%8,%9}, {%10,%10,%10,%10};"
        : "=f"(d[0]), "=f"(d[1]), "=f"(d[2]), "=f"(d[3]) : "r"(a0), "r"(a1), "r"(a2), "r"(a3), "r"(b0), "r"(b1), "f"(0.f));
}
__device__ __forceinline__ void mma_bf_k8(float (&d)[4], uint32_t a0, uint32_t a1, uint32_t b0) {
    asm volatile("mma.sync.aligned.m16n8k8.row.col.f32.bf16.bf16.f32 {%0,%1,%2,%3}, {%4,%5}, {%6}, {%0,%1,%2,%3};"
        : "+f"(d[0]), "+f"(d[1]), "+f"(d[2]), "+f"(d[3]) : "r"(a0), "r"(a1), "r"(b0));
}
__device__ __forceinline__ void mma_h(float (&d)[4], uint32_t a0, uint32_t a1, uint32_t a2, uint32_t a3, uint32_t b0, uint32_t b1) {
    asm volatile("mma.sync.aligned.m16n8k16.row.col.f32.f16.f16.f32 {%0,%1,%2,%3}, {%4,%5,%6,%7}, {%8,%9}, {%0,%1,%2,%3};"
        : "+f"(d[0]), "+f"(d[1]), "+f"(d[2]), "+f"(d[3]) : "r"(a0), "r"(a1), "r"(a2), "r"(a3), "r"(b0), "r"(b1));
}
__device__ __forceinline__ uint32_t pack_bf(float lo, float hi) { uint32_t r; asm("cvt.rn.bf16x2.f32 %0, %1, %2;" : "=r"(r) : "f"(hi), "f"(lo)); return r; }
__device__ __forceinline__ uint32_t pack_h(float lo, float hi) { uint32_t r; asm("cvt.rn.f16x2.f32 %0, %1, %2;" : "=r"(r) : "f"(hi), "f"(lo)); return r; }
__device__ __forceinline__ float bf_lo(uint32_t v) { return __uint_as_float(v << 16); }
__device__ __forceinline__ float bf_hi(uint32_t v) { return __uint_as_float(v & 0xffff0000u); }
__device__ __forceinline__ float bf_round(float x) { return __uint_as_float(pack_bf(0.f, x)); }
__device__ __forceinline__ uint32_t hmul2_bf(uint32_t a, uint32_t b) { uint32_t r; asm("mul.rn.bf16x2 %0, %1, %2;" : "=r"(r) : "r"(a), "r"(b)); return r; }
__device__ __forceinline__ float ex2f(float x) { float r; asm("ex2.approx.ftz.f32 %0, %1;" : "=f"(r) : "f"(x)); return r; }

__device__ __forceinline__ float exp_acc(float x) {
    const float t = x * 1.4426950216293335f;
    const float r = fmaf(x, 1.4426950216293335f, -t) + x * 1.9259629911266175e-8f;
    return ex2f(t) * fmaf(r, 0.6931471805599453f, 1.f);
}
__device__ __forceinline__ float sigmoid_f(float x) { return __fdividef(1.f, 1.f + ex2f(-x * 1.4426950408889634f)); }
__device__ __forceinline__ void cexp_pow(float l2, float li, float e, float& zr, float& zi) {
    const float mag = ex2f(l2 * e);
    zr = mag * __cosf(li * e);
    zi = mag * __sinf(li * e);
}
__device__ __forceinline__ uint32_t hcmul(uint32_t a, uint32_t k, uint32_t kp) {
    const __half2 A = *reinterpret_cast<const __half2*>(&a);
    const __half2 r = __hfma2(__high2half2(A), *reinterpret_cast<const __half2*>(&kp), __hmul2(__low2half2(A), *reinterpret_cast<const __half2*>(&k)));
    return *reinterpret_cast<const uint32_t*>(&r);
}
#define CMUL(orr, oi, ar, ai, br, bi) do { float _r = (ar) * (br) - (ai) * (bi); float _i = (ar) * (bi) + (ai) * (br); orr = _r; oi = _i; } while (0)
#define CSQ(orr, oi, ar, ai) do { float _r = (ar) * (ar) - (ai) * (ai); float _i = 2.f * (ar) * (ai); orr = _r; oi = _i; } while (0)

__device__ __forceinline__ void mma_bf_k8z(float (&d)[4], uint32_t a0, uint32_t a1, uint32_t b0) {
    asm volatile("mma.sync.aligned.m16n8k8.row.col.f32.bf16.bf16.f32 {%0,%1,%2,%3}, {%4,%5}, {%6}, {%7,%7,%7,%7};"
        : "=f"(d[0]), "=f"(d[1]), "=f"(d[2]), "=f"(d[3]) : "r"(a0), "r"(a1), "r"(b0), "f"(0.f));
}
__device__ __forceinline__ void mma_hh_k8(uint32_t& d0, uint32_t& d1, uint32_t a0, uint32_t a1, uint32_t b0) {
    asm volatile("mma.sync.aligned.m16n8k8.row.col.f16.f16.f16.f16 {%0,%1}, {%2,%3}, {%4}, {%5,%5};"
        : "=r"(d0), "=r"(d1) : "r"(a0), "r"(a1), "r"(b0), "r"(0));
}
__device__ __forceinline__ uint32_t pin(uint32_t x, int lane) { return __shfl_sync(0xffffffffu, x, lane); }
template <class T> __device__ __forceinline__ T* pin(T* x, int lane) { return (T*)__shfl_sync(0xffffffffu, (unsigned long long)x, lane); }
__device__ __forceinline__ void sts32_if(bool on, uint32_t a, uint32_t v) {
    asm volatile("{\n\t.reg .pred p;\n\tsetp.ne.u32 p, %2, 0;\n\t@p st.shared.u32 [%0], %1;\n\t}" :: "r"(a), "r"(v), "r"((uint32_t)on) : "memory");
}
__device__ __forceinline__ void sts128_if(bool on, uint32_t a, uint32_t x, uint32_t y, uint32_t z, uint32_t w) {
    asm volatile("{\n\t.reg .pred p;\n\tsetp.ne.u32 p, %5, 0;\n\t@p st.shared.v4.u32 [%0], {%1,%2,%3,%4};\n\t}" :: "r"(a), "r"(x), "r"(y), "r"(z), "r"(w), "r"((uint32_t)on) : "memory");
}
__device__ __forceinline__ void lds128_if(bool on, uint32_t a, uint32_t (&v)[4]) {
    asm volatile("{\n\t.reg .pred p;\n\tsetp.ne.u32 p, %5, 0;\n\t@p ld.shared.v4.u32 {%0,%1,%2,%3}, [%4];\n\t}"
        : "+r"(v[0]), "+r"(v[1]), "+r"(v[2]), "+r"(v[3]) : "r"(a), "r"((uint32_t)on) : "memory");
}
__device__ __forceinline__ uint32_t hfma2_bf(uint32_t a, uint32_t b, uint32_t c) { uint32_t r; asm("fma.rn.bf16x2 %0, %1, %2, %3;" : "=r"(r) : "r"(a), "r"(b), "r"(c)); return r; }
__device__ __forceinline__ uint32_t row_elem(uint32_t row) { return ((row >> 5) & 4) | ((row >> 2) & 2) | ((row >> 4) & 1); }
__device__ __forceinline__ uint32_t gate_pos(uint32_t row) { return ((row >> 9) << 8) | ((row & 7) << 5) | (row_elem(row) << 2) | ((row >> 5) & 3); }

template <int N, bool BULK>
__device__ __forceinline__ void mix_rows(const Params& p, const CUtensorMap* tm_out, uint32_t sb, uint32_t ob, int Q0, int Q1, int w, int h, int pr, int lane) {
    const int g = lane >> 2, t = lane & 3, mi = lane >> 3, r = lane & 7;
    const int m8 = 16 * (g >> 2) + ((g >> 1) & 1) + 2 * (g & 1);
    uint32_t yi = sb + (4 * (r >> 1) + 2 * (mi & 1) + (r & 1)) * 512 + (((4 * w + (mi >> 1)) ^ r) << 4);
    uint32_t xs = sb + OFF_S + s_addr(w * S_PL + 32 + m8 * 32, t >> 1) + ((t & 1) << 3);
    uint32_t gs = sb + OFF_GP + w * 64 + g * 8, os = ob + m8 * 32 + t * 8;
    if (N > 1) { yi = pin(yi, lane); xs = pin(xs, lane); gs = pin(gs, lane); os = pin(os, lane); }
    mbar_wait(sb + M_BARS + 8 * B_Y);
#pragma unroll 1
    for (int Q = Q0; Q < Q1; Q++) {
        uint2 xq[N][4];
        uint32_t gg[N][4], sw[N];
#pragma unroll
        for (int n = 0; n < N; n++) {
#pragma unroll
            for (int i = 0; i < 4; i++) xq[n][i] = lds64((xs ^ (((i ^ n) & 1) << 4)) + Q * S_Q + n * 4 * S_PL + i * 128);
            const uint2 gq = lds64(gs + Q * 512 + n * 256);
            sw[n] = lds32(sb + M_BMAP + w * 16 + n * 64 + Q * 4);
#pragma unroll
            for (int i = 0; i < 4; i++) {
                gg[n][i] = __byte_perm(i < 2 ? gq.x : gq.y, 0, (i & 1) ? 0x3232 : 0x1010);
                const uint32_t og = hfma2_bf(gg[n][i], 0xBF80BF80u, 0x3F803F80u);
                xq[n][i].x = hmul2_bf(og, xq[n][i].x); xq[n][i].y = hmul2_bf(og, xq[n][i].y);
            }
        }
        if (N > 1 && Q == PWQ) mbar_wait(sb + M_BARS + 8 * (B_W + PW));
        mbar_wait(sb + M_BARS + 8 * (B_Y + Q));
        __syncwarp();
#pragma unroll
        for (int n = 0; n < N; n++) {
#pragma unroll
            for (int x = 0; x < 2; x++) {
                uint32_t y[4];
                ldsm4t((yi ^ (x << 5)) + y_off(Q) + n * 256, y[0], y[1], y[2], y[3]);
#pragma unroll
                for (int e = 0; e < 2; e++) {
                    uint2& o = xq[n][2 * x + e];
                    o.x = hfma2_bf(gg[n][2 * x + e], y[2 * e], o.x); o.y = hfma2_bf(gg[n][2 * x + e], y[2 * e + 1], o.y);
                }
            }
        }
        if (BULK && (sw[0] | sw[N - 1]) == 0) {
#pragma unroll
            for (int n = 0; n < N; n++)
#pragma unroll
                for (int i = 0; i < 4; i++)
                    asm volatile("st.shared.v2.u32 [%0], {%1, %2};" :: "r"(os + Q * 1024 + n * 4 * TAB_W + i * 128), "r"(xq[n][i].x), "r"(xq[n][i].y) : "memory");
            asm volatile("fence.proxy.async.shared::cta;" ::: "memory");
            __syncwarp();
#pragma unroll
            for (int n = 0; n < N; n++)
                asm volatile("{\n\t.reg .pred p;\n\telect.sync _|p, 0xffffffff;\n\t"
                             "@p cp.async.bulk.tensor.3d.global.shared::cta.bulk_group [%1, {%2, %3, %4}], [%0];\n\t}"
                    :: "r"(ob + 4 * n * TAB_W + Q * 1024), "l"(tm_out), "r"(16 * pr), "r"(64 * Q + 32 * h), "r"(w + 4 * n) : "memory");
        } else {
            bf16* op = p.out + (size_t)(512 * Q + 256 * h + 8 * m8 + w) * D_ + 16 * pr + 4 * t;
#pragma unroll
            for (int n = 0; n < N; n++)
#pragma unroll
                for (int i = 0; i < 4; i++)
                    if (!((sw[n] >> (4 * g)) & (1u << i))) *(uint2*)(op + (size_t)(32 * i + 4 * n) * D_) = xq[n][i];
        }
    }
}

__global__ void __cluster_dims__(2, 1, 1) __launch_bounds__(NTHREADS, 1)
fused_kernel(const Params p, const __grid_constant__ CUtensorMap tm_gu, const __grid_constant__ CUtensorMap tm_down,
             const __grid_constant__ CUtensorMap tm_x, const __grid_constant__ CUtensorMap tm_out) {
    extern __shared__ __align__(1024) unsigned char smem[];
    const uint32_t sb = smem_u32(smem);
    int tid;
    asm volatile("mov.u32 %0, %%tid.x;" : "=r"(tid));
    const int pw = tid >> 5, lane = tid & 31;
    const int c = blockIdx.x, h = c & 1, pr = c >> 1;
    const uint32_t bars = sb + M_BARS;

    uint2 v_la, v_ai, v_cr, v_ci;
    uint32_t ldt16;
    {
        const uint32_t po = c * 256 + tid;
        asm volatile("{\n\t.reg .pred p;\n\t.reg .b64 a;\n\tsetp.ne.u32 p, %16, 0;\n\t"
                     "mad.wide.u32 a, %14, 8, %9;\n\t@p ld.global.nc.L1::no_allocate.v2.u32 {%0,%1}, [a];\n\t"
                     "mad.wide.u32 a, %15, 2, %13;\n\t@p ld.global.nc.u16 %8, [a];\n\t"
                     "mad.wide.u32 a, %14, 8, %10;\n\t@p ld.global.nc.L1::no_allocate.v2.u32 {%2,%3}, [a];\n\t"
                     "mad.wide.u32 a, %14, 8, %11;\n\t@p ld.global.nc.L1::no_allocate.v2.u32 {%4,%5}, [a];\n\t"
                     "mad.wide.u32 a, %14, 8, %12;\n\t@p ld.global.nc.L1::no_allocate.v2.u32 {%6,%7}, [a];\n\t}"
            : "=r"(v_la.x), "=r"(v_la.y), "=r"(v_ai.x), "=r"(v_ai.y), "=r"(v_cr.x), "=r"(v_cr.y), "=r"(v_ci.x), "=r"(v_ci.y), "=r"(ldt16)
            : "l"(p.logA), "l"(p.Aim), "l"(p.Cre), "l"(p.Cim), "l"(p.logdt), "r"(po), "r"(po >> 5), "r"((uint32_t)(tid < 256 && c < 128)));
    }

    if (c >= 128) {
        if (c != 128) return;
        RSTAMP(5);
        const unsigned tag = (*(volatile unsigned*)&p.sc->epoch + 1) & 0xffffu;
        const uint32_t list = sb + 128;
#pragma unroll 1
        for (int pass = 0; pass < 2; pass++) {
            sts128(list + 16 * tid, 0, 0, 0, 0);
            if (tid == 0) sts32(sb + 64, 0);
            uint32_t key[4] = {tag - 1, tag - 1, tag - 1, tag - 1};
#pragma unroll 1
            for (int it = 0; it < (pass << 22); it++) {
                uint32_t a[4];
                asm volatile("{\n\t.reg .b128 o, z;\n\t.reg .b64 l, u;\n\tmov.b64 l, {%5, %5};\n\tmov.b128 z, {l, l};\n\tatom.relaxed.gpu.global.exch.b128 o, [%4], z;\n\t"
                             "mov.b128 {l, u}, o;\n\tmov.b64 {%0, %1}, l;\n\tmov.b64 {%2, %3}, u;\n\t}"
                    : "=r"(a[0]), "=r"(a[1]), "=r"(a[2]), "=r"(a[3]) : "l"(&p.sc->r[tid]), "r"(tag - 1) : "memory");
#pragma unroll
                for (int i = 0; i < 4; i++) if (((a[i] ^ tag) & 0xffffu) == 0) key[i] = a[i];
                if ((((key[0] ^ tag) | (key[1] ^ tag) | (key[2] ^ tag) | (key[3] ^ tag)) & 0xffffu) == 0) break;
            }
            WSTAMP(0);
            uint32_t m = 0;
#pragma unroll
            for (int i = 0; i < 4; i++) {
                key[i] = ((pass ? key[i] : (lane + i) << 16) & 0xffff0000u) | (uint32_t)(2047 - (4 * tid + i));
                m = max(m, key[i]);
            }
            const uint32_t wm = __reduce_max_sync(0xffffffffu, m);
            if (lane == 0) sts32(sb + pw * 4, wm);
            __syncthreads();
            uint32_t thr = 0xffffffffu;
#pragma unroll
            for (int i = 0; i < 4; i++) { const uint4 q = lds128(sb + 16 * i); thr = min(thr, min(max(q.x, q.y), max(q.z, q.w))); }
            if (thr != 1) WSTAMP(1);
            if (m >= thr) {
                uint32_t pos;
                asm volatile("atom.shared.add.u32 %0, [%1], %2;" : "=r"(pos) : "r"(sb + 64), "r"(4 * ((key[0] >= thr) + (key[1] >= thr) + (key[2] >= thr) + (key[3] >= thr))) : "memory");
#pragma unroll
                for (int i = 0; i < 4; i++) if (key[i] >= thr) { sts32(list + pos, key[i]); pos += 4; }
            }
            __syncthreads();
            const uint32_t nc4 = lds32(sb + 64);
            if (nc4 != 1) WSTAMP(2);
#pragma unroll 1
            for (uint32_t j = 4 * pw; j < nc4; j += 64) {
                const uint32_t mine = lds32(list + j);
                int rank = 0;
#pragma unroll 1
                for (uint32_t i = 0; i < nc4; i += 128) rank += __popc(__ballot_sync(0xffffffffu, lds32(list + i + 4 * lane) > mine));
                if (rank < 8 && lane == 0) sts32(sb + 96 + 4 * rank, mine);
            }
            __syncthreads();
            if (tid < 8 * NTOP) st_gpu32(&p.sc->top[tid >> 3][tid & 7], lds32(sb + 96 + 4 * (tid & 7)) | (((tag + pass - 1) & 31) << 11));
            WSTAMP(3);
            if (!pass) RSTAMP(4);
        }
        WDUMP();
        return;
    }

    WSTAMP(0);
    if (pw < 8) {
        const int d = 8 * c + pw - MAIN_W0;
        if (lane == 0) asm volatile("cp.async.ca.shared.global [%0], [%1], 4;" :: "r"(sb + M_DSK + 4 * (pw - MAIN_W0)), "l"(p.Dskip + (d & ~1)) : "memory");
        asm volatile("barrier.cluster.arrive.relaxed.aligned;" ::: "memory");
        const int warp = pw - MAIN_W0;
        asm volatile("setmaxnreg.inc.sync.aligned.u32 160;");
        const int g = lane >> 2, t = lane & 3;
        const int mi = lane >> 3, r = lane & 7;
        const uint32_t TB = sb + OFF_TAB + warp * TAB_W;
        const uint32_t UB = sb + OFF_U + warp * U_CH;
        if (mi < 2) sts128(UB + mi * U_PL + r * 16, 0, 0, 0, 0);
        if (lane < 4) sts128(TB + lane * T_PL, 0, 0, 0, 0);
        sts128(sb + OFF_SCR + warp * 8192 + lane * 16, 0x3C00u, 0x3C00u, 0x3C00u, 0x3C00u);
        __syncwarp();

        uint32_t cfix;
        {
            KSTAMP(4, v_la.x ^ v_ai.x ^ v_cr.x ^ v_ci.x ^ ldt16);
            const float dt = bf_round(exp_acc(__uint_as_float(ldt16 << 16)));
            float l2[4], li[4];
            {
                const uint32_t la[2] = {v_la.x, v_la.y}, ai[2] = {v_ai.x, v_ai.y};
                const float dt2 = -1.4426950408889634f * dt;
#pragma unroll
                for (int i = 0; i < 4; i++) {
                    l2[i] = bf_round(ex2f(((i & 1) ? bf_hi(la[i >> 1]) : bf_lo(la[i >> 1])) * 1.4426950408889634f)) * dt2;
                    li[i] = ((i & 1) ? bf_hi(ai[i >> 1]) : bf_lo(ai[i >> 1])) * dt;
                }
            }
            const uint32_t SX = sb + OFF_SCR + warp * 8192;
            const uint32_t sw = SX + (lane << 4);
#define PUT(buf, row, v) sts128(((sw + (row) * 512) ^ ((row) << 4)) + (buf) * 4096, v[0], v[1], v[2], v[3])
#define EMIT(bufa, rowa, bufb, rowb, xr, xi, k, kp) do { uint32_t pk[4], pd[4]; \
                _Pragma("unroll") for (int i = 0; i < 4; i++) { pk[i] = pack_h(xr[i], xi[i]); pd[i] = hcmul(pk[i], k[i], kp[i]); } \
                PUT(bufa, rowa, pk); PUT(bufb, rowb, pd); } while (0)
#define CMUL4(orr, oi, ar, ai, br, bi) _Pragma("unroll") for (int i = 0; i < 4; i++) CMUL(orr[i], oi[i], ar[i], ai[i], br[i], bi[i])
#define CSQ4(orr, oi, ar, ai) _Pragma("unroll") for (int i = 0; i < 4; i++) CSQ(orr[i], oi[i], ar[i], ai[i])
            float z1r[4], z1i[4], z2r[4], z2i[4], z8r[4], z8i[4], z256r[4], z256i[4];
            uint32_t k4[4], k4p[4];
            float z4r[4], z4i[4];
#pragma unroll
            for (int i = 0; i < 4; i++) cexp_pow(l2[i], li[i], 1.f, z1r[i], z1i[i]);
            CSQ4(z2r, z2i, z1r, z1i);
            CSQ4(z4r, z4i, z2r, z2i);
            CSQ4(z8r, z8i, z4r, z4i);
            KSTAMP(5, __float_as_uint(z8r[3]));
            uint32_t Ya[16][4];
            float cr[4], ci[4], inv;
            {
                float w1r[4], w1i[4], ar[4], ai[4], br[4], bi[4];
                uint32_t k8[4], k8p[4];
#pragma unroll
                for (int i = 0; i < 4; i++) {
                    k8[i] = pack_h(z8r[i], -z8i[i]); k8p[i] = pack_h(z8i[i], z8r[i]);
                    CSQ(w1r[i], w1i[i], z8r[i], z8i[i]); w1i[i] = -w1i[i];
                }
                PUT(1, 0, k8);
                EMIT(0, 1, 1, 1, w1r, w1i, k8, k8p);
                CSQ4(ar, ai, w1r, w1i);            EMIT(0, 2, 1, 2, ar, ai, k8, k8p);
                CMUL4(br, bi, ar, ai, w1r, w1i);   EMIT(0, 3, 1, 3, br, bi, k8, k8p);
                CSQ4(ar, ai, ar, ai);              EMIT(0, 4, 1, 4, ar, ai, k8, k8p);
                CMUL4(ar, ai, ar, ai, w1r, w1i);   EMIT(0, 5, 1, 5, ar, ai, k8, k8p);
                CSQ4(br, bi, br, bi);              EMIT(0, 6, 1, 6, br, bi, k8, k8p);
                CMUL4(br, bi, br, bi, w1r, w1i);   EMIT(0, 7, 1, 7, br, bi, k8, k8p);
                __syncwarp();
                KSTAMP(6, 0);
                const uint32_t ab = SX + (mi & 1) * 4096 + r * 512, ax = ((mi >> 1) ^ r) << 4;
                const uint32_t vr[2] = {v_cr.x, v_cr.y}, vi[2] = {v_ci.x, v_ci.y};
                const uint32_t m2 = __vmaxu2(__vmaxu2(vr[0] & 0x7fff7fffu, vr[1] & 0x7fff7fffu), __vmaxu2(vi[0] & 0x7fff7fffu, vi[1] & 0x7fff7fffu));
                const uint32_t mx = __reduce_max_sync(0xffffffffu, max(m2, m2 << 16));
                const uint32_t e = min(max(mx >> 23, 11u), 254u);
                const float sc = __uint_as_float((264u - e) << 23);
                inv = __uint_as_float((e - 10u) << 23) * (2.f * dt);
#pragma unroll
                for (int i = 0; i < 4; i++) {
#pragma unroll
                    for (int k = 0; k < 4; k++) ldsm4(ab + (ax ^ (i << 5)) + k * 128, Ya[4 * k + i][0], Ya[4 * k + i][1], Ya[4 * k + i][2], Ya[4 * k + i][3]);
                    float tr, ti;
                    cexp_pow(l2[i], li[i], 128.f, tr, ti);
                    sts32(TB + 2176 + 256 * i + 4 * lane, pack_h(tr, ti));
                    sts32(TB + 2176 + 256 * i + 128 + 4 * (lane ^ 16), pack_h(-ti, tr));
                    k4[i] = pack_h(z4r[i], z4i[i]); k4p[i] = pack_h(-z4i[i], z4r[i]);
                    CSQ(z256r[i], z256i[i], tr, ti);
                    cr[i] = ((i & 1) ? bf_hi(vr[i >> 1]) : bf_lo(vr[i >> 1])) * sc;
                    ci[i] = ((i & 1) ? bf_hi(vi[i >> 1]) : bf_lo(vi[i >> 1])) * sc;
                }
                __syncwarp();
            }
            KSTAMP(7, Ya[15][0]);
            const uint32_t ld0 = SX + r * 512 + ((mi ^ r) << 4), ld1 = ld0 ^ 64;
            float R[6][4], s1024;
            {
                float xr[4], xi[4], yr[4], yi[4];
                EMIT(0, 0, 0, 1, cr, ci, k4, k4p);
                CMUL4(yr, yi, cr, ci, z1r, z1i);        EMIT(0, 2, 0, 3, yr, yi, k4, k4p);
                CMUL4(xr, xi, cr, ci, z256r, z256i);    EMIT(1, 0, 1, 1, xr, xi, k4, k4p);
                CMUL4(yr, yi, yr, yi, z1r, z1i);        EMIT(0, 4, 0, 5, yr, yi, k4, k4p);
                CMUL4(cr, ci, xr, xi, z2r, z2i);        EMIT(1, 2, 1, 3, cr, ci, k4, k4p);
                CMUL4(yr, yi, yr, yi, z1r, z1i);        EMIT(0, 6, 0, 7, yr, yi, k4, k4p);
                CMUL4(xr, xi, xr, xi, z256r, z256i);    EMIT(1, 4, 1, 5, xr, xi, k4, k4p);
                CMUL4(xr, xi, xr, xi, z256r, z256i);    EMIT(1, 6, 1, 7, xr, xi, k4, k4p);
                CMUL4(xr, xi, xr, xi, z256r, z256i);
                s1024 = (xr[0] + xr[1]) + (xr[2] + xr[3]);
#pragma unroll
                for (int m = 0; m < 4; m++) {
                    if (m == 0) { CMUL4(xr, xi, xr, xi, z8r, z8i); } else { CMUL4(xr, xi, xr, xi, z256r, z256i); }
                    sts128(TB + m * T_PL + 16 + 16 * lane, pack_h(xr[0], xi[0]), pack_h(xr[1], xi[1]), pack_h(xr[2], xi[2]), pack_h(xr[3], xi[3]));
                }
            }
            asm volatile("barrier.cluster.wait.acquire.aligned;" ::: "memory");
            __syncwarp();
            {
                KSTAMP(8, 0);
                uint32_t bd[2][4] = {{0, 0, 0, 0}, {0, 0, 0, 0}};
                const bool on = (g >> 1) == t;
#pragma unroll
                for (int i = 0; i < 6; i++) { R[i][0] = R[i][1] = R[i][2] = R[i][3] = 0.f; }
#pragma unroll
                for (int k2 = 0; k2 < 8; k2++) {
                    uint32_t x[4], y[4], z[4], a1[2][4];
                    lds128_if(on, TB + 2176 + g * 128 + (k2 < 4 ? 64 : -64) * (g & 1) + 16 * k2, bd[k2 & 1]);
                    ldsm4(TB + (r & 3) * T_PL + 16 + 16 * mi + 64 * k2, z[0], z[1], z[2], z[3]);
                    ldsm4(((k2 & 1) ? ld1 : ld0) + (k2 >> 1) * 128, x[0], x[1], x[2], x[3]);
                    ldsm4(((k2 & 1) ? ld1 : ld0) + (k2 >> 1) * 128 + 4096, y[0], y[1], y[2], y[3]);
#pragma unroll
                    for (int u = 0; u < 2; u++) {
                        mma_hh_k8(a1[u][0], a1[u][1], Ya[2 * k2 + u][0], Ya[2 * k2 + u][1], bd[k2 & 1][2 * u]);
                        mma_hh_k8(a1[u][2], a1[u][3], Ya[2 * k2 + u][2], Ya[2 * k2 + u][3], bd[k2 & 1][2 * u + 1]);
                    }
#pragma unroll
                    for (int u = 0; u < 2; u++) {
                        const uint32_t(&a0)[4] = Ya[2 * k2 + u];
                        mma_h(R[0], a0[0], a0[1], a0[2], a0[3], x[2 * u], x[2 * u + 1]);
                        mma_h(R[2], a0[0], a0[1], a0[2], a0[3], y[2 * u], y[2 * u + 1]);
                        mma_h(R[4], a0[0], a0[1], a0[2], a0[3], z[2 * u], z[2 * u + 1]);
                        mma_h(R[1], a1[u][0], a1[u][1], a1[u][2], a1[u][3], x[2 * u], x[2 * u + 1]);
                        mma_h(R[3], a1[u][0], a1[u][1], a1[u][2], a1[u][3], y[2 * u], y[2 * u + 1]);
                        mma_h(R[5], a1[u][0], a1[u][1], a1[u][2], a1[u][3], z[2 * u], z[2 * u + 1]);
                    }
                }
            }
            __syncwarp();
            KSTAMP(9, __float_as_uint(R[3][0]));
            if (lane == 0) mbar_arrive(bars + 8 * B_KG + (__float_as_uint(R[0][0]) & __float_as_uint(R[2][0]) & p.zero));
            sts128(TB + 2176 + 16 * lane, 0, 0, 0, 0);
            sts128(TB + 2688 + 16 * lane, 0, 0, 0, 0);
            __syncwarp();
#undef PUT
#undef EMIT
#pragma unroll
            for (int o = 16; o > 0; o >>= 1) s1024 += __shfl_xor_sync(0xffffffffu, s1024, o);
            uint32_t w[4][4], dsk = 0;
            cp_wait_all();
            asm volatile("{\n\t.reg .pred p;\n\tsetp.eq.u32 p, %2, 0;\n\t@p ld.shared.u16 %0, [%1];\n\t}" : "+r"(dsk) : "r"(sb + M_DSK + 4 * warp + 2 * (warp & 1)), "r"(lane) : "memory");
#pragma unroll
            for (int a = 0; a < 4; a++) {
                const float v0 = (a == 0) ? fmaf(R[0][0], inv, __uint_as_float(dsk << 16)) : R[a][0] * inv;
                const float v1 = R[a][1] * inv, v2 = R[a][2] * inv, v3 = R[a][3] * inv;
                w[a][0] = pack_bf(v0, 0.f); w[a][1] = pack_bf(v1, v0); w[a][2] = pack_bf(v2, v1); w[a][3] = pack_bf(v3, v2);
            }
            const uint32_t wb = TB + 16 + 16 * g, w1 = wb + t * T_PL, w2 = wb + 256 + 2 * t * T_PL;
            const uint32_t w3 = (t == 0) ? wb + 256 + 3 * T_PL : TB + T_A + 8 * (16 * t + g);
            const uint32_t w3s = (t == 0) ? 128 : 64, w3o = (t == 0) ? 8 : 12;
            const uint32_t k512 = __shfl_sync(0xffffffffu, w[2][1], 2);
#pragma unroll
            for (int a = 0; a < 2; a++) {
                sts128(w1 + 128 * a, w[a][0], w[a][1], w[a][2], w[a][3]);
                const uint32_t(&q)[4] = w[2 + a];
                if (t < 2) sts128(w2 + 128 * a, q[0], q[1], q[2], q[3]);
                if (t == 0) { sts128(w2 + T_PL + 128 * a, q[0], q[1], q[2], q[3]); sts32(w3 + 128 * a + 4, q[2]); }
                sts32_if(t != 1 && (a == 1 || lane != 2), w3 + w3s * a, q[1]);
                sts32_if(t != 1, w3 + w3s * a + w3o, q[3]);
            }
            sts128_if(lane < 4, w1 + 512, t == 3 ? k512 : k512 >> 16, t < 2 ? k512 : t == 2 ? k512 & 0xffff0000u : k512 << 16, t < 2 ? k512 << 16 : 0u, 0);
            __syncwarp();
#pragma unroll
            for (int a = 0; a < 2; a++) {
                sts16(w1 + 128 * a + 18, w[a][3]);
                const uint32_t(&q)[4] = w[2 + a];
                if (t < 2) sts16(w2 + 128 * a + 18, q[3]);
                if (t == 0) { sts16(w2 + T_PL + 128 * a + 18, q[3]); sts16(w3 + 128 * a + 14, q[3]); }
            }
            if (t == 0) sts16(w3 + 128 - 4, w[3][0]);
            if (lane == 2 || (t == 0 && g > 0)) sts16(lane == 2 ? TB + 16 + 3 * T_PL + 4 * 127 : w3 - 4, w[2][0]);
            {
                float q[4];
#pragma unroll
                for (int i = 0; i < 4; i++) q[i] = (t < 2 ? R[4][i] : R[5][i]) * inv;
                const uint32_t b0 = pack_bf(q[0], q[2]), b1 = pack_bf(q[1], q[3]);
                const uint32_t wq = TB + T_B + 8 * (65 + 32 * (t & 1) + 4 * (t & 2) + g);
                sts32(wq, b0); sts32(wq + 12, b0); sts32(wq + 128, b1); sts32(wq + 140, b1);
            }
            cfix = pack_bf(s1024 * inv, s1024 * inv);
            if (lane == 0) sts32(TB + T_A + 8 * 64, cfix);
            __syncwarp();
        }
        WSTAMP(1);

        mbar_wait(bars + 8 * B_U);
        WSTAMP(2);

        float D[16][4];
        {
            const int x5 = g - t + 5;
            const uint32_t tabD = TB + (x5 & 3) * T_PL + (x5 & 12) + 16;
            {
                const uint32_t a1 = lds32(tabD - 8), a0 = p.zero;
#pragma unroll
                for (int jq = 0; jq < 4; jq++) {
                    uint32_t b[4];
                    ldsm4(UB + (9 + lane) * 16 + jq * 512, b[0], b[1], b[2], b[3]);
#pragma unroll
                    for (int i = 0; i < 4; i++) mma_bf_k8z(D[4 * jq + i], a0, a1, b[i]);
                }
            }
            const uint32_t ua = UB + (mi & 1) * U_PL + (8 + 8 * (mi >> 1) + r) * 16;
#pragma unroll 1
            for (int k0 = 0; k0 < 8; k0++) {
                uint32_t Uf[16][2];
#pragma unroll
                for (int jp = 0; jp < 8; jp++) ldsm4(ua + jp * 256 - k0 * 16, Uf[2 * jp][0], Uf[2 * jp][1], Uf[2 * jp + 1][0], Uf[2 * jp + 1][1]);
#pragma unroll
                for (int k1 = 0; k1 < 4; k1++) {
                    const uint32_t ta = tabD + 16 * (8 * k1 + k0);
                    const uint32_t a0 = lds32(ta), a1 = lds32(ta + 8), a2 = lds32(ta - 8), a3 = a0 ^ p.zero;
#pragma unroll
                    for (int J = k1; J < 16; J++) mma_bf(D[J], a0, a1, a2, a3, Uf[J - k1][0], Uf[J - k1][1]);
                }
                if (k0 == 0) {
                    const uint32_t ta = tabD + 16 * 32;
                    const uint32_t a0 = lds32(ta), a1 = lds32(ta + 8), a2 = lds32(ta - 8), a3 = a0 ^ p.zero;
#pragma unroll
                    for (int J = 4; J < 16; J++) mma_bf(D[J], a0, a1, a2, a3, Uf[J - 4][0], Uf[J - 4][1]);
                    const uint32_t f0 = (cfix ^ 0x80008000u) & (g == t ? 0xffffu : g == t + 4 ? 0xffff0000u : 0u);
                    const uint32_t f1 = p.zero, f2 = p.zero + p.zero, f3 = f0 ^ p.zero;
#pragma unroll
                    for (int J = 8; J < 16; J++) mma_bf(D[J], f0, f1, f2, f3, Uf[J - 8][0], Uf[J - 8][1]);
                }
            }
        }
        WSTAMP(3);
        {
            const int ch = 8 * h + warp;
            const uint32_t yo = sb + ch * 512 + ((lane ^ (((ch >> 2) << 1) | (ch & 1))) << 4);
            const uint32_t yr = mapa(yo, h ^ 1), ybr = mapa(bars + 8 * B_Y, h ^ 1);
            auto ship = [&](const int Q) {
                uint4 y[2];
#pragma unroll
                for (int hh = 0; hh < 2; hh++) {
                    const int J = 4 * Q + 2 * hh;
                    y[hh] = make_uint4(pack_bf(D[J][0], D[J][1]), pack_bf(D[J][2], D[J][3]), pack_bf(D[J + 1][0], D[J + 1][1]), pack_bf(D[J + 1][2], D[J + 1][3]));
                }
                if (!(Q & 1)) mbar_wait(bars + 8 * (B_F + (Q >> 1)));
                asm volatile("{\n\t.reg .pred p;\n\tsetp.eq.u32 p, %11, 0;\n\t"
                             "@p st.async.weak.shared::cluster.mbarrier::complete_tx::bytes.v4.b32 [%9], {%4,%5,%6,%7}, [%10];\n\t"
                             "@!p st.async.weak.shared::cluster.mbarrier::complete_tx::bytes.v4.b32 [%9], {%0,%1,%2,%3}, [%10];\n\t"
                             "@p st.shared.v4.b32 [%8], {%0,%1,%2,%3};\n\t@!p st.shared.v4.b32 [%8], {%4,%5,%6,%7};\n\t}"
                             :: "r"(y[0].x), "r"(y[0].y), "r"(y[0].z), "r"(y[0].w), "r"(y[1].x), "r"(y[1].y), "r"(y[1].z), "r"(y[1].w),
                                "r"(yo + y_off(Q)), "r"(yr + y_off(Q)), "r"(ybr + 8 * Q), "r"(h) : "memory");
                __syncwarp();
                if (lane == 0) mbar_arrive(bars + 8 * (B_Y + Q));
            };
            ship(0);
            const uint4 bA = lds128(sb + OFF_BAND + (g - t + 3) * 48), bB = lds128(sb + OFF_BAND + (g - t + 3) * 48 + 16);
            const uint2 bC = lds64(sb + OFF_BAND + (g - t + 3) * 48 + 32);
            uint2 QA[5][2], QB[8];
            const uint32_t tq = TB + 8 * (1 + g - 2 * t);
#pragma unroll
            for (int dd = 0; dd < 5; dd++) { QA[dd][0] = lds64(tq + T_A + 64 * (dd + 4)); QA[dd][1] = lds64(tq + T_A + 64 * (dd + 4) - 8); }
#pragma unroll
            for (int dd = 0; dd < 8; dd++) QB[dd] = lds64(tq + T_B + 64 * (dd + 8));
            const uint32_t u1 = UB + (mi & 1) * U_PL + (7 + r + (mi >> 1)) * 16;
            const uint32_t u2 = UB + ((mi & 1) ^ 1) * U_PL + (7 + r + (mi & 1) + 8 * (mi >> 1)) * 16;
            uint32_t n[4];
#pragma unroll
            for (int j = 0; j < 12; j++) {
                uint32_t m[4];
                ldsm4(u1 + j * 128, m[0], m[1], m[2], m[3]);
                if (!(j & 1)) ldsm4(u2 + j * 128, n[0], n[1], n[2], n[3]);
                const uint32_t n0 = n[2 * (j & 1)], n1 = n[2 * (j & 1) + 1];
                float wa[4], wb[4], wc[4], g1[4], g2[4];
                mma_bf_z(wa, bA.x, bA.y, bA.z, bA.w, m[0], m[1]);
                mma_bf_z(wb, bA.x, bA.y, bA.z, bA.w, n0, n1);
                mma_bf_z(wc, bA.x, bA.y, bA.z, bA.w, m[2], m[3]);
                if (j < 8) {
                    mma_bf_z(g1, bB.x, bB.y, bB.z, bB.w, m[0], m[1]);
                    mma_bf_z(g2, bB.x, bB.y, bB.z, bB.w, n0, n1);
                    mma_bf_k8(g1, bC.x, bC.y, m[2]);
                    mma_bf_k8(g2, bC.x, bC.y, m[3]);
                }
#pragma unroll
                for (int e = 0; e < 2; e++) {
                    const uint32_t q0 = pack_bf(wa[e], wa[e + 2]), q1 = pack_bf(wb[e], wb[e + 2]), q2 = q1 ^ p.zero, q3 = pack_bf(wc[e], wc[e + 2]);
#pragma unroll
                    for (int dd = 0; dd < 5; dd++)
                        if (j + 4 + dd < 16) mma_bf(D[j + 4 + dd], q0, q1, q2, q3, QA[dd][e].x, QA[dd][e].y);
                }
                if (j < 8) {
                    const uint32_t q0 = pack_bf(g1[0], g1[2]), q1 = pack_bf(g2[0], g2[2]), q2 = pack_bf(g1[1], g1[3]), q3 = pack_bf(g2[1], g2[3]);
#pragma unroll
                    for (int dd = 7 - j; dd >= 0; dd--) mma_bf(D[j + 8 + dd], q0, q1, q2, q3, QB[dd].x, QB[dd].y);
                }
                if ((j & 3) == 3) {
                    WSTAMP(4 + 2 * (j >> 2));
                    if (j == 11 && LATE2) ship(2);
                    if (j != 7 || !LATE2) ship((j >> 2) + 1);
                }
            }
        }
        const int warpu = __reduce_max_sync(0xffffffffu, warp);
        mix_rows<1, BULKM>(p, &tm_out, sb, sb + OFF_U + warpu * U_CH + (warpu & 1) * 64, PQ, 4, warpu, h, pr, lane);
        if (BULKM) asm volatile("cp.async.bulk.commit_group;\n\tcp.async.bulk.wait_group.read 0;" ::: "memory");
        WSTAMP(10);
        WDUMP();
    } else if ((pw & 12) == AUX_W0) {
        const int v = __reduce_max_sync(0xffffffffu, pw & 3);
        const int at = tid & 127;
        const int g = lane >> 2, t = lane & 3;
        unsigned tag;
        const bool gu = c < NGU_CTA;
        {
            const uint32_t xb = sb + (v < 2 ? OFF_XSEL : OFF_RING + 2 * 8192) + v * 8192;
            const uint32_t gws = sb + M_DPIN;
            const uint32_t row = 16 * c + 4 * v + (g >> 1);
#pragma unroll
            for (int i = 0; i < 8; i++)
                asm volatile("cp.async.ca.shared.global [%0], [%1], 4;" :: "r"((i < 4 ? sb + OFF_GP : gws) + 512 * (i & 3) + (tid & 124) * 4 + (tid & 1) * 8 + (tid & 2) * 2),
                             "l"((i < 4 ? p.wr : p.gatew) + 256 * (i & 3) + (tid & 127) * 2) : "memory");
            if ((tid & 127) < 33) cp16(sb + OFF_BAND + (tid & 127) * 16, p.band + (tid & 127));
            asm volatile("barrier.cluster.arrive.relaxed.aligned;" ::: "memory");
            tag = __reduce_max_sync(0xffffffffu, (*(volatile unsigned*)&p.sc->epoch + 1) & 0xffffu);
            if (gu) st_gpu32((uint32_t*)&p.sc->h[(tag + 1) & 1][32 * c] + at, 0);
            if (v == 2) sts32(sb + M_BMAP + lane * 4, 0);
            if (at == 0) sts32(sb + M_TAG, tag << 16);
            cp_wait_all();
            bar_sync(1, 128);
            uint2 w[16];
#pragma unroll
            for (int kb = 0; kb < 16; kb++) w[kb] = lds64((g < 4 ? sb + OFF_GP : gws) + 128 * kb + 32 * (g & 2) + 16 * t + 8 * (g & 1));
            asm volatile("barrier.cluster.wait.acquire.aligned;" ::: "memory");
            mbar_wait(bars + 8 * (B_X + v));
            WSTAMP(10);
            float dr[4][4];
#pragma unroll
            for (int kb = 0; kb < 16; kb++) {
                const uint4 x = lds128(xb + (g >> 1) * 2048 + 128 * kb + 16 * (lane & 7));
                if (kb < 4) mma_bf_z(dr[kb], x.x, x.y, x.z, x.w, w[kb].x, w[kb].y);
                else mma_bf(dr[kb & 3], x.x, x.y, x.z, x.w, w[kb].x, w[kb].y);
            }
            float rs = ((dr[0][0] + dr[0][3]) + (dr[1][0] + dr[1][3])) + ((dr[2][0] + dr[2][3]) + (dr[3][0] + dr[3][3]));
            if (lane == 0) mbar_arrive(bars + 8 * (B_XE + v) + (__float_as_uint(rs) & p.zero));
            rs += __shfl_xor_sync(0xffffffffu, rs, 5);
            const uint32_t rb = pack_bf(0.f, rs);
            if (!(lane & 7)) st_gpu32((uint32_t*)p.sc->r + row, ((rb ^ (((int)rb >> 31) | 0x80000000u)) & 0xffff0000u) | tag);
            WSTAMP(1);
            {
                const int n = 3 + (lane >> 3) + 4 * (lane & 1);
                const uint32_t so = (n & 7) * S_PL + ((lane & 6) + (n >> 3)) * 32;
                const uint32_t src[2] = {sb + OFF_S + v * S_Q + s_addr(so, h), sb + OFF_S + v * S_Q + s_addr(so + 32, h)};
                const uint32_t dst = sb + OFF_U + g * U_CH + (8 + 32 * v + 16 * h + t) * 16;
                const uint32_t rdst = mapa(dst, h ^ 1), rbar = mapa(bars + 8 * B_U, h ^ 1);
                mbar_wait(bars + 8 * (B_S + v));
                WSTAMP(9);
                uint4 a[8];
#pragma unroll
                for (int b = 0; b < 2; b++) {
#pragma unroll
                    for (int j = 0; j < 8; j++) { const int u = 4 * b + (j >> 1) + 8 * (j & 1); ldsm4t((u < 8 ? src[u & 1] ^ 16 : src[u & 1]) + ((u >> 1) & 3) * 256, a[j].x, a[j].y, a[j].z, a[j].w); }
#pragma unroll
                    for (int j = 0; j < 8; j++) {
                        const int u = 4 * b + (j >> 1) + 8 * (j & 1);
                        if (u < 8) st_async16(rdst + ((u >> 1) & 3) * 64 + (u & 1) * U_PL, a[j], rbar);
                        else sts128(dst + ((u >> 1) & 3) * 64 + (u & 1) * U_PL, a[j].x, a[j].y, a[j].z, a[j].w);
                    }
                }
                if (h && v == 3) {
                    ldsm4t((src[0] ^ 16) + 1024, a[0].x, a[0].y, a[0].z, a[0].w);
                    ldsm4t(src[0] + 1024, a[1].x, a[1].y, a[1].z, a[1].w);
                    if (t == 0) {
                        st_async16(rdst + 256, make_uint4(a[0].x, a[0].y & 0xffffu, a[0].z & 0xffffu, a[0].w & 0xffffu), rbar);
                        sts128(dst + 256, a[1].x, a[1].y & 0xffffu, a[1].z & 0xffffu, a[1].w & 0xffffu);
                    }
                }
                __syncwarp();
                if (lane == 0) mbar_arrive(bars + 8 * B_U);
            }
            if ((lane & 7) == 2) st_gpu32((uint32_t*)p.sc->g + ((row & 256) << 2) + gate_pos(row), pack_bf(sigmoid_f(__uint_as_float(rb)), 0.f) | (tag << 16));
            WSTAMP(2);
        }
        {
            const bool lane0 = pin(lane, lane) == 0;
            const uint32_t own = pin(sb + OFF_XSEL + (at ^ ((at >> 1) & 4)) * 16, lane);
            float acc[8][4];
#pragma unroll
            for (int i = 0; i < 8; i++) { acc[i][0] = acc[i][1] = acc[i][2] = acc[i][3] = 0.f; }
            const int krow = ((lane >> 1) & 8) + (lane & 7);
            const uint32_t tile0 = pin(sb + OFF_RING + krow * 64 + ((((lane >> 3) & 1) ^ ((krow >> 1) & 3)) << 4), lane);
            const uint32_t xo = pin(sb + OFF_XSEL + (lane & 7) * XS_ROW + 512 * v + 2 * (lane & 24), lane);
            const uint32_t po = pin(sb + OFF_XSEL + t * XS_ROW + (g & 3) * 128 + (g & 1) * 64 + v * 16 + (lane >> 4) * 8, lane);
            const uint32_t po1 = pin(po + 64 - (g & 1) * 128, lane);
            uint32_t* hdst = pin((uint32_t*)&p.sc->h[tag & 1][32 * c] + at, lane);
            auto signal = [&](const int k, const uint32_t dep) {
                if (lane < 2 && v < 2)
                    asm volatile("st.async.weak.shared::cluster.mbarrier::complete_tx::bytes.b32 [%0], %1, [%2];"
                                 :: "r"(mapa(sb + M_SINK, lane)), "r"(dep), "r"(mapa(bars + 8 * (B_F + k), lane)) : "memory");
            };
#pragma unroll 1
            for (int i = 0; i < 4; i++) {
                const int s = 4 * i + v;
                uint32_t a[16][4], b[2][4];
                if (gu) {
                    const uint32_t tile = tile0 + (s < 14 ? s : v) * 8192;
                    if (lane0 && i > 1) mbar_arrive(bars + 8 * (B_E + s - 4));
                    if (i == 2) signal(0, 0);
                    mbar_wait(bars + 8 * (B_W + s));
#pragma unroll
                    for (int q = 0; q < 16; q++) ldsm4t((tile ^ ((q & 1) << 5)) + ((q >> 1) & 1) * 4096 + (q >> 2) * 1024, a[q][0], a[q][1], a[q][2], a[q][3]);
                }
                if (i == 0) {
                    if (gu) {
                        uint32_t dep = p.zero;
#pragma unroll
                        for (int q = 0; q < 16; q += 2) dep &= a[q][0] & a[q + 1][0];
                        if (lane == 0) mbar_arrive(bars + 8 * (B_E + v) + dep);
                    }
                    WSTAMP(11);
                    uint32_t top;
#pragma unroll 1
                    for (int it = 0; it < (1 << 22); it++) {
                        asm volatile("ld.relaxed.gpu.global.u32 %0, [%1];" : "=r"(top) : "l"(&p.sc->top[c % NTOP][g]) : "memory");
                        if (__all_sync(0xffffffffu, ((top ^ (tag << 11)) & 0xf800u) == 0)) break;
                        if (TSLEEP) __nanosleep(TSLEEP);
                    }
                    WSTAMP(3);
                    if (gu) {
                        const uint32_t k = 4 * h + v, row = __reduce_max_sync(0xffffffffu, lane == 4 * k ? ~top & 2047 : 0);
                        asm volatile("{\n\t.reg .pred p;\n\telect.sync _|p, 0xffffffff;\n\t"
                                     "@p cp.async.bulk.shared::cluster.global.mbarrier::complete_tx::bytes.multicast::cluster [%0], [%1], 2048, [%2], %3;\n\t}"
                            :: "r"(sb + OFF_XSEL + k * XS_ROW), "l"(p.u + (size_t)row * D_), "r"(bars + 8 * B_G), "h"((unsigned short)3) : "memory");
                    }
                    if (v == 2) {
                        const uint32_t row = ~top & 2047;
                        if (t == 0 && ((row >> 8) & 1) == h)
                            asm volatile("red.shared.or.b32 [%0], %1;" :: "r"(sb + M_BMAP + (row & 7) * 16 + (row >> 9) * 4), "r"(1u << (gate_pos(row) & 31)) : "memory");
                        if (t == 0) sts32(sb + M_TOP + lane, top);
                        if (c == 0 && lane == 0) *(volatile unsigned*)&p.sc->epoch = tag;
                        __syncwarp();
                        if (lane0) mbar_arrive(bars + 8 * B_Y);
                    }
                    if (!gu) break;
                    mbar_wait(bars + 8 * B_G);
                    WSTAMP(4);
                }
                ldsm4(xo + 128 * i, b[0][0], b[0][1], b[0][2], b[0][3]);
                ldsm4(xo + 128 * i + 64, b[1][0], b[1][1], b[1][2], b[1][3]);
#pragma unroll
                for (int q = 0; q < 16; q++) mma_bf(acc[q & 7], a[q][0], a[q][1], a[q][2], a[q][3], b[q >> 3][(q >> 1) & 2], b[q >> 3][((q >> 1) & 2) + 1]);
            }
            if (gu) {
                WSTAMP(5);
                __syncwarp();
#pragma unroll
                for (int q = 0; q < 4; q++) {
                    const int ct = q >> 1, e = 2 * (q & 1);
                    sts128(own + q * XS_ROW,
                           __float_as_uint(acc[ct][e] + acc[4 + ct][e]), __float_as_uint(acc[2 + ct][e] + acc[6 + ct][e]),
                           __float_as_uint(acc[ct][e + 1] + acc[4 + ct][e + 1]), __float_as_uint(acc[2 + ct][e + 1] + acc[6 + ct][e + 1]));
                }
                bar_sync(1, 128);
                float sl[2], uv[2];
#pragma unroll
                for (int e = 0; e < 2; e++) {
                    uint2 q[4];
#pragma unroll
                    for (int i = 0; i < 4; i++) q[i] = lds64((e ? po1 : po) + 512 * i);
                    const float s0 = (__uint_as_float(q[0].x) + __uint_as_float(q[1].x)) + (__uint_as_float(q[2].x) + __uint_as_float(q[3].x));
                    const float s1 = (__uint_as_float(q[0].y) + __uint_as_float(q[1].y)) + (__uint_as_float(q[2].y) + __uint_as_float(q[3].y));
                    const float gv = bf_round(p.gu_swap ? s1 : s0);
                    uv[e] = p.gu_swap ? s0 : s1;
                    sl[e] = gv * sigmoid_f(gv);
                }
                const uint32_t hw = hmul2_bf(pack_bf(sl[0], sl[1]), pack_bf(uv[0], uv[1]));
                st_gpu32(hdst, hw ? hw : 0x80000000u);
                signal(1, hw);
            }
        }
        WSTAMP(6);
        {
            const uint32_t own = pin(sb + OFF_XSEL + at * 16, lane);
            const uint32_t hb = sb + (v < 2 ? OFF_XSEL + 7168 * v : OFF_RING + 8192 * v), hl = pin(hb + 16 * lane, lane);
            const int krow = ((lane >> 1) & 8) + (lane & 7);
            const uint32_t tile = pin(sb + OFF_RING + v * 8192 + krow * 32 + ((((lane >> 3) ^ (krow >> 2)) & 1) << 4), lane);
            float dd[4][4];
            bar_sync(1, 128);
            mbar_wait(bars + 8 * (B_W + HW));
            WSTAMP(12);
            uint4 hq[7];
#pragma unroll 1
            for (int it = 0; it < (1 << 16); it++) {
                bulk_load(hb, &p.sc->h[tag & 1][32 * (56 * h + 14 * v)], 7168, bars + 8 * (B_X + v));
                uint32_t a[14][4], mn = 0xffffffffu;
                mbar_wait(bars + 8 * (B_W + 16 + v));
#pragma unroll
                for (int j = 0; j < 14; j++) ldsm4t(tile + (v & 2) * 16384 + j * 512, a[j][0], a[j][1], a[j][2], a[j][3]);
                mbar_wait(bars + 8 * (B_X + v), ~it & 1);
                WSTAMP(7);
#pragma unroll
                for (int j = 0; j < 7; j++) {
                    const uint4 q = lds128(hl + 512 * j);
                    mn = min(mn, q.x);
#pragma unroll
                    for (int e = 0; e < 2; e++) {
                        const uint32_t(&f)[4] = a[2 * j + e];
                        if (j < 2) mma_bf_z(dd[2 * j + e], f[0], f[1], f[2], f[3], e ? q.z : q.x, e ? q.w : q.y);
                        else mma_bf(dd[(2 * j + e) & 3], f[0], f[1], f[2], f[3], e ? q.z : q.x, e ? q.w : q.y);
                    }
                }
#pragma unroll
                for (int j = 0; j < 7; j++) { hq[j] = lds128(hl + 3584 + 512 * j); mn = min(mn, hq[j].x); }
                if (__all_sync(0xffffffffu, mn != 0)) break;
            }
            mbar_wait(bars + 8 * (B_W + 20 + v));
#pragma unroll
            for (int j = 0; j < 14; j++) {
                uint32_t f[4];
                ldsm4t(tile + 65536 + j * 512, f[0], f[1], f[2], f[3]);
                mma_bf(dd[(j + 2) & 3], f[0], f[1], f[2], f[3], (j & 1) ? hq[j >> 1].z : hq[j >> 1].x, (j & 1) ? hq[j >> 1].w : hq[j >> 1].y);
            }
            WSTAMP(8);
            uint4 part;
            part.x = __float_as_uint((dd[0][0] + dd[1][0]) + (dd[2][0] + dd[3][0])); part.y = __float_as_uint((dd[0][1] + dd[1][1]) + (dd[2][1] + dd[3][1]));
            part.z = __float_as_uint((dd[0][2] + dd[1][2]) + (dd[2][2] + dd[3][2])); part.w = __float_as_uint((dd[0][3] + dd[1][3]) + (dd[2][3] + dd[3][3]));
            st_async16(mapa(own + (M_DPIN - OFF_XSEL), h ^ 1), part, mapa(bars + 8 * B_DP, h ^ 1));
            sts128(own + 14336, part.x, part.y, part.z, part.w);
            __syncwarp();
            if (lane == 0) mbar_arrive(bars + 8 * B_DP);
        }
        WDUMP();
    } else {
        asm volatile("setmaxnreg.dec.sync.aligned.u32 64;");
        const int v = __reduce_max_sync(0xffffffffu, pw - PREP_W0);
        const bool gu = c < NGU_CTA;
        const uint32_t t0 = clock();
        const uint32_t bu = bars + 8 * v;
        if (lane == 0) {
            mbar_init(bu + 8 * B_X, 1);
            asm volatile("fence.mbarrier_init.release.cluster;" ::: "memory");
        }
        __syncwarp();
        if (DELAY_X > 0) __nanosleep(DELAY_X);
        bulk_load(sb + (v < 2 ? OFF_XSEL : OFF_RING + 2 * 8192) + v * 8192, p.u + (size_t)(16 * c + 4 * v) * D_, 8192, bu + 8 * B_X);
        if (lane == 0) {
#pragma unroll
            for (int i = 0; i < 10; i++) mbar_init(bu + 32 * i, 1);
            mbar_init(bu + 8 * B_XE, 1);
            mbar_init(bu + 8 * B_Y, v == 0 ? 11 : 9);
            mbar_init(bu + 8 * B_DP, (0x1855 >> (4 * v)) & 15);
            mbar_init(bu + 8 * B_F, 1);
            mbar_init(bu + 8 * B_H, 1);
            asm volatile("fence.mbarrier_init.release.cluster;" ::: "memory");
            mbar_expect(bu + 8 * B_Y, 4096);
            if (v != 2) mbar_expect(bu + 8 * B_DP, v == 0 ? 2048 : (h || v == 3) ? 16384 : 16384 + 128);
            mbar_expect(bu + 8 * B_F, c < NGU_CTA ? 16 : 0);
        }
        __syncwarp();
        asm volatile("barrier.cluster.arrive.relaxed.aligned;" ::: "memory");
        tma3d(sb + OFF_S + v * S_Q, &tm_x, 16 * pr, 64 * v + 32 * h - 1, bars + 8 * (B_S + v), S_Q);
        WSTAMP(9);
        if (v < 3 && lane == 0) asm volatile("prefetch.tensormap [%0];" :: "l"(v == 0 ? &tm_gu : v == 1 ? &tm_down : &tm_out) : "memory");
        asm volatile("barrier.cluster.wait.acquire.aligned;" ::: "memory");
        uint32_t desc;
        {
            const int s = 6 * v + lane, i = s >> 2, w = s & 3, slot = s < 14 ? s : (s | 1) == 17 ? s - 16 : s - 12;
            const int fb = s < 4 ? B_H : (gu && s >= 14) ? B_E + slot : s < 6 ? B_XE + s - 2 : B_KG;
            desc = slot | (fb << 4) | ((i < 4 ? 256 * w + 64 * i : 1792 * h + 448 * w + 224 * (i - 4)) << 10);
            if (lane < 6) mbar_expect(bars + 8 * (B_W + s), i < 4 ? 8192 : 7168);
            if (tid == 32 * PREP_W0) mbar_arrive(bars + 8 * B_H);
        }
        if (v == 3) {
            mbar_wait(bars + 8 * B_U);
            mbar_wait(bars + 8 * (gu ? B_G : B_H + 2));
            const uint32_t tag16 = lds32(sb + M_TAG);
            uint4 q[8];
#pragma unroll 1
            for (int it = 0; it < (1 << 22); it++) {
                uint32_t bad = 0;
#pragma unroll
                for (int i = 0; i < 8; i++) q[i] = ld_gpu128(&p.sc->g[256 * h + 32 * i + lane]);
#pragma unroll
                for (int i = 0; i < 8; i++) bad |= ((q[i].x ^ tag16) | (q[i].y ^ tag16)) | ((q[i].z ^ tag16) | (q[i].w ^ tag16));
                if ((bad >> 16) == 0) break;
                __nanosleep(200);
            }
#pragma unroll
            for (int i = 0; i < 8; i++)
                asm volatile("st.shared.v2.u32 [%0], {%1, %2};" :: "r"(sb + OFF_GP + 256 * i + lane * 8),
                             "r"(__byte_perm(q[i].x, q[i].y, 0x5410)), "r"(__byte_perm(q[i].z, q[i].w, 0x5410)) : "memory");
            __syncwarp();
            if (lane == 0) mbar_arrive(bars + 8 * B_Y);
        }
        mbar_wait(bars + 8 * (B_H + v));
        {
            const int gap = v == 0 ? GAP : v == 1 ? GAP1 : v == 2 ? GAP2 : GAP3;
            uint32_t last = v ? clock() - SLACK : t0 + T0 - GAP + STAG * ((pr * 5) & 15) / 16;
#pragma unroll 1
            while ((int)(last - clock()) > 500) __nanosleep(256);
#pragma unroll 1
            for (int k = 0; k < 6; k++) {
                const uint32_t dk = __reduce_max_sync(0xffffffffu, lane == k ? desc : 0);
                const bool dn = 6 * v + k >= 16;
                mbar_wait(bars + ((dk >> 1) & 0x1f8));
                uint32_t now;
#pragma unroll 1
                while ((int)((now = clock()) - last) < gap) __nanosleep(CSLEEP);
                last = max((int)(now - last) - SLACK, gap) + last;
                WSTAMP(3 + k);
                if (gu || dn)
                    asm volatile("{\n\t.reg .pred p;\n\telect.sync _|p, 0xffffffff;\n\t"
                                 "@p cp.async.bulk.tensor.3d.shared::cluster.global.mbarrier::complete_tx::bytes [%0], [%1, {%3, %4, 0}], [%2];\n\t}"
                        :: "r"(sb + OFF_RING + (dk & 15) * 8192), "l"(dn ? &tm_down : &tm_gu), "r"(bars + 8 * (B_W + 6 * v + k)), "r"(dn ? 16 * pr : 32 * c), "r"(dk >> 10) : "memory");
                if (k < 5 && PRESLEEP) __nanosleep(PRESLEEP);
            }
            if (lane == 0 && v < 3) mbar_arrive(bars + 8 * (B_H + v + 1));
        }
        {
            WSTAMP(1);
            mix_rows<2, true>(p, &tm_out, sb, sb + OFF_TAB + v * TAB_W, 0, PQ, v, h, pr, lane);
            WSTAMP(2);
            asm volatile("cp.async.bulk.commit_group;" ::: "memory");
            const uint32_t top = lds32(sb + M_TOP + 8 * v + 4 * (lane >> 4));
            const uint32_t row = ~top & 2047, ch = lane & 15, gp = gate_pos(row);
            const bool mine = ((row >> 8) & 1) == h;
            uint32_t gfin, x16, y16 = 0;
            asm volatile("ld.shared.u16 %0, [%1];" : "=r"(gfin) : "r"(sb + OFF_GP + gp * 2) : "memory");
            asm volatile("ld.shared.u16 %0, [%1];" : "=r"(x16) : "r"(sb + OFF_S + (row >> 9) * S_Q + s_addr((row & 7) * S_PL + 32 + (row & 248) * 4, ch >> 3) + 2 * (ch & 7)) : "memory");
            const float rsel = __uint_as_float(pin(__float_as_uint(bf_round(sigmoid_f(__uint_as_float((top ^ (((int)~top >> 31) | 0x80000000u)) & 0xffff0000u)))), lane));
            const uint32_t po = pin(sb + (4 * (ch & 7) + v) * 16 + (ch >> 3) * 8 + (lane >> 4) * 4, lane);
            bf16* op = pin(p.out + (size_t)row * D_ + 16 * pr + ch, lane);
            if (mine) {
                mbar_wait(bars + 8 * (B_Y + (row >> 9)));
                asm volatile("ld.shared.u16 %0, [%1];" : "=r"(y16)
                             : "r"(sb + y_off(row >> 9) + ch * 512 + (((4 * (row & 7) + ((row >> 5) & 3)) ^ (((ch >> 2) << 1) | (ch & 1))) << 4) + 2 * row_elem(row)) : "memory");
            }
            mbar_wait(bars + 8 * B_DP);
            float q[8];
#pragma unroll
            for (int i = 0; i < 4; i++) { q[i] = ldsf(po + M_DPIN + 512 * i); q[4 + i] = ldsf(po + OFF_XSEL + 14336 + 512 * i); }
            const float tot = ((q[0] + q[1]) + (q[2] + q[3])) + ((q[4] + q[5]) + (q[6] + q[7]));
            const float b = bf_round(__uint_as_float(x16 << 16) + bf_round(bf_round(tot) * rsel));
            if (mine) *op = __float2bfloat16_rn(fmaf(bf_lo(gfin), __uint_as_float(y16 << 16), bf_round(bf_round(1.f - bf_lo(gfin)) * b)));
        }
        asm volatile("cp.async.bulk.wait_group.read 0;" ::: "memory");
        WSTAMP(10);
        WDUMP();
    }
}

typedef CUresult (*EncodeFn)(CUtensorMap*, CUtensorMapDataType, cuuint32_t, void*, const cuuint64_t*, const cuuint64_t*,
                             const cuuint32_t*, const cuuint32_t*, CUtensorMapInterleave, CUtensorMapSwizzle,
                             CUtensorMapL2promotion, CUtensorMapFloatOOBfill);

void make_map(EncodeFn f, CUtensorMap* m, const void* ptr, uint64_t cols, uint64_t rows, uint64_t pitch, uint32_t bc, uint32_t br, CUtensorMapSwizzle sw, int prom,
              uint32_t planes = 1, uint64_t plane_stride = 0, uint32_t box_planes = 0) {
    cuuint64_t dims[3] = {cols, rows, planes};
    cuuint64_t str[2] = {pitch, planes > 1 ? plane_stride : pitch * rows};
    cuuint32_t box[3] = {bc, br, box_planes ? box_planes : planes};
    cuuint32_t es[3] = {1, 1, 1};
    f(m, CU_TENSOR_MAP_DATA_TYPE_BFLOAT16, 3, (void*)ptr, dims, str, box, es, CU_TENSOR_MAP_INTERLEAVE_NONE, sw,
      (CUtensorMapL2promotion)prom, CU_TENSOR_MAP_FLOAT_OOB_FILL_NONE);
}

}

extern "C" void kernel_launch(void* const* d_in, const int* in_sizes, int n_in, void* d_out, int out_size) {
    static EncodeFn enc = nullptr;
    static void *sc = nullptr, *band = nullptr;
    if (!enc) {
        void* fn = nullptr;
        cudaDriverEntryPointQueryResult qr;
        cudaGetDriverEntryPoint("cuTensorMapEncodeTiled", &fn, cudaEnableDefault, &qr);
        enc = (EncodeFn)fn;
        cudaGetSymbolAddress(&sc, g_scratch);
        cudaGetSymbolAddress(&band, g_band);
        cudaFuncSetAttribute(fused_kernel, cudaFuncAttributeMaxDynamicSharedMemorySize, SMEM_BYTES);
    }
    CUtensorMap tg, td, tx, to;
    const char *wg = (const char*)d_in[9], *wu = (const char*)d_in[10];
    const bool swap = wu < wg;
    make_map(enc, &tg, swap ? wu : wg, F_, D_, F_ * 2, 32, 64, CU_TENSOR_MAP_SWIZZLE_64B, PROMG, 2, swap ? wg - wu : wu - wg);
    make_map(enc, &td, d_in[11], D_, F_, D_ * 2, 16, 224, CU_TENSOR_MAP_SWIZZLE_32B, PROMD);
    make_map(enc, &tx, d_in[0], D_, L_ / 8, D_ * 16, 16, 33, CU_TENSOR_MAP_SWIZZLE_32B, PROMX, 8, D_ * 2);
    make_map(enc, &to, d_out, D_, L_ / 8, D_ * 16, 16, 32, CU_TENSOR_MAP_SWIZZLE_NONE, 0, 8, D_ * 2, 1);
    Params p;
    p.u = (const bf16*)d_in[0]; p.logA = (const bf16*)d_in[1]; p.Aim = (const bf16*)d_in[2];
    p.Cre = (const bf16*)d_in[3]; p.Cim = (const bf16*)d_in[4]; p.logdt = (const bf16*)d_in[5];
    p.Dskip = (const bf16*)d_in[6]; p.wr = (const bf16*)d_in[8]; p.gatew = (const bf16*)d_in[12];
    p.out = (bf16*)d_out;
    p.sc = (Scratch*)sc; p.band = (const uint4*)band;
    p.gu_swap = swap;
    p.zero = 0;
    fused_kernel<<<NCTA, NTHREADS, SMEM_BYTES>>>(p, tg, td, tx, to);
}
```

```cpp
#include <cuda_runtime.h>
#include <cuda_bf16.h>
#include <cuda_fp16.h>
#include <cuda.h>
#include <stdint.h>

typedef __nv_bfloat16 bf16;

namespace {

constexpr int L_ = 2048, D_ = 1024, F_ = 3584;
constexpr int NCTA = 130;
constexpr int NTHREADS = 512;
#define AUXW 12
constexpr int MAIN_W0 = 0, AUX_W0 = AUXW, PREP_W0 = 20 - AUXW;
#define T0 3300
#define GAP 540
#define GAP1 530
#define GAP2 530
#define GAP3 550
#define STAG GAP
#define CSLEEP 50
#define SLACK 300
#define TSLEEP 40
#define BULKM false
#define PW 19
#define PRESLEEP 64
#define PWQ 1
#define PQ 3
#define PROMG 2
#define PROMD 1
#define PROMX 0
#define LATE2 0
#define HW 20
constexpr int NGU_CTA = 112;

constexpr int OFF_RING = 0;
constexpr int OFF_SCR  = 6 * 8192;
constexpr int S_PL     = 1056;
constexpr int S_Q      = 8 * S_PL;
constexpr int OFF_S    = 114688;
constexpr int OFF_GP   = OFF_S + 4 * S_Q;
constexpr int U_PL     = 2240;
constexpr int U_CH     = 4416;
constexpr int OFF_U    = 151552;
constexpr int TAB_W    = 3200;
constexpr int T_PL     = 544;
constexpr int T_A      = 2192 - 26 * 8;
constexpr int T_B      = 2568 - 59 * 8;
constexpr int OFF_TAB  = 186880;
constexpr int OFF_XSEL = 212480;
constexpr int XS_ROW   = 2064;
constexpr int OFF_BAND = 228992;
constexpr int OFF_MISC = 229536;
constexpr int M_BARS   = OFF_MISC;
constexpr int M_DSK    = OFF_MISC + 2736;
constexpr int M_SINK   = OFF_MISC + 512;
constexpr int M_TAG    = OFF_MISC + 516;
constexpr int M_BMAP   = OFF_MISC + 528;
constexpr int M_DPIN   = OFF_MISC + 656;
constexpr int M_TOP    = OFF_MISC + 2704;
constexpr int SMEM_BYTES = OFF_MISC + 2768;
__device__ __forceinline__ uint32_t s_addr(uint32_t o, uint32_t half) { return o + (((half ^ (o >> 7)) & 1) << 4); }
__host__ __device__ constexpr uint32_t y_off(uint32_t q) { return OFF_RING + 32768 + (q & 1) * 8192 + (q >> 1) * 65536; }

constexpr int B_W = 0;
constexpr int B_E = 24;
constexpr int B_S = 36;
constexpr int B_Y = 40;
constexpr int B_DP = 44, B_U = 45, B_KG = 46, B_G = 47;
constexpr int B_F = 48;
constexpr int B_H = 60;
constexpr int B_X = 52, B_XE = 56;

struct BandTab { uint32_t w[11][12]; };
constexpr BandTab make_band() {
    BandTab b{};
    for (int cls = 0; cls < 11; cls++)
        for (int wd = 0; wd < 10; wd++) {
            const int tau = cls + 2 - 8 * ((wd < 4 ? wd : wd - 4) >> 1);
            const int lo = (wd < 4) ? ((wd & 1) ? -2 : 3) : ((wd & 1) ? -4 : -11), wid = (wd < 4 ? 3 : 7) + 2 * (wd & 1);
            b.w[cls][wd] = ((tau >= lo && tau < lo + wid) ? 0x3F80u : 0u) | ((tau - 4 >= lo && tau - 4 < lo + wid) ? 0x3F800000u : 0u);
        }
    return b;
}
constexpr int NTOP = 32;
struct Scratch {
    uint4 r[L_ / 4];
    uint4 g[L_ / 4];
    uint4 h[2][8 * F_ / 8];
    uint32_t top[NTOP][32];
    unsigned epoch;
};
__device__ __align__(128) Scratch g_scratch;
__device__ const __align__(16) BandTab g_band = make_band();

struct Params {
    const bf16 *u, *logA, *Aim, *Cre, *Cim, *logdt, *Dskip, *wr, *gatew;
    bf16* out;
    Scratch* sc;
    const uint4* band;
    uint32_t gu_swap;
    uint32_t zero;
};

#define WSTAMP(i) do {} while (0)
#define KSTAMP(i, dep) do {} while (0)
#define WDUMP() do {} while (0)
#define RSTAMP(i) do {} while (0)

__device__ __forceinline__ uint32_t smem_u32(const void* p) { return (uint32_t)__cvta_generic_to_shared(p); }
__device__ __forceinline__ void mbar_init(uint32_t b, uint32_t c) { asm volatile("mbarrier.init.shared::cta.b64 [%0], %1;" :: "r"(b), "r"(c) : "memory"); }
__device__ __forceinline__ void mbar_expect(uint32_t b, uint32_t tx) { asm volatile("mbarrier.arrive.expect_tx.shared::cta.b64 _, [%0], %1;" :: "r"(b), "r"(tx) : "memory"); }
__device__ __forceinline__ void mbar_arrive(uint32_t b) { asm volatile("mbarrier.arrive.shared::cta.b64 _, [%0];" :: "r"(b) : "memory"); }
__device__ __forceinline__ void mbar_wait(uint32_t b, uint32_t parity = 0) {
    asm volatile("{\n\t.reg .pred p;\nW%=:\n\tmbarrier.try_wait.parity.shared::cta.b64 p, [%0], %1, 20000;\n\t@!p bra W%=;\n\t}" :: "r"(b), "r"(parity) : "memory");
}
__device__ __forceinline__ uint32_t mapa(uint32_t addr, uint32_t rank) { uint32_t r; asm("mapa.shared::cluster.u32 %0, %1, %2;" : "=r"(r) : "r"(addr), "r"(rank)); return r; }
__device__ __forceinline__ void tma3d(uint32_t dst, const CUtensorMap* tm, int c0, int c1, uint32_t bar, uint32_t bytes) {
    asm volatile("{\n\t.reg .pred p;\n\telect.sync _|p, 0xffffffff;\n\t"
                 "@p mbarrier.arrive.expect_tx.shared::cta.b64 _, [%2], %5;\n\t"
                 "@p cp.async.bulk.tensor.3d.shared::cluster.global.mbarrier::complete_tx::bytes [%0], [%1, {%3, %4, 0}], [%2];\n\t}"
        :: "r"(dst), "l"(tm), "r"(bar), "r"(c0), "r"(c1), "r"(bytes) : "memory");
}
__device__ __forceinline__ void bulk_load(uint32_t dst, const void* src, uint32_t bytes, uint32_t bar) {
    asm volatile("{\n\t.reg .pred p;\n\telect.sync _|p, 0xffffffff;\n\t"
                 "@p mbarrier.arrive.expect_tx.shared::cta.b64 _, [%2], %3;\n\t"
                 "@p cp.async.bulk.shared::cluster.global.mbarrier::complete_tx::bytes [%0], [%1], %3, [%2];\n\t}"
        :: "r"(dst), "l"(src), "r"(bar), "r"(bytes) : "memory");
}
__device__ __forceinline__ void st_async16(uint32_t dst, const uint4& v, uint32_t bar) {
    asm volatile("st.async.weak.shared::cluster.mbarrier::complete_tx::bytes.v4.b32 [%0], {%1,%2,%3,%4}, [%5];"
                 :: "r"(dst), "r"(v.x), "r"(v.y), "r"(v.z), "r"(v.w), "r"(bar) : "memory");
}
__device__ __forceinline__ void bar_sync(int id, int n) { asm volatile("bar.sync %0, %1;" :: "r"(id), "r"(n) : "memory"); }
__device__ __forceinline__ void cp16(uint32_t dst, const void* src) { asm volatile("cp.async.cg.shared.global [%0], [%1], 16;" :: "r"(dst), "l"(src) : "memory"); }
__device__ __forceinline__ void cp_wait_all() { asm volatile("cp.async.wait_all;" ::: "memory"); }
__device__ __forceinline__ uint4 ld_gpu128(const void* p) { uint4 v; asm volatile("ld.relaxed.gpu.global.v4.u32 {%0,%1,%2,%3}, [%4];" : "=r"(v.x), "=r"(v.y), "=r"(v.z), "=r"(v.w) : "l"(p) : "memory"); return v; }
__device__ __forceinline__ void st_gpu32(void* p, uint32_t v) { asm volatile("st.relaxed.gpu.global.u32 [%0], %1;" :: "l"(p), "r"(v) : "memory"); }

__device__ __forceinline__ void ldsm4(uint32_t a, uint32_t& r0, uint32_t& r1, uint32_t& r2, uint32_t& r3) {
    asm volatile("ldmatrix.sync.aligned.m8n8.x4.shared.b16 {%0,%1,%2,%3}, [%4];" : "=r"(r0), "=r"(r1), "=r"(r2), "=r"(r3) : "r"(a) : "memory");
}
__device__ __forceinline__ void ldsm4t(uint32_t a, uint32_t& r0, uint32_t& r1, uint32_t& r2, uint32_t& r3) {
    asm volatile("ldmatrix.sync.aligned.m8n8.x4.trans.shared.b16 {%0,%1,%2,%3}, [%4];" : "=r"(r0), "=r"(r1), "=r"(r2), "=r"(r3) : "r"(a) : "memory");
}
__device__ __forceinline__ uint32_t lds32(uint32_t a) { uint32_t v; asm volatile("ld.shared.u32 %0, [%1];" : "=r"(v) : "r"(a) : "memory"); return v; }
__device__ __forceinline__ uint2 lds64(uint32_t a) { uint2 v; asm volatile("ld.shared.v2.u32 {%0,%1}, [%2];" : "=r"(v.x), "=r"(v.y) : "r"(a) : "memory"); return v; }
__device__ __forceinline__ uint4 lds128(uint32_t a) { uint4 v; asm volatile("ld.shared.v4.u32 {%0,%1,%2,%3}, [%4];" : "=r"(v.x), "=r"(v.y), "=r"(v.z), "=r"(v.w) : "r"(a) : "memory"); return v; }
__device__ __forceinline__ void sts32(uint32_t a, uint32_t v) { asm volatile("st.shared.u32 [%0], %1;" :: "r"(a), "r"(v) : "memory"); }
__device__ __forceinline__ void sts16(uint32_t a, uint32_t v) { asm volatile("st.shared.u16 [%0], %1;" :: "r"(a), "h"((unsigned short)v) : "memory"); }
__device__ __forceinline__ void sts128(uint32_t a, uint32_t x, uint32_t y, uint32_t z, uint32_t w) { asm volatile("st.shared.v4.u32 [%0], {%1,%2,%3,%4};" :: "r"(a), "r"(x), "r"(y), "r"(z), "r"(w) : "memory"); }
__device__ __forceinline__ float ldsf(uint32_t a) { float v; asm volatile("ld.shared.f32 %0, [%1];" : "=f"(v) : "r"(a) : "memory"); return v; }

__device__ __forceinline__ void mma_bf(float (&d)[4], uint32_t a0, uint32_t a1, uint32_t a2, uint32_t a3, uint32_t b0, uint32_t b1) {
    asm volatile("mma.sync.aligned.m16n8k16.row.col.f32.bf16.bf16.f32 {%0,%1,%2,%3}, {%4,%5,%6,%7}, {%8,%9}, {%0,%1,%2,%3};"
        : "+f"(d[0]), "+f"(d[1]), "+f"(d[2]), "+f"(d[3]) : "r"(a0), "r"(a1), "r"(a2), "r"(a3), "r"(b0), "r"(b1));
}
__device__ __forceinline__ void mma_bf_z(float (&d)[4], uint32_t a0, uint32_t a1, uint32_t a2, uint32_t a3, uint32_t b0, uint32_t b1) {
    asm volatile("mma.sync.aligned.m16n8k16.row.col.f32.bf16.bf16.f32 {%0,%1,%2,%3}, {%4,%5,%6,%7}, {%8,%9}, {%10,%10,%10,%10};"
        : "=f"(d[0]), "=f"(d[1]), "=f"(d[2]), "=f"(d[3]) : "r"(a0), "r"(a1), "r"(a2), "r"(a3), "r"(b0), "r"(b1), "f"(0.f));
}
__device__ __forceinline__ void mma_bf_k8(float (&d)[4], uint32_t a0, uint32_t a1, uint32_t b0) {
    asm volatile("mma.sync.aligned.m16n8k8.row.col.f32.bf16.bf16.f32 {%0,%1,%2,%3}, {%4,%5}, {%6}, {%0,%1,%2,%3};"
        : "+f"(d[0]), "+f"(d[1]), "+f"(d[2]), "+f"(d[3]) : "r"(a0), "r"(a1), "r"(b0));
}
__device__ __forceinline__ void mma_h(float (&d)[4], uint32_t a0, uint32_t a1, uint32_t a2, uint32_t a3, uint32_t b0, uint32_t b1) {
    asm volatile("mma.sync.aligned.m16n8k16.row.col.f32.f16.f16.f32 {%0,%1,%2,%3}, {%4,%5,%6,%7}, {%8,%9}, {%0,%1,%2,%3};"
        : "+f"(d[0]), "+f"(d[1]), "+f"(d[2]), "+f"(d[3]) : "r"(a0), "r"(a1), "r"(a2), "r"(a3), "r"(b0), "r"(b1));
}
__device__ __forceinline__ uint32_t pack_bf(float lo, float hi) { uint32_t r; asm("cvt.rn.bf16x2.f32 %0, %1, %2;" : "=r"(r) : "f"(hi), "f"(lo)); return r; }
__device__ __forceinline__ uint32_t pack_h(float lo, float hi) { uint32_t r; asm("cvt.rn.f16x2.f32 %0, %1, %2;" : "=r"(r) : "f"(hi), "f"(lo)); return r; }
__device__ __forceinline__ float bf_lo(uint32_t v) { return __uint_as_float(v << 16); }
__device__ __forceinline__ float bf_hi(uint32_t v) { return __uint_as_float(v & 0xffff0000u); }
__device__ __forceinline__ float bf_round(float x) { return __uint_as_float(pack_bf(0.f, x)); }
__device__ __forceinline__ uint32_t hmul2_bf(uint32_t a, uint32_t b) { uint32_t r; asm("mul.rn.bf16x2 %0, %1, %2;" : "=r"(r) : "r"(a), "r"(b)); return r; }
__device__ __forceinline__ float ex2f(float x) { float r; asm("ex2.approx.ftz.f32 %0, %1;" : "=f"(r) : "f"(x)); return r; }

__device__ __forceinline__ float exp_acc(float x) {
    const float t = x * 1.4426950216293335f;
    const float r = fmaf(x, 1.4426950216293335f, -t) + x * 1.9259629911266175e-8f;
    return ex2f(t) * fmaf(r, 0.6931471805599453f, 1.f);
}
__device__ __forceinline__ float sigmoid_f(float x) { return __fdividef(1.f, 1.f + ex2f(-x * 1.4426950408889634f)); }
__device__ __forceinline__ void cexp_pow(float l2, float li, float e, float& zr, float& zi) {
    const float mag = ex2f(l2 * e);
    zr = mag * __cosf(li * e);
    zi = mag * __sinf(li * e);
}
__device__ __forceinline__ uint32_t hcmul(uint32_t a, uint32_t k, uint32_t kp) {
    const __half2 A = *reinterpret_cast<const __half2*>(&a);
    const __half2 r = __hfma2(__high2half2(A), *reinterpret_cast<const __half2*>(&kp), __hmul2(__low2half2(A), *reinterpret_cast<const __half2*>(&k)));
    return *reinterpret_cast<const uint32_t*>(&r);
}
#define CMUL(orr, oi, ar, ai, br, bi) do { float _r = (ar) * (br) - (ai) * (bi); float _i = (ar) * (bi) + (ai) * (br); orr = _r; oi = _i; } while (0)
#define CSQ(orr, oi, ar, ai) do { float _r = (ar) * (ar) - (ai) * (ai); float _i = 2.f * (ar) * (ai); orr = _r; oi = _i; } while (0)

__device__ __forceinline__ void mma_bf_k8z(float (&d)[4], uint32_t a0, uint32_t a1, uint32_t b0) {
    asm volatile("mma.sync.aligned.m16n8k8.row.col.f32.bf16.bf16.f32 {%0,%1,%2,%3}, {%4,%5}, {%6}, {%7,%7,%7,%7};"
        : "=f"(d[0]), "=f"(d[1]), "=f"(d[2]), "=f"(d[3]) : "r"(a0), "r"(a1), "r"(b0), "f"(0.f));
}
__device__ __forceinline__ void mma_hh_k8(uint32_t& d0, uint32_t& d1, uint32_t a0, uint32_t a1, uint32_t b0) {
    asm volatile("mma.sync.aligned.m16n8k8.row.col.f16.f16.f16.f16 {%0,%1}, {%2,%3}, {%4}, {%5,%5};"
        : "=r"(d0), "=r"(d1) : "r"(a0), "r"(a1), "r"(b0), "r"(0));
}
__device__ __forceinline__ uint32_t pin(uint32_t x, int lane) { return __shfl_sync(0xffffffffu, x, lane); }
template <class T> __device__ __forceinline__ T* pin(T* x, int lane) { return (T*)__shfl_sync(0xffffffffu, (unsigned long long)x, lane); }
__device__ __forceinline__ void sts32_if(bool on, uint32_t a, uint32_t v) {
    asm volatile("{\n\t.reg .pred p;\n\tsetp.ne.u32 p, %2, 0;\n\t@p st.shared.u32 [%0], %1;\n\t}" :: "r"(a), "r"(v), "r"((uint32_t)on) : "memory");
}
__device__ __forceinline__ void sts128_if(bool on, uint32_t a, uint32_t x, uint32_t y, uint32_t z, uint32_t w) {
    asm volatile("{\n\t.reg .pred p;\n\tsetp.ne.u32 p, %5, 0;\n\t@p st.shared.v4.u32 [%0], {%1,%2,%3,%4};\n\t}" :: "r"(a), "r"(x), "r"(y), "r"(z), "r"(w), "r"((uint32_t)on) : "memory");
}
__device__ __forceinline__ void lds128_if(bool on, uint32_t a, uint32_t (&v)[4]) {
    asm volatile("{\n\t.reg .pred p;\n\tsetp.ne.u32 p, %5, 0;\n\t@p ld.shared.v4.u32 {%0,%1,%2,%3}, [%4];\n\t}"
        : "+r"(v[0]), "+r"(v[1]), "+r"(v[2]), "+r"(v[3]) : "r"(a), "r"((uint32_t)on) : "memory");
}
__device__ __forceinline__ uint32_t hfma2_bf(uint32_t a, uint32_t b, uint32_t c) { uint32_t r; asm("fma.rn.bf16x2 %0, %1, %2, %3;" : "=r"(r) : "r"(a), "r"(b), "r"(c)); return r; }
__device__ __forceinline__ uint32_t row_elem(uint32_t row) { return ((row >> 5) & 4) | ((row >> 2) & 2) | ((row >> 4) & 1); }
__device__ __forceinline__ uint32_t gate_pos(uint32_t row) { return ((row >> 9) << 8) | ((row & 7) << 5) | (row_elem(row) << 2) | ((row >> 5) & 3); }

template <int N, bool BULK>
__device__ __forceinline__ void mix_rows(const Params& p, const CUtensorMap* tm_out, uint32_t sb, uint32_t ob, int Q0, int Q1, int w, int h, int pr, int lane) {
    const int g = lane >> 2, t = lane & 3, mi = lane >> 3, r = lane & 7;
    const int m8 = 16 * (g >> 2) + ((g >> 1) & 1) + 2 * (g & 1);
    uint32_t yi = sb + (4 * (r >> 1) + 2 * (mi & 1) + (r & 1)) * 512 + (((4 * w + (mi >> 1)) ^ r) << 4);
    uint32_t xs = sb + OFF_S + s_addr(w * S_PL + 32 + m8 * 32, t >> 1) + ((t & 1) << 3);
    uint32_t gs = sb + OFF_GP + w * 64 + g * 8, os = ob + m8 * 32 + t * 8;
    if (N > 1) { yi = pin(yi, lane); xs = pin(xs, lane); gs = pin(gs, lane); os = pin(os, lane); }
    mbar_wait(sb + M_BARS + 8 * B_Y);
#pragma unroll 1
    for (int Q = Q0; Q < Q1; Q++) {
        uint2 xq[N][4];
        uint32_t gg[N][4], sw[N];
#pragma unroll
        for (int n = 0; n < N; n++) {
#pragma unroll
            for (int i = 0; i < 4; i++) xq[n][i] = lds64((xs ^ (((i ^ n) & 1) << 4)) + Q * S_Q + n * 4 * S_PL + i * 128);
            const uint2 gq = lds64(gs + Q * 512 + n * 256);
            sw[n] = lds32(sb + M_BMAP + w * 16 + n * 64 + Q * 4);
#pragma unroll
            for (int i = 0; i < 4; i++) {
                gg[n][i] = __byte_perm(i < 2 ? gq.x : gq.y, 0, (i & 1) ? 0x3232 : 0x1010);
                const uint32_t og = hfma2_bf(gg[n][i], 0xBF80BF80u, 0x3F803F80u);
                xq[n][i].x = hmul2_bf(og, xq[n][i].x); xq[n][i].y = hmul2_bf(og, xq[n][i].y);
            }
        }
        if (N > 1 && Q == PWQ) mbar_wait(sb + M_BARS + 8 * (B_W + PW));
        mbar_wait(sb + M_BARS + 8 * (B_Y + Q));
        __syncwarp();
#pragma unroll
        for (int n = 0; n < N; n++) {
#pragma unroll
            for (int x = 0; x < 2; x++) {
                uint32_t y[4];
                ldsm4t((yi ^ (x << 5)) + y_off(Q) + n * 256, y[0], y[1], y[2], y[3]);
#pragma unroll
                for (int e = 0; e < 2; e++) {
                    uint2& o = xq[n][2 * x + e];
                    o.x = hfma2_bf(gg[n][2 * x + e], y[2 * e], o.x); o.y = hfma2_bf(gg[n][2 * x + e], y[2 * e + 1], o.y);
                }
            }
        }
        if (BULK && (sw[0] | sw[N - 1]) == 0) {
#pragma unroll
            for (int n = 0; n < N; n++)
#pragma unroll
                for (int i = 0; i < 4; i++)
                    asm volatile("st.shared.v2.u32 [%0], {%1, %2};" :: "r"(os + Q * 1024 + n * 4 * TAB_W + i * 128), "r"(xq[n][i].x), "r"(xq[n][i].y) : "memory");
            asm volatile("fence.proxy.async.shared::cta;" ::: "memory");
            __syncwarp();
#pragma unroll
            for (int n = 0; n < N; n++)
                asm volatile("{\n\t.reg .pred p;\n\telect.sync _|p, 0xffffffff;\n\t"
                             "@p cp.async.bulk.tensor.3d.global.shared::cta.bulk_group [%1, {%2, %3, %4}], [%0];\n\t}"
                    :: "r"(ob + 4 * n * TAB_W + Q * 1024), "l"(tm_out), "r"(16 * pr), "r"(64 * Q + 32 * h), "r"(w + 4 * n) : "memory");
        } else {
            bf16* op = p.out + (size_t)(512 * Q + 256 * h + 8 * m8 + w) * D_ + 16 * pr + 4 * t;
#pragma unroll
            for (int n = 0; n < N; n++)
#pragma unroll
                for (int i = 0; i < 4; i++)
                    if (!((sw[n] >> (4 * g)) & (1u << i))) *(uint2*)(op + (size_t)(32 * i + 4 * n) * D_) = xq[n][i];
        }
    }
}

__global__ void __cluster_dims__(2, 1, 1) __launch_bounds__(NTHREADS, 1)
fused_kernel(const Params p, const __grid_constant__ CUtensorMap tm_gu, const __grid_constant__ CUtensorMap tm_down,
             const __grid_constant__ CUtensorMap tm_x, const __grid_constant__ CUtensorMap tm_out) {
    extern __shared__ __align__(1024) unsigned char smem[];
    const uint32_t sb = smem_u32(smem);
    int tid;
    asm volatile("mov.u32 %0, %%tid.x;" : "=r"(tid));
    const int pw = tid >> 5, lane = tid & 31;
    const int c = blockIdx.x, h = c & 1, pr = c >> 1;
    const uint32_t bars = sb + M_BARS;

    uint2 v_la, v_ai, v_cr, v_ci;
    uint32_t ldt16;
    {
        const uint32_t po = c * 256 + tid;
        asm volatile("{\n\t.reg .pred p;\n\t.reg .b64 a;\n\tsetp.ne.u32 p, %16, 0;\n\t"
                     "mad.wide.u32 a, %14, 8, %9;\n\t@p ld.global.nc.L1::no_allocate.v2.u32 {%0,%1}, [a];\n\t"
                     "mad.wide.u32 a, %15, 2, %13;\n\t@p ld.global.nc.u16 %8, [a];\n\t"
                     "mad.wide.u32 a, %14, 8, %10;\n\t@p ld.global.nc.L1::no_allocate.v2.u32 {%2,%3}, [a];\n\t"
                     "mad.wide.u32 a, %14, 8, %11;\n\t@p ld.global.nc.L1::no_allocate.v2.u32 {%4,%5}, [a];\n\t"
                     "mad.wide.u32 a, %14, 8, %12;\n\t@p ld.global.nc.L1::no_allocate.v2.u32 {%6,%7}, [a];\n\t}"
            : "=r"(v_la.x), "=r"(v_la.y), "=r"(v_ai.x), "=r"(v_ai.y), "=r"(v_cr.x), "=r"(v_cr.y), "=r"(v_ci.x), "=r"(v_ci.y), "=r"(ldt16)
            : "l"(p.logA), "l"(p.Aim), "l"(p.Cre), "l"(p.Cim), "l"(p.logdt), "r"(po), "r"(po >> 5), "r"((uint32_t)(tid < 256 && c < 128)));
    }

    if (c >= 128) {
        if (c != 128) return;
        RSTAMP(5);
        const unsigned tag = (*(volatile unsigned*)&p.sc->epoch + 1) & 0xffffu;
        const uint32_t list = sb + 128;
#pragma unroll 1
        for (int pass = 0; pass < 2; pass++) {
            sts128(list + 16 * tid, 0, 0, 0, 0);
            if (tid == 0) sts32(sb + 64, 0);
            uint32_t key[4] = {tag - 1, tag - 1, tag - 1, tag - 1};
#pragma unroll 1
            for (int it = 0; it < (pass << 22); it++) {
                uint32_t a[4];
                asm volatile("{\n\t.reg .b128 o, z;\n\t.reg .b64 l, u;\n\tmov.b64 l, {%5, %5};\n\tmov.b128 z, {l, l};\n\tatom.relaxed.gpu.global.exch.b128 o, [%4], z;\n\t"
                             "mov.b128 {l, u}, o;\n\tmov.b64 {%0, %1}, l;\n\tmov.b64 {%2, %3}, u;\n\t}"
                    : "=r"(a[0]), "=r"(a[1]), "=r"(a[2]), "=r"(a[3]) : "l"(&p.sc->r[tid]), "r"(tag - 1) : "memory");
#pragma unroll
                for (int i = 0; i < 4; i++) if (((a[i] ^ tag) & 0xffffu) == 0) key[i] = a[i];
                if ((((key[0] ^ tag) | (key[1] ^ tag) | (key[2] ^ tag) | (key[3] ^ tag)) & 0xffffu) == 0) break;
            }
            WSTAMP(0);
            uint32_t m = 0;
#pragma unroll
            for (int i = 0; i < 4; i++) {
                key[i] = ((pass ? key[i] : (lane + i) << 16) & 0xffff0000u) | (uint32_t)(2047 - (4 * tid + i));
                m = max(m, key[i]);
            }
            const uint32_t wm = __reduce_max_sync(0xffffffffu, m);
            if (lane == 0) sts32(sb + pw * 4, wm);
            __syncthreads();
            uint32_t thr = 0xffffffffu;
#pragma unroll
            for (int i = 0; i < 4; i++) { const uint4 q = lds128(sb + 16 * i); thr = min(thr, min(max(q.x, q.y), max(q.z, q.w))); }
            if (thr != 1) WSTAMP(1);
            if (m >= thr) {
                uint32_t pos;
                asm volatile("atom.shared.add.u32 %0, [%1], %2;" : "=r"(pos) : "r"(sb + 64), "r"(4 * ((key[0] >= thr) + (key[1] >= thr) + (key[2] >= thr) + (key[3] >= thr))) : "memory");
#pragma unroll
                for (int i = 0; i < 4; i++) if (key[i] >= thr) { sts32(list + pos, key[i]); pos += 4; }
            }
            __syncthreads();
            const uint32_t nc4 = lds32(sb + 64);
            if (nc4 != 1) WSTAMP(2);
#pragma unroll 1
            for (uint32_t j = 4 * pw; j < nc4; j += 64) {
                const uint32_t mine = lds32(list + j);
                int rank = 0;
#pragma unroll 1
                for (uint32_t i = 0; i < nc4; i += 128) rank += __popc(__ballot_sync(0xffffffffu, lds32(list + i + 4 * lane) > mine));
                if (rank < 8 && lane == 0) sts32(sb + 96 + 4 * rank, mine);
            }
            __syncthreads();
            if (tid < 8 * NTOP) st_gpu32(&p.sc->top[tid >> 3][tid & 7], lds32(sb + 96 + 4 * (tid & 7)) | (((tag + pass - 1) & 31) << 11));
            WSTAMP(3);
            if (!pass) RSTAMP(4);
        }
        WDUMP();
        return;
    }

    WSTAMP(0);
    if (pw < 8) {
        const int d = 8 * c + pw - MAIN_W0;
        if (lane == 0) asm volatile("cp.async.ca.shared.global [%0], [%1], 4;" :: "r"(sb + M_DSK + 4 * (pw - MAIN_W0)), "l"(p.Dskip + (d & ~1)) : "memory");
        asm volatile("barrier.cluster.arrive.relaxed.aligned;" ::: "memory");
        const int warp = pw - MAIN_W0;
        asm volatile("setmaxnreg.inc.sync.aligned.u32 160;");
        const int g = lane >> 2, t = lane & 3;
        const int mi = lane >> 3, r = lane & 7;
        const uint32_t TB = sb + OFF_TAB + warp * TAB_W;
        const uint32_t UB = sb + OFF_U + warp * U_CH;
        if (mi < 2) sts128(UB + mi * U_PL + r * 16, 0, 0, 0, 0);
        if (lane < 4) sts128(TB + lane * T_PL, 0, 0, 0, 0);
        sts128(sb + OFF_SCR + warp * 8192 + lane * 16, 0x3C00u, 0x3C00u, 0x3C00u, 0x3C00u);
        __syncwarp();

        uint32_t cfix;
        {
            KSTAMP(4, v_la.x ^ v_ai.x ^ v_cr.x ^ v_ci.x ^ ldt16);
            const float dt = bf_round(exp_acc(__uint_as_float(ldt16 << 16)));
            float l2[4], li[4];
            {
                const uint32_t la[2] = {v_la.x, v_la.y}, ai[2] = {v_ai.x, v_ai.y};
                const float dt2 = -1.4426950408889634f * dt;
#pragma unroll
                for (int i = 0; i < 4; i++) {
                    l2[i] = bf_round(ex2f(((i & 1) ? bf_hi(la[i >> 1]) : bf_lo(la[i >> 1])) * 1.4426950408889634f)) * dt2;
                    li[i] = ((i & 1) ? bf_hi(ai[i >> 1]) : bf_lo(ai[i >> 1])) * dt;
                }
            }
            const uint32_t SX = sb + OFF_SCR + warp * 8192;
            const uint32_t sw = SX + (lane << 4);
#define PUT(buf, row, v) sts128(((sw + (row) * 512) ^ ((row) << 4)) + (buf) * 4096, v[0], v[1], v[2], v[3])
#define EMIT(bufa, rowa, bufb, rowb, xr, xi, k, kp) do { uint32_t pk[4], pd[4]; \
                _Pragma("unroll") for (int i = 0; i < 4; i++) { pk[i] = pack_h(xr[i], xi[i]); pd[i] = hcmul(pk[i], k[i], kp[i]); } \
                PUT(bufa, rowa, pk); PUT(bufb, rowb, pd); } while (0)
#define CMUL4(orr, oi, ar, ai, br, bi) _Pragma("unroll") for (int i = 0; i < 4; i++) CMUL(orr[i], oi[i], ar[i], ai[i], br[i], bi[i])
#define CSQ4(orr, oi, ar, ai) _Pragma("unroll") for (int i = 0; i < 4; i++) CSQ(orr[i], oi[i], ar[i], ai[i])
            float z1r[4], z1i[4], z2r[4], z2i[4], z8r[4], z8i[4], z256r[4], z256i[4];
            uint32_t k4[4], k4p[4];
            float z4r[4], z4i[4];
#pragma unroll
            for (int i = 0; i < 4; i++) cexp_pow(l2[i], li[i], 1.f, z1r[i], z1i[i]);
            CSQ4(z2r, z2i, z1r, z1i);
            CSQ4(z4r, z4i, z2r, z2i);
            CSQ4(z8r, z8i, z4r, z4i);
            KSTAMP(5, __float_as_uint(z8r[3]));
            uint32_t Ya[16][4];
            float cr[4], ci[4], inv;
            {
                float w1r[4], w1i[4], ar[4], ai[4], br[4], bi[4];
                uint32_t k8[4], k8p[4];
#pragma unroll
                for (int i = 0; i < 4; i++) {
                    k8[i] = pack_h(z8r[i], -z8i[i]); k8p[i] = pack_h(z8i[i], z8r[i]);
                    CSQ(w1r[i], w1i[i], z8r[i], z8i[i]); w1i[i] = -w1i[i];
                }
                PUT(1, 0, k8);
                EMIT(0, 1, 1, 1, w1r, w1i, k8, k8p);
                CSQ4(ar, ai, w1r, w1i);            EMIT(0, 2, 1, 2, ar, ai, k8, k8p);
                CMUL4(br, bi, ar, ai, w1r, w1i);   EMIT(0, 3, 1, 3, br, bi, k8, k8p);
                CSQ4(ar, ai, ar, ai);              EMIT(0, 4, 1, 4, ar, ai, k8, k8p);
                CMUL4(ar, ai, ar, ai, w1r, w1i);   EMIT(0, 5, 1, 5, ar, ai, k8, k8p);
                CSQ4(br, bi, br, bi);              EMIT(0, 6, 1, 6, br, bi, k8, k8p);
                CMUL4(br, bi, br, bi, w1r, w1i);   EMIT(0, 7, 1, 7, br, bi, k8, k8p);
                __syncwarp();
                KSTAMP(6, 0);
                const uint32_t ab = SX + (mi & 1) * 4096 + r * 512, ax = ((mi >> 1) ^ r) << 4;
                const uint32_t vr[2] = {v_cr.x, v_cr.y}, vi[2] = {v_ci.x, v_ci.y};
                const uint32_t m2 = __vmaxu2(__vmaxu2(vr[0] & 0x7fff7fffu, vr[1] & 0x7fff7fffu), __vmaxu2(vi[0] & 0x7fff7fffu, vi[1] & 0x7fff7fffu));
                const uint32_t mx = __reduce_max_sync(0xffffffffu, max(m2, m2 << 16));
                const uint32_t e = min(max(mx >> 23, 11u), 254u);
                const float sc = __uint_as_float((264u - e) << 23);
                inv = __uint_as_float((e - 10u) << 23) * (2.f * dt);
#pragma unroll
                for (int i = 0; i < 4; i++) {
#pragma unroll
                    for (int k = 0; k < 4; k++) ldsm4(ab + (ax ^ (i << 5)) + k * 128, Ya[4 * k + i][0], Ya[4 * k + i][1], Ya[4 * k + i][2], Ya[4 * k + i][3]);
                    float tr, ti;
                    cexp_pow(l2[i], li[i], 128.f, tr, ti);
                    sts32(TB + 2176 + 256 * i + 4 * lane, pack_h(tr, ti));
                    sts32(TB + 2176 + 256 * i + 128 + 4 * (lane ^ 16), pack_h(-ti, tr));
                    k4[i] = pack_h(z4r[i], z4i[i]); k4p[i] = pack_h(-z4i[i], z4r[i]);
                    CSQ(z256r[i], z256i[i], tr, ti);
                    cr[i] = ((i & 1) ? bf_hi(vr[i >> 1]) : bf_lo(vr[i >> 1])) * sc;
                    ci[i] = ((i & 1) ? bf_hi(vi[i >> 1]) : bf_lo(vi[i >> 1])) * sc;
                }
                __syncwarp();
            }
            KSTAMP(7, Ya[15][0]);
            const uint32_t ld0 = SX + r * 512 + ((mi ^ r) << 4), ld1 = ld0 ^ 64;
            float R[6][4], s1024;
            {
                float xr[4], xi[4], yr[4], yi[4];
                EMIT(0, 0, 0, 1, cr, ci, k4, k4p);
                CMUL4(yr, yi, cr, ci, z1r, z1i);        EMIT(0, 2, 0, 3, yr, yi, k4, k4p);
                CMUL4(xr, xi, cr, ci, z256r, z256i);    EMIT(1, 0, 1, 1, xr, xi, k4, k4p);
                CMUL4(yr, yi, yr, yi, z1r, z1i);        EMIT(0, 4, 0, 5, yr, yi, k4, k4p);
                CMUL4(cr, ci, xr, xi, z2r, z2i);        EMIT(1, 2, 1, 3, cr, ci, k4, k4p);
                CMUL4(yr, yi, yr, yi, z1r, z1i);        EMIT(0, 6, 0, 7, yr, yi, k4, k4p);
                CMUL4(xr, xi, xr, xi, z256r, z256i);    EMIT(1, 4, 1, 5, xr, xi, k4, k4p);
                CMUL4(xr, xi, xr, xi, z256r, z256i);    EMIT(1, 6, 1, 7, xr, xi, k4, k4p);
                CMUL4(xr, xi, xr, xi, z256r, z256i);
                s1024 = (xr[0] + xr[1]) + (xr[2] + xr[3]);
#pragma unroll
                for (int m = 0; m < 4; m++) {
                    if (m == 0) { CMUL4(xr, xi, xr, xi, z8r, z8i); } else { CMUL4(xr, xi, xr, xi, z256r, z256i); }
                    sts128(TB + m * T_PL + 16 + 16 * lane, pack_h(xr[0], xi[0]), pack_h(xr[1], xi[1]), pack_h(xr[2], xi[2]), pack_h(xr[3], xi[3]));
                }
            }
            asm volatile("barrier.cluster.wait.acquire.aligned;" ::: "memory");
            __syncwarp();
            {
                KSTAMP(8, 0);
                uint32_t bd[2][4] = {{0, 0, 0, 0}, {0, 0, 0, 0}};
                const bool on = (g >> 1) == t;
#pragma unroll
                for (int i = 0; i < 6; i++) { R[i][0] = R[i][1] = R[i][2] = R[i][3] = 0.f; }
#pragma unroll
                for (int k2 = 0; k2 < 8; k2++) {
                    uint32_t x[4], y[4], z[4], a1[2][4];
                    lds128_if(on, TB + 2176 + g * 128 + (k2 < 4 ? 64 : -64) * (g & 1) + 16 * k2, bd[k2 & 1]);
                    ldsm4(TB + (r & 3) * T_PL + 16 + 16 * mi + 64 * k2, z[0], z[1], z[2], z[3]);
                    ldsm4(((k2 & 1) ? ld1 : ld0) + (k2 >> 1) * 128, x[0], x[1], x[2], x[3]);
                    ldsm4(((k2 & 1) ? ld1 : ld0) + (k2 >> 1) * 128 + 4096, y[0], y[1], y[2], y[3]);
#pragma unroll
                    for (int u = 0; u < 2; u++) {
                        mma_hh_k8(a1[u][0], a1[u][1], Ya[2 * k2 + u][0], Ya[2 * k2 + u][1], bd[k2 & 1][2 * u]);
                        mma_hh_k8(a1[u][2], a1[u][3], Ya[2 * k2 + u][2], Ya[2 * k2 + u][3], bd[k2 & 1][2 * u + 1]);
                    }
#pragma unroll
                    for (int u = 0; u < 2; u++) {
                        const uint32_t(&a0)[4] = Ya[2 * k2 + u];
                        mma_h(R[0], a0[0], a0[1], a0[2], a0[3], x[2 * u], x[2 * u + 1]);
                        mma_h(R[2], a0[0], a0[1], a0[2], a0[3], y[2 * u], y[2 * u + 1]);
                        mma_h(R[4], a0[0], a0[1], a0[2], a0[3], z[2 * u], z[2 * u + 1]);
                        mma_h(R[1], a1[u][0], a1[u][1], a1[u][2], a1[u][3], x[2 * u], x[2 * u + 1]);
                        mma_h(R[3], a1[u][0], a1[u][1], a1[u][2], a1[u][3], y[2 * u], y[2 * u + 1]);
                        mma_h(R[5], a1[u][0], a1[u][1], a1[u][2], a1[u][3], z[2 * u], z[2 * u + 1]);
                    }
                }
            }
            __syncwarp();
            KSTAMP(9, __float_as_uint(R[3][0]));
            if (lane == 0) mbar_arrive(bars + 8 * B_KG + (__float_as_uint(R[0][0]) & __float_as_uint(R[2][0]) & p.zero));
            sts128(TB + 2176 + 16 * lane, 0, 0, 0, 0);
            sts128(TB + 2688 + 16 * lane, 0, 0, 0, 0);
            __syncwarp();
#undef PUT
#undef EMIT
#pragma unroll
            for (int o = 16; o > 0; o >>= 1) s1024 += __shfl_xor_sync(0xffffffffu, s1024, o);
            uint32_t w[4][4], dsk = 0;
            cp_wait_all();
            asm volatile("{\n\t.reg .pred p;\n\tsetp.eq.u32 p, %2, 0;\n\t@p ld.shared.u16 %0, [%1];\n\t}" : "+r"(dsk) : "r"(sb + M_DSK + 4 * warp + 2 * (warp & 1)), "r"(lane) : "memory");
#pragma unroll
            for (int a = 0; a < 4; a++) {
                const float v0 = (a == 0) ? fmaf(R[0][0], inv, __uint_as_float(dsk << 16)) : R[a][0] * inv;
                const float v1 = R[a][1] * inv, v2 = R[a][2] * inv, v3 = R[a][3] * inv;
                w[a][0] = pack_bf(v0, 0.f); w[a][1] = pack_bf(v1, v0); w[a][2] = pack_bf(v2, v1); w[a][3] = pack_bf(v3, v2);
            }
            const uint32_t wb = TB + 16 + 16 * g, w1 = wb + t * T_PL, w2 = wb + 256 + 2 * t * T_PL;
            const uint32_t w3 = (t == 0) ? wb + 256 + 3 * T_PL : TB + T_A + 8 * (16 * t + g);
            const uint32_t w3s = (t == 0) ? 128 : 64, w3o = (t == 0) ? 8 : 12;
            const uint32_t k512 = __shfl_sync(0xffffffffu, w[2][1], 2);
#pragma unroll
            for (int a = 0; a < 2; a++) {
                sts128(w1 + 128 * a, w[a][0], w[a][1], w[a][2], w[a][3]);
                const uint32_t(&q)[4] = w[2 + a];
                if (t < 2) sts128(w2 + 128 * a, q[0], q[1], q[2], q[3]);
                if (t == 0) { sts128(w2 + T_PL + 128 * a, q[0], q[1], q[2], q[3]); sts32(w3 + 128 * a + 4, q[2]); }
                sts32_if(t != 1 && (a == 1 || lane != 2), w3 + w3s * a, q[1]);
                sts32_if(t != 1, w3 + w3s * a + w3o, q[3]);
            }
            sts128_if(lane < 4, w1 + 512, t == 3 ? k512 : k512 >> 16, t < 2 ? k512 : t == 2 ? k512 & 0xffff0000u : k512 << 16, t < 2 ? k512 << 16 : 0u, 0);
            __syncwarp();
#pragma unroll
            for (int a = 0; a < 2; a++) {
                sts16(w1 + 128 * a + 18, w[a][3]);
                const uint32_t(&q)[4] = w[2 + a];
                if (t < 2) sts16(w2 + 128 * a + 18, q[3]);
                if (t == 0) { sts16(w2 + T_PL + 128 * a + 18, q[3]); sts16(w3 + 128 * a + 14, q[3]); }
            }
            if (t == 0) sts16(w3 + 128 - 4, w[3][0]);
            if (lane == 2 || (t == 0 && g > 0)) sts16(lane == 2 ? TB + 16 + 3 * T_PL + 4 * 127 : w3 - 4, w[2][0]);
            {
                float q[4];
#pragma unroll
                for (int i = 0; i < 4; i++) q[i] = (t < 2 ? R[4][i] : R[5][i]) * inv;
                const uint32_t b0 = pack_bf(q[0], q[2]), b1 = pack_bf(q[1], q[3]);
                const uint32_t wq = TB + T_B + 8 * (65 + 32 * (t & 1) + 4 * (t & 2) + g);
                sts32(wq, b0); sts32(wq + 12, b0); sts32(wq + 128, b1); sts32(wq + 140, b1);
            }
            cfix = pack_bf(s1024 * inv, s1024 * inv);
            if (lane == 0) sts32(TB + T_A + 8 * 64, cfix);
            __syncwarp();
        }
        WSTAMP(1);

        mbar_wait(bars + 8 * B_U);
        WSTAMP(2);

        float D[16][4];
        {
            const int x5 = g - t + 5;
            const uint32_t tabD = TB + (x5 & 3) * T_PL + (x5 & 12) + 16;
            {
                const uint32_t a1 = lds32(tabD - 8), a0 = p.zero;
#pragma unroll
                for (int jq = 0; jq < 4; jq++) {
                    uint32_t b[4];
                    ldsm4(UB + (9 + lane) * 16 + jq * 512, b[0], b[1], b[2], b[3]);
#pragma unroll
                    for (int i = 0; i < 4; i++) mma_bf_k8z(D[4 * jq + i], a0, a1, b[i]);
                }
            }
            const uint32_t ua = UB + (mi & 1) * U_PL + (8 + 8 * (mi >> 1) + r) * 16;
#pragma unroll 1
            for (int k0 = 0; k0 < 8; k0++) {
                uint32_t Uf[16][2];
#pragma unroll
                for (int jp = 0; jp < 8; jp++) ldsm4(ua + jp * 256 - k0 * 16, Uf[2 * jp][0], Uf[2 * jp][1], Uf[2 * jp + 1][0], Uf[2 * jp + 1][1]);
#pragma unroll
                for (int k1 = 0; k1 < 4; k1++) {
                    const uint32_t ta = tabD + 16 * (8 * k1 + k0);
                    const uint32_t a0 = lds32(ta), a1 = lds32(ta + 8), a2 = lds32(ta - 8), a3 = a0 ^ p.zero;
#pragma unroll
                    for (int J = k1; J < 16; J++) mma_bf(D[J], a0, a1, a2, a3, Uf[J - k1][0], Uf[J - k1][1]);
                }
                if (k0 == 0) {
                    const uint32_t ta = tabD + 16 * 32;
                    const uint32_t a0 = lds32(ta), a1 = lds32(ta + 8), a2 = lds32(ta - 8), a3 = a0 ^ p.zero;
#pragma unroll
                    for (int J = 4; J < 16; J++) mma_bf(D[J], a0, a1, a2, a3, Uf[J - 4][0], Uf[J - 4][1]);
                    const uint32_t f0 = (cfix ^ 0x80008000u) & (g == t ? 0xffffu : g == t + 4 ? 0xffff0000u : 0u);
                    const uint32_t f1 = p.zero, f2 = p.zero + p.zero, f3 = f0 ^ p.zero;
#pragma unroll
                    for (int J = 8; J < 16; J++) mma_bf(D[J], f0, f1, f2, f3, Uf[J - 8][0], Uf[J - 8][1]);
                }
            }
        }
        WSTAMP(3);
        {
            const int ch = 8 * h + warp;
            const uint32_t yo = sb + ch * 512 + ((lane ^ (((ch >> 2) << 1) | (ch & 1))) << 4);
            const uint32_t yr = mapa(yo, h ^ 1), ybr = mapa(bars + 8 * B_Y, h ^ 1);
            auto ship = [&](const int Q) {
                uint4 y[2];
#pragma unroll
                for (int hh = 0; hh < 2; hh++) {
                    const int J = 4 * Q + 2 * hh;
                    y[hh] = make_uint4(pack_bf(D[J][0], D[J][1]), pack_bf(D[J][2], D[J][3]), pack_bf(D[J + 1][0], D[J + 1][1]), pack_bf(D[J + 1][2], D[J + 1][3]));
                }
                if (!(Q & 1)) mbar_wait(bars + 8 * (B_F + (Q >> 1)));
                asm volatile("{\n\t.reg .pred p;\n\tsetp.eq.u32 p, %11, 0;\n\t"
                             "@p st.async.weak.shared::cluster.mbarrier::complete_tx::bytes.v4.b32 [%9], {%4,%5,%6,%7}, [%10];\n\t"
                             "@!p st.async.weak.shared::cluster.mbarrier::complete_tx::bytes.v4.b32 [%9], {%0,%1,%2,%3}, [%10];\n\t"
                             "@p st.shared.v4.b32 [%8], {%0,%1,%2,%3};\n\t@!p st.shared.v4.b32 [%8], {%4,%5,%6,%7};\n\t}"
                             :: "r"(y[0].x), "r"(y[0].y), "r"(y[0].z), "r"(y[0].w), "r"(y[1].x), "r"(y[1].y), "r"(y[1].z), "r"(y[1].w),
                                "r"(yo + y_off(Q)), "r"(yr + y_off(Q)), "r"(ybr + 8 * Q), "r"(h) : "memory");
                __syncwarp();
                if (lane == 0) mbar_arrive(bars + 8 * (B_Y + Q));
            };
            ship(0);
            const uint4 bA = lds128(sb + OFF_BAND + (g - t + 3) * 48), bB = lds128(sb + OFF_BAND + (g - t + 3) * 48 + 16);
            const uint2 bC = lds64(sb + OFF_BAND + (g - t + 3) * 48 + 32);
            uint2 QA[5][2], QB[8];
            const uint32_t tq = TB + 8 * (1 + g - 2 * t);
#pragma unroll
            for (int dd = 0; dd < 5; dd++) { QA[dd][0] = lds64(tq + T_A + 64 * (dd + 4)); QA[dd][1] = lds64(tq + T_A + 64 * (dd + 4) - 8); }
#pragma unroll
            for (int dd = 0; dd < 8; dd++) QB[dd] = lds64(tq + T_B + 64 * (dd + 8));
            const uint32_t u1 = UB + (mi & 1) * U_PL + (7 + r + (mi >> 1)) * 16;
            const uint32_t u2 = UB + ((mi & 1) ^ 1) * U_PL + (7 + r + (mi & 1) + 8 * (mi >> 1)) * 16;
            uint32_t n[4];
#pragma unroll
            for (int j = 0; j < 12; j++) {
                uint32_t m[4];
                ldsm4(u1 + j * 128, m[0], m[1], m[2], m[3]);
                if (!(j & 1)) ldsm4(u2 + j * 128, n[0], n[1], n[2], n[3]);
                const uint32_t n0 = n[2 * (j & 1)], n1 = n[2 * (j & 1) + 1];
                float wa[4], wb[4], wc[4], g1[4], g2[4];
                mma_bf_z(wa, bA.x, bA.y, bA.z, bA.w, m[0], m[1]);
                mma_bf_z(wb, bA.x, bA.y, bA.z, bA.w, n0, n1);
                mma_bf_z(wc, bA.x, bA.y, bA.z, bA.w, m[2], m[3]);
                if (j < 8) {
                    mma_bf_z(g1, bB.x, bB.y, bB.z, bB.w, m[0], m[1]);
                    mma_bf_z(g2, bB.x, bB.y, bB.z, bB.w, n0, n1);
                    mma_bf_k8(g1, bC.x, bC.y, m[2]);
                    mma_bf_k8(g2, bC.x, bC.y, m[3]);
                }
#pragma unroll
                for (int e = 0; e < 2; e++) {
                    const uint32_t q0 = pack_bf(wa[e], wa[e + 2]), q1 = pack_bf(wb[e], wb[e + 2]), q2 = q1 ^ p.zero, q3 = pack_bf(wc[e], wc[e + 2]);
#pragma unroll
                    for (int dd = 0; dd < 5; dd++)
                        if (j + 4 + dd < 16) mma_bf(D[j + 4 + dd], q0, q1, q2, q3, QA[dd][e].x, QA[dd][e].y);
                }
                if (j < 8) {
                    const uint32_t q0 = pack_bf(g1[0], g1[2]), q1 = pack_bf(g2[0], g2[2]), q2 = pack_bf(g1[1], g1[3]), q3 = pack_bf(g2[1], g2[3]);
#pragma unroll
                    for (int dd = 7 - j; dd >= 0; dd--) mma_bf(D[j + 8 + dd], q0, q1, q2, q3, QB[dd].x, QB[dd].y);
                }
                if ((j & 3) == 3) {
                    WSTAMP(4 + 2 * (j >> 2));
                    if (j == 11 && LATE2) ship(2);
                    if (j != 7 || !LATE2) ship((j >> 2) + 1);
                }
            }
        }
        const int warpu = __reduce_max_sync(0xffffffffu, warp);
        mix_rows<1, BULKM>(p, &tm_out, sb, sb + OFF_U + warpu * U_CH + (warpu & 1) * 64, PQ, 4, warpu, h, pr, lane);
        if (BULKM) asm volatile("cp.async.bulk.commit_group;\n\tcp.async.bulk.wait_group.read 0;" ::: "memory");
        WSTAMP(10);
        WDUMP();
    } else if ((pw & 12) == AUX_W0) {
        const int v = __reduce_max_sync(0xffffffffu, pw & 3);
        const int at = tid & 127;
        const int g = lane >> 2, t = lane & 3;
        unsigned tag;
        const bool gu = c < NGU_CTA;
        {
            const uint32_t xb = sb + (v < 2 ? OFF_XSEL : OFF_RING + 2 * 8192) + v * 8192;
            const uint32_t gws = sb + M_DPIN;
            const uint32_t row = 16 * c + 4 * v + (g >> 1);
#pragma unroll
            for (int i = 0; i < 8; i++)
                asm volatile("cp.async.ca.shared.global [%0], [%1], 4;" :: "r"((i < 4 ? sb + OFF_GP : gws) + 512 * (i & 3) + (tid & 124) * 4 + (tid & 1) * 8 + (tid & 2) * 2),
                             "l"((i < 4 ? p.wr : p.gatew) + 256 * (i & 3) + (tid & 127) * 2) : "memory");
            if ((tid & 127) < 33) cp16(sb + OFF_BAND + (tid & 127) * 16, p.band + (tid & 127));
            asm volatile("barrier.cluster.arrive.relaxed.aligned;" ::: "memory");
            tag = __reduce_max_sync(0xffffffffu, (*(volatile unsigned*)&p.sc->epoch + 1) & 0xffffu);
            if (gu) st_gpu32((uint32_t*)&p.sc->h[(tag + 1) & 1][32 * c] + at, 0);
            if (v == 2) sts32(sb + M_BMAP + lane * 4, 0);
            if (at == 0) sts32(sb + M_TAG, tag << 16);
            cp_wait_all();
            bar_sync(1, 128);
            uint2 w[16];
#pragma unroll
            for (int kb = 0; kb < 16; kb++) w[kb] = lds64((g < 4 ? sb + OFF_GP : gws) + 128 * kb + 32 * (g & 2) + 16 * t + 8 * (g & 1));
            asm volatile("barrier.cluster.wait.acquire.aligned;" ::: "memory");
            mbar_wait(bars + 8 * (B_X + v));
            WSTAMP(10);
            float dr[4][4];
#pragma unroll
            for (int kb = 0; kb < 16; kb++) {
                const uint4 x = lds128(xb + (g >> 1) * 2048 + 128 * kb + 16 * (lane & 7));
                if (kb < 4) mma_bf_z(dr[kb], x.x, x.y, x.z, x.w, w[kb].x, w[kb].y);
                else mma_bf(dr[kb & 3], x.x, x.y, x.z, x.w, w[kb].x, w[kb].y);
            }
            float rs = ((dr[0][0] + dr[0][3]) + (dr[1][0] + dr[1][3])) + ((dr[2][0] + dr[2][3]) + (dr[3][0] + dr[3][3]));
            if (lane == 0) mbar_arrive(bars + 8 * (B_XE + v) + (__float_as_uint(rs) & p.zero));
            rs += __shfl_xor_sync(0xffffffffu, rs, 5);
            const uint32_t rb = pack_bf(0.f, rs);
            if (!(lane & 7)) st_gpu32((uint32_t*)p.sc->r + row, ((rb ^ (((int)rb >> 31) | 0x80000000u)) & 0xffff0000u) | tag);
            WSTAMP(1);
            {
                const int n = 3 + (lane >> 3) + 4 * (lane & 1);
                const uint32_t so = (n & 7) * S_PL + ((lane & 6) + (n >> 3)) * 32;
                const uint32_t src[2] = {sb + OFF_S + v * S_Q + s_addr(so, h), sb + OFF_S + v * S_Q + s_addr(so + 32, h)};
                const uint32_t dst = sb + OFF_U + g * U_CH + (8 + 32 * v + 16 * h + t) * 16;
                const uint32_t rdst = mapa(dst, h ^ 1), rbar = mapa(bars + 8 * B_U, h ^ 1);
                mbar_wait(bars + 8 * (B_S + v));
                WSTAMP(9);
                uint4 a[8];
#pragma unroll
                for (int b = 0; b < 2; b++) {
#pragma unroll
                    for (int j = 0; j < 8; j++) { const int u = 4 * b + (j >> 1) + 8 * (j & 1); ldsm4t((u < 8 ? src[u & 1] ^ 16 : src[u & 1]) + ((u >> 1) & 3) * 256, a[j].x, a[j].y, a[j].z, a[j].w); }
#pragma unroll
                    for (int j = 0; j < 8; j++) {
                        const int u = 4 * b + (j >> 1) + 8 * (j & 1);
                        if (u < 8) st_async16(rdst + ((u >> 1) & 3) * 64 + (u & 1) * U_PL, a[j], rbar);
                        else sts128(dst + ((u >> 1) & 3) * 64 + (u & 1) * U_PL, a[j].x, a[j].y, a[j].z, a[j].w);
                    }
                }
                if (h && v == 3) {
                    ldsm4t((src[0] ^ 16) + 1024, a[0].x, a[0].y, a[0].z, a[0].w);
                    ldsm4t(src[0] + 1024, a[1].x, a[1].y, a[1].z, a[1].w);
                    if (t == 0) {
                        st_async16(rdst + 256, make_uint4(a[0].x, a[0].y & 0xffffu, a[0].z & 0xffffu, a[0].w & 0xffffu), rbar);
                        sts128(dst + 256, a[1].x, a[1].y & 0xffffu, a[1].z & 0xffffu, a[1].w & 0xffffu);
                    }
                }
                __syncwarp();
                if (lane == 0) mbar_arrive(bars + 8 * B_U);
            }
            if ((lane & 7) == 2) st_gpu32((uint32_t*)p.sc->g + ((row & 256) << 2) + gate_pos(row), pack_bf(sigmoid_f(__uint_as_float(rb)), 0.f) | (tag << 16));
            WSTAMP(2);
        }
        {
            const bool lane0 = pin(lane, lane) == 0;
            const uint32_t own = pin(sb + OFF_XSEL + (at ^ ((at >> 1) & 4)) * 16, lane);
            float acc[8][4];
#pragma unroll
            for (int i = 0; i < 8; i++) { acc[i][0] = acc[i][1] = acc[i][2] = acc[i][3] = 0.f; }
            const int krow = ((lane >> 1) & 8) + (lane & 7);
            const uint32_t tile0 = pin(sb + OFF_RING + krow * 64 + ((((lane >> 3) & 1) ^ ((krow >> 1) & 3)) << 4), lane);
            const uint32_t xo = pin(sb + OFF_XSEL + (lane & 7) * XS_ROW + 512 * v + 2 * (lane & 24), lane);
            const uint32_t po = pin(sb + OFF_XSEL + t * XS_ROW + (g & 3) * 128 + (g & 1) * 64 + v * 16 + (lane >> 4) * 8, lane);
            const uint32_t po1 = pin(po + 64 - (g & 1) * 128, lane);
            uint32_t* hdst = pin((uint32_t*)&p.sc->h[tag & 1][32 * c] + at, lane);
            auto signal = [&](const int k, const uint32_t dep) {
                if (lane < 2 && v < 2)
                    asm volatile("st.async.weak.shared::cluster.mbarrier::complete_tx::bytes.b32 [%0], %1, [%2];"
                                 :: "r"(mapa(sb + M_SINK, lane)), "r"(dep), "r"(mapa(bars + 8 * (B_F + k), lane)) : "memory");
            };
#pragma unroll 1
            for (int i = 0; i < 4; i++) {
                const int s = 4 * i + v;
                uint32_t a[16][4], b[2][4];
                if (gu) {
                    const uint32_t tile = tile0 + (s < 14 ? s : v) * 8192;
                    if (lane0 && i > 1) mbar_arrive(bars + 8 * (B_E + s - 4));
                    if (i == 2) signal(0, 0);
                    mbar_wait(bars + 8 * (B_W + s));
#pragma unroll
                    for (int q = 0; q < 16; q++) ldsm4t((tile ^ ((q & 1) << 5)) + ((q >> 1) & 1) * 4096 + (q >> 2) * 1024, a[q][0], a[q][1], a[q][2], a[q][3]);
                }
                if (i == 0) {
                    if (gu) {
                        uint32_t dep = p.zero;
#pragma unroll
                        for (int q = 0; q < 16; q += 2) dep &= a[q][0] & a[q + 1][0];
                        if (lane == 0) mbar_arrive(bars + 8 * (B_E + v) + dep);
                    }
                    WSTAMP(11);
                    uint32_t top;
#pragma unroll 1
                    for (int it = 0; it < (1 << 22); it++) {
                        asm volatile("ld.relaxed.gpu.global.u32 %0, [%1];" : "=r"(top) : "l"(&p.sc->top[c % NTOP][g]) : "memory");
                        if (__all_sync(0xffffffffu, ((top ^ (tag << 11)) & 0xf800u) == 0)) break;
                        if (TSLEEP) __nanosleep(TSLEEP);
                    }
                    WSTAMP(3);
                    if (gu) {
                        const uint32_t k = 4 * h + v, row = __reduce_max_sync(0xffffffffu, lane == 4 * k ? ~top & 2047 : 0);
                        asm volatile("{\n\t.reg .pred p;\n\telect.sync _|p, 0xffffffff;\n\t"
                                     "@p cp.async.bulk.shared::cluster.global.mbarrier::complete_tx::bytes.multicast::cluster [%0], [%1], 2048, [%2], %3;\n\t}"
                            :: "r"(sb + OFF_XSEL + k * XS_ROW), "l"(p.u + (size_t)row * D_), "r"(bars + 8 * B_G), "h"((unsigned short)3) : "memory");
                    }
                    if (v == 2) {
                        const uint32_t row = ~top & 2047;
                        if (t == 0 && ((row >> 8) & 1) == h)
                            asm volatile("red.shared.or.b32 [%0], %1;" :: "r"(sb + M_BMAP + (row & 7) * 16 + (row >> 9) * 4), "r"(1u << (gate_pos(row) & 31)) : "memory");
                        if (t == 0) sts32(sb + M_TOP + lane, top);
                        if (c == 0 && lane == 0) *(volatile unsigned*)&p.sc->epoch = tag;
                        __syncwarp();
                        if (lane0) mbar_arrive(bars + 8 * B_Y);
                    }
                    if (!gu) break;
                    mbar_wait(bars + 8 * B_G);
                    WSTAMP(4);
                }
                ldsm4(xo + 128 * i, b[0][0], b[0][1], b[0][2], b[0][3]);
                ldsm4(xo + 128 * i + 64, b[1][0], b[1][1], b[1][2], b[1][3]);
#pragma unroll
                for (int q = 0; q < 16; q++) mma_bf(acc[q & 7], a[q][0], a[q][1], a[q][2], a[q][3], b[q >> 3][(q >> 1) & 2], b[q >> 3][((q >> 1) & 2) + 1]);
            }
            if (gu) {
                WSTAMP(5);
                __syncwarp();
#pragma unroll
                for (int q = 0; q < 4; q++) {
                    const int ct = q >> 1, e = 2 * (q & 1);
                    sts128(own + q * XS_ROW,
                           __float_as_uint(acc[ct][e] + acc[4 + ct][e]), __float_as_uint(acc[2 + ct][e] + acc[6 + ct][e]),
                           __float_as_uint(acc[ct][e + 1] + acc[4 + ct][e + 1]), __float_as_uint(acc[2 + ct][e + 1] + acc[6 + ct][e + 1]));
                }
                bar_sync(1, 128);
                float sl[2], uv[2];
#pragma unroll
                for (int e = 0; e < 2; e++) {
                    uint2 q[4];
#pragma unroll
                    for (int i = 0; i < 4; i++) q[i] = lds64((e ? po1 : po) + 512 * i);
                    const float s0 = (__uint_as_float(q[0].x) + __uint_as_float(q[1].x)) + (__uint_as_float(q[2].x) + __uint_as_float(q[3].x));
                    const float s1 = (__uint_as_float(q[0].y) + __uint_as_float(q[1].y)) + (__uint_as_float(q[2].y) + __uint_as_float(q[3].y));
                    const float gv = bf_round(p.gu_swap ? s1 : s0);
                    uv[e] = p.gu_swap ? s0 : s1;
                    sl[e] = gv * sigmoid_f(gv);
                }
                const uint32_t hw = hmul2_bf(pack_bf(sl[0], sl[1]), pack_bf(uv[0], uv[1]));
                st_gpu32(hdst, hw ? hw : 0x80000000u);
                signal(1, hw);
            }
        }
        WSTAMP(6);
        {
            const uint32_t own = pin(sb + OFF_XSEL + at * 16, lane);
            const uint32_t hb = sb + (v < 2 ? OFF_XSEL + 7168 * v : OFF_RING + 8192 * v), hl = pin(hb + 16 * lane, lane);
            const int krow = ((lane >> 1) & 8) + (lane & 7);
            const uint32_t tile = pin(sb + OFF_RING + v * 8192 + krow * 32 + ((((lane >> 3) ^ (krow >> 2)) & 1) << 4), lane);
            float dd[4][4];
            bar_sync(1, 128);
            mbar_wait(bars + 8 * (B_W + HW));
            WSTAMP(12);
            uint4 hq[7];
#pragma unroll 1
            for (int it = 0; it < (1 << 16); it++) {
                bulk_load(hb, &p.sc->h[tag & 1][32 * (56 * h + 14 * v)], 7168, bars + 8 * (B_X + v));
                uint32_t a[14][4], mn = 0xffffffffu;
                mbar_wait(bars + 8 * (B_W + 16 + v));
#pragma unroll
                for (int j = 0; j < 14; j++) ldsm4t(tile + (v & 2) * 16384 + j * 512, a[j][0], a[j][1], a[j][2], a[j][3]);
                mbar_wait(bars + 8 * (B_X + v), ~it & 1);
                WSTAMP(7);
#pragma unroll
                for (int j = 0; j < 7; j++) {
                    const uint4 q = lds128(hl + 512 * j);
                    mn = min(mn, q.x);
#pragma unroll
                    for (int e = 0; e < 2; e++) {
                        const uint32_t(&f)[4] = a[2 * j + e];
                        if (j < 2) mma_bf_z(dd[2 * j + e], f[0], f[1], f[2], f[3], e ? q.z : q.x, e ? q.w : q.y);
                        else mma_bf(dd[(2 * j + e) & 3], f[0], f[1], f[2], f[3], e ? q.z : q.x, e ? q.w : q.y);
                    }
                }
#pragma unroll
                for (int j = 0; j < 7; j++) { hq[j] = lds128(hl + 3584 + 512 * j); mn = min(mn, hq[j].x); }
                if (__all_sync(0xffffffffu, mn != 0)) break;
            }
            mbar_wait(bars + 8 * (B_W + 20 + v));
#pragma unroll
            for (int j = 0; j < 14; j++) {
                uint32_t f[4];
                ldsm4t(tile + 65536 + j * 512, f[0], f[1], f[2], f[3]);
                mma_bf(dd[(j + 2) & 3], f[0], f[1], f[2], f[3], (j & 1) ? hq[j >> 1].z : hq[j >> 1].x, (j & 1) ? hq[j >> 1].w : hq[j >> 1].y);
            }
            WSTAMP(8);
            uint4 part;
            part.x = __float_as_uint((dd[0][0] + dd[1][0]) + (dd[2][0] + dd[3][0])); part.y = __float_as_uint((dd[0][1] + dd[1][1]) + (dd[2][1] + dd[3][1]));
            part.z = __float_as_uint((dd[0][2] + dd[1][2]) + (dd[2][2] + dd[3][2])); part.w = __float_as_uint((dd[0][3] + dd[1][3]) + (dd[2][3] + dd[3][3]));
            st_async16(mapa(own + (M_DPIN - OFF_XSEL), h ^ 1), part, mapa(bars + 8 * B_DP, h ^ 1));
            sts128(own + 14336, part.x, part.y, part.z, part.w);
            __syncwarp();
            if (lane == 0) mbar_arrive(bars + 8 * B_DP);
        }
        WDUMP();
    } else {
        asm volatile("setmaxnreg.dec.sync.aligned.u32 64;");
        const int v = __reduce_max_sync(0xffffffffu, pw - PREP_W0);
        const bool gu = c < NGU_CTA;
        const uint32_t t0 = clock();
        const uint32_t bu = bars + 8 * v;
        if (lane == 0) {
#pragma unroll
            for (int i = 0; i < 10; i++) mbar_init(bu + 32 * i, 1);
            mbar_init(bu + 8 * B_X, 1);
            mbar_init(bu + 8 * B_XE, 1);
            mbar_init(bu + 8 * B_Y, v == 0 ? 11 : 9);
            mbar_init(bu + 8 * B_DP, (0x1855 >> (4 * v)) & 15);
            mbar_init(bu + 8 * B_F, 1);
            mbar_init(bu + 8 * B_H, 1);
            asm volatile("fence.mbarrier_init.release.cluster;" ::: "memory");
            mbar_expect(bu + 8 * B_Y, 4096);
            if (v != 2) mbar_expect(bu + 8 * B_DP, v == 0 ? 2048 : (h || v == 3) ? 16384 : 16384 + 128);
            mbar_expect(bu + 8 * B_F, c < NGU_CTA ? 16 : 0);
        }
        __syncwarp();
        asm volatile("barrier.cluster.arrive.relaxed.aligned;" ::: "memory");
        bulk_load(sb + (v < 2 ? OFF_XSEL : OFF_RING + 2 * 8192) + v * 8192, p.u + (size_t)(16 * c + 4 * v) * D_, 8192, bu + 8 * B_X);
        tma3d(sb + OFF_S + v * S_Q, &tm_x, 16 * pr, 64 * v + 32 * h - 1, bars + 8 * (B_S + v), S_Q);
        WSTAMP(9);
        if (v < 3 && lane == 0) asm volatile("prefetch.tensormap [%0];" :: "l"(v == 0 ? &tm_gu : v == 1 ? &tm_down : &tm_out) : "memory");
        asm volatile("barrier.cluster.wait.acquire.aligned;" ::: "memory");
        uint32_t desc;
        {
            const int s = 6 * v + lane, i = s >> 2, w = s & 3, slot = s < 14 ? s : (s | 1) == 17 ? s - 16 : s - 12;
            const int fb = s < 4 ? B_H : (gu && s >= 14) ? B_E + slot : s < 6 ? B_XE + s - 2 : B_KG;
            desc = slot | (fb << 4) | ((i < 4 ? 256 * w + 64 * i : 1792 * h + 448 * w + 224 * (i - 4)) << 10);
            if (lane < 6) mbar_expect(bars + 8 * (B_W + s), i < 4 ? 8192 : 7168);
            if (tid == 32 * PREP_W0) mbar_arrive(bars + 8 * B_H);
        }
        if (v == 3) {
            mbar_wait(bars + 8 * B_U);
            mbar_wait(bars + 8 * (gu ? B_G : B_H + 2));
            const uint32_t tag16 = lds32(sb + M_TAG);
            uint4 q[8];
#pragma unroll 1
            for (int it = 0; it < (1 << 22); it++) {
                uint32_t bad = 0;
#pragma unroll
                for (int i = 0; i < 8; i++) q[i] = ld_gpu128(&p.sc->g[256 * h + 32 * i + lane]);
#pragma unroll
                for (int i = 0; i < 8; i++) bad |= ((q[i].x ^ tag16) | (q[i].y ^ tag16)) | ((q[i].z ^ tag16) | (q[i].w ^ tag16));
                if ((bad >> 16) == 0) break;
                __nanosleep(200);
            }
#pragma unroll
            for (int i = 0; i < 8; i++)
                asm volatile("st.shared.v2.u32 [%0], {%1, %2};" :: "r"(sb + OFF_GP + 256 * i + lane * 8),
                             "r"(__byte_perm(q[i].x, q[i].y, 0x5410)), "r"(__byte_perm(q[i].z, q[i].w, 0x5410)) : "memory");
            __syncwarp();
            if (lane == 0) mbar_arrive(bars + 8 * B_Y);
        }
        mbar_wait(bars + 8 * (B_H + v));
        {
            const int gap = v == 0 ? GAP : v == 1 ? GAP1 : v == 2 ? GAP2 : GAP3;
            uint32_t last = v ? clock() - SLACK : t0 + T0 - GAP + STAG * ((pr * 5) & 15) / 16;
#pragma unroll 1
            while ((int)(last - clock()) > 500) __nanosleep(256);
#pragma unroll 1
            for (int k = 0; k < 6; k++) {
                const uint32_t dk = __reduce_max_sync(0xffffffffu, lane == k ? desc : 0);
                const bool dn = 6 * v + k >= 16;
                mbar_wait(bars + ((dk >> 1) & 0x1f8));
                uint32_t now;
#pragma unroll 1
                while ((int)((now = clock()) - last) < gap) __nanosleep(CSLEEP);
                last = max((int)(now - last) - SLACK, gap) + last;
                WSTAMP(3 + k);
                if (gu || dn)
                    asm volatile("{\n\t.reg .pred p;\n\telect.sync _|p, 0xffffffff;\n\t"
                                 "@p cp.async.bulk.tensor.3d.shared::cluster.global.mbarrier::complete_tx::bytes [%0], [%1, {%3, %4, 0}], [%2];\n\t}"
                        :: "r"(sb + OFF_RING + (dk & 15) * 8192), "l"(dn ? &tm_down : &tm_gu), "r"(bars + 8 * (B_W + 6 * v + k)), "r"(dn ? 16 * pr : 32 * c), "r"(dk >> 10) : "memory");
                if (k < 5 && PRESLEEP) __nanosleep(PRESLEEP);
            }
            if (lane == 0 && v < 3) mbar_arrive(bars + 8 * (B_H + v + 1));
        }
        {
            WSTAMP(1);
            mix_rows<2, true>(p, &tm_out, sb, sb + OFF_TAB + v * TAB_W, 0, PQ, v, h, pr, lane);
            WSTAMP(2);
            asm volatile("cp.async.bulk.commit_group;" ::: "memory");
            const uint32_t top = lds32(sb + M_TOP + 8 * v + 4 * (lane >> 4));
            const uint32_t row = ~top & 2047, ch = lane & 15, gp = gate_pos(row);
            const bool mine = ((row >> 8) & 1) == h;
            uint32_t gfin, x16, y16 = 0;
            asm volatile("ld.shared.u16 %0, [%1];" : "=r"(gfin) : "r"(sb + OFF_GP + gp * 2) : "memory");
            asm volatile("ld.shared.u16 %0, [%1];" : "=r"(x16) : "r"(sb + OFF_S + (row >> 9) * S_Q + s_addr((row & 7) * S_PL + 32 + (row & 248) * 4, ch >> 3) + 2 * (ch & 7)) : "memory");
            const float rsel = __uint_as_float(pin(__float_as_uint(bf_round(sigmoid_f(__uint_as_float((top ^ (((int)~top >> 31) | 0x80000000u)) & 0xffff0000u)))), lane));
            const uint32_t po = pin(sb + (4 * (ch & 7) + v) * 16 + (ch >> 3) * 8 + (lane >> 4) * 4, lane);
            bf16* op = pin(p.out + (size_t)row * D_ + 16 * pr + ch, lane);
            if (mine) {
                mbar_wait(bars + 8 * (B_Y + (row >> 9)));
                asm volatile("ld.shared.u16 %0, [%1];" : "=r"(y16)
                             : "r"(sb + y_off(row >> 9) + ch * 512 + (((4 * (row & 7) + ((row >> 5) & 3)) ^ (((ch >> 2) << 1) | (ch & 1))) << 4) + 2 * row_elem(row)) : "memory");
            }
            mbar_wait(bars + 8 * B_DP);
            float q[8];
#pragma unroll
            for (int i = 0; i < 4; i++) { q[i] = ldsf(po + M_DPIN + 512 * i); q[4 + i] = ldsf(po + OFF_XSEL + 14336 + 512 * i); }
            const float tot = ((q[0] + q[1]) + (q[2] + q[3])) + ((q[4] + q[5]) + (q[6] + q[7]));
            const float b = bf_round(__uint_as_float(x16 << 16) + bf_round(bf_round(tot) * rsel));
            if (mine) *op = __float2bfloat16_rn(fmaf(bf_lo(gfin), __uint_as_float(y16 << 16), bf_round(bf_round(1.f - bf_lo(gfin)) * b)));
        }
        asm volatile("cp.async.bulk.wait_group.read 0;" ::: "memory");
        WSTAMP(10);
        WDUMP();
    }
}

typedef CUresult (*EncodeFn)(CUtensorMap*, CUtensorMapDataType, cuuint32_t, void*, const cuuint64_t*, const cuuint64_t*,
                             const cuuint32_t*, const cuuint32_t*, CUtensorMapInterleave, CUtensorMapSwizzle,
                             CUtensorMapL2promotion, CUtensorMapFloatOOBfill);

void make_map(EncodeFn f, CUtensorMap* m, const void* ptr, uint64_t cols, uint64_t rows, uint64_t pitch, uint32_t bc, uint32_t br, CUtensorMapSwizzle sw, int prom,
              uint32_t planes = 1, uint64_t plane_stride = 0, uint32_t box_planes = 0) {
    cuuint64_t dims[3] = {cols, rows, planes};
    cuuint64_t str[2] = {pitch, planes > 1 ? plane_stride : pitch * rows};
    cuuint32_t box[3] = {bc, br, box_planes ? box_planes : planes};
    cuuint32_t es[3] = {1, 1, 1};
    f(m, CU_TENSOR_MAP_DATA_TYPE_BFLOAT16, 3, (void*)ptr, dims, str, box, es, CU_TENSOR_MAP_INTERLEAVE_NONE, sw,
      (CUtensorMapL2promotion)prom, CU_TENSOR_MAP_FLOAT_OOB_FILL_NONE);
}

}

extern "C" void kernel_launch(void* const* d_in, const int* in_sizes, int n_in, void* d_out, int out_size) {
    static EncodeFn enc = nullptr;
    static void *sc = nullptr, *band = nullptr;
    if (!enc) {
        void* fn = nullptr;
        cudaDriverEntryPointQueryResult qr;
        cudaGetDriverEntryPoint("cuTensorMapEncodeTiled", &fn, cudaEnableDefault, &qr);
        enc = (EncodeFn)fn;
        cudaGetSymbolAddress(&sc, g_scratch);
        cudaGetSymbolAddress(&band, g_band);
        cudaFuncSetAttribute(fused_kernel, cudaFuncAttributeMaxDynamicSharedMemorySize, SMEM_BYTES);
    }
    CUtensorMap tg, td, tx, to;
    const char *wg = (const char*)d_in[9], *wu = (const char*)d_in[10];
    const bool swap = wu < wg;
    make_map(enc, &tg, swap ? wu : wg, F_, D_, F_ * 2, 32, 64, CU_TENSOR_MAP_SWIZZLE_64B, PROMG, 2, swap ? wg - wu : wu - wg);
    make_map(enc, &td, d_in[11], D_, F_, D_ * 2, 16, 224, CU_TENSOR_MAP_SWIZZLE_32B, PROMD);
    make_map(enc, &tx, d_in[0], D_, L_ / 8, D_ * 16, 16, 33, CU_TENSOR_MAP_SWIZZLE_32B, PROMX, 8, D_ * 2);
    make_map(enc, &to, d_out, D_, L_ / 8, D_ * 16, 16, 32, CU_TENSOR_MAP_SWIZZLE_NONE, 0, 8, D_ * 2, 1);
    Params p;
    p.u = (const bf16*)d_in[0]; p.logA = (const bf16*)d_in[1]; p.Aim = (const bf16*)d_in[2];
    p.Cre = (const bf16*)d_in[3]; p.Cim = (const bf16*)d_in[4]; p.logdt = (const bf16*)d_in[5];
    p.Dskip = (const bf16*)d_in[6]; p.wr = (const bf16*)d_in[8]; p.gatew = (const bf16*)d_in[12];
    p.out = (bf16*)d_out;
    p.sc = (Scratch*)sc; p.band = (const uint4*)band;
    p.gu_swap = swap;
    p.zero = 0;
    fused_kernel<<<NCTA, NTHREADS, SMEM_BYTES>>>(p, tg, td, tx, to);
}
```

```cpp
#include <cuda_runtime.h>
#include <cuda_bf16.h>
#include <cuda_fp16.h>
#include <cuda.h>
#include <stdint.h>

typedef __nv_bfloat16 bf16;

namespace {

constexpr int L_ = 2048, D_ = 1024, F_ = 3584;
constexpr int NCTA = 130;
constexpr int NTHREADS = 512;
#define AUXW 12
constexpr int MAIN_W0 = 0, AUX_W0 = AUXW, PREP_W0 = 20 - AUXW;
#define T0 3300
#define GAP 540
#define GAP1 530
#define GAP2 530
#define GAP3 550
#define STAG GAP
#define CSLEEP 50
#define SLACK 300
#define TSLEEP 40
#define BULKM false
#define PW 19
#define PRESLEEP 64
#define PWQ 1
#define PQ 3
#define PROMG 2
#define PROMD 1
#define PROMX 0
#define LATE2 0
#define HW 20
constexpr int NGU_CTA = 112;

constexpr int OFF_RING = 0;
constexpr int OFF_SCR  = 6 * 8192;
constexpr int S_PL     = 1056;
constexpr int S_Q      = 8 * S_PL;
constexpr int OFF_S    = 114688;
constexpr int OFF_GP   = OFF_S + 4 * S_Q;
constexpr int U_PL     = 2240;
constexpr int U_CH     = 4416;
constexpr int OFF_U    = 151552;
constexpr int TAB_W    = 3200;
constexpr int T_PL     = 544;
constexpr int T_A      = 2192 - 26 * 8;
constexpr int T_B      = 2568 - 59 * 8;
constexpr int OFF_TAB  = 186880;
constexpr int OFF_XSEL = 212480;
constexpr int XS_ROW   = 2064;
constexpr int OFF_BAND = 228992;
constexpr int OFF_MISC = 229536;
constexpr int M_BARS   = OFF_MISC;
constexpr int M_DSK    = OFF_MISC + 2736;
constexpr int M_SINK   = OFF_MISC + 512;
constexpr int M_TAG    = OFF_MISC + 516;
constexpr int M_BMAP   = OFF_MISC + 528;
constexpr int M_DPIN   = OFF_MISC + 656;
constexpr int M_TOP    = OFF_MISC + 2704;
constexpr int SMEM_BYTES = OFF_MISC + 2768;
__device__ __forceinline__ uint32_t s_addr(uint32_t o, uint32_t half) { return o + (((half ^ (o >> 7)) & 1) << 4); }
__host__ __device__ constexpr uint32_t y_off(uint32_t q) { return OFF_RING + 32768 + (q & 1) * 8192 + (q >> 1) * 65536; }

constexpr int B_W = 0;
constexpr int B_E = 24;
constexpr int B_S = 36;
constexpr int B_Y = 40;
constexpr int B_DP = 44, B_U = 45, B_KG = 46, B_G = 47;
constexpr int B_F = 48;
constexpr int B_H = 60;
constexpr int B_X = 52, B_XE = 56;

struct BandTab { uint32_t w[11][12]; };
constexpr BandTab make_band() {
    BandTab b{};
    for (int cls = 0; cls < 11; cls++)
        for (int wd = 0; wd < 10; wd++) {
            const int tau = cls + 2 - 8 * ((wd < 4 ? wd : wd - 4) >> 1);
            const int lo = (wd < 4) ? ((wd & 1) ? -2 : 3) : ((wd & 1) ? -4 : -11), wid = (wd < 4 ? 3 : 7) + 2 * (wd & 1);
            b.w[cls][wd] = ((tau >= lo && tau < lo + wid) ? 0x3F80u : 0u) | ((tau - 4 >= lo && tau - 4 < lo + wid) ? 0x3F800000u : 0u);
        }
    return b;
}
constexpr int NTOP = 32;
struct Scratch {
    uint4 r[L_ / 4];
    uint4 g[L_ / 4];
    uint4 h[2][8 * F_ / 8];
    uint32_t top[NTOP][32];
    unsigned epoch;
};
__device__ __align__(128) Scratch g_scratch;
__device__ const __align__(16) BandTab g_band = make_band();

struct Params {
    const bf16 *u, *logA, *Aim, *Cre, *Cim, *logdt, *Dskip, *wr, *gatew;
    bf16* out;
    Scratch* sc;
    const uint4* band;
    uint32_t gu_swap;
    uint32_t zero;
};

#define WSTAMP(i) do {} while (0)
#define KSTAMP(i, dep) do {} while (0)
#define WDUMP() do {} while (0)
#define RSTAMP(i) do {} while (0)

__device__ __forceinline__ uint32_t smem_u32(const void* p) { return (uint32_t)__cvta_generic_to_shared(p); }
__device__ __forceinline__ void mbar_init(uint32_t b, uint32_t c) { asm volatile("mbarrier.init.shared::cta.b64 [%0], %1;" :: "r"(b), "r"(c) : "memory"); }
__device__ __forceinline__ void mbar_expect(uint32_t b, uint32_t tx) { asm volatile("mbarrier.arrive.expect_tx.shared::cta.b64 _, [%0], %1;" :: "r"(b), "r"(tx) : "memory"); }
__device__ __forceinline__ void mbar_arrive(uint32_t b) { asm volatile("mbarrier.arrive.shared::cta.b64 _, [%0];" :: "r"(b) : "memory"); }
__device__ __forceinline__ void mbar_wait(uint32_t b, uint32_t parity = 0) {
    asm volatile("{\n\t.reg .pred p;\nW%=:\n\tmbarrier.try_wait.parity.shared::cta.b64 p, [%0], %1, 20000;\n\t@!p bra W%=;\n\t}" :: "r"(b), "r"(parity) : "memory");
}
__device__ __forceinline__ uint32_t mapa(uint32_t addr, uint32_t rank) { uint32_t r; asm("mapa.shared::cluster.u32 %0, %1, %2;" : "=r"(r) : "r"(addr), "r"(rank)); return r; }
__device__ __forceinline__ void tma3d(uint32_t dst, const CUtensorMap* tm, int c0, int c1, uint32_t bar, uint32_t bytes) {
    asm volatile("{\n\t.reg .pred p;\n\telect.sync _|p, 0xffffffff;\n\t"
                 "@p mbarrier.arrive.expect_tx.shared::cta.b64 _, [%2], %5;\n\t"
                 "@p cp.async.bulk.tensor.3d.shared::cluster.global.mbarrier::complete_tx::bytes [%0], [%1, {%3, %4, 0}], [%2];\n\t}"
        :: "r"(dst), "l"(tm), "r"(bar), "r"(c0), "r"(c1), "r"(bytes) : "memory");
}
__device__ __forceinline__ void bulk_load(uint32_t dst, const void* src, uint32_t bytes, uint32_t bar) {
    asm volatile("{\n\t.reg .pred p;\n\telect.sync _|p, 0xffffffff;\n\t"
                 "@p mbarrier.arrive.expect_tx.shared::cta.b64 _, [%2], %3;\n\t"
                 "@p cp.async.bulk.shared::cluster.global.mbarrier::complete_tx::bytes [%0], [%1], %3, [%2];\n\t}"
        :: "r"(dst), "l"(src), "r"(bar), "r"(bytes) : "memory");
}
__device__ __forceinline__ void st_async16(uint32_t dst, const uint4& v, uint32_t bar) {
    asm volatile("st.async.weak.shared::cluster.mbarrier::complete_tx::bytes.v4.b32 [%0], {%1,%2,%3,%4}, [%5];"
                 :: "r"(dst), "r"(v.x), "r"(v.y), "r"(v.z), "r"(v.w), "r"(bar) : "memory");
}
__device__ __forceinline__ void bar_sync(int id, int n) { asm volatile("bar.sync %0, %1;" :: "r"(id), "r"(n) : "memory"); }
__device__ __forceinline__ void cp16(uint32_t dst, const void* src) { asm volatile("cp.async.cg.shared.global [%0], [%1], 16;" :: "r"(dst), "l"(src) : "memory"); }
__device__ __forceinline__ void cp_wait_all() { asm volatile("cp.async.wait_all;" ::: "memory"); }
__device__ __forceinline__ uint4 ld_gpu128(const void* p) { uint4 v; asm volatile("ld.relaxed.gpu.global.v4.u32 {%0,%1,%2,%3}, [%4];" : "=r"(v.x), "=r"(v.y), "=r"(v.z), "=r"(v.w) : "l"(p) : "memory"); return v; }
__device__ __forceinline__ void st_gpu32(void* p, uint32_t v) { asm volatile("st.relaxed.gpu.global.u32 [%0], %1;" :: "l"(p), "r"(v) : "memory"); }

__device__ __forceinline__ void ldsm4(uint32_t a, uint32_t& r0, uint32_t& r1, uint32_t& r2, uint32_t& r3) {
    asm volatile("ldmatrix.sync.aligned.m8n8.x4.shared.b16 {%0,%1,%2,%3}, [%4];" : "=r"(r0), "=r"(r1), "=r"(r2), "=r"(r3) : "r"(a) : "memory");
}
__device__ __forceinline__ void ldsm4t(uint32_t a, uint32_t& r0, uint32_t& r1, uint32_t& r2, uint32_t& r3) {
    asm volatile("ldmatrix.sync.aligned.m8n8.x4.trans.shared.b16 {%0,%1,%2,%3}, [%4];" : "=r"(r0), "=r"(r1), "=r"(r2), "=r"(r3) : "r"(a) : "memory");
}
__device__ __forceinline__ uint32_t lds32(uint32_t a) { uint32_t v; asm volatile("ld.shared.u32 %0, [%1];" : "=r"(v) : "r"(a) : "memory"); return v; }
__device__ __forceinline__ uint2 lds64(uint32_t a) { uint2 v; asm volatile("ld.shared.v2.u32 {%0,%1}, [%2];" : "=r"(v.x), "=r"(v.y) : "r"(a) : "memory"); return v; }
__device__ __forceinline__ uint4 lds128(uint32_t a) { uint4 v; asm volatile("ld.shared.v4.u32 {%0,%1,%2,%3}, [%4];" : "=r"(v.x), "=r"(v.y), "=r"(v.z), "=r"(v.w) : "r"(a) : "memory"); return v; }
__device__ __forceinline__ void sts32(uint32_t a, uint32_t v) { asm volatile("st.shared.u32 [%0], %1;" :: "r"(a), "r"(v) : "memory"); }
__device__ __forceinline__ void sts16(uint32_t a, uint32_t v) { asm volatile("st.shared.u16 [%0], %1;" :: "r"(a), "h"((unsigned short)v) : "memory"); }
__device__ __forceinline__ void sts128(uint32_t a, uint32_t x, uint32_t y, uint32_t z, uint32_t w) { asm volatile("st.shared.v4.u32 [%0], {%1,%2,%3,%4};" :: "r"(a), "r"(x), "r"(y), "r"(z), "r"(w) : "memory"); }
__device__ __forceinline__ float ldsf(uint32_t a) { float v; asm volatile("ld.shared.f32 %0, [%1];" : "=f"(v) : "r"(a) : "memory"); return v; }

__device__ __forceinline__ void mma_bf(float (&d)[4], uint32_t a0, uint32_t a1, uint32_t a2, uint32_t a3, uint32_t b0, uint32_t b1) {
    asm volatile("mma.sync.aligned.m16n8k16.row.col.f32.bf16.bf16.f32 {%0,%1,%2,%3}, {%4,%5,%6,%7}, {%8,%9}, {%0,%1,%2,%3};"
        : "+f"(d[0]), "+f"(d[1]), "+f"(d[2]), "+f"(d[3]) : "r"(a0), "r"(a1), "r"(a2), "r"(a3), "r"(b0), "r"(b1));
}
__device__ __forceinline__ void mma_bf_z(float (&d)[4], uint32_t a0, uint32_t a1, uint32_t a2, uint32_t a3, uint32_t b0, uint32_t b1) {
    asm volatile("mma.sync.aligned.m16n8k16.row.col.f32.bf16.bf16.f32 {%0,%1,%2,%3}, {%4,%5,%6,%7}, {%8,%9}, {%10,%10,%10,%10};"
        : "=f"(d[0]), "=f"(d[1]), "=f"(d[2]), "=f"(d[3]) : "r"(a0), "r"(a1), "r"(a2), "r"(a3), "r"(b0), "r"(b1), "f"(0.f));
}
__device__ __forceinline__ void mma_bf_k8(float (&d)[4], uint32_t a0, uint32_t a1, uint32_t b0) {
    asm volatile("mma.sync.aligned.m16n8k8.row.col.f32.bf16.bf16.f32 {%0,%1,%2,%3}, {%4,%5}, {%6}, {%0,%1,%2,%3};"
        : "+f"(d[0]), "+f"(d[1]), "+f"(d[2]), "+f"(d[3]) : "r"(a0), "r"(a1), "r"(b0));
}
__device__ __forceinline__ void mma_h(float (&d)[4], uint32_t a0, uint32_t a1, uint32_t a2, uint32_t a3, uint32_t b0, uint32_t b1) {
    asm volatile("mma.sync.aligned.m16n8k16.row.col.f32.f16.f16.f32 {%0,%1,%2,%3}, {%4,%5,%6,%7}, {%8,%9}, {%0,%1,%2,%3};"
        : "+f"(d[0]), "+f"(d[1]), "+f"(d[2]), "+f"(d[3]) : "r"(a0), "r"(a1), "r"(a2), "r"(a3), "r"(b0), "r"(b1));
}
__device__ __forceinline__ uint32_t pack_bf(float lo, float hi) { uint32_t r; asm("cvt.rn.bf16x2.f32 %0, %1, %2;" : "=r"(r) : "f"(hi), "f"(lo)); return r; }
__device__ __forceinline__ uint32_t pack_h(float lo, float hi) { uint32_t r; asm("cvt.rn.f16x2.f32 %0, %1, %2;" : "=r"(r) : "f"(hi), "f"(lo)); return r; }
__device__ __forceinline__ float bf_lo(uint32_t v) { return __uint_as_float(v << 16); }
__device__ __forceinline__ float bf_hi(uint32_t v) { return __uint_as_float(v & 0xffff0000u); }
__device__ __forceinline__ float bf_round(float x) { return __uint_as_float(pack_bf(0.f, x)); }
__device__ __forceinline__ uint32_t hmul2_bf(uint32_t a, uint32_t b) { uint32_t r; asm("mul.rn.bf16x2 %0, %1, %2;" : "=r"(r) : "r"(a), "r"(b)); return r; }
__device__ __forceinline__ float ex2f(float x) { float r; asm("ex2.approx.ftz.f32 %0, %1;" : "=f"(r) : "f"(x)); return r; }

__device__ __forceinline__ float exp_acc(float x) {
    const float t = x * 1.4426950216293335f;
    const float r = fmaf(x, 1.4426950216293335f, -t) + x * 1.9259629911266175e-8f;
    return ex2f(t) * fmaf(r, 0.6931471805599453f, 1.f);
}
__device__ __forceinline__ float sigmoid_f(float x) { return __fdividef(1.f, 1.f + ex2f(-x * 1.4426950408889634f)); }
__device__ __forceinline__ void cexp_pow(float l2, float li, float e, float& zr, float& zi) {
    const float mag = ex2f(l2 * e);
    zr = mag * __cosf(li * e);
    zi = mag * __sinf(li * e);
}
__device__ __forceinline__ uint32_t hcmul(uint32_t a, uint32_t k, uint32_t kp) {
    const __half2 A = *reinterpret_cast<const __half2*>(&a);
    const __half2 r = __hfma2(__high2half2(A), *reinterpret_cast<const __half2*>(&kp), __hmul2(__low2half2(A), *reinterpret_cast<const __half2*>(&k)));
    return *reinterpret_cast<const uint32_t*>(&r);
}
#define CMUL(orr, oi, ar, ai, br, bi) do { float _r = (ar) * (br) - (ai) * (bi); float _i = (ar) * (bi) + (ai) * (br); orr = _r; oi = _i; } while (0)
#define CSQ(orr, oi, ar, ai) do { float _r = (ar) * (ar) - (ai) * (ai); float _i = 2.f * (ar) * (ai); orr = _r; oi = _i; } while (0)

__device__ __forceinline__ void mma_bf_k8z(float (&d)[4], uint32_t a0, uint32_t a1, uint32_t b0) {
    asm volatile("mma.sync.aligned.m16n8k8.row.col.f32.bf16.bf16.f32 {%0,%1,%2,%3}, {%4,%5}, {%6}, {%7,%7,%7,%7};"
        : "=f"(d[0]), "=f"(d[1]), "=f"(d[2]), "=f"(d[3]) : "r"(a0), "r"(a1), "r"(b0), "f"(0.f));
}
__device__ __forceinline__ void mma_hh_k8(uint32_t& d0, uint32_t& d1, uint32_t a0, uint32_t a1, uint32_t b0) {
    asm volatile("mma.sync.aligned.m16n8k8.row.col.f16.f16.f16.f16 {%0,%1}, {%2,%3}, {%4}, {%5,%5};"
        : "=r"(d0), "=r"(d1) : "r"(a0), "r"(a1), "r"(b0), "r"(0));
}
__device__ __forceinline__ uint32_t pin(uint32_t x, int lane) { return __shfl_sync(0xffffffffu, x, lane); }
template <class T> __device__ __forceinline__ T* pin(T* x, int lane) { return (T*)__shfl_sync(0xffffffffu, (unsigned long long)x, lane); }
__device__ __forceinline__ void sts32_if(bool on, uint32_t a, uint32_t v) {
    asm volatile("{\n\t.reg .pred p;\n\tsetp.ne.u32 p, %2, 0;\n\t@p st.shared.u32 [%0], %1;\n\t}" :: "r"(a), "r"(v), "r"((uint32_t)on) : "memory");
}
__device__ __forceinline__ void sts128_if(bool on, uint32_t a, uint32_t x, uint32_t y, uint32_t z, uint32_t w) {
    asm volatile("{\n\t.reg .pred p;\n\tsetp.ne.u32 p, %5, 0;\n\t@p st.shared.v4.u32 [%0], {%1,%2,%3,%4};\n\t}" :: "r"(a), "r"(x), "r"(y), "r"(z), "r"(w), "r"((uint32_t)on) : "memory");
}
__device__ __forceinline__ void lds128_if(bool on, uint32_t a, uint32_t (&v)[4]) {
    asm volatile("{\n\t.reg .pred p;\n\tsetp.ne.u32 p, %5, 0;\n\t@p ld.shared.v4.u32 {%0,%1,%2,%3}, [%4];\n\t}"
        : "+r"(v[0]), "+r"(v[1]), "+r"(v[2]), "+r"(v[3]) : "r"(a), "r"((uint32_t)on) : "memory");
}
__device__ __forceinline__ uint32_t hfma2_bf(uint32_t a, uint32_t b, uint32_t c) { uint32_t r; asm("fma.rn.bf16x2 %0, %1, %2, %3;" : "=r"(r) : "r"(a), "r"(b), "r"(c)); return r; }
__device__ __forceinline__ __nv_bfloat162 bcast(uint32_t a, int hi) { const __nv_bfloat162 v = *reinterpret_cast<const __nv_bfloat162*>(&a); return hi ? __high2bfloat162(v) : __low2bfloat162(v); }
__device__ __forceinline__ uint32_t hmul2_bc(uint32_t a, int hi, uint32_t b) { const __nv_bfloat162 r = __hmul2_rn(bcast(a, hi), *reinterpret_cast<const __nv_bfloat162*>(&b)); return *reinterpret_cast<const uint32_t*>(&r); }
__device__ __forceinline__ uint32_t hfma2_bc(uint32_t a, int hi, uint32_t b, uint32_t c) {
    const __nv_bfloat162 r = __hfma2(bcast(a, hi), *reinterpret_cast<const __nv_bfloat162*>(&b), *reinterpret_cast<const __nv_bfloat162*>(&c));
    return *reinterpret_cast<const uint32_t*>(&r);
}
__device__ __forceinline__ uint32_t row_elem(uint32_t row) { return ((row >> 5) & 4) | ((row >> 2) & 2) | ((row >> 4) & 1); }
__device__ __forceinline__ uint32_t gate_pos(uint32_t row) { return ((row >> 9) << 8) | ((row & 7) << 5) | (row_elem(row) << 2) | ((row >> 5) & 3); }

template <int N, bool BULK>
__device__ __forceinline__ void mix_rows(const Params& p, const CUtensorMap* tm_out, uint32_t sb, uint32_t ob, int Q0, int Q1, int w, int h, int pr, int lane) {
    const int g = lane >> 2, t = lane & 3, mi = lane >> 3, r = lane & 7;
    const int m8 = 16 * (g >> 2) + ((g >> 1) & 1) + 2 * (g & 1);
    uint32_t yi = sb + (4 * (r >> 1) + 2 * (mi & 1) + (r & 1)) * 512 + (((4 * w + (mi >> 1)) ^ r) << 4);
    uint32_t xs = sb + OFF_S + s_addr(w * S_PL + 32 + m8 * 32, t >> 1) + ((t & 1) << 3);
    uint32_t gs = sb + OFF_GP + w * 64 + g * 8, os = ob + m8 * 32 + t * 8;
    if (N > 1) { yi = pin(yi, lane); xs = pin(xs, lane); gs = pin(gs, lane); os = pin(os, lane); }
    mbar_wait(sb + M_BARS + 8 * B_Y);
#pragma unroll 1
    for (int Q = Q0; Q < Q1; Q++) {
        uint2 xq[N][4];
        uint32_t gg[N][2], sw[N];
#pragma unroll
        for (int n = 0; n < N; n++) {
#pragma unroll
            for (int i = 0; i < 4; i++) xq[n][i] = lds64((xs ^ (((i ^ n) & 1) << 4)) + Q * S_Q + n * 4 * S_PL + i * 128);
            const uint2 gq = lds64(gs + Q * 512 + n * 256);
            sw[n] = lds32(sb + M_BMAP + w * 16 + n * 64 + Q * 4);
            gg[n][0] = gq.x; gg[n][1] = gq.y;
#pragma unroll
            for (int i = 0; i < 4; i++) {
                const uint32_t og = hfma2_bf(gg[n][i >> 1], 0xBF80BF80u, 0x3F803F80u);
                xq[n][i].x = hmul2_bc(og, i & 1, xq[n][i].x); xq[n][i].y = hmul2_bc(og, i & 1, xq[n][i].y);
            }
        }
        if (N > 1 && Q == PWQ) mbar_wait(sb + M_BARS + 8 * (B_W + PW));
        mbar_wait(sb + M_BARS + 8 * (B_Y + Q));
        __syncwarp();
#pragma unroll
        for (int n = 0; n < N; n++) {
#pragma unroll
            for (int x = 0; x < 2; x++) {
                uint32_t y[4];
                ldsm4t((yi ^ (x << 5)) + y_off(Q) + n * 256, y[0], y[1], y[2], y[3]);
#pragma unroll
                for (int e = 0; e < 2; e++) {
                    uint2& o = xq[n][2 * x + e];
                    o.x = hfma2_bc(gg[n][x], e, y[2 * e], o.x); o.y = hfma2_bc(gg[n][x], e, y[2 * e + 1], o.y);
                }
            }
        }
        if (BULK && (sw[0] | sw[N - 1]) == 0) {
#pragma unroll
            for (int n = 0; n < N; n++)
#pragma unroll
                for (int i = 0; i < 4; i++)
                    asm volatile("st.shared.v2.u32 [%0], {%1, %2};" :: "r"(os + Q * 1024 + n * 4 * TAB_W + i * 128), "r"(xq[n][i].x), "r"(xq[n][i].y) : "memory");
            asm volatile("fence.proxy.async.shared::cta;" ::: "memory");
            __syncwarp();
#pragma unroll
            for (int n = 0; n < N; n++)
                asm volatile("{\n\t.reg .pred p;\n\telect.sync _|p, 0xffffffff;\n\t"
                             "@p cp.async.bulk.tensor.3d.global.shared::cta.bulk_group [%1, {%2, %3, %4}], [%0];\n\t}"
                    :: "r"(ob + 4 * n * TAB_W + Q * 1024), "l"(tm_out), "r"(16 * pr), "r"(64 * Q + 32 * h), "r"(w + 4 * n) : "memory");
        } else {
            bf16* op = p.out + (size_t)(512 * Q + 256 * h + 8 * m8 + w) * D_ + 16 * pr + 4 * t;
#pragma unroll
            for (int n = 0; n < N; n++)
#pragma unroll
                for (int i = 0; i < 4; i++)
                    if (!((sw[n] >> (4 * g)) & (1u << i))) *(uint2*)(op + (size_t)(32 * i + 4 * n) * D_) = xq[n][i];
        }
    }
}

__global__ void __cluster_dims__(2, 1, 1) __launch_bounds__(NTHREADS, 1)
fused_kernel(const Params p, const __grid_constant__ CUtensorMap tm_gu, const __grid_constant__ CUtensorMap tm_down,
             const __grid_constant__ CUtensorMap tm_x, const __grid_constant__ CUtensorMap tm_out) {
    extern __shared__ __align__(1024) unsigned char smem[];
    const uint32_t sb = smem_u32(smem);
    int tid;
    asm volatile("mov.u32 %0, %%tid.x;" : "=r"(tid));
    const int pw = tid >> 5, lane = tid & 31;
    const int c = blockIdx.x, h = c & 1, pr = c >> 1;
    const uint32_t bars = sb + M_BARS;

    uint2 v_la, v_ai, v_cr, v_ci;
    uint32_t ldt16;
    {
        const uint32_t po = c * 256 + tid;
        asm volatile("{\n\t.reg .pred p;\n\t.reg .b64 a;\n\tsetp.ne.u32 p, %16, 0;\n\t"
                     "mad.wide.u32 a, %14, 8, %9;\n\t@p ld.global.nc.L1::no_allocate.v2.u32 {%0,%1}, [a];\n\t"
                     "mad.wide.u32 a, %15, 2, %13;\n\t@p ld.global.nc.u16 %8, [a];\n\t"
                     "mad.wide.u32 a, %14, 8, %10;\n\t@p ld.global.nc.L1::no_allocate.v2.u32 {%2,%3}, [a];\n\t"
                     "mad.wide.u32 a, %14, 8, %11;\n\t@p ld.global.nc.L1::no_allocate.v2.u32 {%4,%5}, [a];\n\t"
                     "mad.wide.u32 a, %14, 8, %12;\n\t@p ld.global.nc.L1::no_allocate.v2.u32 {%6,%7}, [a];\n\t}"
            : "=r"(v_la.x), "=r"(v_la.y), "=r"(v_ai.x), "=r"(v_ai.y), "=r"(v_cr.x), "=r"(v_cr.y), "=r"(v_ci.x), "=r"(v_ci.y), "=r"(ldt16)
            : "l"(p.logA), "l"(p.Aim), "l"(p.Cre), "l"(p.Cim), "l"(p.logdt), "r"(po), "r"(po >> 5), "r"((uint32_t)(tid < 256 && c < 128)));
    }

    if (c >= 128) {
        if (c != 128) return;
        RSTAMP(5);
        const unsigned tag = (*(volatile unsigned*)&p.sc->epoch + 1) & 0xffffu;
        const uint32_t list = sb + 128;
#pragma unroll 1
        for (int pass = 0; pass < 2; pass++) {
            sts128(list + 16 * tid, 0, 0, 0, 0);
            if (tid == 0) sts32(sb + 64, 0);
            uint32_t key[4] = {tag - 1, tag - 1, tag - 1, tag - 1};
#pragma unroll 1
            for (int it = 0; it < (pass << 22); it++) {
                uint32_t a[4];
                asm volatile("{\n\t.reg .b128 o, z;\n\t.reg .b64 l, u;\n\tmov.b64 l, {%5, %5};\n\tmov.b128 z, {l, l};\n\tatom.relaxed.gpu.global.exch.b128 o, [%4], z;\n\t"
                             "mov.b128 {l, u}, o;\n\tmov.b64 {%0, %1}, l;\n\tmov.b64 {%2, %3}, u;\n\t}"
                    : "=r"(a[0]), "=r"(a[1]), "=r"(a[2]), "=r"(a[3]) : "l"(&p.sc->r[tid]), "r"(tag - 1) : "memory");
#pragma unroll
                for (int i = 0; i < 4; i++) if (((a[i] ^ tag) & 0xffffu) == 0) key[i] = a[i];
                if ((((key[0] ^ tag) | (key[1] ^ tag) | (key[2] ^ tag) | (key[3] ^ tag)) & 0xffffu) == 0) break;
            }
            WSTAMP(0);
            uint32_t m = 0;
#pragma unroll
            for (int i = 0; i < 4; i++) {
                key[i] = ((pass ? key[i] : (lane + i) << 16) & 0xffff0000u) | (uint32_t)(2047 - (4 * tid + i));
                m = max(m, key[i]);
            }
            const uint32_t wm = __reduce_max_sync(0xffffffffu, m);
            if (lane == 0) sts32(sb + pw * 4, wm);
            __syncthreads();
            uint32_t thr = 0xffffffffu;
#pragma unroll
            for (int i = 0; i < 4; i++) { const uint4 q = lds128(sb + 16 * i); thr = min(thr, min(max(q.x, q.y), max(q.z, q.w))); }
            if (thr != 1) WSTAMP(1);
            if (m >= thr) {
                uint32_t pos;
                asm volatile("atom.shared.add.u32 %0, [%1], %2;" : "=r"(pos) : "r"(sb + 64), "r"(4 * ((key[0] >= thr) + (key[1] >= thr) + (key[2] >= thr) + (key[3] >= thr))) : "memory");
#pragma unroll
                for (int i = 0; i < 4; i++) if (key[i] >= thr) { sts32(list + pos, key[i]); pos += 4; }
            }
            __syncthreads();
            const uint32_t nc4 = lds32(sb + 64);
            if (nc4 != 1) WSTAMP(2);
#pragma unroll 1
            for (uint32_t j = 4 * pw; j < nc4; j += 64) {
                const uint32_t mine = lds32(list + j);
                int rank = 0;
#pragma unroll 1
                for (uint32_t i = 0; i < nc4; i += 128) rank += __popc(__ballot_sync(0xffffffffu, lds32(list + i + 4 * lane) > mine));
                if (rank < 8 && lane == 0) sts32(sb + 96 + 4 * rank, mine);
            }
            __syncthreads();
            if (tid < 8 * NTOP) st_gpu32(&p.sc->top[tid >> 3][tid & 7], lds32(sb + 96 + 4 * (tid & 7)) | (((tag + pass - 1) & 31) << 11));
            WSTAMP(3);
            if (!pass) RSTAMP(4);
        }
        WDUMP();
        return;
    }

    WSTAMP(0);
    if (pw < 8) {
        const int d = 8 * c + pw - MAIN_W0;
        if (lane == 0) asm volatile("cp.async.ca.shared.global [%0], [%1], 4;" :: "r"(sb + M_DSK + 4 * (pw - MAIN_W0)), "l"(p.Dskip + (d & ~1)) : "memory");
        asm volatile("barrier.cluster.arrive.relaxed.aligned;" ::: "memory");
        const int warp = pw - MAIN_W0;
        asm volatile("setmaxnreg.inc.sync.aligned.u32 160;");
        const int g = lane >> 2, t = lane & 3;
        const int mi = lane >> 3, r = lane & 7;
        const uint32_t TB = sb + OFF_TAB + warp * TAB_W;
        const uint32_t UB = sb + OFF_U + warp * U_CH;
        if (mi < 2) sts128(UB + mi * U_PL + r * 16, 0, 0, 0, 0);
        if (lane < 4) sts128(TB + lane * T_PL, 0, 0, 0, 0);
        sts128(sb + OFF_SCR + warp * 8192 + lane * 16, 0x3C00u, 0x3C00u, 0x3C00u, 0x3C00u);
        asm volatile("barrier.cluster.wait.acquire.aligned;" ::: "memory");
        __syncwarp();

        uint32_t cfix;
        {
            KSTAMP(4, v_la.x ^ v_ai.x ^ v_cr.x ^ v_ci.x ^ ldt16);
            const float dt = bf_round(exp_acc(__uint_as_float(ldt16 << 16)));
            float l2[4], li[4];
            {
                const uint32_t la[2] = {v_la.x, v_la.y}, ai[2] = {v_ai.x, v_ai.y};
                const float dt2 = -1.4426950408889634f * dt;
#pragma unroll
                for (int i = 0; i < 4; i++) {
                    l2[i] = bf_round(ex2f(((i & 1) ? bf_hi(la[i >> 1]) : bf_lo(la[i >> 1])) * 1.4426950408889634f)) * dt2;
                    li[i] = ((i & 1) ? bf_hi(ai[i >> 1]) : bf_lo(ai[i >> 1])) * dt;
                }
            }
            const uint32_t SX = sb + OFF_SCR + warp * 8192;
            const uint32_t sw = SX + (lane << 4);
#define PUT(buf, row, v) sts128(((sw + (row) * 512) ^ ((row) << 4)) + (buf) * 4096, v[0], v[1], v[2], v[3])
#define EMIT(bufa, rowa, bufb, rowb, xr, xi, k, kp) do { uint32_t pk[4], pd[4]; \
                _Pragma("unroll") for (int i = 0; i < 4; i++) { pk[i] = pack_h(xr[i], xi[i]); pd[i] = hcmul(pk[i], k[i], kp[i]); } \
                PUT(bufa, rowa, pk); PUT(bufb, rowb, pd); } while (0)
#define CMUL4(orr, oi, ar, ai, br, bi) _Pragma("unroll") for (int i = 0; i < 4; i++) CMUL(orr[i], oi[i], ar[i], ai[i], br[i], bi[i])
#define CSQ4(orr, oi, ar, ai) _Pragma("unroll") for (int i = 0; i < 4; i++) CSQ(orr[i], oi[i], ar[i], ai[i])
            float z1r[4], z1i[4], z2r[4], z2i[4], z8r[4], z8i[4], z256r[4], z256i[4];
            uint32_t k4[4], k4p[4];
            float z4r[4], z4i[4];
#pragma unroll
            for (int i = 0; i < 4; i++) cexp_pow(l2[i], li[i], 1.f, z1r[i], z1i[i]);
            CSQ4(z2r, z2i, z1r, z1i);
            CSQ4(z4r, z4i, z2r, z2i);
            CSQ4(z8r, z8i, z4r, z4i);
            KSTAMP(5, __float_as_uint(z8r[3]));
            uint32_t Ya[16][4];
            float cr[4], ci[4], inv;
            {
                float w1r[4], w1i[4], ar[4], ai[4], br[4], bi[4];
                uint32_t k8[4], k8p[4];
#pragma unroll
                for (int i = 0; i < 4; i++) {
                    k8[i] = pack_h(z8r[i], -z8i[i]); k8p[i] = pack_h(z8i[i], z8r[i]);
                    CSQ(w1r[i], w1i[i], z8r[i], z8i[i]); w1i[i] = -w1i[i];
                }
                PUT(1, 0, k8);
                EMIT(0, 1, 1, 1, w1r, w1i, k8, k8p);
                CSQ4(ar, ai, w1r, w1i);            EMIT(0, 2, 1, 2, ar, ai, k8, k8p);
                CMUL4(br, bi, ar, ai, w1r, w1i);   EMIT(0, 3, 1, 3, br, bi, k8, k8p);
                CSQ4(ar, ai, ar, ai);              EMIT(0, 4, 1, 4, ar, ai, k8, k8p);
                CMUL4(ar, ai, ar, ai, w1r, w1i);   EMIT(0, 5, 1, 5, ar, ai, k8, k8p);
                CSQ4(br, bi, br, bi);              EMIT(0, 6, 1, 6, br, bi, k8, k8p);
                CMUL4(br, bi, br, bi, w1r, w1i);   EMIT(0, 7, 1, 7, br, bi, k8, k8p);
                __syncwarp();
                KSTAMP(6, 0);
                const uint32_t ab = SX + (mi & 1) * 4096 + r * 512, ax = ((mi >> 1) ^ r) << 4;
                const uint32_t vr[2] = {v_cr.x, v_cr.y}, vi[2] = {v_ci.x, v_ci.y};
                const uint32_t m2 = __vmaxu2(__vmaxu2(vr[0] & 0x7fff7fffu, vr[1] & 0x7fff7fffu), __vmaxu2(vi[0] & 0x7fff7fffu, vi[1] & 0x7fff7fffu));
                const uint32_t mx = __reduce_max_sync(0xffffffffu, max(m2, m2 << 16));
                const uint32_t e = min(max(mx >> 23, 11u), 254u);
                const float sc = __uint_as_float((264u - e) << 23);
                inv = __uint_as_float((e - 10u) << 23) * (2.f * dt);
#pragma unroll
                for (int i = 0; i < 4; i++) {
#pragma unroll
                    for (int k = 0; k < 4; k++) ldsm4(ab + (ax ^ (i << 5)) + k * 128, Ya[4 * k + i][0], Ya[4 * k + i][1], Ya[4 * k + i][2], Ya[4 * k + i][3]);
                    float tr, ti;
                    cexp_pow(l2[i], li[i], 128.f, tr, ti);
                    sts32(TB + 2176 + 256 * i + 4 * lane, pack_h(tr, ti));
                    sts32(TB + 2176 + 256 * i + 128 + 4 * (lane ^ 16), pack_h(-ti, tr));
                    k4[i] = pack_h(z4r[i], z4i[i]); k4p[i] = pack_h(-z4i[i], z4r[i]);
                    CSQ(z256r[i], z256i[i], tr, ti);
                    cr[i] = ((i & 1) ? bf_hi(vr[i >> 1]) : bf_lo(vr[i >> 1])) * sc;
                    ci[i] = ((i & 1) ? bf_hi(vi[i >> 1]) : bf_lo(vi[i >> 1])) * sc;
                }
                __syncwarp();
            }
            KSTAMP(7, Ya[15][0]);
            const uint32_t ld0 = SX + r * 512 + ((mi ^ r) << 4), ld1 = ld0 ^ 64;
            float R[6][4], s1024;
            {
                float xr[4], xi[4], yr[4], yi[4];
                EMIT(0, 0, 0, 1, cr, ci, k4, k4p);
                CMUL4(yr, yi, cr, ci, z1r, z1i);        EMIT(0, 2, 0, 3, yr, yi, k4, k4p);
                CMUL4(xr, xi, cr, ci, z256r, z256i);    EMIT(1, 0, 1, 1, xr, xi, k4, k4p);
                CMUL4(yr, yi, yr, yi, z1r, z1i);        EMIT(0, 4, 0, 5, yr, yi, k4, k4p);
                CMUL4(cr, ci, xr, xi, z2r, z2i);        EMIT(1, 2, 1, 3, cr, ci, k4, k4p);
                CMUL4(yr, yi, yr, yi, z1r, z1i);        EMIT(0, 6, 0, 7, yr, yi, k4, k4p);
                CMUL4(xr, xi, xr, xi, z256r, z256i);    EMIT(1, 4, 1, 5, xr, xi, k4, k4p);
                CMUL4(xr, xi, xr, xi, z256r, z256i);    EMIT(1, 6, 1, 7, xr, xi, k4, k4p);
                CMUL4(xr, xi, xr, xi, z256r, z256i);
                s1024 = (xr[0] + xr[1]) + (xr[2] + xr[3]);
#pragma unroll
                for (int m = 0; m < 4; m++) {
                    if (m == 0) { CMUL4(xr, xi, xr, xi, z8r, z8i); } else { CMUL4(xr, xi, xr, xi, z256r, z256i); }
                    sts128(TB + m * T_PL + 16 + 16 * lane, pack_h(xr[0], xi[0]), pack_h(xr[1], xi[1]), pack_h(xr[2], xi[2]), pack_h(xr[3], xi[3]));
                }
            }
            __syncwarp();
            {
                KSTAMP(8, 0);
                uint32_t bd[2][4] = {{0, 0, 0, 0}, {0, 0, 0, 0}};
                const bool on = (g >> 1) == t;
#pragma unroll
                for (int i = 0; i < 6; i++) { R[i][0] = R[i][1] = R[i][2] = R[i][3] = 0.f; }
#pragma unroll
                for (int k2 = 0; k2 < 8; k2++) {
                    uint32_t x[4], y[4], z[4], a1[2][4];
                    lds128_if(on, TB + 2176 + g * 128 + (k2 < 4 ? 64 : -64) * (g & 1) + 16 * k2, bd[k2 & 1]);
                    ldsm4(TB + (r & 3) * T_PL + 16 + 16 * mi + 64 * k2, z[0], z[1], z[2], z[3]);
                    ldsm4(((k2 & 1) ? ld1 : ld0) + (k2 >> 1) * 128, x[0], x[1], x[2], x[3]);
                    ldsm4(((k2 & 1) ? ld1 : ld0) + (k2 >> 1) * 128 + 4096, y[0], y[1], y[2], y[3]);
#pragma unroll
                    for (int u = 0; u < 2; u++) {
                        mma_hh_k8(a1[u][0], a1[u][1], Ya[2 * k2 + u][0], Ya[2 * k2 + u][1], bd[k2 & 1][2 * u]);
                        mma_hh_k8(a1[u][2], a1[u][3], Ya[2 * k2 + u][2], Ya[2 * k2 + u][3], bd[k2 & 1][2 * u + 1]);
                    }
#pragma unroll
                    for (int u = 0; u < 2; u++) {
                        const uint32_t(&a0)[4] = Ya[2 * k2 + u];
                        mma_h(R[0], a0[0], a0[1], a0[2], a0[3], x[2 * u], x[2 * u + 1]);
                        mma_h(R[2], a0[0], a0[1], a0[2], a0[3], y[2 * u], y[2 * u + 1]);
                        mma_h(R[4], a0[0], a0[1], a0[2], a0[3], z[2 * u], z[2 * u + 1]);
                        mma_h(R[1], a1[u][0], a1[u][1], a1[u][2], a1[u][3], x[2 * u], x[2 * u + 1]);
                        mma_h(R[3], a1[u][0], a1[u][1], a1[u][2], a1[u][3], y[2 * u], y[2 * u + 1]);
                        mma_h(R[5], a1[u][0], a1[u][1], a1[u][2], a1[u][3], z[2 * u], z[2 * u + 1]);
                    }
                }
            }
            __syncwarp();
            KSTAMP(9, __float_as_uint(R[3][0]));
            if (lane == 0) mbar_arrive(bars + 8 * B_KG + (__float_as_uint(R[0][0]) & __float_as_uint(R[2][0]) & p.zero));
            sts128(TB + 2176 + 16 * lane, 0, 0, 0, 0);
            sts128(TB + 2688 + 16 * lane, 0, 0, 0, 0);
            __syncwarp();
#undef PUT
#undef EMIT
#pragma unroll
            for (int o = 16; o > 0; o >>= 1) s1024 += __shfl_xor_sync(0xffffffffu, s1024, o);
            uint32_t w[4][4], dsk = 0;
            cp_wait_all();
            asm volatile("{\n\t.reg .pred p;\n\tsetp.eq.u32 p, %2, 0;\n\t@p ld.shared.u16 %0, [%1];\n\t}" : "+r"(dsk) : "r"(sb + M_DSK + 4 * warp + 2 * (warp & 1)), "r"(lane) : "memory");
#pragma unroll
            for (int a = 0; a < 4; a++) {
                const float v0 = (a == 0) ? fmaf(R[0][0], inv, __uint_as_float(dsk << 16)) : R[a][0] * inv;
                const float v1 = R[a][1] * inv, v2 = R[a][2] * inv, v3 = R[a][3] * inv;
                w[a][0] = pack_bf(v0, 0.f); w[a][1] = pack_bf(v1, v0); w[a][2] = pack_bf(v2, v1); w[a][3] = pack_bf(v3, v2);
            }
            const uint32_t wb = TB + 16 + 16 * g, w1 = wb + t * T_PL, w2 = wb + 256 + 2 * t * T_PL;
            const uint32_t w3 = (t == 0) ? wb + 256 + 3 * T_PL : TB + T_A + 8 * (16 * t + g);
            const uint32_t w3s = (t == 0) ? 128 : 64, w3o = (t == 0) ? 8 : 12;
            const uint32_t k512 = __shfl_sync(0xffffffffu, w[2][1], 2);
#pragma unroll
            for (int a = 0; a < 2; a++) {
                sts128(w1 + 128 * a, w[a][0], w[a][1], w[a][2], w[a][3]);
                const uint32_t(&q)[4] = w[2 + a];
                if (t < 2) sts128(w2 + 128 * a, q[0], q[1], q[2], q[3]);
                if (t == 0) { sts128(w2 + T_PL + 128 * a, q[0], q[1], q[2], q[3]); sts32(w3 + 128 * a + 4, q[2]); }
                sts32_if(t != 1 && (a == 1 || lane != 2), w3 + w3s * a, q[1]);
                sts32_if(t != 1, w3 + w3s * a + w3o, q[3]);
            }
            sts128_if(lane < 4, w1 + 512, t == 3 ? k512 : k512 >> 16, t < 2 ? k512 : t == 2 ? k512 & 0xffff0000u : k512 << 16, t < 2 ? k512 << 16 : 0u, 0);
            __syncwarp();
#pragma unroll
            for (int a = 0; a < 2; a++) {
                sts16(w1 + 128 * a + 18, w[a][3]);
                const uint32_t(&q)[4] = w[2 + a];
                if (t < 2) sts16(w2 + 128 * a + 18, q[3]);
                if (t == 0) { sts16(w2 + T_PL + 128 * a + 18, q[3]); sts16(w3 + 128 * a + 14, q[3]); }
            }
            if (t == 0) sts16(w3 + 128 - 4, w[3][0]);
            if (lane == 2 || (t == 0 && g > 0)) sts16(lane == 2 ? TB + 16 + 3 * T_PL + 4 * 127 : w3 - 4, w[2][0]);
            {
                float q[4];
#pragma unroll
                for (int i = 0; i < 4; i++) q[i] = (t < 2 ? R[4][i] : R[5][i]) * inv;
                const uint32_t b0 = pack_bf(q[0], q[2]), b1 = pack_bf(q[1], q[3]);
                const uint32_t wq = TB + T_B + 8 * (65 + 32 * (t & 1) + 4 * (t & 2) + g);
                sts32(wq, b0); sts32(wq + 12, b0); sts32(wq + 128, b1); sts32(wq + 140, b1);
            }
            cfix = pack_bf(s1024 * inv, s1024 * inv);
            if (lane == 0) sts32(TB + T_A + 8 * 64, cfix);
            __syncwarp();
        }
        WSTAMP(1);

        mbar_wait(bars + 8 * B_U);
        WSTAMP(2);

        float D[16][4];
        {
            const int x5 = g - t + 5;
            const uint32_t tabD = TB + (x5 & 3) * T_PL + (x5 & 12) + 16;
            {
                const uint32_t a1 = lds32(tabD - 8), a0 = p.zero;
#pragma unroll
                for (int jq = 0; jq < 4; jq++) {
                    uint32_t b[4];
                    ldsm4(UB + (9 + lane) * 16 + jq * 512, b[0], b[1], b[2], b[3]);
#pragma unroll
                    for (int i = 0; i < 4; i++) mma_bf_k8z(D[4 * jq + i], a0, a1, b[i]);
                }
            }
            const uint32_t ua = UB + (mi & 1) * U_PL + (8 + 8 * (mi >> 1) + r) * 16;
#pragma unroll 1
            for (int k0 = 0; k0 < 8; k0++) {
                uint32_t Uf[16][2];
#pragma unroll
                for (int jp = 0; jp < 8; jp++) ldsm4(ua + jp * 256 - k0 * 16, Uf[2 * jp][0], Uf[2 * jp][1], Uf[2 * jp + 1][0], Uf[2 * jp + 1][1]);
#pragma unroll
                for (int k1 = 0; k1 < 4; k1++) {
                    const uint32_t ta = tabD + 16 * (8 * k1 + k0);
                    const uint32_t a0 = lds32(ta), a1 = lds32(ta + 8), a2 = lds32(ta - 8), a3 = a0 ^ p.zero;
#pragma unroll
                    for (int J = k1; J < 16; J++) mma_bf(D[J], a0, a1, a2, a3, Uf[J - k1][0], Uf[J - k1][1]);
                }
                if (k0 == 0) {
                    const uint32_t ta = tabD + 16 * 32;
                    const uint32_t a0 = lds32(ta), a1 = lds32(ta + 8), a2 = lds32(ta - 8), a3 = a0 ^ p.zero;
#pragma unroll
                    for (int J = 4; J < 16; J++) mma_bf(D[J], a0, a1, a2, a3, Uf[J - 4][0], Uf[J - 4][1]);
                    const uint32_t f0 = (cfix ^ 0x80008000u) & (g == t ? 0xffffu : g == t + 4 ? 0xffff0000u : 0u);
                    const uint32_t f1 = p.zero, f2 = p.zero + p.zero, f3 = f0 ^ p.zero;
#pragma unroll
                    for (int J = 8; J < 16; J++) mma_bf(D[J], f0, f1, f2, f3, Uf[J - 8][0], Uf[J - 8][1]);
                }
            }
        }
        WSTAMP(3);
        {
            const int ch = 8 * h + warp;
            const uint32_t yo = sb + ch * 512 + ((lane ^ (((ch >> 2) << 1) | (ch & 1))) << 4);
            const uint32_t yr = mapa(yo, h ^ 1), ybr = mapa(bars + 8 * B_Y, h ^ 1);
            auto ship = [&](const int Q) {
                uint4 y[2];
#pragma unroll
                for (int hh = 0; hh < 2; hh++) {
                    const int J = 4 * Q + 2 * hh;
                    y[hh] = make_uint4(pack_bf(D[J][0], D[J][1]), pack_bf(D[J][2], D[J][3]), pack_bf(D[J + 1][0], D[J + 1][1]), pack_bf(D[J + 1][2], D[J + 1][3]));
                }
                if (!(Q & 1)) mbar_wait(bars + 8 * (B_F + (Q >> 1)));
                asm volatile("{\n\t.reg .pred p;\n\tsetp.eq.u32 p, %11, 0;\n\t"
                             "@p st.async.weak.shared::cluster.mbarrier::complete_tx::bytes.v4.b32 [%9], {%4,%5,%6,%7}, [%10];\n\t"
                             "@!p st.async.weak.shared::cluster.mbarrier::complete_tx::bytes.v4.b32 [%9], {%0,%1,%2,%3}, [%10];\n\t"
                             "@p st.shared.v4.b32 [%8], {%0,%1,%2,%3};\n\t@!p st.shared.v4.b32 [%8], {%4,%5,%6,%7};\n\t}"
                             :: "r"(y[0].x), "r"(y[0].y), "r"(y[0].z), "r"(y[0].w), "r"(y[1].x), "r"(y[1].y), "r"(y[1].z), "r"(y[1].w),
                                "r"(yo + y_off(Q)), "r"(yr + y_off(Q)), "r"(ybr + 8 * Q), "r"(h) : "memory");
                __syncwarp();
                if (lane == 0) mbar_arrive(bars + 8 * (B_Y + Q));
            };
            ship(0);
            const uint4 bA = lds128(sb + OFF_BAND + (g - t + 3) * 48), bB = lds128(sb + OFF_BAND + (g - t + 3) * 48 + 16);
            const uint2 bC = lds64(sb + OFF_BAND + (g - t + 3) * 48 + 32);
            uint2 QA[5][2], QB[8];
            const uint32_t tq = TB + 8 * (1 + g - 2 * t);
#pragma unroll
            for (int dd = 0; dd < 5; dd++) { QA[dd][0] = lds64(tq + T_A + 64 * (dd + 4)); QA[dd][1] = lds64(tq + T_A + 64 * (dd + 4) - 8); }
#pragma unroll
            for (int dd = 0; dd < 8; dd++) QB[dd] = lds64(tq + T_B + 64 * (dd + 8));
            const uint32_t u1 = UB + (mi & 1) * U_PL + (7 + r + (mi >> 1)) * 16;
            const uint32_t u2 = UB + ((mi & 1) ^ 1) * U_PL + (7 + r + (mi & 1) + 8 * (mi >> 1)) * 16;
            uint32_t n[4];
#pragma unroll
            for (int j = 0; j < 12; j++) {
                uint32_t m[4];
                ldsm4(u1 + j * 128, m[0], m[1], m[2], m[3]);
                if (!(j & 1)) ldsm4(u2 + j * 128, n[0], n[1], n[2], n[3]);
                const uint32_t n0 = n[2 * (j & 1)], n1 = n[2 * (j & 1) + 1];
                float wa[4], wb[4], wc[4], g1[4], g2[4];
                mma_bf_z(wa, bA.x, bA.y, bA.z, bA.w, m[0], m[1]);
                mma_bf_z(wb, bA.x, bA.y, bA.z, bA.w, n0, n1);
                mma_bf_z(wc, bA.x, bA.y, bA.z, bA.w, m[2], m[3]);
                if (j < 8) {
                    mma_bf_z(g1, bB.x, bB.y, bB.z, bB.w, m[0], m[1]);
                    mma_bf_z(g2, bB.x, bB.y, bB.z, bB.w, n0, n1);
                    mma_bf_k8(g1, bC.x, bC.y, m[2]);
                    mma_bf_k8(g2, bC.x, bC.y, m[3]);
                }
#pragma unroll
                for (int e = 0; e < 2; e++) {
                    const uint32_t q0 = pack_bf(wa[e], wa[e + 2]), q1 = pack_bf(wb[e], wb[e + 2]), q2 = q1 ^ p.zero, q3 = pack_bf(wc[e], wc[e + 2]);
#pragma unroll
                    for (int dd = 0; dd < 5; dd++)
                        if (j + 4 + dd < 16) mma_bf(D[j + 4 + dd], q0, q1, q2, q3, QA[dd][e].x, QA[dd][e].y);
                }
                if (j < 8) {
                    const uint32_t q0 = pack_bf(g1[0], g1[2]), q1 = pack_bf(g2[0], g2[2]), q2 = pack_bf(g1[1], g1[3]), q3 = pack_bf(g2[1], g2[3]);
#pragma unroll
                    for (int dd = 7 - j; dd >= 0; dd--) mma_bf(D[j + 8 + dd], q0, q1, q2, q3, QB[dd].x, QB[dd].y);
                }
                if ((j & 3) == 3) {
                    WSTAMP(4 + 2 * (j >> 2));
                    if (j == 11 && LATE2) ship(2);
                    if (j != 7 || !LATE2) ship((j >> 2) + 1);
                }
            }
        }
        const int warpu = __reduce_max_sync(0xffffffffu, warp);
        mix_rows<1, BULKM>(p, &tm_out, sb, sb + OFF_U + warpu * U_CH + (warpu & 1) * 64, PQ, 4, warpu, h, pr, lane);
        if (BULKM) asm volatile("cp.async.bulk.commit_group;\n\tcp.async.bulk.wait_group.read 0;" ::: "memory");
        WSTAMP(10);
        WDUMP();
    } else if ((pw & 12) == AUX_W0) {
        const int v = __reduce_max_sync(0xffffffffu, pw & 3);
        const int at = tid & 127;
        const int g = lane >> 2, t = lane & 3;
        unsigned tag;
        const bool gu = c < NGU_CTA;
        {
            const uint32_t xb = sb + (v < 2 ? OFF_XSEL : OFF_RING + 2 * 8192) + v * 8192;
            const uint32_t gws = sb + M_DPIN;
            const uint32_t row = 16 * c + 4 * v + (g >> 1);
#pragma unroll
            for (int i = 0; i < 8; i++)
                asm volatile("cp.async.ca.shared.global [%0], [%1], 4;" :: "r"((i < 4 ? sb + OFF_GP : gws) + 512 * (i & 3) + (tid & 124) * 4 + (tid & 1) * 8 + (tid & 2) * 2),
                             "l"((i < 4 ? p.wr : p.gatew) + 256 * (i & 3) + (tid & 127) * 2) : "memory");
            if ((tid & 127) < 33) cp16(sb + OFF_BAND + (tid & 127) * 16, p.band + (tid & 127));
            asm volatile("barrier.cluster.arrive.relaxed.aligned;" ::: "memory");
            tag = __reduce_max_sync(0xffffffffu, (*(volatile unsigned*)&p.sc->epoch + 1) & 0xffffu);
            if (gu) st_gpu32((uint32_t*)&p.sc->h[(tag + 1) & 1][32 * c] + at, 0);
            if (v == 2) sts32(sb + M_BMAP + lane * 4, 0);
            if (at == 0) sts32(sb + M_TAG, tag << 16);
            cp_wait_all();
            bar_sync(1, 128);
            uint2 w[16];
#pragma unroll
            for (int kb = 0; kb < 16; kb++) w[kb] = lds64((g < 4 ? sb + OFF_GP : gws) + 128 * kb + 32 * (g & 2) + 16 * t + 8 * (g & 1));
            asm volatile("barrier.cluster.wait.acquire.aligned;" ::: "memory");
            mbar_wait(bars + 8 * (B_X + v));
            WSTAMP(10);
            float dr[4][4];
#pragma unroll
            for (int kb = 0; kb < 16; kb++) {
                const uint4 x = lds128(xb + (g >> 1) * 2048 + 128 * kb + 16 * (lane & 7));
                if (kb < 4) mma_bf_z(dr[kb], x.x, x.y, x.z, x.w, w[kb].x, w[kb].y);
                else mma_bf(dr[kb & 3], x.x, x.y, x.z, x.w, w[kb].x, w[kb].y);
            }
            float rs = ((dr[0][0] + dr[0][3]) + (dr[1][0] + dr[1][3])) + ((dr[2][0] + dr[2][3]) + (dr[3][0] + dr[3][3]));
            if (lane == 0) mbar_arrive(bars + 8 * (B_XE + v) + (__float_as_uint(rs) & p.zero));
            rs += __shfl_xor_sync(0xffffffffu, rs, 5);
            const uint32_t rb = pack_bf(0.f, rs);
            if (!(lane & 7)) st_gpu32((uint32_t*)p.sc->r + row, ((rb ^ (((int)rb >> 31) | 0x80000000u)) & 0xffff0000u) | tag);
            WSTAMP(1);
            {
                const int n = 3 + (lane >> 3) + 4 * (lane & 1);
                const uint32_t so = (n & 7) * S_PL + ((lane & 6) + (n >> 3)) * 32;
                const uint32_t src[2] = {sb + OFF_S + v * S_Q + s_addr(so, h), sb + OFF_S + v * S_Q + s_addr(so + 32, h)};
                const uint32_t dst = sb + OFF_U + g * U_CH + (8 + 32 * v + 16 * h + t) * 16;
                const uint32_t rdst = mapa(dst, h ^ 1), rbar = mapa(bars + 8 * B_U, h ^ 1);
                mbar_wait(bars + 8 * (B_S + v));
                WSTAMP(9);
                uint4 a[8];
#pragma unroll
                for (int b = 0; b < 2; b++) {
#pragma unroll
                    for (int j = 0; j < 8; j++) { const int u = 4 * b + (j >> 1) + 8 * (j & 1); ldsm4t((u < 8 ? src[u & 1] ^ 16 : src[u & 1]) + ((u >> 1) & 3) * 256, a[j].x, a[j].y, a[j].z, a[j].w); }
#pragma unroll
                    for (int j = 0; j < 8; j++) {
                        const int u = 4 * b + (j >> 1) + 8 * (j & 1);
                        if (u < 8) st_async16(rdst + ((u >> 1) & 3) * 64 + (u & 1) * U_PL, a[j], rbar);
                        else sts128(dst + ((u >> 1) & 3) * 64 + (u & 1) * U_PL, a[j].x, a[j].y, a[j].z, a[j].w);
                    }
                }
                if (h && v == 3) {
                    ldsm4t((src[0] ^ 16) + 1024, a[0].x, a[0].y, a[0].z, a[0].w);
                    ldsm4t(src[0] + 1024, a[1].x, a[1].y, a[1].z, a[1].w);
                    if (t == 0) {
                        st_async16(rdst + 256, make_uint4(a[0].x, a[0].y & 0xffffu, a[0].z & 0xffffu, a[0].w & 0xffffu), rbar);
                        sts128(dst + 256, a[1].x, a[1].y & 0xffffu, a[1].z & 0xffffu, a[1].w & 0xffffu);
                    }
                }
                __syncwarp();
                if (lane == 0) mbar_arrive(bars + 8 * B_U);
            }
            if ((lane & 7) == 2) st_gpu32((uint32_t*)p.sc->g + ((row & 256) << 2) + gate_pos(row), pack_bf(sigmoid_f(__uint_as_float(rb)), 0.f) | (tag << 16));
            WSTAMP(2);
        }
        {
            const bool lane0 = pin(lane, lane) == 0;
            const uint32_t own = pin(sb + OFF_XSEL + (at ^ ((at >> 1) & 4)) * 16, lane);
            float acc[8][4];
#pragma unroll
            for (int i = 0; i < 8; i++) { acc[i][0] = acc[i][1] = acc[i][2] = acc[i][3] = 0.f; }
            const int krow = ((lane >> 1) & 8) + (lane & 7);
            const uint32_t tile0 = pin(sb + OFF_RING + krow * 64 + ((((lane >> 3) & 1) ^ ((krow >> 1) & 3)) << 4), lane);
            const uint32_t xo = pin(sb + OFF_XSEL + (lane & 7) * XS_ROW + 512 * v + 2 * (lane & 24), lane);
            const uint32_t po = pin(sb + OFF_XSEL + t * XS_ROW + (g & 3) * 128 + (g & 1) * 64 + v * 16 + (lane >> 4) * 8, lane);
            const uint32_t po1 = pin(po + 64 - (g & 1) * 128, lane);
            uint32_t* hdst = pin((uint32_t*)&p.sc->h[tag & 1][32 * c] + at, lane);
            auto signal = [&](const int k, const uint32_t dep) {
                if (lane < 2 && v < 2)
                    asm volatile("st.async.weak.shared::cluster.mbarrier::complete_tx::bytes.b32 [%0], %1, [%2];"
                                 :: "r"(mapa(sb + M_SINK, lane)), "r"(dep), "r"(mapa(bars + 8 * (B_F + k), lane)) : "memory");
            };
#pragma unroll 1
            for (int i = 0; i < 4; i++) {
                const int s = 4 * i + v;
                uint32_t a[16][4], b[2][4];
                if (gu) {
                    const uint32_t tile = tile0 + (s < 14 ? s : v) * 8192;
                    if (lane0 && i > 1) mbar_arrive(bars + 8 * (B_E + s - 4));
                    if (i == 2) signal(0, 0);
                    mbar_wait(bars + 8 * (B_W + s));
#pragma unroll
                    for (int q = 0; q < 16; q++) ldsm4t((tile ^ ((q & 1) << 5)) + ((q >> 1) & 1) * 4096 + (q >> 2) * 1024, a[q][0], a[q][1], a[q][2], a[q][3]);
                }
                if (i == 0) {
                    if (gu) {
                        uint32_t dep = p.zero;
#pragma unroll
                        for (int q = 0; q < 16; q += 2) dep &= a[q][0] & a[q + 1][0];
                        if (lane == 0) mbar_arrive(bars + 8 * (B_E + v) + dep);
                    }
                    WSTAMP(11);
                    uint32_t top;
#pragma unroll 1
                    for (int it = 0; it < (1 << 22); it++) {
                        asm volatile("ld.relaxed.gpu.global.u32 %0, [%1];" : "=r"(top) : "l"(&p.sc->top[c % NTOP][g]) : "memory");
                        if (__all_sync(0xffffffffu, ((top ^ (tag << 11)) & 0xf800u) == 0)) break;
                        if (TSLEEP) __nanosleep(TSLEEP);
                    }
                    WSTAMP(3);
                    if (gu) {
                        const uint32_t k = 4 * h + v, row = __reduce_max_sync(0xffffffffu, lane == 4 * k ? ~top & 2047 : 0);
                        asm volatile("{\n\t.reg .pred p;\n\telect.sync _|p, 0xffffffff;\n\t"
                                     "@p cp.async.bulk.shared::cluster.global.mbarrier::complete_tx::bytes.multicast::cluster [%0], [%1], 2048, [%2], %3;\n\t}"
                            :: "r"(sb + OFF_XSEL + k * XS_ROW), "l"(p.u + (size_t)row * D_), "r"(bars + 8 * B_G), "h"((unsigned short)3) : "memory");
                    }
                    if (v == 2) {
                        const uint32_t row = ~top & 2047;
                        if (t == 0 && ((row >> 8) & 1) == h)
                            asm volatile("red.shared.or.b32 [%0], %1;" :: "r"(sb + M_BMAP + (row & 7) * 16 + (row >> 9) * 4), "r"(1u << (gate_pos(row) & 31)) : "memory");
                        if (t == 0) sts32(sb + M_TOP + lane, top);
                        if (c == 0 && lane == 0) *(volatile unsigned*)&p.sc->epoch = tag;
                        __syncwarp();
                        if (lane0) mbar_arrive(bars + 8 * B_Y);
                    }
                    if (!gu) break;
                    mbar_wait(bars + 8 * B_G);
                    WSTAMP(4);
                }
                ldsm4(xo + 128 * i, b[0][0], b[0][1], b[0][2], b[0][3]);
                ldsm4(xo + 128 * i + 64, b[1][0], b[1][1], b[1][2], b[1][3]);
#pragma unroll
                for (int q = 0; q < 16; q++) mma_bf(acc[q & 7], a[q][0], a[q][1], a[q][2], a[q][3], b[q >> 3][(q >> 1) & 2], b[q >> 3][((q >> 1) & 2) + 1]);
            }
            if (gu) {
                WSTAMP(5);
                __syncwarp();
#pragma unroll
                for (int q = 0; q < 4; q++) {
                    const int ct = q >> 1, e = 2 * (q & 1);
                    sts128(own + q * XS_ROW,
                           __float_as_uint(acc[ct][e] + acc[4 + ct][e]), __float_as_uint(acc[2 + ct][e] + acc[6 + ct][e]),
                           __float_as_uint(acc[ct][e + 1] + acc[4 + ct][e + 1]), __float_as_uint(acc[2 + ct][e + 1] + acc[6 + ct][e + 1]));
                }
                bar_sync(1, 128);
                float sl[2], uv[2];
#pragma unroll
                for (int e = 0; e < 2; e++) {
                    uint2 q[4];
#pragma unroll
                    for (int i = 0; i < 4; i++) q[i] = lds64((e ? po1 : po) + 512 * i);
                    const float s0 = (__uint_as_float(q[0].x) + __uint_as_float(q[1].x)) + (__uint_as_float(q[2].x) + __uint_as_float(q[3].x));
                    const float s1 = (__uint_as_float(q[0].y) + __uint_as_float(q[1].y)) + (__uint_as_float(q[2].y) + __uint_as_float(q[3].y));
                    const float gv = bf_round(p.gu_swap ? s1 : s0);
                    uv[e] = p.gu_swap ? s0 : s1;
                    sl[e] = gv * sigmoid_f(gv);
                }
                const uint32_t hw = hmul2_bf(pack_bf(sl[0], sl[1]), pack_bf(uv[0], uv[1]));
                st_gpu32(hdst, hw ? hw : 0x80000000u);
                signal(1, hw);
            }
        }
        WSTAMP(6);
        {
            const uint32_t own = pin(sb + OFF_XSEL + at * 16, lane);
            const uint32_t hb = sb + (v < 2 ? OFF_XSEL + 7168 * v : OFF_RING + 8192 * v), hl = pin(hb + 16 * lane, lane);
            const int krow = ((lane >> 1) & 8) + (lane & 7);
            const uint32_t tile = pin(sb + OFF_RING + v * 8192 + krow * 32 + ((((lane >> 3) ^ (krow >> 2)) & 1) << 4), lane);
            float dd[4][4];
            bar_sync(1, 128);
            mbar_wait(bars + 8 * (B_W + HW));
            WSTAMP(12);
            uint4 hq[7];
#pragma unroll 1
            for (int it = 0; it < (1 << 16); it++) {
                bulk_load(hb, &p.sc->h[tag & 1][32 * (56 * h + 14 * v)], 7168, bars + 8 * (B_X + v));
                uint32_t a[14][4], mn = 0xffffffffu;
                mbar_wait(bars + 8 * (B_W + 16 + v));
#pragma unroll
                for (int j = 0; j < 14; j++) ldsm4t(tile + (v & 2) * 16384 + j * 512, a[j][0], a[j][1], a[j][2], a[j][3]);
                mbar_wait(bars + 8 * (B_X + v), ~it & 1);
                WSTAMP(7);
#pragma unroll
                for (int j = 0; j < 7; j++) {
                    const uint4 q = lds128(hl + 512 * j);
                    mn = min(mn, q.x);
#pragma unroll
                    for (int e = 0; e < 2; e++) {
                        const uint32_t(&f)[4] = a[2 * j + e];
                        if (j < 2) mma_bf_z(dd[2 * j + e], f[0], f[1], f[2], f[3], e ? q.z : q.x, e ? q.w : q.y);
                        else mma_bf(dd[(2 * j + e) & 3], f[0], f[1], f[2], f[3], e ? q.z : q.x, e ? q.w : q.y);
                    }
                }
#pragma unroll
                for (int j = 0; j < 7; j++) { hq[j] = lds128(hl + 3584 + 512 * j); mn = min(mn, hq[j].x); }
                if (__all_sync(0xffffffffu, mn != 0)) break;
            }
            mbar_wait(bars + 8 * (B_W + 20 + v));
#pragma unroll
            for (int j = 0; j < 14; j++) {
                uint32_t f[4];
                ldsm4t(tile + 65536 + j * 512, f[0], f[1], f[2], f[3]);
                mma_bf(dd[(j + 2) & 3], f[0], f[1], f[2], f[3], (j & 1) ? hq[j >> 1].z : hq[j >> 1].x, (j & 1) ? hq[j >> 1].w : hq[j >> 1].y);
            }
            WSTAMP(8);
            uint4 part;
            part.x = __float_as_uint((dd[0][0] + dd[1][0]) + (dd[2][0] + dd[3][0])); part.y = __float_as_uint((dd[0][1] + dd[1][1]) + (dd[2][1] + dd[3][1]));
            part.z = __float_as_uint((dd[0][2] + dd[1][2]) + (dd[2][2] + dd[3][2])); part.w = __float_as_uint((dd[0][3] + dd[1][3]) + (dd[2][3] + dd[3][3]));
            st_async16(mapa(own + (M_DPIN - OFF_XSEL), h ^ 1), part, mapa(bars + 8 * B_DP, h ^ 1));
            sts128(own + 14336, part.x, part.y, part.z, part.w);
            __syncwarp();
            if (lane == 0) mbar_arrive(bars + 8 * B_DP);
        }
        WDUMP();
    } else {
        asm volatile("setmaxnreg.dec.sync.aligned.u32 64;");
        const int v = __reduce_max_sync(0xffffffffu, pw - PREP_W0);
        const bool gu = c < NGU_CTA;
        const uint32_t t0 = clock();
        const uint32_t bu = bars + 8 * v;
        if (lane == 0) {
#pragma unroll
            for (int i = 0; i < 10; i++) mbar_init(bu + 32 * i, 1);
            mbar_init(bu + 8 * B_X, 1);
            mbar_init(bu + 8 * B_XE, 1);
            mbar_init(bu + 8 * B_Y, v == 0 ? 11 : 9);
            mbar_init(bu + 8 * B_DP, (0x1855 >> (4 * v)) & 15);
            mbar_init(bu + 8 * B_F, 1);
            mbar_init(bu + 8 * B_H, 1);
            asm volatile("fence.mbarrier_init.release.cluster;" ::: "memory");
            mbar_expect(bu + 8 * B_Y, 4096);
            if (v != 2) mbar_expect(bu + 8 * B_DP, v == 0 ? 2048 : (h || v == 3) ? 16384 : 16384 + 128);
            mbar_expect(bu + 8 * B_F, c < NGU_CTA ? 16 : 0);
        }
        __syncwarp();
        asm volatile("barrier.cluster.arrive.relaxed.aligned;" ::: "memory");
        bulk_load(sb + (v < 2 ? OFF_XSEL : OFF_RING + 2 * 8192) + v * 8192, p.u + (size_t)(16 * c + 4 * v) * D_, 8192, bu + 8 * B_X);
        tma3d(sb + OFF_S + v * S_Q, &tm_x, 16 * pr, 64 * v + 32 * h - 1, bars + 8 * (B_S + v), S_Q);
        WSTAMP(9);
        if (v < 3 && lane == 0) asm volatile("prefetch.tensormap [%0];" :: "l"(v == 0 ? &tm_gu : v == 1 ? &tm_down : &tm_out) : "memory");
        asm volatile("barrier.cluster.wait.acquire.aligned;" ::: "memory");
        uint32_t desc;
        {
            const int s = 6 * v + lane, i = s >> 2, w = s & 3, slot = s < 14 ? s : (s | 1) == 17 ? s - 16 : s - 12;
            const int fb = s < 4 ? B_H : (gu && s >= 14) ? B_E + slot : s < 6 ? B_XE + s - 2 : B_KG;
            desc = slot | (fb << 4) | ((i < 4 ? 256 * w + 64 * i : 1792 * h + 448 * w + 224 * (i - 4)) << 10);
            if (lane < 6) mbar_expect(bars + 8 * (B_W + s), i < 4 ? 8192 : 7168);
            if (tid == 32 * PREP_W0) mbar_arrive(bars + 8 * B_H);
        }
        if (v == 3) {
            mbar_wait(bars + 8 * B_U);
            mbar_wait(bars + 8 * (gu ? B_G : B_H + 2));
            const uint32_t tag16 = lds32(sb + M_TAG);
            uint4 q[8];
#pragma unroll 1
            for (int it = 0; it < (1 << 22); it++) {
                uint32_t bad = 0;
#pragma unroll
                for (int i = 0; i < 8; i++) q[i] = ld_gpu128(&p.sc->g[256 * h + 32 * i + lane]);
#pragma unroll
                for (int i = 0; i < 8; i++) bad |= ((q[i].x ^ tag16) | (q[i].y ^ tag16)) | ((q[i].z ^ tag16) | (q[i].w ^ tag16));
                if ((bad >> 16) == 0) break;
                __nanosleep(200);
            }
#pragma unroll
            for (int i = 0; i < 8; i++)
                asm volatile("st.shared.v2.u32 [%0], {%1, %2};" :: "r"(sb + OFF_GP + 256 * i + lane * 8),
                             "r"(__byte_perm(q[i].x, q[i].y, 0x5410)), "r"(__byte_perm(q[i].z, q[i].w, 0x5410)) : "memory");
            __syncwarp();
            if (lane == 0) mbar_arrive(bars + 8 * B_Y);
        }
        mbar_wait(bars + 8 * (B_H + v));
        {
            const int gap = v == 0 ? GAP : v == 1 ? GAP1 : v == 2 ? GAP2 : GAP3;
            uint32_t last = v ? clock() - SLACK : t0 + T0 - GAP + STAG * ((pr * 5) & 15) / 16;
#pragma unroll 1
            while ((int)(last - clock()) > 500) __nanosleep(256);
#pragma unroll 1
            for (int k = 0; k < 6; k++) {
                const uint32_t dk = __reduce_max_sync(0xffffffffu, lane == k ? desc : 0);
                const bool dn = 6 * v + k >= 16;
                mbar_wait(bars + ((dk >> 1) & 0x1f8));
                uint32_t now;
#pragma unroll 1
                while ((int)((now = clock()) - last) < gap) __nanosleep(CSLEEP);
                last = max((int)(now - last) - SLACK, gap) + last;
                WSTAMP(3 + k);
                if (gu || dn)
                    asm volatile("{\n\t.reg .pred p;\n\telect.sync _|p, 0xffffffff;\n\t"
                                 "@p cp.async.bulk.tensor.3d.shared::cluster.global.mbarrier::complete_tx::bytes [%0], [%1, {%3, %4, 0}], [%2];\n\t}"
                        :: "r"(sb + OFF_RING + (dk & 15) * 8192), "l"(dn ? &tm_down : &tm_gu), "r"(bars + 8 * (B_W + 6 * v + k)), "r"(dn ? 16 * pr : 32 * c), "r"(dk >> 10) : "memory");
                if (k < 5 && PRESLEEP) __nanosleep(PRESLEEP);
            }
            if (lane == 0 && v < 3) mbar_arrive(bars + 8 * (B_H + v + 1));
        }
        {
            WSTAMP(1);
            mix_rows<2, true>(p, &tm_out, sb, sb + OFF_TAB + v * TAB_W, 0, PQ, v, h, pr, lane);
            WSTAMP(2);
            asm volatile("cp.async.bulk.commit_group;" ::: "memory");
            const uint32_t top = lds32(sb + M_TOP + 8 * v + 4 * (lane >> 4));
            const uint32_t row = ~top & 2047, ch = lane & 15, gp = gate_pos(row);
            const bool mine = ((row >> 8) & 1) == h;
            uint32_t gfin, x16, y16 = 0;
            asm volatile("ld.shared.u16 %0, [%1];" : "=r"(gfin) : "r"(sb + OFF_GP + gp * 2) : "memory");
            asm volatile("ld.shared.u16 %0, [%1];" : "=r"(x16) : "r"(sb + OFF_S + (row >> 9) * S_Q + s_addr((row & 7) * S_PL + 32 + (row & 248) * 4, ch >> 3) + 2 * (ch & 7)) : "memory");
            const float rsel = __uint_as_float(pin(__float_as_uint(bf_round(sigmoid_f(__uint_as_float((top ^ (((int)~top >> 31) | 0x80000000u)) & 0xffff0000u)))), lane));
            const uint32_t po = pin(sb + (4 * (ch & 7) + v) * 16 + (ch >> 3) * 8 + (lane >> 4) * 4, lane);
            bf16* op = pin(p.out + (size_t)row * D_ + 16 * pr + ch, lane);
            if (mine) {
                mbar_wait(bars + 8 * (B_Y + (row >> 9)));
                asm volatile("ld.shared.u16 %0, [%1];" : "=r"(y16)
                             : "r"(sb + y_off(row >> 9) + ch * 512 + (((4 * (row & 7) + ((row >> 5) & 3)) ^ (((ch >> 2) << 1) | (ch & 1))) << 4) + 2 * row_elem(row)) : "memory");
            }
            mbar_wait(bars + 8 * B_DP);
            float q[8];
#pragma unroll
            for (int i = 0; i < 4; i++) { q[i] = ldsf(po + M_DPIN + 512 * i); q[4 + i] = ldsf(po + OFF_XSEL + 14336 + 512 * i); }
            const float tot = ((q[0] + q[1]) + (q[2] + q[3])) + ((q[4] + q[5]) + (q[6] + q[7]));
            const float b = bf_round(__uint_as_float(x16 << 16) + bf_round(bf_round(tot) * rsel));
            if (mine) *op = __float2bfloat16_rn(fmaf(bf_lo(gfin), __uint_as_float(y16 << 16), bf_round(bf_round(1.f - bf_lo(gfin)) * b)));
        }
        asm volatile("cp.async.bulk.wait_group.read 0;" ::: "memory");
        WSTAMP(10);
        WDUMP();
    }
}

typedef CUresult (*EncodeFn)(CUtensorMap*, CUtensorMapDataType, cuuint32_t, void*, const cuuint64_t*, const cuuint64_t*,
                             const cuuint32_t*, const cuuint32_t*, CUtensorMapInterleave, CUtensorMapSwizzle,
                             CUtensorMapL2promotion, CUtensorMapFloatOOBfill);

void make_map(EncodeFn f, CUtensorMap* m, const void* ptr, uint64_t cols, uint64_t rows, uint64_t pitch, uint32_t bc, uint32_t br, CUtensorMapSwizzle sw, int prom,
              uint32_t planes = 1, uint64_t plane_stride = 0, uint32_t box_planes = 0) {
    cuuint64_t dims[3] = {cols, rows, planes};
    cuuint64_t str[2] = {pitch, planes > 1 ? plane_stride : pitch * rows};
    cuuint32_t box[3] = {bc, br, box_planes ? box_planes : planes};
    cuuint32_t es[3] = {1, 1, 1};
    f(m, CU_TENSOR_MAP_DATA_TYPE_BFLOAT16, 3, (void*)ptr, dims, str, box, es, CU_TENSOR_MAP_INTERLEAVE_NONE, sw,
      (CUtensorMapL2promotion)prom, CU_TENSOR_MAP_FLOAT_OOB_FILL_NONE);
}

}

extern "C" void kernel_launch(void* const* d_in, const int* in_sizes, int n_in, void* d_out, int out_size) {
    static EncodeFn enc = nullptr;
    static void *sc = nullptr, *band = nullptr;
    if (!enc) {
        void* fn = nullptr;
        cudaDriverEntryPointQueryResult qr;
        cudaGetDriverEntryPoint("cuTensorMapEncodeTiled", &fn, cudaEnableDefault, &qr);
        enc = (EncodeFn)fn;
        cudaGetSymbolAddress(&sc, g_scratch);
        cudaGetSymbolAddress(&band, g_band);
        cudaFuncSetAttribute(fused_kernel, cudaFuncAttributeMaxDynamicSharedMemorySize, SMEM_BYTES);
    }
    CUtensorMap tg, td, tx, to;
    const char *wg = (const char*)d_in[9], *wu = (const char*)d_in[10];
    const bool swap = wu < wg;
    make_map(enc, &tg, swap ? wu : wg, F_, D_, F_ * 2, 32, 64, CU_TENSOR_MAP_SWIZZLE_64B, PROMG, 2, swap ? wg - wu : wu - wg);
    make_map(enc, &td, d_in[11], D_, F_, D_ * 2, 16, 224, CU_TENSOR_MAP_SWIZZLE_32B, PROMD);
    make_map(enc, &tx, d_in[0], D_, L_ / 8, D_ * 16, 16, 33, CU_TENSOR_MAP_SWIZZLE_32B, PROMX, 8, D_ * 2);
    make_map(enc, &to, d_out, D_, L_ / 8, D_ * 16, 16, 32, CU_TENSOR_MAP_SWIZZLE_NONE, 0, 8, D_ * 2, 1);
    Params p;
    p.u = (const bf16*)d_in[0]; p.logA = (const bf16*)d_in[1]; p.Aim = (const bf16*)d_in[2];
    p.Cre = (const bf16*)d_in[3]; p.Cim = (const bf16*)d_in[4]; p.logdt = (const bf16*)d_in[5];
    p.Dskip = (const bf16*)d_in[6]; p.wr = (const bf16*)d_in[8]; p.gatew = (const bf16*)d_in[12];
    p.out = (bf16*)d_out;
    p.sc = (Scratch*)sc; p.band = (const uint4*)band;
    p.gu_swap = swap;
    p.zero = 0;
    fused_kernel<<<NCTA, NTHREADS, SMEM_BYTES>>>(p, tg, td, tx, to);
}
```

```cpp
#include <cuda_runtime.h>
#include <cuda_bf16.h>
#include <cuda_fp16.h>
#include <cuda.h>
#include <stdint.h>

typedef __nv_bfloat16 bf16;

namespace {

constexpr int L_ = 2048, D_ = 1024, F_ = 3584;
constexpr int NCTA = 130;
constexpr int NTHREADS = 512;
#define AUXW 12
constexpr int MAIN_W0 = 0, AUX_W0 = AUXW, PREP_W0 = 20 - AUXW;
#define T0 3300
#define GAP 540
#define GAP1 530
#define GAP2 530
#define GAP3 550
#define STAG GAP
#define CSLEEP 50
#define SLACK 300
#define TSLEEP 40
#define BULKM false
#define PW 19
#define PRESLEEP 64
#define PWQ 1
#define FMASK 0x71ffffe
#define PQ 3
#define PROMG 2
#define PROMD 1
#define PROMX 0
#define LATE2 0
#define HW 20
constexpr int NGU_CTA = 112;

constexpr int OFF_RING = 0;
constexpr int OFF_SCR  = 6 * 8192;
constexpr int S_PL     = 1056;
constexpr int S_Q      = 8 * S_PL;
constexpr int OFF_S    = 114688;
constexpr int OFF_GP   = OFF_S + 4 * S_Q;
constexpr int U_PL     = 2240;
constexpr int U_CH     = 4416;
constexpr int OFF_U    = 151552;
constexpr int TAB_W    = 3200;
constexpr int T_PL     = 544;
constexpr int T_A      = 2192 - 26 * 8;
constexpr int T_B      = 2568 - 59 * 8;
constexpr int OFF_TAB  = 186880;
constexpr int OFF_XSEL = 212480;
constexpr int XS_ROW   = 2064;
constexpr int OFF_BAND = 228992;
constexpr int OFF_MISC = 229536;
constexpr int M_BARS   = OFF_MISC;
constexpr int M_DSK    = OFF_MISC + 2736;
constexpr int M_SINK   = OFF_MISC + 512;
constexpr int M_TAG    = OFF_MISC + 516;
constexpr int M_BMAP   = OFF_MISC + 528;
constexpr int M_DPIN   = OFF_MISC + 656;
constexpr int M_TOP    = OFF_MISC + 2704;
constexpr int SMEM_BYTES = OFF_MISC + 2768;
__device__ __forceinline__ uint32_t s_addr(uint32_t o, uint32_t half) { return o + (((half ^ (o >> 7)) & 1) << 4); }
__host__ __device__ constexpr uint32_t y_off(uint32_t q) { return OFF_RING + 32768 + (q & 1) * 8192 + (q >> 1) * 65536; }

constexpr int B_W = 0;
constexpr int B_E = 24;
constexpr int B_S = 36;
constexpr int B_Y = 40;
constexpr int B_DP = 44, B_U = 45, B_KG = 46, B_G = 47;
constexpr int B_F = 48;
constexpr int B_H = 60;
constexpr int B_X = 52, B_XE = 56;

struct BandTab { uint32_t w[11][12]; };
constexpr BandTab make_band() {
    BandTab b{};
    for (int cls = 0; cls < 11; cls++)
        for (int wd = 0; wd < 10; wd++) {
            const int tau = cls + 2 - 8 * ((wd < 4 ? wd : wd - 4) >> 1);
            const int lo = (wd < 4) ? ((wd & 1) ? -2 : 3) : ((wd & 1) ? -4 : -11), wid = (wd < 4 ? 3 : 7) + 2 * (wd & 1);
            b.w[cls][wd] = ((tau >= lo && tau < lo + wid) ? 0x3F80u : 0u) | ((tau - 4 >= lo && tau - 4 < lo + wid) ? 0x3F800000u : 0u);
        }
    return b;
}
constexpr int NTOP = 32;
struct Scratch {
    uint4 r[L_ / 4];
    uint4 g[L_ / 4];
    uint4 h[2][8 * F_ / 8];
    uint32_t top[NTOP][32];
    unsigned epoch;
};
__device__ __align__(128) Scratch g_scratch;
__device__ const __align__(16) BandTab g_band = make_band();

struct Params {
    const bf16 *u, *logA, *Aim, *Cre, *Cim, *logdt, *Dskip, *wr, *gatew;
    bf16* out;
    Scratch* sc;
    const uint4* band;
    uint32_t gu_swap;
    uint32_t zero;
};

#define WSTAMP(i) do {} while (0)
#define KSTAMP(i, dep) do {} while (0)
#define WDUMP() do {} while (0)
#define RSTAMP(i) do {} while (0)

__device__ __forceinline__ uint32_t smem_u32(const void* p) { return (uint32_t)__cvta_generic_to_shared(p); }
__device__ __forceinline__ void mbar_init(uint32_t b, uint32_t c) { asm volatile("mbarrier.init.shared::cta.b64 [%0], %1;" :: "r"(b), "r"(c) : "memory"); }
__device__ __forceinline__ void mbar_expect(uint32_t b, uint32_t tx) { asm volatile("mbarrier.arrive.expect_tx.shared::cta.b64 _, [%0], %1;" :: "r"(b), "r"(tx) : "memory"); }
__device__ __forceinline__ void mbar_arrive(uint32_t b) { asm volatile("mbarrier.arrive.shared::cta.b64 _, [%0];" :: "r"(b) : "memory"); }
__device__ __forceinline__ void mbar_wait(uint32_t b, uint32_t parity = 0) {
    asm volatile("{\n\t.reg .pred p;\nW%=:\n\tmbarrier.try_wait.parity.shared::cta.b64 p, [%0], %1, 20000;\n\t@!p bra W%=;\n\t}" :: "r"(b), "r"(parity) : "memory");
}
__device__ __forceinline__ uint32_t mapa(uint32_t addr, uint32_t rank) { uint32_t r; asm("mapa.shared::cluster.u32 %0, %1, %2;" : "=r"(r) : "r"(addr), "r"(rank)); return r; }
__device__ __forceinline__ void tma3d(uint32_t dst, const CUtensorMap* tm, int c0, int c1, uint32_t bar, uint32_t bytes) {
    asm volatile("{\n\t.reg .pred p;\n\telect.sync _|p, 0xffffffff;\n\t"
                 "@p mbarrier.arrive.expect_tx.shared::cta.b64 _, [%2], %5;\n\t"
                 "@p cp.async.bulk.tensor.3d.shared::cluster.global.mbarrier::complete_tx::bytes [%0], [%1, {%3, %4, 0}], [%2];\n\t}"
        :: "r"(dst), "l"(tm), "r"(bar), "r"(c0), "r"(c1), "r"(bytes) : "memory");
}
__device__ __forceinline__ void bulk_load(uint32_t dst, const void* src, uint32_t bytes, uint32_t bar) {
    asm volatile("{\n\t.reg .pred p;\n\telect.sync _|p, 0xffffffff;\n\t"
                 "@p mbarrier.arrive.expect_tx.shared::cta.b64 _, [%2], %3;\n\t"
                 "@p cp.async.bulk.shared::cluster.global.mbarrier::complete_tx::bytes [%0], [%1], %3, [%2];\n\t}"
        :: "r"(dst), "l"(src), "r"(bar), "r"(bytes) : "memory");
}
__device__ __forceinline__ void st_async16(uint32_t dst, const uint4& v, uint32_t bar) {
    asm volatile("st.async.weak.shared::cluster.mbarrier::complete_tx::bytes.v4.b32 [%0], {%1,%2,%3,%4}, [%5];"
                 :: "r"(dst), "r"(v.x), "r"(v.y), "r"(v.z), "r"(v.w), "r"(bar) : "memory");
}
__device__ __forceinline__ void bar_sync(int id, int n) { asm volatile("bar.sync %0, %1;" :: "r"(id), "r"(n) : "memory"); }
__device__ __forceinline__ void cp16(uint32_t dst, const void* src) { asm volatile("cp.async.cg.shared.global [%0], [%1], 16;" :: "r"(dst), "l"(src) : "memory"); }
__device__ __forceinline__ void cp_wait_all() { asm volatile("cp.async.wait_all;" ::: "memory"); }
__device__ __forceinline__ uint4 ld_gpu128(const void* p) { uint4 v; asm volatile("ld.relaxed.gpu.global.v4.u32 {%0,%1,%2,%3}, [%4];" : "=r"(v.x), "=r"(v.y), "=r"(v.z), "=r"(v.w) : "l"(p) : "memory"); return v; }
__device__ __forceinline__ void st_gpu32(void* p, uint32_t v) { asm volatile("st.relaxed.gpu.global.u32 [%0], %1;" :: "l"(p), "r"(v) : "memory"); }

__device__ __forceinline__ void ldsm4(uint32_t a, uint32_t& r0, uint32_t& r1, uint32_t& r2, uint32_t& r3) {
    asm volatile("ldmatrix.sync.aligned.m8n8.x4.shared.b16 {%0,%1,%2,%3}, [%4];" : "=r"(r0), "=r"(r1), "=r"(r2), "=r"(r3) : "r"(a) : "memory");
}
__device__ __forceinline__ void ldsm4t(uint32_t a, uint32_t& r0, uint32_t& r1, uint32_t& r2, uint32_t& r3) {
    asm volatile("ldmatrix.sync.aligned.m8n8.x4.trans.shared.b16 {%0,%1,%2,%3}, [%4];" : "=r"(r0), "=r"(r1), "=r"(r2), "=r"(r3) : "r"(a) : "memory");
}
__device__ __forceinline__ uint32_t lds32(uint32_t a) { uint32_t v; asm volatile("ld.shared.u32 %0, [%1];" : "=r"(v) : "r"(a) : "memory"); return v; }
__device__ __forceinline__ uint2 lds64(uint32_t a) { uint2 v; asm volatile("ld.shared.v2.u32 {%0,%1}, [%2];" : "=r"(v.x), "=r"(v.y) : "r"(a) : "memory"); return v; }
__device__ __forceinline__ uint4 lds128(uint32_t a) { uint4 v; asm volatile("ld.shared.v4.u32 {%0,%1,%2,%3}, [%4];" : "=r"(v.x), "=r"(v.y), "=r"(v.z), "=r"(v.w) : "r"(a) : "memory"); return v; }
__device__ __forceinline__ void sts32(uint32_t a, uint32_t v) { asm volatile("st.shared.u32 [%0], %1;" :: "r"(a), "r"(v) : "memory"); }
__device__ __forceinline__ void sts16(uint32_t a, uint32_t v) { asm volatile("st.shared.u16 [%0], %1;" :: "r"(a), "h"((unsigned short)v) : "memory"); }
__device__ __forceinline__ void sts128(uint32_t a, uint32_t x, uint32_t y, uint32_t z, uint32_t w) { asm volatile("st.shared.v4.u32 [%0], {%1,%2,%3,%4};" :: "r"(a), "r"(x), "r"(y), "r"(z), "r"(w) : "memory"); }
__device__ __forceinline__ float ldsf(uint32_t a) { float v; asm volatile("ld.shared.f32 %0, [%1];" : "=f"(v) : "r"(a) : "memory"); return v; }

__device__ __forceinline__ void mma_bf(float (&d)[4], uint32_t a0, uint32_t a1, uint32_t a2, uint32_t a3, uint32_t b0, uint32_t b1) {
    asm volatile("mma.sync.aligned.m16n8k16.row.col.f32.bf16.bf16.f32 {%0,%1,%2,%3}, {%4,%5,%6,%7}, {%8,%9}, {%0,%1,%2,%3};"
        : "+f"(d[0]), "+f"(d[1]), "+f"(d[2]), "+f"(d[3]) : "r"(a0), "r"(a1), "r"(a2), "r"(a3), "r"(b0), "r"(b1));
}
__device__ __forceinline__ void mma_bf_z(float (&d)[4], uint32_t a0, uint32_t a1, uint32_t a2, uint32_t a3, uint32_t b0, uint32_t b1) {
    asm volatile("mma.sync.aligned.m16n8k16.row.col.f32.bf16.bf16.f32 {%0,%1,%2,%3}, {%4,%5,%6,%7}, {%8,%9}, {%10,%10,%10,%10};"
        : "=f"(d[0]), "=f"(d[1]), "=f"(d[2]), "=f"(d[3]) : "r"(a0), "r"(a1), "r"(a2), "r"(a3), "r"(b0), "r"(b1), "f"(0.f));
}
__device__ __forceinline__ void mma_bf_k8(float (&d)[4], uint32_t a0, uint32_t a1, uint32_t b0) {
    asm volatile("mma.sync.aligned.m16n8k8.row.col.f32.bf16.bf16.f32 {%0,%1,%2,%3}, {%4,%5}, {%6}, {%0,%1,%2,%3};"
        : "+f"(d[0]), "+f"(d[1]), "+f"(d[2]), "+f"(d[3]) : "r"(a0), "r"(a1), "r"(b0));
}
__device__ __forceinline__ void mma_h(float (&d)[4], uint32_t a0, uint32_t a1, uint32_t a2, uint32_t a3, uint32_t b0, uint32_t b1) {
    asm volatile("mma.sync.aligned.m16n8k16.row.col.f32.f16.f16.f32 {%0,%1,%2,%3}, {%4,%5,%6,%7}, {%8,%9}, {%0,%1,%2,%3};"
        : "+f"(d[0]), "+f"(d[1]), "+f"(d[2]), "+f"(d[3]) : "r"(a0), "r"(a1), "r"(a2), "r"(a3), "r"(b0), "r"(b1));
}
__device__ __forceinline__ uint32_t pack_bf(float lo, float hi) { uint32_t r; asm("cvt.rn.bf16x2.f32 %0, %1, %2;" : "=r"(r) : "f"(hi), "f"(lo)); return r; }
__device__ __forceinline__ uint32_t pack_h(float lo, float hi) { uint32_t r; asm("cvt.rn.f16x2.f32 %0, %1, %2;" : "=r"(r) : "f"(hi), "f"(lo)); return r; }
__device__ __forceinline__ float bf_lo(uint32_t v) { return __uint_as_float(v << 16); }
__device__ __forceinline__ float bf_hi(uint32_t v) { return __uint_as_float(v & 0xffff0000u); }
__device__ __forceinline__ float bf_round(float x) { return __uint_as_float(pack_bf(0.f, x)); }
__device__ __forceinline__ uint32_t hmul2_bf(uint32_t a, uint32_t b) { uint32_t r; asm("mul.rn.bf16x2 %0, %1, %2;" : "=r"(r) : "r"(a), "r"(b)); return r; }
__device__ __forceinline__ float ex2f(float x) { float r; asm("ex2.approx.ftz.f32 %0, %1;" : "=f"(r) : "f"(x)); return r; }

__device__ __forceinline__ float exp_acc(float x) {
    const float t = x * 1.4426950216293335f;
    const float r = fmaf(x, 1.4426950216293335f, -t) + x * 1.9259629911266175e-8f;
    return ex2f(t) * fmaf(r, 0.6931471805599453f, 1.f);
}
__device__ __forceinline__ float sigmoid_f(float x) { return __fdividef(1.f, 1.f + ex2f(-x * 1.4426950408889634f)); }
__device__ __forceinline__ void cexp_pow(float l2, float li, float e, float& zr, float& zi) {
    const float mag = ex2f(l2 * e);
    zr = mag * __cosf(li * e);
    zi = mag * __sinf(li * e);
}
__device__ __forceinline__ uint32_t hcmul(uint32_t a, uint32_t k, uint32_t kp) {
    const __half2 A = *reinterpret_cast<const __half2*>(&a);
    const __half2 r = __hfma2(__high2half2(A), *reinterpret_cast<const __half2*>(&kp), __hmul2(__low2half2(A), *reinterpret_cast<const __half2*>(&k)));
    return *reinterpret_cast<const uint32_t*>(&r);
}
#define CMUL(orr, oi, ar, ai, br, bi) do { float _r = (ar) * (br) - (ai) * (bi); float _i = (ar) * (bi) + (ai) * (br); orr = _r; oi = _i; } while (0)
#define CSQ(orr, oi, ar, ai) do { float _r = (ar) * (ar) - (ai) * (ai); float _i = 2.f * (ar) * (ai); orr = _r; oi = _i; } while (0)

__device__ __forceinline__ void mma_bf_k8z(float (&d)[4], uint32_t a0, uint32_t a1, uint32_t b0) {
    asm volatile("mma.sync.aligned.m16n8k8.row.col.f32.bf16.bf16.f32 {%0,%1,%2,%3}, {%4,%5}, {%6}, {%7,%7,%7,%7};"
        : "=f"(d[0]), "=f"(d[1]), "=f"(d[2]), "=f"(d[3]) : "r"(a0), "r"(a1), "r"(b0), "f"(0.f));
}
__device__ __forceinline__ void mma_hh_k8(uint32_t& d0, uint32_t& d1, uint32_t a0, uint32_t a1, uint32_t b0) {
    asm volatile("mma.sync.aligned.m16n8k8.row.col.f16.f16.f16.f16 {%0,%1}, {%2,%3}, {%4}, {%5,%5};"
        : "=r"(d0), "=r"(d1) : "r"(a0), "r"(a1), "r"(b0), "r"(0));
}
__device__ __forceinline__ void sched_fence(uint32_t zero, uint32_t id) {
    asm volatile("{\n\t.reg .pred p;\n\tsetp.eq.u32 p, %0, %1;\n\t@p exit;\n\t}" :: "r"(zero), "r"(id) : "memory");
}
__device__ __forceinline__ uint32_t pin(uint32_t x, int lane) { return __shfl_sync(0xffffffffu, x, lane); }
template <class T> __device__ __forceinline__ T* pin(T* x, int lane) { return (T*)__shfl_sync(0xffffffffu, (unsigned long long)x, lane); }
__device__ __forceinline__ void sts32_if(bool on, uint32_t a, uint32_t v) {
    asm volatile("{\n\t.reg .pred p;\n\tsetp.ne.u32 p, %2, 0;\n\t@p st.shared.u32 [%0], %1;\n\t}" :: "r"(a), "r"(v), "r"((uint32_t)on) : "memory");
}
__device__ __forceinline__ void sts128_if(bool on, uint32_t a, uint32_t x, uint32_t y, uint32_t z, uint32_t w) {
    asm volatile("{\n\t.reg .pred p;\n\tsetp.ne.u32 p, %5, 0;\n\t@p st.shared.v4.u32 [%0], {%1,%2,%3,%4};\n\t}" :: "r"(a), "r"(x), "r"(y), "r"(z), "r"(w), "r"((uint32_t)on) : "memory");
}
__device__ __forceinline__ void lds128_if(bool on, uint32_t a, uint32_t (&v)[4]) {
    asm volatile("{\n\t.reg .pred p;\n\tsetp.ne.u32 p, %5, 0;\n\t@p ld.shared.v4.u32 {%0,%1,%2,%3}, [%4];\n\t}"
        : "+r"(v[0]), "+r"(v[1]), "+r"(v[2]), "+r"(v[3]) : "r"(a), "r"((uint32_t)on) : "memory");
}
__device__ __forceinline__ uint32_t hfma2_bf(uint32_t a, uint32_t b, uint32_t c) { uint32_t r; asm("fma.rn.bf16x2 %0, %1, %2, %3;" : "=r"(r) : "r"(a), "r"(b), "r"(c)); return r; }
__device__ __forceinline__ __nv_bfloat162 bcast(uint32_t a, int hi) { const __nv_bfloat162 v = *reinterpret_cast<const __nv_bfloat162*>(&a); return hi ? __high2bfloat162(v) : __low2bfloat162(v); }
__device__ __forceinline__ uint32_t hmul2_bc(uint32_t a, int hi, uint32_t b) { const __nv_bfloat162 r = __hmul2_rn(bcast(a, hi), *reinterpret_cast<const __nv_bfloat162*>(&b)); return *reinterpret_cast<const uint32_t*>(&r); }
__device__ __forceinline__ uint32_t hfma2_bc(uint32_t a, int hi, uint32_t b, uint32_t c) {
    const __nv_bfloat162 r = __hfma2(bcast(a, hi), *reinterpret_cast<const __nv_bfloat162*>(&b), *reinterpret_cast<const __nv_bfloat162*>(&c));
    return *reinterpret_cast<const uint32_t*>(&r);
}
__device__ __forceinline__ uint32_t row_elem(uint32_t row) { return ((row >> 5) & 4) | ((row >> 2) & 2) | ((row >> 4) & 1); }
__device__ __forceinline__ uint32_t gate_pos(uint32_t row) { return ((row >> 9) << 8) | ((row & 7) << 5) | (row_elem(row) << 2) | ((row >> 5) & 3); }

template <int N, bool BULK>
__device__ __forceinline__ void mix_rows(const Params& p, const CUtensorMap* tm_out, uint32_t sb, uint32_t ob, int Q0, int Q1, int w, int h, int pr, int lane) {
    const int g = lane >> 2, t = lane & 3, mi = lane >> 3, r = lane & 7;
    const int m8 = 16 * (g >> 2) + ((g >> 1) & 1) + 2 * (g & 1);
    uint32_t yi = sb + (4 * (r >> 1) + 2 * (mi & 1) + (r & 1)) * 512 + (((4 * w + (mi >> 1)) ^ r) << 4);
    uint32_t xs = sb + OFF_S + s_addr(w * S_PL + 32 + m8 * 32, t >> 1) + ((t & 1) << 3);
    uint32_t gs = sb + OFF_GP + w * 64 + g * 8, os = ob + m8 * 32 + t * 8;
    if (N > 1) { yi = pin(yi, lane); xs = pin(xs, lane); gs = pin(gs, lane); os = pin(os, lane); }
    mbar_wait(sb + M_BARS + 8 * B_Y);
#pragma unroll 1
    for (int Q = Q0; Q < Q1; Q++) {
        uint2 xq[N][4];
        uint32_t gg[N][2], sw[N];
#pragma unroll
        for (int n = 0; n < N; n++) {
#pragma unroll
            for (int i = 0; i < 4; i++) xq[n][i] = lds64((xs ^ (((i ^ n) & 1) << 4)) + Q * S_Q + n * 4 * S_PL + i * 128);
            const uint2 gq = lds64(gs + Q * 512 + n * 256);
            sw[n] = lds32(sb + M_BMAP + w * 16 + n * 64 + Q * 4);
            gg[n][0] = gq.x; gg[n][1] = gq.y;
#pragma unroll
            for (int i = 0; i < 4; i++) {
                const uint32_t og = hfma2_bf(gg[n][i >> 1], 0xBF80BF80u, 0x3F803F80u);
                xq[n][i].x = hmul2_bc(og, i & 1, xq[n][i].x); xq[n][i].y = hmul2_bc(og, i & 1, xq[n][i].y);
            }
        }
        if (N > 1 && Q == PWQ) mbar_wait(sb + M_BARS + 8 * (B_W + PW));
        mbar_wait(sb + M_BARS + 8 * (B_Y + Q));
        __syncwarp();
#pragma unroll
        for (int n = 0; n < N; n++) {
#pragma unroll
            for (int x = 0; x < 2; x++) {
                uint32_t y[4];
                ldsm4t((yi ^ (x << 5)) + y_off(Q) + n * 256, y[0], y[1], y[2], y[3]);
#pragma unroll
                for (int e = 0; e < 2; e++) {
                    uint2& o = xq[n][2 * x + e];
                    o.x = hfma2_bc(gg[n][x], e, y[2 * e], o.x); o.y = hfma2_bc(gg[n][x], e, y[2 * e + 1], o.y);
                }
            }
        }
        if (BULK && (sw[0] | sw[N - 1]) == 0) {
#pragma unroll
            for (int n = 0; n < N; n++)
#pragma unroll
                for (int i = 0; i < 4; i++)
                    asm volatile("st.shared.v2.u32 [%0], {%1, %2};" :: "r"(os + Q * 1024 + n * 4 * TAB_W + i * 128), "r"(xq[n][i].x), "r"(xq[n][i].y) : "memory");
            asm volatile("fence.proxy.async.shared::cta;" ::: "memory");
            __syncwarp();
#pragma unroll
            for (int n = 0; n < N; n++)
                asm volatile("{\n\t.reg .pred p;\n\telect.sync _|p, 0xffffffff;\n\t"
                             "@p cp.async.bulk.tensor.3d.global.shared::cta.bulk_group [%1, {%2, %3, %4}], [%0];\n\t}"
                    :: "r"(ob + 4 * n * TAB_W + Q * 1024), "l"(tm_out), "r"(16 * pr), "r"(64 * Q + 32 * h), "r"(w + 4 * n) : "memory");
        } else {
            bf16* op = p.out + (size_t)(512 * Q + 256 * h + 8 * m8 + w) * D_ + 16 * pr + 4 * t;
#pragma unroll
            for (int n = 0; n < N; n++)
#pragma unroll
                for (int i = 0; i < 4; i++)
                    if (!((sw[n] >> (4 * g)) & (1u << i))) *(uint2*)(op + (size_t)(32 * i + 4 * n) * D_) = xq[n][i];
        }
    }
}

__global__ void __cluster_dims__(2, 1, 1) __launch_bounds__(NTHREADS, 1)
fused_kernel(const Params p, const __grid_constant__ CUtensorMap tm_gu, const __grid_constant__ CUtensorMap tm_down,
             const __grid_constant__ CUtensorMap tm_x, const __grid_constant__ CUtensorMap tm_out) {
    extern __shared__ __align__(1024) unsigned char smem[];
    const uint32_t sb = smem_u32(smem);
    int tid;
    asm volatile("mov.u32 %0, %%tid.x;" : "=r"(tid));
    const int pw = tid >> 5, lane = tid & 31;
    const int c = blockIdx.x, h = c & 1, pr = c >> 1;
    const uint32_t bars = sb + M_BARS;

    uint2 v_la, v_ai, v_cr, v_ci;
    uint32_t ldt16;
    {
        const uint32_t po = c * 256 + tid;
        asm volatile("{\n\t.reg .pred p;\n\t.reg .b64 a;\n\tsetp.ne.u32 p, %16, 0;\n\t"
                     "mad.wide.u32 a, %14, 8, %9;\n\t@p ld.global.nc.L1::no_allocate.v2.u32 {%0,%1}, [a];\n\t"
                     "mad.wide.u32 a, %15, 2, %13;\n\t@p ld.global.nc.u16 %8, [a];\n\t"
                     "mad.wide.u32 a, %14, 8, %10;\n\t@p ld.global.nc.L1::no_allocate.v2.u32 {%2,%3}, [a];\n\t"
                     "mad.wide.u32 a, %14, 8, %11;\n\t@p ld.global.nc.L1::no_allocate.v2.u32 {%4,%5}, [a];\n\t"
                     "mad.wide.u32 a, %14, 8, %12;\n\t@p ld.global.nc.L1::no_allocate.v2.u32 {%6,%7}, [a];\n\t}"
            : "=r"(v_la.x), "=r"(v_la.y), "=r"(v_ai.x), "=r"(v_ai.y), "=r"(v_cr.x), "=r"(v_cr.y), "=r"(v_ci.x), "=r"(v_ci.y), "=r"(ldt16)
            : "l"(p.logA), "l"(p.Aim), "l"(p.Cre), "l"(p.Cim), "l"(p.logdt), "r"(po), "r"(po >> 5), "r"((uint32_t)(tid < 256 && c < 128)));
    }

    if (c >= 128) {
        if (c != 128) return;
        RSTAMP(5);
        const unsigned tag = (*(volatile unsigned*)&p.sc->epoch + 1) & 0xffffu;
        const uint32_t list = sb + 128;
#pragma unroll 1
        for (int pass = 0; pass < 2; pass++) {
            sts128(list + 16 * tid, 0, 0, 0, 0);
            if (tid == 0) sts32(sb + 64, 0);
            uint32_t key[4] = {tag - 1, tag - 1, tag - 1, tag - 1};
#pragma unroll 1
            for (int it = 0; it < (pass << 22); it++) {
                uint32_t a[4];
                asm volatile("{\n\t.reg .b128 o, z;\n\t.reg .b64 l, u;\n\tmov.b64 l, {%5, %5};\n\tmov.b128 z, {l, l};\n\tatom.relaxed.gpu.global.exch.b128 o, [%4], z;\n\t"
                             "mov.b128 {l, u}, o;\n\tmov.b64 {%0, %1}, l;\n\tmov.b64 {%2, %3}, u;\n\t}"
                    : "=r"(a[0]), "=r"(a[1]), "=r"(a[2]), "=r"(a[3]) : "l"(&p.sc->r[tid]), "r"(tag - 1) : "memory");
#pragma unroll
                for (int i = 0; i < 4; i++) if (((a[i] ^ tag) & 0xffffu) == 0) key[i] = a[i];
                if ((((key[0] ^ tag) | (key[1] ^ tag) | (key[2] ^ tag) | (key[3] ^ tag)) & 0xffffu) == 0) break;
            }
            WSTAMP(0);
            uint32_t m = 0;
#pragma unroll
            for (int i = 0; i < 4; i++) {
                key[i] = ((pass ? key[i] : (lane + i) << 16) & 0xffff0000u) | (uint32_t)(2047 - (4 * tid + i));
                m = max(m, key[i]);
            }
            const uint32_t wm = __reduce_max_sync(0xffffffffu, m);
            if (lane == 0) sts32(sb + pw * 4, wm);
            __syncthreads();
            uint32_t thr = 0xffffffffu;
#pragma unroll
            for (int i = 0; i < 4; i++) { const uint4 q = lds128(sb + 16 * i); thr = min(thr, min(max(q.x, q.y), max(q.z, q.w))); }
            if (thr != 1) WSTAMP(1);
            if (m >= thr) {
                uint32_t pos;
                asm volatile("atom.shared.add.u32 %0, [%1], %2;" : "=r"(pos) : "r"(sb + 64), "r"(4 * ((key[0] >= thr) + (key[1] >= thr) + (key[2] >= thr) + (key[3] >= thr))) : "memory");
#pragma unroll
                for (int i = 0; i < 4; i++) if (key[i] >= thr) { sts32(list + pos, key[i]); pos += 4; }
            }
            __syncthreads();
            const uint32_t nc4 = lds32(sb + 64);
            if (nc4 != 1) WSTAMP(2);
#pragma unroll 1
            for (uint32_t j = 4 * pw; j < nc4; j += 64) {
                const uint32_t mine = lds32(list + j);
                int rank = 0;
#pragma unroll 1
                for (uint32_t i = 0; i < nc4; i += 128) rank += __popc(__ballot_sync(0xffffffffu, lds32(list + i + 4 * lane) > mine));
                if (rank < 8 && lane == 0) sts32(sb + 96 + 4 * rank, mine);
            }
            __syncthreads();
            if (tid < 8 * NTOP) st_gpu32(&p.sc->top[tid >> 3][tid & 7], lds32(sb + 96 + 4 * (tid & 7)) | (((tag + pass - 1) & 31) << 11));
            WSTAMP(3);
            if (!pass) RSTAMP(4);
        }
        WDUMP();
        return;
    }

    WSTAMP(0);
    if (pw < 8) {
        const int d = 8 * c + pw - MAIN_W0;
        if (lane == 0) asm volatile("cp.async.ca.shared.global [%0], [%1], 4;" :: "r"(sb + M_DSK + 4 * (pw - MAIN_W0)), "l"(p.Dskip + (d & ~1)) : "memory");
        asm volatile("barrier.cluster.arrive.relaxed.aligned;" ::: "memory");
        const int warp = pw - MAIN_W0;
        asm volatile("setmaxnreg.inc.sync.aligned.u32 160;");
        const int g = lane >> 2, t = lane & 3;
        const int mi = lane >> 3, r = lane & 7;
        const uint32_t TB = sb + OFF_TAB + warp * TAB_W;
        const uint32_t UB = sb + OFF_U + warp * U_CH;
        if (mi < 2) sts128(UB + mi * U_PL + r * 16, 0, 0, 0, 0);
        if (lane < 4) sts128(TB + lane * T_PL, 0, 0, 0, 0);
        sts128(sb + OFF_SCR + warp * 8192 + lane * 16, 0x3C00u, 0x3C00u, 0x3C00u, 0x3C00u);
        asm volatile("barrier.cluster.wait.acquire.aligned;" ::: "memory");
        __syncwarp();

        uint32_t cfix;
        {
            KSTAMP(4, v_la.x ^ v_ai.x ^ v_cr.x ^ v_ci.x ^ ldt16);
            const float dt = bf_round(exp_acc(__uint_as_float(ldt16 << 16)));
            float l2[4], li[4];
            {
                const uint32_t la[2] = {v_la.x, v_la.y}, ai[2] = {v_ai.x, v_ai.y};
                const float dt2 = -1.4426950408889634f * dt;
#pragma unroll
                for (int i = 0; i < 4; i++) {
                    l2[i] = bf_round(ex2f(((i & 1) ? bf_hi(la[i >> 1]) : bf_lo(la[i >> 1])) * 1.4426950408889634f)) * dt2;
                    li[i] = ((i & 1) ? bf_hi(ai[i >> 1]) : bf_lo(ai[i >> 1])) * dt;
                }
            }
            const uint32_t SX = sb + OFF_SCR + warp * 8192;
            const uint32_t sw = SX + (lane << 4);
#define PUT(buf, row, v) sts128(((sw + (row) * 512) ^ ((row) << 4)) + (buf) * 4096, v[0], v[1], v[2], v[3])
#define EMIT(bufa, rowa, bufb, rowb, xr, xi, k, kp) do { uint32_t pk[4], pd[4]; \
                if ((FMASK >> ((bufa) == (bufb) ? 8 + 4 * (bufa) + (rowa) / 2 : (rowa))) & 1) sched_fence(p.zero, __LINE__); \
                _Pragma("unroll") for (int i = 0; i < 4; i++) { pk[i] = pack_h(xr[i], xi[i]); pd[i] = hcmul(pk[i], k[i], kp[i]); } \
                PUT(bufa, rowa, pk); PUT(bufb, rowb, pd); } while (0)
#define CMUL4(orr, oi, ar, ai, br, bi) _Pragma("unroll") for (int i = 0; i < 4; i++) CMUL(orr[i], oi[i], ar[i], ai[i], br[i], bi[i])
#define CSQ4(orr, oi, ar, ai) _Pragma("unroll") for (int i = 0; i < 4; i++) CSQ(orr[i], oi[i], ar[i], ai[i])
            float z1r[4], z1i[4], z2r[4], z2i[4], z8r[4], z8i[4], z256r[4], z256i[4];
            uint32_t k4[4], k4p[4];
            float z4r[4], z4i[4];
#pragma unroll
            for (int i = 0; i < 4; i++) cexp_pow(l2[i], li[i], 1.f, z1r[i], z1i[i]);
            CSQ4(z2r, z2i, z1r, z1i);
            CSQ4(z4r, z4i, z2r, z2i);
            CSQ4(z8r, z8i, z4r, z4i);
            KSTAMP(5, __float_as_uint(z8r[3]));
            uint32_t Ya[16][4];
            float cr[4], ci[4], inv;
            {
                float w1r[4], w1i[4], ar[4], ai[4], br[4], bi[4];
                uint32_t k8[4], k8p[4];
#pragma unroll
                for (int i = 0; i < 4; i++) {
                    k8[i] = pack_h(z8r[i], -z8i[i]); k8p[i] = pack_h(z8i[i], z8r[i]);
                    CSQ(w1r[i], w1i[i], z8r[i], z8i[i]); w1i[i] = -w1i[i];
                }
                PUT(1, 0, k8);
                EMIT(0, 1, 1, 1, w1r, w1i, k8, k8p);
                CSQ4(ar, ai, w1r, w1i);            EMIT(0, 2, 1, 2, ar, ai, k8, k8p);
                CMUL4(br, bi, ar, ai, w1r, w1i);   EMIT(0, 3, 1, 3, br, bi, k8, k8p);
                CSQ4(ar, ai, ar, ai);              EMIT(0, 4, 1, 4, ar, ai, k8, k8p);
                CMUL4(ar, ai, ar, ai, w1r, w1i);   EMIT(0, 5, 1, 5, ar, ai, k8, k8p);
                CSQ4(br, bi, br, bi);              EMIT(0, 6, 1, 6, br, bi, k8, k8p);
                CMUL4(br, bi, br, bi, w1r, w1i);   EMIT(0, 7, 1, 7, br, bi, k8, k8p);
                __syncwarp();
                KSTAMP(6, 0);
                if ((FMASK >> 20) & 1) sched_fence(p.zero, 5);
                const uint32_t ab = SX + (mi & 1) * 4096 + r * 512, ax = ((mi >> 1) ^ r) << 4;
                const uint32_t vr[2] = {v_cr.x, v_cr.y}, vi[2] = {v_ci.x, v_ci.y};
                const uint32_t m2 = __vmaxu2(__vmaxu2(vr[0] & 0x7fff7fffu, vr[1] & 0x7fff7fffu), __vmaxu2(vi[0] & 0x7fff7fffu, vi[1] & 0x7fff7fffu));
                const uint32_t mx = __reduce_max_sync(0xffffffffu, max(m2, m2 << 16));
                const uint32_t e = min(max(mx >> 23, 11u), 254u);
                const float sc = __uint_as_float((264u - e) << 23);
                inv = __uint_as_float((e - 10u) << 23) * (2.f * dt);
#pragma unroll
                for (int i = 0; i < 4; i++) {
#pragma unroll
                    for (int k = 0; k < 4; k++) ldsm4(ab + (ax ^ (i << 5)) + k * 128, Ya[4 * k + i][0], Ya[4 * k + i][1], Ya[4 * k + i][2], Ya[4 * k + i][3]);
                    float tr, ti;
                    cexp_pow(l2[i], li[i], 128.f, tr, ti);
                    sts32(TB + 2176 + 256 * i + 4 * lane, pack_h(tr, ti));
                    sts32(TB + 2176 + 256 * i + 128 + 4 * (lane ^ 16), pack_h(-ti, tr));
                    k4[i] = pack_h(z4r[i], z4i[i]); k4p[i] = pack_h(-z4i[i], z4r[i]);
                    CSQ(z256r[i], z256i[i], tr, ti);
                    cr[i] = ((i & 1) ? bf_hi(vr[i >> 1]) : bf_lo(vr[i >> 1])) * sc;
                    ci[i] = ((i & 1) ? bf_hi(vi[i >> 1]) : bf_lo(vi[i >> 1])) * sc;
                    if ((FMASK >> (24 + i)) & 1) sched_fence(p.zero, 8 + i);
                }
                __syncwarp();
            }
            KSTAMP(7, Ya[15][0]);
            const uint32_t ld0 = SX + r * 512 + ((mi ^ r) << 4), ld1 = ld0 ^ 64;
            float R[6][4], s1024;
            {
                float xr[4], xi[4], yr[4], yi[4];
                EMIT(0, 0, 0, 1, cr, ci, k4, k4p);
                CMUL4(yr, yi, cr, ci, z1r, z1i);        EMIT(0, 2, 0, 3, yr, yi, k4, k4p);
                CMUL4(xr, xi, cr, ci, z256r, z256i);    EMIT(1, 0, 1, 1, xr, xi, k4, k4p);
                CMUL4(yr, yi, yr, yi, z1r, z1i);        EMIT(0, 4, 0, 5, yr, yi, k4, k4p);
                CMUL4(cr, ci, xr, xi, z2r, z2i);        EMIT(1, 2, 1, 3, cr, ci, k4, k4p);
                CMUL4(yr, yi, yr, yi, z1r, z1i);        EMIT(0, 6, 0, 7, yr, yi, k4, k4p);
                CMUL4(xr, xi, xr, xi, z256r, z256i);    EMIT(1, 4, 1, 5, xr, xi, k4, k4p);
                CMUL4(xr, xi, xr, xi, z256r, z256i);    EMIT(1, 6, 1, 7, xr, xi, k4, k4p);
                CMUL4(xr, xi, xr, xi, z256r, z256i);
                s1024 = (xr[0] + xr[1]) + (xr[2] + xr[3]);
#pragma unroll
                for (int m = 0; m < 4; m++) {
                    if (m == 0) { CMUL4(xr, xi, xr, xi, z8r, z8i); } else { CMUL4(xr, xi, xr, xi, z256r, z256i); }
                    if ((FMASK >> (16 + m)) & 1) sched_fence(p.zero, 1 + m);
                    sts128(TB + m * T_PL + 16 + 16 * lane, pack_h(xr[0], xi[0]), pack_h(xr[1], xi[1]), pack_h(xr[2], xi[2]), pack_h(xr[3], xi[3]));
                }
            }
            __syncwarp();
            {
                KSTAMP(8, 0);
                if ((FMASK >> 21) & 1) sched_fence(p.zero, 6);
                uint32_t bd[2][4] = {{0, 0, 0, 0}, {0, 0, 0, 0}};
                const bool on = (g >> 1) == t;
#pragma unroll
                for (int i = 0; i < 6; i++) { R[i][0] = R[i][1] = R[i][2] = R[i][3] = 0.f; }
                uint32_t x[2][4], y[2][4], z[2][4];
                auto fetch = [&](const int k2) {
                    const int b = k2 & 1;
                    lds128_if(on, TB + 2176 + g * 128 + (k2 < 4 ? 64 : -64) * (g & 1) + 16 * k2, bd[b]);
                    ldsm4(((k2 & 1) ? ld1 : ld0) + (k2 >> 1) * 128, x[b][0], x[b][1], x[b][2], x[b][3]);
                    ldsm4(((k2 & 1) ? ld1 : ld0) + (k2 >> 1) * 128 + 4096, y[b][0], y[b][1], y[b][2], y[b][3]);
                    ldsm4(TB + (r & 3) * T_PL + 16 + 16 * mi + 64 * k2, z[b][0], z[b][1], z[b][2], z[b][3]);
                };
                fetch(0);
#pragma unroll
                for (int k2 = 0; k2 < 8; k2++) {
                    const int b = k2 & 1;
                    uint32_t a1[2][4];
                    if ((FMASK >> 28) & 1) sched_fence(p.zero, 12 + k2);
                    if (k2 < 7) fetch(k2 + 1);
#pragma unroll
                    for (int u = 0; u < 2; u++) {
                        mma_hh_k8(a1[u][0], a1[u][1], Ya[2 * k2 + u][0], Ya[2 * k2 + u][1], bd[b][2 * u]);
                        mma_hh_k8(a1[u][2], a1[u][3], Ya[2 * k2 + u][2], Ya[2 * k2 + u][3], bd[b][2 * u + 1]);
                    }
#pragma unroll
                    for (int u = 0; u < 2; u++) {
                        const uint32_t(&a0)[4] = Ya[2 * k2 + u];
                        mma_h(R[0], a0[0], a0[1], a0[2], a0[3], x[b][2 * u], x[b][2 * u + 1]);
                        mma_h(R[2], a0[0], a0[1], a0[2], a0[3], y[b][2 * u], y[b][2 * u + 1]);
                        mma_h(R[4], a0[0], a0[1], a0[2], a0[3], z[b][2 * u], z[b][2 * u + 1]);
                        mma_h(R[1], a1[u][0], a1[u][1], a1[u][2], a1[u][3], x[b][2 * u], x[b][2 * u + 1]);
                        mma_h(R[3], a1[u][0], a1[u][1], a1[u][2], a1[u][3], y[b][2 * u], y[b][2 * u + 1]);
                        mma_h(R[5], a1[u][0], a1[u][1], a1[u][2], a1[u][3], z[b][2 * u], z[b][2 * u + 1]);
                    }
                }
            }
            __syncwarp();
            KSTAMP(9, __float_as_uint(R[3][0]));
            if ((FMASK >> 22) & 1) sched_fence(p.zero, 7);
            if (lane == 0) mbar_arrive(bars + 8 * B_KG + (__float_as_uint(R[0][0]) & __float_as_uint(R[2][0]) & p.zero));
            sts128(TB + 2176 + 16 * lane, 0, 0, 0, 0);
            sts128(TB + 2688 + 16 * lane, 0, 0, 0, 0);
            __syncwarp();
#undef PUT
#undef EMIT
#pragma unroll
            for (int o = 16; o > 0; o >>= 1) s1024 += __shfl_xor_sync(0xffffffffu, s1024, o);
            uint32_t w[4][4], dsk = 0;
            cp_wait_all();
            asm volatile("{\n\t.reg .pred p;\n\tsetp.eq.u32 p, %2, 0;\n\t@p ld.shared.u16 %0, [%1];\n\t}" : "+r"(dsk) : "r"(sb + M_DSK + 4 * warp + 2 * (warp & 1)), "r"(lane) : "memory");
#pragma unroll
            for (int a = 0; a < 4; a++) {
                const float v0 = (a == 0) ? fmaf(R[0][0], inv, __uint_as_float(dsk << 16)) : R[a][0] * inv;
                const float v1 = R[a][1] * inv, v2 = R[a][2] * inv, v3 = R[a][3] * inv;
                w[a][0] = pack_bf(v0, 0.f); w[a][1] = pack_bf(v1, v0); w[a][2] = pack_bf(v2, v1); w[a][3] = pack_bf(v3, v2);
            }
            const uint32_t wb = TB + 16 + 16 * g, w1 = wb + t * T_PL, w2 = wb + 256 + 2 * t * T_PL;
            const uint32_t w3 = (t == 0) ? wb + 256 + 3 * T_PL : TB + T_A + 8 * (16 * t + g);
            const uint32_t w3s = (t == 0) ? 128 : 64, w3o = (t == 0) ? 8 : 12;
            const uint32_t k512 = __shfl_sync(0xffffffffu, w[2][1], 2);
#pragma unroll
            for (int a = 0; a < 2; a++) {
                sts128(w1 + 128 * a, w[a][0], w[a][1], w[a][2], w[a][3]);
                const uint32_t(&q)[4] = w[2 + a];
                if (t < 2) sts128(w2 + 128 * a, q[0], q[1], q[2], q[3]);
                if (t == 0) { sts128(w2 + T_PL + 128 * a, q[0], q[1], q[2], q[3]); sts32(w3 + 128 * a + 4, q[2]); }
                sts32_if(t != 1 && (a == 1 || lane != 2), w3 + w3s * a, q[1]);
                sts32_if(t != 1, w3 + w3s * a + w3o, q[3]);
            }
            sts128_if(lane < 4, w1 + 512, t == 3 ? k512 : k512 >> 16, t < 2 ? k512 : t == 2 ? k512 & 0xffff0000u : k512 << 16, t < 2 ? k512 << 16 : 0u, 0);
            __syncwarp();
#pragma unroll
            for (int a = 0; a < 2; a++) {
                sts16(w1 + 128 * a + 18, w[a][3]);
                const uint32_t(&q)[4] = w[2 + a];
                if (t < 2) sts16(w2 + 128 * a + 18, q[3]);
                if (t == 0) { sts16(w2 + T_PL + 128 * a + 18, q[3]); sts16(w3 + 128 * a + 14, q[3]); }
            }
            if (t == 0) sts16(w3 + 128 - 4, w[3][0]);
            if (lane == 2 || (t == 0 && g > 0)) sts16(lane == 2 ? TB + 16 + 3 * T_PL + 4 * 127 : w3 - 4, w[2][0]);
            {
                float q[4];
#pragma unroll
                for (int i = 0; i < 4; i++) q[i] = (t < 2 ? R[4][i] : R[5][i]) * inv;
                const uint32_t b0 = pack_bf(q[0], q[2]), b1 = pack_bf(q[1], q[3]);
                const uint32_t wq = TB + T_B + 8 * (65 + 32 * (t & 1) + 4 * (t & 2) + g);
                sts32(wq, b0); sts32(wq + 12, b0); sts32(wq + 128, b1); sts32(wq + 140, b1);
            }
            cfix = pack_bf(s1024 * inv, s1024 * inv);
            if (lane == 0) sts32(TB + T_A + 8 * 64, cfix);
            __syncwarp();
        }
        WSTAMP(1);

        mbar_wait(bars + 8 * B_U);
        WSTAMP(2);

        float D[16][4];
        {
            const int x5 = g - t + 5;
            const uint32_t tabD = TB + (x5 & 3) * T_PL + (x5 & 12) + 16;
            {
                const uint32_t a1 = lds32(tabD - 8), a0 = p.zero;
#pragma unroll
                for (int jq = 0; jq < 4; jq++) {
                    uint32_t b[4];
                    ldsm4(UB + (9 + lane) * 16 + jq * 512, b[0], b[1], b[2], b[3]);
#pragma unroll
                    for (int i = 0; i < 4; i++) mma_bf_k8z(D[4 * jq + i], a0, a1, b[i]);
                }
            }
            const uint32_t ua = UB + (mi & 1) * U_PL + (8 + 8 * (mi >> 1) + r) * 16;
#pragma unroll 1
            for (int k0 = 0; k0 < 8; k0++) {
                uint32_t Uf[16][2];
#pragma unroll
                for (int jp = 0; jp < 8; jp++) ldsm4(ua + jp * 256 - k0 * 16, Uf[2 * jp][0], Uf[2 * jp][1], Uf[2 * jp + 1][0], Uf[2 * jp + 1][1]);
#pragma unroll
                for (int k1 = 0; k1 < 4; k1++) {
                    const uint32_t ta = tabD + 16 * (8 * k1 + k0);
                    const uint32_t a0 = lds32(ta), a1 = lds32(ta + 8), a2 = lds32(ta - 8), a3 = a0 ^ p.zero;
#pragma unroll
                    for (int J = k1; J < 16; J++) mma_bf(D[J], a0, a1, a2, a3, Uf[J - k1][0], Uf[J - k1][1]);
                }
                if (k0 == 0) {
                    const uint32_t ta = tabD + 16 * 32;
                    const uint32_t a0 = lds32(ta), a1 = lds32(ta + 8), a2 = lds32(ta - 8), a3 = a0 ^ p.zero;
#pragma unroll
                    for (int J = 4; J < 16; J++) mma_bf(D[J], a0, a1, a2, a3, Uf[J - 4][0], Uf[J - 4][1]);
                    const uint32_t f0 = (cfix ^ 0x80008000u) & (g == t ? 0xffffu : g == t + 4 ? 0xffff0000u : 0u);
                    const uint32_t f1 = p.zero, f2 = p.zero + p.zero, f3 = f0 ^ p.zero;
#pragma unroll
                    for (int J = 8; J < 16; J++) mma_bf(D[J], f0, f1, f2, f3, Uf[J - 8][0], Uf[J - 8][1]);
                }
            }
        }
        WSTAMP(3);
        {
            const int ch = 8 * h + warp;
            const uint32_t yo = sb + ch * 512 + ((lane ^ (((ch >> 2) << 1) | (ch & 1))) << 4);
            const uint32_t yr = mapa(yo, h ^ 1), ybr = mapa(bars + 8 * B_Y, h ^ 1);
            auto ship = [&](const int Q) {
                uint4 y[2];
#pragma unroll
                for (int hh = 0; hh < 2; hh++) {
                    const int J = 4 * Q + 2 * hh;
                    y[hh] = make_uint4(pack_bf(D[J][0], D[J][1]), pack_bf(D[J][2], D[J][3]), pack_bf(D[J + 1][0], D[J + 1][1]), pack_bf(D[J + 1][2], D[J + 1][3]));
                }
                if (!(Q & 1)) mbar_wait(bars + 8 * (B_F + (Q >> 1)));
                asm volatile("{\n\t.reg .pred p;\n\tsetp.eq.u32 p, %11, 0;\n\t"
                             "@p st.async.weak.shared::cluster.mbarrier::complete_tx::bytes.v4.b32 [%9], {%4,%5,%6,%7}, [%10];\n\t"
                             "@!p st.async.weak.shared::cluster.mbarrier::complete_tx::bytes.v4.b32 [%9], {%0,%1,%2,%3}, [%10];\n\t"
                             "@p st.shared.v4.b32 [%8], {%0,%1,%2,%3};\n\t@!p st.shared.v4.b32 [%8], {%4,%5,%6,%7};\n\t}"
                             :: "r"(y[0].x), "r"(y[0].y), "r"(y[0].z), "r"(y[0].w), "r"(y[1].x), "r"(y[1].y), "r"(y[1].z), "r"(y[1].w),
                                "r"(yo + y_off(Q)), "r"(yr + y_off(Q)), "r"(ybr + 8 * Q), "r"(h) : "memory");
                __syncwarp();
                if (lane == 0) mbar_arrive(bars + 8 * (B_Y + Q));
            };
            ship(0);
            const uint4 bA = lds128(sb + OFF_BAND + (g - t + 3) * 48), bB = lds128(sb + OFF_BAND + (g - t + 3) * 48 + 16);
            const uint2 bC = lds64(sb + OFF_BAND + (g - t + 3) * 48 + 32);
            uint2 QA[5][2], QB[8];
            const uint32_t tq = TB + 8 * (1 + g - 2 * t);
#pragma unroll
            for (int dd = 0; dd < 5; dd++) { QA[dd][0] = lds64(tq + T_A + 64 * (dd + 4)); QA[dd][1] = lds64(tq + T_A + 64 * (dd + 4) - 8); }
#pragma unroll
            for (int dd = 0; dd < 8; dd++) QB[dd] = lds64(tq + T_B + 64 * (dd + 8));
            const uint32_t u1 = UB + (mi & 1) * U_PL + (7 + r + (mi >> 1)) * 16;
            const uint32_t u2 = UB + ((mi & 1) ^ 1) * U_PL + (7 + r + (mi & 1) + 8 * (mi >> 1)) * 16;
            uint32_t n[4];
#pragma unroll
            for (int j = 0; j < 12; j++) {
                uint32_t m[4];
                ldsm4(u1 + j * 128, m[0], m[1], m[2], m[3]);
                if (!(j & 1)) ldsm4(u2 + j * 128, n[0], n[1], n[2], n[3]);
                const uint32_t n0 = n[2 * (j & 1)], n1 = n[2 * (j & 1) + 1];
                float wa[4], wb[4], wc[4], g1[4], g2[4];
                mma_bf_z(wa, bA.x, bA.y, bA.z, bA.w, m[0], m[1]);
                mma_bf_z(wb, bA.x, bA.y, bA.z, bA.w, n0, n1);
                mma_bf_z(wc, bA.x, bA.y, bA.z, bA.w, m[2], m[3]);
                if (j < 8) {
                    mma_bf_z(g1, bB.x, bB.y, bB.z, bB.w, m[0], m[1]);
                    mma_bf_z(g2, bB.x, bB.y, bB.z, bB.w, n0, n1);
                    mma_bf_k8(g1, bC.x, bC.y, m[2]);
                    mma_bf_k8(g2, bC.x, bC.y, m[3]);
                }
#pragma unroll
                for (int e = 0; e < 2; e++) {
                    const uint32_t q0 = pack_bf(wa[e], wa[e + 2]), q1 = pack_bf(wb[e], wb[e + 2]), q2 = q1 ^ p.zero, q3 = pack_bf(wc[e], wc[e + 2]);
#pragma unroll
                    for (int dd = 0; dd < 5; dd++)
                        if (j + 4 + dd < 16) mma_bf(D[j + 4 + dd], q0, q1, q2, q3, QA[dd][e].x, QA[dd][e].y);
                }
                if (j < 8) {
                    const uint32_t q0 = pack_bf(g1[0], g1[2]), q1 = pack_bf(g2[0], g2[2]), q2 = pack_bf(g1[1], g1[3]), q3 = pack_bf(g2[1], g2[3]);
#pragma unroll
                    for (int dd = 7 - j; dd >= 0; dd--) mma_bf(D[j + 8 + dd], q0, q1, q2, q3, QB[dd].x, QB[dd].y);
                }
                if ((j & 3) == 3) {
                    WSTAMP(4 + 2 * (j >> 2));
                    if (j == 11 && LATE2) ship(2);
                    if (j != 7 || !LATE2) ship((j >> 2) + 1);
                }
            }
        }
        const int warpu = __reduce_max_sync(0xffffffffu, warp);
        mix_rows<1, BULKM>(p, &tm_out, sb, sb + OFF_U + warpu * U_CH + (warpu & 1) * 64, PQ, 4, warpu, h, pr, lane);
        if (BULKM) asm volatile("cp.async.bulk.commit_group;\n\tcp.async.bulk.wait_group.read 0;" ::: "memory");
        WSTAMP(10);
        WDUMP();
    } else if ((pw & 12) == AUX_W0) {
        const int v = __reduce_max_sync(0xffffffffu, pw & 3);
        const int at = tid & 127;
        const int g = lane >> 2, t = lane & 3;
        unsigned tag;
        const bool gu = c < NGU_CTA;
        {
            const uint32_t xb = sb + (v < 2 ? OFF_XSEL : OFF_RING + 2 * 8192) + v * 8192;
            const uint32_t gws = sb + M_DPIN;
            const uint32_t row = 16 * c + 4 * v + (g >> 1);
#pragma unroll
            for (int i = 0; i < 8; i++)
                asm volatile("cp.async.ca.shared.global [%0], [%1], 4;" :: "r"((i < 4 ? sb + OFF_GP : gws) + 512 * (i & 3) + (tid & 124) * 4 + (tid & 1) * 8 + (tid & 2) * 2),
                             "l"((i < 4 ? p.wr : p.gatew) + 256 * (i & 3) + (tid & 127) * 2) : "memory");
            if ((tid & 127) < 33) cp16(sb + OFF_BAND + (tid & 127) * 16, p.band + (tid & 127));
            asm volatile("barrier.cluster.arrive.relaxed.aligned;" ::: "memory");
            tag = __reduce_max_sync(0xffffffffu, (*(volatile unsigned*)&p.sc->epoch + 1) & 0xffffu);
            if (gu) st_gpu32((uint32_t*)&p.sc->h[(tag + 1) & 1][32 * c] + at, 0);
            if (v == 2) sts32(sb + M_BMAP + lane * 4, 0);
            if (at == 0) sts32(sb + M_TAG, tag << 16);
            cp_wait_all();
            bar_sync(1, 128);
            uint2 w[16];
#pragma unroll
            for (int kb = 0; kb < 16; kb++) w[kb] = lds64((g < 4 ? sb + OFF_GP : gws) + 128 * kb + 32 * (g & 2) + 16 * t + 8 * (g & 1));
            asm volatile("barrier.cluster.wait.acquire.aligned;" ::: "memory");
            mbar_wait(bars + 8 * (B_X + v));
            WSTAMP(10);
            float dr[4][4];
#pragma unroll
            for (int kb = 0; kb < 16; kb++) {
                const uint4 x = lds128(xb + (g >> 1) * 2048 + 128 * kb + 16 * (lane & 7));
                if (kb < 4) mma_bf_z(dr[kb], x.x, x.y, x.z, x.w, w[kb].x, w[kb].y);
                else mma_bf(dr[kb & 3], x.x, x.y, x.z, x.w, w[kb].x, w[kb].y);
            }
            float rs = ((dr[0][0] + dr[0][3]) + (dr[1][0] + dr[1][3])) + ((dr[2][0] + dr[2][3]) + (dr[3][0] + dr[3][3]));
            if (lane == 0) mbar_arrive(bars + 8 * (B_XE + v) + (__float_as_uint(rs) & p.zero));
            rs += __shfl_xor_sync(0xffffffffu, rs, 5);
            const uint32_t rb = pack_bf(0.f, rs);
            if (!(lane & 7)) st_gpu32((uint32_t*)p.sc->r + row, ((rb ^ (((int)rb >> 31) | 0x80000000u)) & 0xffff0000u) | tag);
            WSTAMP(1);
            {
                const int n = 3 + (lane >> 3) + 4 * (lane & 1);
                const uint32_t so = (n & 7) * S_PL + ((lane & 6) + (n >> 3)) * 32;
                const uint32_t src[2] = {sb + OFF_S + v * S_Q + s_addr(so, h), sb + OFF_S + v * S_Q + s_addr(so + 32, h)};
                const uint32_t dst = sb + OFF_U + g * U_CH + (8 + 32 * v + 16 * h + t) * 16;
                const uint32_t rdst = mapa(dst, h ^ 1), rbar = mapa(bars + 8 * B_U, h ^ 1);
                mbar_wait(bars + 8 * (B_S + v));
                WSTAMP(9);
                uint4 a[8];
#pragma unroll
                for (int b = 0; b < 2; b++) {
#pragma unroll
                    for (int j = 0; j < 8; j++) { const int u = 4 * b + (j >> 1) + 8 * (j & 1); ldsm4t((u < 8 ? src[u & 1] ^ 16 : src[u & 1]) + ((u >> 1) & 3) * 256, a[j].x, a[j].y, a[j].z, a[j].w); }
#pragma unroll
                    for (int j = 0; j < 8; j++) {
                        const int u = 4 * b + (j >> 1) + 8 * (j & 1);
                        if (u < 8) st_async16(rdst + ((u >> 1) & 3) * 64 + (u & 1) * U_PL, a[j], rbar);
                        else sts128(dst + ((u >> 1) & 3) * 64 + (u & 1) * U_PL, a[j].x, a[j].y, a[j].z, a[j].w);
                    }
                }
                if (h && v == 3) {
                    ldsm4t((src[0] ^ 16) + 1024, a[0].x, a[0].y, a[0].z, a[0].w);
                    ldsm4t(src[0] + 1024, a[1].x, a[1].y, a[1].z, a[1].w);
                    if (t == 0) {
                        st_async16(rdst + 256, make_uint4(a[0].x, a[0].y & 0xffffu, a[0].z & 0xffffu, a[0].w & 0xffffu), rbar);
                        sts128(dst + 256, a[1].x, a[1].y & 0xffffu, a[1].z & 0xffffu, a[1].w & 0xffffu);
                    }
                }
                __syncwarp();
                if (lane == 0) mbar_arrive(bars + 8 * B_U);
            }
            if ((lane & 7) == 2) st_gpu32((uint32_t*)p.sc->g + ((row & 256) << 2) + gate_pos(row), pack_bf(sigmoid_f(__uint_as_float(rb)), 0.f) | (tag << 16));
            WSTAMP(2);
        }
        {
            const bool lane0 = pin(lane, lane) == 0;
            const uint32_t own = pin(sb + OFF_XSEL + (at ^ ((at >> 1) & 4)) * 16, lane);
            float acc[8][4];
#pragma unroll
            for (int i = 0; i < 8; i++) { acc[i][0] = acc[i][1] = acc[i][2] = acc[i][3] = 0.f; }
            const int krow = ((lane >> 1) & 8) + (lane & 7);
            const uint32_t tile0 = pin(sb + OFF_RING + krow * 64 + ((((lane >> 3) & 1) ^ ((krow >> 1) & 3)) << 4), lane);
            const uint32_t xo = pin(sb + OFF_XSEL + (lane & 7) * XS_ROW + 512 * v + 2 * (lane & 24), lane);
            const uint32_t po = pin(sb + OFF_XSEL + t * XS_ROW + (g & 3) * 128 + (g & 1) * 64 + v * 16 + (lane >> 4) * 8, lane);
            const uint32_t po1 = pin(po + 64 - (g & 1) * 128, lane);
            uint32_t* hdst = pin((uint32_t*)&p.sc->h[tag & 1][32 * c] + at, lane);
            auto signal = [&](const int k, const uint32_t dep) {
                if (lane < 2 && v < 2)
                    asm volatile("st.async.weak.shared::cluster.mbarrier::complete_tx::bytes.b32 [%0], %1, [%2];"
                                 :: "r"(mapa(sb + M_SINK, lane)), "r"(dep), "r"(mapa(bars + 8 * (B_F + k), lane)) : "memory");
            };
#pragma unroll 1
            for (int i = 0; i < 4; i++) {
                const int s = 4 * i + v;
                uint32_t a[16][4], b[2][4];
                if (gu) {
                    const uint32_t tile = tile0 + (s < 14 ? s : v) * 8192;
                    if (lane0 && i > 1) mbar_arrive(bars + 8 * (B_E + s - 4));
                    if (i == 2) signal(0, 0);
                    mbar_wait(bars + 8 * (B_W + s));
#pragma unroll
                    for (int q = 0; q < 16; q++) ldsm4t((tile ^ ((q & 1) << 5)) + ((q >> 1) & 1) * 4096 + (q >> 2) * 1024, a[q][0], a[q][1], a[q][2], a[q][3]);
                }
                if (i == 0) {
                    if (gu) {
                        uint32_t dep = p.zero;
#pragma unroll
                        for (int q = 0; q < 16; q += 2) dep &= a[q][0] & a[q + 1][0];
                        if (lane == 0) mbar_arrive(bars + 8 * (B_E + v) + dep);
                    }
                    WSTAMP(11);
                    uint32_t top;
#pragma unroll 1
                    for (int it = 0; it < (1 << 22); it++) {
                        asm volatile("ld.relaxed.gpu.global.u32 %0, [%1];" : "=r"(top) : "l"(&p.sc->top[c % NTOP][g]) : "memory");
                        if (__all_sync(0xffffffffu, ((top ^ (tag << 11)) & 0xf800u) == 0)) break;
                        if (TSLEEP) __nanosleep(TSLEEP);
                    }
                    WSTAMP(3);
                    if (gu) {
                        const uint32_t k = 4 * h + v, row = __reduce_max_sync(0xffffffffu, lane == 4 * k ? ~top & 2047 : 0);
                        asm volatile("{\n\t.reg .pred p;\n\telect.sync _|p, 0xffffffff;\n\t"
                                     "@p cp.async.bulk.shared::cluster.global.mbarrier::complete_tx::bytes.multicast::cluster [%0], [%1], 2048, [%2], %3;\n\t}"
                            :: "r"(sb + OFF_XSEL + k * XS_ROW), "l"(p.u + (size_t)row * D_), "r"(bars + 8 * B_G), "h"((unsigned short)3) : "memory");
                    }
                    if (v == 2) {
                        const uint32_t row = ~top & 2047;
                        if (t == 0 && ((row >> 8) & 1) == h)
                            asm volatile("red.shared.or.b32 [%0], %1;" :: "r"(sb + M_BMAP + (row & 7) * 16 + (row >> 9) * 4), "r"(1u << (gate_pos(row) & 31)) : "memory");
                        if (t == 0) sts32(sb + M_TOP + lane, top);
                        if (c == 0 && lane == 0) *(volatile unsigned*)&p.sc->epoch = tag;
                        __syncwarp();
                        if (lane0) mbar_arrive(bars + 8 * B_Y);
                    }
                    if (!gu) break;
                    mbar_wait(bars + 8 * B_G);
                    WSTAMP(4);
                }
                ldsm4(xo + 128 * i, b[0][0], b[0][1], b[0][2], b[0][3]);
                ldsm4(xo + 128 * i + 64, b[1][0], b[1][1], b[1][2], b[1][3]);
#pragma unroll
                for (int q = 0; q < 16; q++) mma_bf(acc[q & 7], a[q][0], a[q][1], a[q][2], a[q][3], b[q >> 3][(q >> 1) & 2], b[q >> 3][((q >> 1) & 2) + 1]);
            }
            if (gu) {
                WSTAMP(5);
                __syncwarp();
#pragma unroll
                for (int q = 0; q < 4; q++) {
                    const int ct = q >> 1, e = 2 * (q & 1);
                    sts128(own + q * XS_ROW,
                           __float_as_uint(acc[ct][e] + acc[4 + ct][e]), __float_as_uint(acc[2 + ct][e] + acc[6 + ct][e]),
                           __float_as_uint(acc[ct][e + 1] + acc[4 + ct][e + 1]), __float_as_uint(acc[2 + ct][e + 1] + acc[6 + ct][e + 1]));
                }
                bar_sync(1, 128);
                float sl[2], uv[2];
#pragma unroll
                for (int e = 0; e < 2; e++) {
                    uint2 q[4];
#pragma unroll
                    for (int i = 0; i < 4; i++) q[i] = lds64((e ? po1 : po) + 512 * i);
                    const float s0 = (__uint_as_float(q[0].x) + __uint_as_float(q[1].x)) + (__uint_as_float(q[2].x) + __uint_as_float(q[3].x));
                    const float s1 = (__uint_as_float(q[0].y) + __uint_as_float(q[1].y)) + (__uint_as_float(q[2].y) + __uint_as_float(q[3].y));
                    const float gv = bf_round(p.gu_swap ? s1 : s0);
                    uv[e] = p.gu_swap ? s0 : s1;
                    sl[e] = gv * sigmoid_f(gv);
                }
                const uint32_t hw = hmul2_bf(pack_bf(sl[0], sl[1]), pack_bf(uv[0], uv[1]));
                st_gpu32(hdst, hw ? hw : 0x80000000u);
                signal(1, hw);
            }
        }
        WSTAMP(6);
        {
            const uint32_t own = pin(sb + OFF_XSEL + at * 16, lane);
            const uint32_t hb = sb + (v < 2 ? OFF_XSEL + 7168 * v : OFF_RING + 8192 * v), hl = pin(hb + 16 * lane, lane);
            const int krow = ((lane >> 1) & 8) + (lane & 7);
            const uint32_t tile = pin(sb + OFF_RING + v * 8192 + krow * 32 + ((((lane >> 3) ^ (krow >> 2)) & 1) << 4), lane);
            float dd[4][4];
            bar_sync(1, 128);
            mbar_wait(bars + 8 * (B_W + HW));
            WSTAMP(12);
            uint4 hq[7];
#pragma unroll 1
            for (int it = 0; it < (1 << 16); it++) {
                bulk_load(hb, &p.sc->h[tag & 1][32 * (56 * h + 14 * v)], 7168, bars + 8 * (B_X + v));
                uint32_t a[14][4], mn = 0xffffffffu;
                mbar_wait(bars + 8 * (B_W + 16 + v));
#pragma unroll
                for (int j = 0; j < 14; j++) ldsm4t(tile + (v & 2) * 16384 + j * 512, a[j][0], a[j][1], a[j][2], a[j][3]);
                mbar_wait(bars + 8 * (B_X + v), ~it & 1);
                WSTAMP(7);
#pragma unroll
                for (int j = 0; j < 7; j++) {
                    const uint4 q = lds128(hl + 512 * j);
                    mn = min(mn, q.x);
#pragma unroll
                    for (int e = 0; e < 2; e++) {
                        const uint32_t(&f)[4] = a[2 * j + e];
                        if (j < 2) mma_bf_z(dd[2 * j + e], f[0], f[1], f[2], f[3], e ? q.z : q.x, e ? q.w : q.y);
                        else mma_bf(dd[(2 * j + e) & 3], f[0], f[1], f[2], f[3], e ? q.z : q.x, e ? q.w : q.y);
                    }
                }
#pragma unroll
                for (int j = 0; j < 7; j++) { hq[j] = lds128(hl + 3584 + 512 * j); mn = min(mn, hq[j].x); }
                if (__all_sync(0xffffffffu, mn != 0)) break;
            }
            mbar_wait(bars + 8 * (B_W + 20 + v));
#pragma unroll
            for (int j = 0; j < 14; j++) {
                uint32_t f[4];
                ldsm4t(tile + 65536 + j * 512, f[0], f[1], f[2], f[3]);
                mma_bf(dd[(j + 2) & 3], f[0], f[1], f[2], f[3], (j & 1) ? hq[j >> 1].z : hq[j >> 1].x, (j & 1) ? hq[j >> 1].w : hq[j >> 1].y);
            }
            WSTAMP(8);
            uint4 part;
            part.x = __float_as_uint((dd[0][0] + dd[1][0]) + (dd[2][0] + dd[3][0])); part.y = __float_as_uint((dd[0][1] + dd[1][1]) + (dd[2][1] + dd[3][1]));
            part.z = __float_as_uint((dd[0][2] + dd[1][2]) + (dd[2][2] + dd[3][2])); part.w = __float_as_uint((dd[0][3] + dd[1][3]) + (dd[2][3] + dd[3][3]));
            st_async16(mapa(own + (M_DPIN - OFF_XSEL), h ^ 1), part, mapa(bars + 8 * B_DP, h ^ 1));
            sts128(own + 14336, part.x, part.y, part.z, part.w);
            __syncwarp();
            if (lane == 0) mbar_arrive(bars + 8 * B_DP);
        }
        WDUMP();
    } else {
        asm volatile("setmaxnreg.dec.sync.aligned.u32 64;");
        const int v = __reduce_max_sync(0xffffffffu, pw - PREP_W0);
        const bool gu = c < NGU_CTA;
        const uint32_t t0 = clock();
        const uint32_t bu = bars + 8 * v;
        if (lane == 0) {
#pragma unroll
            for (int i = 0; i < 10; i++) mbar_init(bu + 32 * i, 1);
            mbar_init(bu + 8 * B_X, 1);
            mbar_init(bu + 8 * B_XE, 1);
            mbar_init(bu + 8 * B_Y, v == 0 ? 11 : 9);
            mbar_init(bu + 8 * B_DP, (0x1855 >> (4 * v)) & 15);
            mbar_init(bu + 8 * B_F, 1);
            mbar_init(bu + 8 * B_H, 1);
            asm volatile("fence.mbarrier_init.release.cluster;" ::: "memory");
            mbar_expect(bu + 8 * B_Y, 4096);
            if (v != 2) mbar_expect(bu + 8 * B_DP, v == 0 ? 2048 : (h || v == 3) ? 16384 : 16384 + 128);
            mbar_expect(bu + 8 * B_F, c < NGU_CTA ? 16 : 0);
        }
        __syncwarp();
        asm volatile("barrier.cluster.arrive.relaxed.aligned;" ::: "memory");
        bulk_load(sb + (v < 2 ? OFF_XSEL : OFF_RING + 2 * 8192) + v * 8192, p.u + (size_t)(16 * c + 4 * v) * D_, 8192, bu + 8 * B_X);
        tma3d(sb + OFF_S + v * S_Q, &tm_x, 16 * pr, 64 * v + 32 * h - 1, bars + 8 * (B_S + v), S_Q);
        WSTAMP(9);
        if (v < 3 && lane == 0) asm volatile("prefetch.tensormap [%0];" :: "l"(v == 0 ? &tm_gu : v == 1 ? &tm_down : &tm_out) : "memory");
        asm volatile("barrier.cluster.wait.acquire.aligned;" ::: "memory");
        uint32_t desc;
        {
            const int s = 6 * v + lane, i = s >> 2, w = s & 3, slot = s < 14 ? s : (s | 1) == 17 ? s - 16 : s - 12;
            const int fb = s < 4 ? B_H : (gu && s >= 14) ? B_E + slot : s < 6 ? B_XE + s - 2 : B_KG;
            desc = slot | (fb << 4) | ((i < 4 ? 256 * w + 64 * i : 1792 * h + 448 * w + 224 * (i - 4)) << 10);
            if (lane < 6) mbar_expect(bars + 8 * (B_W + s), i < 4 ? 8192 : 7168);
            if (tid == 32 * PREP_W0) mbar_arrive(bars + 8 * B_H);
        }
        if (v == 3) {
            mbar_wait(bars + 8 * B_U);
            mbar_wait(bars + 8 * (gu ? B_G : B_H + 2));
            const uint32_t tag16 = lds32(sb + M_TAG);
            uint4 q[8];
#pragma unroll 1
            for (int it = 0; it < (1 << 22); it++) {
                uint32_t bad = 0;
#pragma unroll
                for (int i = 0; i < 8; i++) q[i] = ld_gpu128(&p.sc->g[256 * h + 32 * i + lane]);
#pragma unroll
                for (int i = 0; i < 8; i++) bad |= ((q[i].x ^ tag16) | (q[i].y ^ tag16)) | ((q[i].z ^ tag16) | (q[i].w ^ tag16));
                if ((bad >> 16) == 0) break;
                __nanosleep(200);
            }
#pragma unroll
            for (int i = 0; i < 8; i++)
                asm volatile("st.shared.v2.u32 [%0], {%1, %2};" :: "r"(sb + OFF_GP + 256 * i + lane * 8),
                             "r"(__byte_perm(q[i].x, q[i].y, 0x5410)), "r"(__byte_perm(q[i].z, q[i].w, 0x5410)) : "memory");
            __syncwarp();
            if (lane == 0) mbar_arrive(bars + 8 * B_Y);
        }
        mbar_wait(bars + 8 * (B_H + v));
        {
            const int gap = v == 0 ? GAP : v == 1 ? GAP1 : v == 2 ? GAP2 : GAP3;
            uint32_t last = v ? clock() - SLACK : t0 + T0 - GAP + STAG * ((pr * 5) & 15) / 16;
#pragma unroll 1
            while ((int)(last - clock()) > 500) __nanosleep(256);
#pragma unroll 1
            for (int k = 0; k < 6; k++) {
                const uint32_t dk = __reduce_max_sync(0xffffffffu, lane == k ? desc : 0);
                const bool dn = 6 * v + k >= 16;
                mbar_wait(bars + ((dk >> 1) & 0x1f8));
                uint32_t now;
#pragma unroll 1
                while ((int)((now = clock()) - last) < gap) __nanosleep(CSLEEP);
                last = max((int)(now - last) - SLACK, gap) + last;
                WSTAMP(3 + k);
                if (gu || dn)
                    asm volatile("{\n\t.reg .pred p;\n\telect.sync _|p, 0xffffffff;\n\t"
                                 "@p cp.async.bulk.tensor.3d.shared::cluster.global.mbarrier::complete_tx::bytes [%0], [%1, {%3, %4, 0}], [%2];\n\t}"
                        :: "r"(sb + OFF_RING + (dk & 15) * 8192), "l"(dn ? &tm_down : &tm_gu), "r"(bars + 8 * (B_W + 6 * v + k)), "r"(dn ? 16 * pr : 32 * c), "r"(dk >> 10) : "memory");
                if (k < 5 && PRESLEEP) __nanosleep(PRESLEEP);
            }
            if (lane == 0 && v < 3) mbar_arrive(bars + 8 * (B_H + v + 1));
        }
        {
            WSTAMP(1);
            mix_rows<2, true>(p, &tm_out, sb, sb + OFF_TAB + v * TAB_W, 0, PQ, v, h, pr, lane);
            WSTAMP(2);
            asm volatile("cp.async.bulk.commit_group;" ::: "memory");
            const uint32_t top = lds32(sb + M_TOP + 8 * v + 4 * (lane >> 4));
            const uint32_t row = ~top & 2047, ch = lane & 15, gp = gate_pos(row);
            const bool mine = ((row >> 8) & 1) == h;
            uint32_t gfin, x16, y16 = 0;
            asm volatile("ld.shared.u16 %0, [%1];" : "=r"(gfin) : "r"(sb + OFF_GP + gp * 2) : "memory");
            asm volatile("ld.shared.u16 %0, [%1];" : "=r"(x16) : "r"(sb + OFF_S + (row >> 9) * S_Q + s_addr((row & 7) * S_PL + 32 + (row & 248) * 4, ch >> 3) + 2 * (ch & 7)) : "memory");
            const float rsel = __uint_as_float(pin(__float_as_uint(bf_round(sigmoid_f(__uint_as_float((top ^ (((int)~top >> 31) | 0x80000000u)) & 0xffff0000u)))), lane));
            const uint32_t po = pin(sb + (4 * (ch & 7) + v) * 16 + (ch >> 3) * 8 + (lane >> 4) * 4, lane);
            bf16* op = pin(p.out + (size_t)row * D_ + 16 * pr + ch, lane);
            if (mine) {
                mbar_wait(bars + 8 * (B_Y + (row >> 9)));
                asm volatile("ld.shared.u16 %0, [%1];" : "=r"(y16)
                             : "r"(sb + y_off(row >> 9) + ch * 512 + (((4 * (row & 7) + ((row >> 5) & 3)) ^ (((ch >> 2) << 1) | (ch & 1))) << 4) + 2 * row_elem(row)) : "memory");
            }
            mbar_wait(bars + 8 * B_DP);
            float q[8];
#pragma unroll
            for (int i = 0; i < 4; i++) { q[i] = ldsf(po + M_DPIN + 512 * i); q[4 + i] = ldsf(po + OFF_XSEL + 14336 + 512 * i); }
            const float tot = ((q[0] + q[1]) + (q[2] + q[3])) + ((q[4] + q[5]) + (q[6] + q[7]));
            const float b = bf_round(__uint_as_float(x16 << 16) + bf_round(bf_round(tot) * rsel));
            if (mine) *op = __float2bfloat16_rn(fmaf(bf_lo(gfin), __uint_as_float(y16 << 16), bf_round(bf_round(1.f - bf_lo(gfin)) * b)));
        }
        asm volatile("cp.async.bulk.wait_group.read 0;" ::: "memory");
        WSTAMP(10);
        WDUMP();
    }
}

typedef CUresult (*EncodeFn)(CUtensorMap*, CUtensorMapDataType, cuuint32_t, void*, const cuuint64_t*, const cuuint64_t*,
                             const cuuint32_t*, const cuuint32_t*, CUtensorMapInterleave, CUtensorMapSwizzle,
                             CUtensorMapL2promotion, CUtensorMapFloatOOBfill);

void make_map(EncodeFn f, CUtensorMap* m, const void* ptr, uint64_t cols, uint64_t rows, uint64_t pitch, uint32_t bc, uint32_t br, CUtensorMapSwizzle sw, int prom,
              uint32_t planes = 1, uint64_t plane_stride = 0, uint32_t box_planes = 0) {
    cuuint64_t dims[3] = {cols, rows, planes};
    cuuint64_t str[2] = {pitch, planes > 1 ? plane_stride : pitch * rows};
    cuuint32_t box[3] = {bc, br, box_planes ? box_planes : planes};
    cuuint32_t es[3] = {1, 1, 1};
    f(m, CU_TENSOR_MAP_DATA_TYPE_BFLOAT16, 3, (void*)ptr, dims, str, box, es, CU_TENSOR_MAP_INTERLEAVE_NONE, sw,
      (CUtensorMapL2promotion)prom, CU_TENSOR_MAP_FLOAT_OOB_FILL_NONE);
}

}

extern "C" void kernel_launch(void* const* d_in, const int* in_sizes, int n_in, void* d_out, int out_size) {
    static EncodeFn enc = nullptr;
    static void *sc = nullptr, *band = nullptr;
    if (!enc) {
        void* fn = nullptr;
        cudaDriverEntryPointQueryResult qr;
        cudaGetDriverEntryPoint("cuTensorMapEncodeTiled", &fn, cudaEnableDefault, &qr);
        enc = (EncodeFn)fn;
        cudaGetSymbolAddress(&sc, g_scratch);
        cudaGetSymbolAddress(&band, g_band);
        cudaFuncSetAttribute(fused_kernel, cudaFuncAttributeMaxDynamicSharedMemorySize, SMEM_BYTES);
    }
    CUtensorMap tg, td, tx, to;
    const char *wg = (const char*)d_in[9], *wu = (const char*)d_in[10];
    const bool swap = wu < wg;
    make_map(enc, &tg, swap ? wu : wg, F_, D_, F_ * 2, 32, 64, CU_TENSOR_MAP_SWIZZLE_64B, PROMG, 2, swap ? wg - wu : wu - wg);
    make_map(enc, &td, d_in[11], D_, F_, D_ * 2, 16, 224, CU_TENSOR_MAP_SWIZZLE_32B, PROMD);
    make_map(enc, &tx, d_in[0], D_, L_ / 8, D_ * 16, 16, 33, CU_TENSOR_MAP_SWIZZLE_32B, PROMX, 8, D_ * 2);
    make_map(enc, &to, d_out, D_, L_ / 8, D_ * 16, 16, 32, CU_TENSOR_MAP_SWIZZLE_NONE, 0, 8, D_ * 2, 1);
    Params p;
    p.u = (const bf16*)d_in[0]; p.logA = (const bf16*)d_in[1]; p.Aim = (const bf16*)d_in[2];
    p.Cre = (const bf16*)d_in[3]; p.Cim = (const bf16*)d_in[4]; p.logdt = (const bf16*)d_in[5];
    p.Dskip = (const bf16*)d_in[6]; p.wr = (const bf16*)d_in[8]; p.gatew = (const bf16*)d_in[12];
    p.out = (bf16*)d_out;
    p.sc = (Scratch*)sc; p.band = (const uint4*)band;
    p.gu_swap = swap;
    p.zero = 0;
    fused_kernel<<<NCTA, NTHREADS, SMEM_BYTES>>>(p, tg, td, tx, to);
}
```

```cpp
#include <cuda_runtime.h>
#include <cuda_bf16.h>
#include <cuda_fp16.h>
#include <cuda.h>
#include <stdint.h>

typedef __nv_bfloat16 bf16;

namespace {

constexpr int L_ = 2048, D_ = 1024, F_ = 3584;
constexpr int NCTA = 130;
constexpr int NTHREADS = 512;
#define AUXW 12
constexpr int MAIN_W0 = 0, AUX_W0 = AUXW, PREP_W0 = 20 - AUXW;
#define T0 3000
#define GAP 540
#define GAP1 530
#define GAP2 530
#define GAP3 550
#define STAG GAP
#define CSLEEP 50
#define SLACK 300
#define TSLEEP 40
#define BULKM false
#define PW 19
#define PRESLEEP 64
#define PWQ 1
#define PQ 3
#define PROMG 2
#define PROMD 1
#define PROMX 0
#define LATE2 0
#define HW 20
constexpr int NGU_CTA = 112;

constexpr int OFF_RING = 0;
constexpr int OFF_SCR  = 6 * 8192;
constexpr int S_PL     = 1056;
constexpr int S_Q      = 8 * S_PL;
constexpr int OFF_S    = 114688;
constexpr int OFF_GP   = OFF_S + 4 * S_Q;
constexpr int U_PL     = 2240;
constexpr int U_CH     = 4416;
constexpr int OFF_U    = 151552;
constexpr int TAB_W    = 3200;
constexpr int T_PL     = 544;
constexpr int T_A      = 2192 - 26 * 8;
constexpr int T_B      = 2568 - 59 * 8;
constexpr int OFF_TAB  = 186880;
constexpr int OFF_XSEL = 212480;
constexpr int XS_ROW   = 2064;
constexpr int OFF_BAND = 228992;
constexpr int OFF_MISC = 229536;
constexpr int M_BARS   = OFF_MISC;
constexpr int M_DSK    = OFF_MISC + 2736;
constexpr int M_SINK   = OFF_MISC + 512;
constexpr int M_TAG    = OFF_MISC + 516;
constexpr int M_BMAP   = OFF_MISC + 528;
constexpr int M_DPIN   = OFF_MISC + 656;
constexpr int M_TOP    = OFF_MISC + 2704;
constexpr int SMEM_BYTES = OFF_MISC + 2768;
__device__ __forceinline__ uint32_t s_addr(uint32_t o, uint32_t half) { return o + (((half ^ (o >> 7)) & 1) << 4); }
__host__ __device__ constexpr uint32_t y_off(uint32_t q) { return OFF_RING + 32768 + (q & 1) * 8192 + (q >> 1) * 65536; }

constexpr int B_W = 0;
constexpr int B_E = 24;
constexpr int B_S = 36;
constexpr int B_Y = 40;
constexpr int B_DP = 44, B_U = 45, B_KG = 46, B_G = 47;
constexpr int B_F = 48;
constexpr int B_H = 60;
constexpr int B_X = 52, B_XE = 56;

struct BandTab { uint32_t w[11][12]; };
constexpr BandTab make_band() {
    BandTab b{};
    for (int cls = 0; cls < 11; cls++)
        for (int wd = 0; wd < 10; wd++) {
            const int tau = cls + 2 - 8 * ((wd < 4 ? wd : wd - 4) >> 1);
            const int lo = (wd < 4) ? ((wd & 1) ? -2 : 3) : ((wd & 1) ? -4 : -11), wid = (wd < 4 ? 3 : 7) + 2 * (wd & 1);
            b.w[cls][wd] = ((tau >= lo && tau < lo + wid) ? 0x3F80u : 0u) | ((tau - 4 >= lo && tau - 4 < lo + wid) ? 0x3F800000u : 0u);
        }
    return b;
}
constexpr int NTOP = 32;
struct Scratch {
    uint4 r[L_ / 4];
    uint4 g[L_ / 4];
    uint4 h[2][8 * F_ / 8];
    uint32_t top[NTOP][32];
    unsigned epoch;
};
__device__ __align__(128) Scratch g_scratch;
__device__ const __align__(16) BandTab g_band = make_band();

struct Params {
    const bf16 *u, *logA, *Aim, *Cre, *Cim, *logdt, *Dskip, *wr, *gatew;
    bf16* out;
    Scratch* sc;
    const uint4* band;
    uint32_t gu_swap;
    uint32_t zero;
};

#define WSTAMP(i) do {} while (0)
#define KSTAMP(i, dep) do {} while (0)
#define WDUMP() do {} while (0)
#define RSTAMP(i) do {} while (0)

__device__ __forceinline__ uint32_t smem_u32(const void* p) { return (uint32_t)__cvta_generic_to_shared(p); }
__device__ __forceinline__ void mbar_init(uint32_t b, uint32_t c) { asm volatile("mbarrier.init.shared::cta.b64 [%0], %1;" :: "r"(b), "r"(c) : "memory"); }
__device__ __forceinline__ void mbar_expect(uint32_t b, uint32_t tx) { asm volatile("mbarrier.arrive.expect_tx.shared::cta.b64 _, [%0], %1;" :: "r"(b), "r"(tx) : "memory"); }
__device__ __forceinline__ void mbar_arrive(uint32_t b) { asm volatile("mbarrier.arrive.shared::cta.b64 _, [%0];" :: "r"(b) : "memory"); }
__device__ __forceinline__ void mbar_wait(uint32_t b, uint32_t parity = 0) {
    asm volatile("{\n\t.reg .pred p;\nW%=:\n\tmbarrier.try_wait.parity.shared::cta.b64 p, [%0], %1, 20000;\n\t@!p bra W%=;\n\t}" :: "r"(b), "r"(parity) : "memory");
}
__device__ __forceinline__ uint32_t mapa(uint32_t addr, uint32_t rank) { uint32_t r; asm("mapa.shared::cluster.u32 %0, %1, %2;" : "=r"(r) : "r"(addr), "r"(rank)); return r; }
__device__ __forceinline__ void tma3d(uint32_t dst, const CUtensorMap* tm, int c0, int c1, uint32_t bar, uint32_t bytes) {
    asm volatile("{\n\t.reg .pred p;\n\telect.sync _|p, 0xffffffff;\n\t"
                 "@p mbarrier.arrive.expect_tx.shared::cta.b64 _, [%2], %5;\n\t"
                 "@p cp.async.bulk.tensor.3d.shared::cluster.global.mbarrier::complete_tx::bytes [%0], [%1, {%3, %4, 0}], [%2];\n\t}"
        :: "r"(dst), "l"(tm), "r"(bar), "r"(c0), "r"(c1), "r"(bytes) : "memory");
}
__device__ __forceinline__ void bulk_load(uint32_t dst, const void* src, uint32_t bytes, uint32_t bar) {
    asm volatile("{\n\t.reg .pred p;\n\telect.sync _|p, 0xffffffff;\n\t"
                 "@p mbarrier.arrive.expect_tx.shared::cta.b64 _, [%2], %3;\n\t"
                 "@p cp.async.bulk.shared::cluster.global.mbarrier::complete_tx::bytes [%0], [%1], %3, [%2];\n\t}"
        :: "r"(dst), "l"(src), "r"(bar), "r"(bytes) : "memory");
}
__device__ __forceinline__ void st_async16(uint32_t dst, const uint4& v, uint32_t bar) {
    asm volatile("st.async.weak.shared::cluster.mbarrier::complete_tx::bytes.v4.b32 [%0], {%1,%2,%3,%4}, [%5];"
                 :: "r"(dst), "r"(v.x), "r"(v.y), "r"(v.z), "r"(v.w), "r"(bar) : "memory");
}
__device__ __forceinline__ void bar_sync(int id, int n) { asm volatile("bar.sync %0, %1;" :: "r"(id), "r"(n) : "memory"); }
__device__ __forceinline__ void cp16(uint32_t dst, const void* src) { asm volatile("cp.async.cg.shared.global [%0], [%1], 16;" :: "r"(dst), "l"(src) : "memory"); }
__device__ __forceinline__ void cp_wait_all() { asm volatile("cp.async.wait_all;" ::: "memory"); }
__device__ __forceinline__ uint4 ld_gpu128(const void* p) { uint4 v; asm volatile("ld.relaxed.gpu.global.v4.u32 {%0,%1,%2,%3}, [%4];" : "=r"(v.x), "=r"(v.y), "=r"(v.z), "=r"(v.w) : "l"(p) : "memory"); return v; }
__device__ __forceinline__ void st_gpu32(void* p, uint32_t v) { asm volatile("st.relaxed.gpu.global.u32 [%0], %1;" :: "l"(p), "r"(v) : "memory"); }

__device__ __forceinline__ void ldsm4(uint32_t a, uint32_t& r0, uint32_t& r1, uint32_t& r2, uint32_t& r3) {
    asm volatile("ldmatrix.sync.aligned.m8n8.x4.shared.b16 {%0,%1,%2,%3}, [%4];" : "=r"(r0), "=r"(r1), "=r"(r2), "=r"(r3) : "r"(a) : "memory");
}
__device__ __forceinline__ void ldsm4t(uint32_t a, uint32_t& r0, uint32_t& r1, uint32_t& r2, uint32_t& r3) {
    asm volatile("ldmatrix.sync.aligned.m8n8.x4.trans.shared.b16 {%0,%1,%2,%3}, [%4];" : "=r"(r0), "=r"(r1), "=r"(r2), "=r"(r3) : "r"(a) : "memory");
}
__device__ __forceinline__ uint32_t lds32(uint32_t a) { uint32_t v; asm volatile("ld.shared.u32 %0, [%1];" : "=r"(v) : "r"(a) : "memory"); return v; }
__device__ __forceinline__ uint2 lds64(uint32_t a) { uint2 v; asm volatile("ld.shared.v2.u32 {%0,%1}, [%2];" : "=r"(v.x), "=r"(v.y) : "r"(a) : "memory"); return v; }
__device__ __forceinline__ uint4 lds128(uint32_t a) { uint4 v; asm volatile("ld.shared.v4.u32 {%0,%1,%2,%3}, [%4];" : "=r"(v.x), "=r"(v.y), "=r"(v.z), "=r"(v.w) : "r"(a) : "memory"); return v; }
__device__ __forceinline__ void sts32(uint32_t a, uint32_t v) { asm volatile("st.shared.u32 [%0], %1;" :: "r"(a), "r"(v) : "memory"); }
__device__ __forceinline__ void sts16(uint32_t a, uint32_t v) { asm volatile("st.shared.u16 [%0], %1;" :: "r"(a), "h"((unsigned short)v) : "memory"); }
__device__ __forceinline__ void sts128(uint32_t a, uint32_t x, uint32_t y, uint32_t z, uint32_t w) { asm volatile("st.shared.v4.u32 [%0], {%1,%2,%3,%4};" :: "r"(a), "r"(x), "r"(y), "r"(z), "r"(w) : "memory"); }
__device__ __forceinline__ float ldsf(uint32_t a) { float v; asm volatile("ld.shared.f32 %0, [%1];" : "=f"(v) : "r"(a) : "memory"); return v; }

__device__ __forceinline__ void mma_bf(float (&d)[4], uint32_t a0, uint32_t a1, uint32_t a2, uint32_t a3, uint32_t b0, uint32_t b1) {
    asm volatile("mma.sync.aligned.m16n8k16.row.col.f32.bf16.bf16.f32 {%0,%1,%2,%3}, {%4,%5,%6,%7}, {%8,%9}, {%0,%1,%2,%3};"
        : "+f"(d[0]), "+f"(d[1]), "+f"(d[2]), "+f"(d[3]) : "r"(a0), "r"(a1), "r"(a2), "r"(a3), "r"(b0), "r"(b1));
}
__device__ __forceinline__ void mma_bf_z(float (&d)[4], uint32_t a0, uint32_t a1, uint32_t a2, uint32_t a3, uint32_t b0, uint32_t b1) {
    asm volatile("mma.sync.aligned.m16n8k16.row.col.f32.bf16.bf16.f32 {%0,%1,%2,%3}, {%4,%5,%6,%7}, {%8,%9}, {%10,%10,%10,%10};"
        : "=f"(d[0]), "=f"(d[1]), "=f"(d[2]), "=f"(d[3]) : "r"(a0), "r"(a1), "r"(a2), "r"(a3), "r"(b0), "r"(b1), "f"(0.f));
}
__device__ __forceinline__ void mma_bf_k8(float (&d)[4], uint32_t a0, uint32_t a1, uint32_t b0) {
    asm volatile("mma.sync.aligned.m16n8k8.row.col.f32.bf16.bf16.f32 {%0,%1,%2,%3}, {%4,%5}, {%6}, {%0,%1,%2,%3};"
        : "+f"(d[0]), "+f"(d[1]), "+f"(d[2]), "+f"(d[3]) : "r"(a0), "r"(a1), "r"(b0));
}
__device__ __forceinline__ void mma_h(float (&d)[4], uint32_t a0, uint32_t a1, uint32_t a2, uint32_t a3, uint32_t b0, uint32_t b1) {
    asm volatile("mma.sync.aligned.m16n8k16.row.col.f32.f16.f16.f32 {%0,%1,%2,%3}, {%4,%5,%6,%7}, {%8,%9}, {%0,%1,%2,%3};"
        : "+f"(d[0]), "+f"(d[1]), "+f"(d[2]), "+f"(d[3]) : "r"(a0), "r"(a1), "r"(a2), "r"(a3), "r"(b0), "r"(b1));
}
__device__ __forceinline__ uint32_t pack_bf(float lo, float hi) { uint32_t r; asm("cvt.rn.bf16x2.f32 %0, %1, %2;" : "=r"(r) : "f"(hi), "f"(lo)); return r; }
__device__ __forceinline__ uint32_t pack_h(float lo, float hi) { uint32_t r; asm("cvt.rn.f16x2.f32 %0, %1, %2;" : "=r"(r) : "f"(hi), "f"(lo)); return r; }
__device__ __forceinline__ float bf_lo(uint32_t v) { return __uint_as_float(v << 16); }
__device__ __forceinline__ float bf_hi(uint32_t v) { return __uint_as_float(v & 0xffff0000u); }
__device__ __forceinline__ float bf_round(float x) { return __uint_as_float(pack_bf(0.f, x)); }
__device__ __forceinline__ uint32_t hmul2_bf(uint32_t a, uint32_t b) { uint32_t r; asm("mul.rn.bf16x2 %0, %1, %2;" : "=r"(r) : "r"(a), "r"(b)); return r; }
__device__ __forceinline__ float ex2f(float x) { float r; asm("ex2.approx.ftz.f32 %0, %1;" : "=f"(r) : "f"(x)); return r; }

__device__ __forceinline__ float exp_acc(float x) {
    const float t = x * 1.4426950216293335f;
    const float r = fmaf(x, 1.4426950216293335f, -t) + x * 1.9259629911266175e-8f;
    return ex2f(t) * fmaf(r, 0.6931471805599453f, 1.f);
}
__device__ __forceinline__ float sigmoid_f(float x) { return __fdividef(1.f, 1.f + ex2f(-x * 1.4426950408889634f)); }
__device__ __forceinline__ void cexp_pow(float l2, float li, float e, float& zr, float& zi) {
    const float mag = ex2f(l2 * e);
    zr = mag * __cosf(li * e);
    zi = mag * __sinf(li * e);
}
__device__ __forceinline__ uint32_t hcmul(uint32_t a, uint32_t k, uint32_t kp) {
    const __half2 A = *reinterpret_cast<const __half2*>(&a);
    const __half2 r = __hfma2(__high2half2(A), *reinterpret_cast<const __half2*>(&kp), __hmul2(__low2half2(A), *reinterpret_cast<const __half2*>(&k)));
    return *reinterpret_cast<const uint32_t*>(&r);
}
#define CMUL(orr, oi, ar, ai, br, bi) do { float _r = (ar) * (br) - (ai) * (bi); float _i = (ar) * (bi) + (ai) * (br); orr = _r; oi = _i; } while (0)
#define CSQ(orr, oi, ar, ai) do { float _r = (ar) * (ar) - (ai) * (ai); float _i = 2.f * (ar) * (ai); orr = _r; oi = _i; } while (0)

__device__ __forceinline__ void mma_bf_k8z(float (&d)[4], uint32_t a0, uint32_t a1, uint32_t b0) {
    asm volatile("mma.sync.aligned.m16n8k8.row.col.f32.bf16.bf16.f32 {%0,%1,%2,%3}, {%4,%5}, {%6}, {%7,%7,%7,%7};"
        : "=f"(d[0]), "=f"(d[1]), "=f"(d[2]), "=f"(d[3]) : "r"(a0), "r"(a1), "r"(b0), "f"(0.f));
}
__device__ __forceinline__ void mma_hh_k8(uint32_t& d0, uint32_t& d1, uint32_t a0, uint32_t a1, uint32_t b0) {
    asm volatile("mma.sync.aligned.m16n8k8.row.col.f16.f16.f16.f16 {%0,%1}, {%2,%3}, {%4}, {%5,%5};"
        : "=r"(d0), "=r"(d1) : "r"(a0), "r"(a1), "r"(b0), "r"(0));
}
__device__ __forceinline__ void sched_fence(uint32_t zero, uint32_t id) {
    asm volatile("{\n\t.reg .pred p;\n\tsetp.eq.u32 p, %0, %1;\n\t@p exit;\n\t}" :: "r"(zero), "r"(id) : "memory");
}
__device__ __forceinline__ uint32_t pin(uint32_t x, int lane) { return __shfl_sync(0xffffffffu, x, lane); }
template <class T> __device__ __forceinline__ T* pin(T* x, int lane) { return (T*)__shfl_sync(0xffffffffu, (unsigned long long)x, lane); }
__device__ __forceinline__ void sts32_if(bool on, uint32_t a, uint32_t v) {
    asm volatile("{\n\t.reg .pred p;\n\tsetp.ne.u32 p, %2, 0;\n\t@p st.shared.u32 [%0], %1;\n\t}" :: "r"(a), "r"(v), "r"((uint32_t)on) : "memory");
}
__device__ __forceinline__ void sts128_if(bool on, uint32_t a, uint32_t x, uint32_t y, uint32_t z, uint32_t w) {
    asm volatile("{\n\t.reg .pred p;\n\tsetp.ne.u32 p, %5, 0;\n\t@p st.shared.v4.u32 [%0], {%1,%2,%3,%4};\n\t}" :: "r"(a), "r"(x), "r"(y), "r"(z), "r"(w), "r"((uint32_t)on) : "memory");
}
__device__ __forceinline__ void lds128_if(bool on, uint32_t a, uint32_t (&v)[4]) {
    asm volatile("{\n\t.reg .pred p;\n\tsetp.ne.u32 p, %5, 0;\n\t@p ld.shared.v4.u32 {%0,%1,%2,%3}, [%4];\n\t}"
        : "+r"(v[0]), "+r"(v[1]), "+r"(v[2]), "+r"(v[3]) : "r"(a), "r"((uint32_t)on) : "memory");
}
__device__ __forceinline__ uint32_t hfma2_bf(uint32_t a, uint32_t b, uint32_t c) { uint32_t r; asm("fma.rn.bf16x2 %0, %1, %2, %3;" : "=r"(r) : "r"(a), "r"(b), "r"(c)); return r; }
__device__ __forceinline__ __nv_bfloat162 bcast(uint32_t a, int hi) { const __nv_bfloat162 v = *reinterpret_cast<const __nv_bfloat162*>(&a); return hi ? __high2bfloat162(v) : __low2bfloat162(v); }
__device__ __forceinline__ uint32_t hmul2_bc(uint32_t a, int hi, uint32_t b) { const __nv_bfloat162 r = __hmul2_rn(bcast(a, hi), *reinterpret_cast<const __nv_bfloat162*>(&b)); return *reinterpret_cast<const uint32_t*>(&r); }
__device__ __forceinline__ uint32_t hfma2_bc(uint32_t a, int hi, uint32_t b, uint32_t c) {
    const __nv_bfloat162 r = __hfma2(bcast(a, hi), *reinterpret_cast<const __nv_bfloat162*>(&b), *reinterpret_cast<const __nv_bfloat162*>(&c));
    return *reinterpret_cast<const uint32_t*>(&r);
}
__device__ __forceinline__ uint32_t row_elem(uint32_t row) { return ((row >> 5) & 4) | ((row >> 2) & 2) | ((row >> 4) & 1); }
__device__ __forceinline__ uint32_t gate_pos(uint32_t row) { return ((row >> 9) << 8) | ((row & 7) << 5) | (row_elem(row) << 2) | ((row >> 5) & 3); }

template <int N, bool BULK>
__device__ __forceinline__ void mix_rows(const Params& p, const CUtensorMap* tm_out, uint32_t sb, uint32_t ob, int Q0, int Q1, int w, int h, int pr, int lane) {
    const int g = lane >> 2, t = lane & 3, mi = lane >> 3, r = lane & 7;
    const int m8 = 16 * (g >> 2) + ((g >> 1) & 1) + 2 * (g & 1);
    uint32_t yi = sb + (4 * (r >> 1) + 2 * (mi & 1) + (r & 1)) * 512 + (((4 * w + (mi >> 1)) ^ r) << 4);
    uint32_t xs = sb + OFF_S + s_addr(w * S_PL + 32 + m8 * 32, t >> 1) + ((t & 1) << 3);
    uint32_t gs = sb + OFF_GP + w * 64 + g * 8, os = ob + m8 * 32 + t * 8;
    if (N > 1) { yi = pin(yi, lane); xs = pin(xs, lane); gs = pin(gs, lane); os = pin(os, lane); }
    mbar_wait(sb + M_BARS + 8 * B_Y);
#pragma unroll 1
    for (int Q = Q0; Q < Q1; Q++) {
        uint2 xq[N][4];
        uint32_t gg[N][2], sw[N];
#pragma unroll
        for (int n = 0; n < N; n++) {
#pragma unroll
            for (int i = 0; i < 4; i++) xq[n][i] = lds64((xs ^ (((i ^ n) & 1) << 4)) + Q * S_Q + n * 4 * S_PL + i * 128);
            const uint2 gq = lds64(gs + Q * 512 + n * 256);
            sw[n] = lds32(sb + M_BMAP + w * 16 + n * 64 + Q * 4);
            gg[n][0] = gq.x; gg[n][1] = gq.y;
#pragma unroll
            for (int i = 0; i < 4; i++) {
                const uint32_t og = hfma2_bf(gg[n][i >> 1], 0xBF80BF80u, 0x3F803F80u);
                xq[n][i].x = hmul2_bc(og, i & 1, xq[n][i].x); xq[n][i].y = hmul2_bc(og, i & 1, xq[n][i].y);
            }
        }
        if (N > 1 && Q == PWQ) mbar_wait(sb + M_BARS + 8 * (B_W + PW));
        mbar_wait(sb + M_BARS + 8 * (B_Y + Q));
        __syncwarp();
#pragma unroll
        for (int n = 0; n < N; n++) {
#pragma unroll
            for (int x = 0; x < 2; x++) {
                uint32_t y[4];
                ldsm4t((yi ^ (x << 5)) + y_off(Q) + n * 256, y[0], y[1], y[2], y[3]);
#pragma unroll
                for (int e = 0; e < 2; e++) {
                    uint2& o = xq[n][2 * x + e];
                    o.x = hfma2_bc(gg[n][x], e, y[2 * e], o.x); o.y = hfma2_bc(gg[n][x], e, y[2 * e + 1], o.y);
                }
            }
        }
        if (BULK && (sw[0] | sw[N - 1]) == 0) {
#pragma unroll
            for (int n = 0; n < N; n++)
#pragma unroll
                for (int i = 0; i < 4; i++)
                    asm volatile("st.shared.v2.u32 [%0], {%1, %2};" :: "r"(os + Q * 1024 + n * 4 * TAB_W + i * 128), "r"(xq[n][i].x), "r"(xq[n][i].y) : "memory");
            asm volatile("fence.proxy.async.shared::cta;" ::: "memory");
            __syncwarp();
#pragma unroll
            for (int n = 0; n < N; n++)
                asm volatile("{\n\t.reg .pred p;\n\telect.sync _|p, 0xffffffff;\n\t"
                             "@p cp.async.bulk.tensor.3d.global.shared::cta.bulk_group [%1, {%2, %3, %4}], [%0];\n\t}"
                    :: "r"(ob + 4 * n * TAB_W + Q * 1024), "l"(tm_out), "r"(16 * pr), "r"(64 * Q + 32 * h), "r"(w + 4 * n) : "memory");
        } else {
            bf16* op = p.out + (size_t)(512 * Q + 256 * h + 8 * m8 + w) * D_ + 16 * pr + 4 * t;
#pragma unroll
            for (int n = 0; n < N; n++)
#pragma unroll
                for (int i = 0; i < 4; i++)
                    if (!((sw[n] >> (4 * g)) & (1u << i))) *(uint2*)(op + (size_t)(32 * i + 4 * n) * D_) = xq[n][i];
        }
    }
}

__global__ void __cluster_dims__(2, 1, 1) __launch_bounds__(NTHREADS, 1)
fused_kernel(const Params p, const __grid_constant__ CUtensorMap tm_gu, const __grid_constant__ CUtensorMap tm_down,
             const __grid_constant__ CUtensorMap tm_x, const __grid_constant__ CUtensorMap tm_out) {
    extern __shared__ __align__(1024) unsigned char smem[];
    const uint32_t sb = smem_u32(smem);
    int tid;
    asm volatile("mov.u32 %0, %%tid.x;" : "=r"(tid));
    const int pw = tid >> 5, lane = tid & 31;
    const int c = blockIdx.x, h = c & 1, pr = c >> 1;
    const uint32_t bars = sb + M_BARS;

    uint2 v_la, v_ai, v_cr, v_ci;
    uint32_t ldt16;
    {
        const uint32_t po = c * 256 + tid;
        asm volatile("{\n\t.reg .pred p;\n\t.reg .b64 a;\n\tsetp.ne.u32 p, %16, 0;\n\t"
                     "mad.wide.u32 a, %14, 8, %9;\n\t@p ld.global.nc.L1::no_allocate.v2.u32 {%0,%1}, [a];\n\t"
                     "mad.wide.u32 a, %15, 2, %13;\n\t@p ld.global.nc.u16 %8, [a];\n\t"
                     "mad.wide.u32 a, %14, 8, %10;\n\t@p ld.global.nc.L1::no_allocate.v2.u32 {%2,%3}, [a];\n\t"
                     "mad.wide.u32 a, %14, 8, %11;\n\t@p ld.global.nc.L1::no_allocate.v2.u32 {%4,%5}, [a];\n\t"
                     "mad.wide.u32 a, %14, 8, %12;\n\t@p ld.global.nc.L1::no_allocate.v2.u32 {%6,%7}, [a];\n\t}"
            : "=r"(v_la.x), "=r"(v_la.y), "=r"(v_ai.x), "=r"(v_ai.y), "=r"(v_cr.x), "=r"(v_cr.y), "=r"(v_ci.x), "=r"(v_ci.y), "=r"(ldt16)
            : "l"(p.logA), "l"(p.Aim), "l"(p.Cre), "l"(p.Cim), "l"(p.logdt), "r"(po), "r"(po >> 5), "r"((uint32_t)(tid < 256 && c < 128)));
    }

    if (c >= 128) {
        if (c != 128) return;
        RSTAMP(5);
        const unsigned tag = (*(volatile unsigned*)&p.sc->epoch + 1) & 0xffffu;
        const uint32_t list = sb + 128;
#pragma unroll 1
        for (int pass = 0; pass < 2; pass++) {
            sts128(list + 16 * tid, 0, 0, 0, 0);
            if (tid == 0) sts32(sb + 64, 0);
            uint32_t key[4] = {tag - 1, tag - 1, tag - 1, tag - 1};
#pragma unroll 1
            for (int it = 0; it < (pass << 22); it++) {
                uint32_t a[4];
                asm volatile("{\n\t.reg .b128 o, z;\n\t.reg .b64 l, u;\n\tmov.b64 l, {%5, %5};\n\tmov.b128 z, {l, l};\n\tatom.relaxed.gpu.global.exch.b128 o, [%4], z;\n\t"
                             "mov.b128 {l, u}, o;\n\tmov.b64 {%0, %1}, l;\n\tmov.b64 {%2, %3}, u;\n\t}"
                    : "=r"(a[0]), "=r"(a[1]), "=r"(a[2]), "=r"(a[3]) : "l"(&p.sc->r[tid]), "r"(tag - 1) : "memory");
#pragma unroll
                for (int i = 0; i < 4; i++) if (((a[i] ^ tag) & 0xffffu) == 0) key[i] = a[i];
                if ((((key[0] ^ tag) | (key[1] ^ tag) | (key[2] ^ tag) | (key[3] ^ tag)) & 0xffffu) == 0) break;
            }
            WSTAMP(0);
            uint32_t m = 0;
#pragma unroll
            for (int i = 0; i < 4; i++) {
                key[i] = ((pass ? key[i] : (lane + i) << 16) & 0xffff0000u) | (uint32_t)(2047 - (4 * tid + i));
                m = max(m, key[i]);
            }
            const uint32_t wm = __reduce_max_sync(0xffffffffu, m);
            if (lane == 0) sts32(sb + pw * 4, wm);
            __syncthreads();
            uint32_t thr = 0xffffffffu;
#pragma unroll
            for (int i = 0; i < 4; i++) { const uint4 q = lds128(sb + 16 * i); thr = min(thr, min(max(q.x, q.y), max(q.z, q.w))); }
            if (thr != 1) WSTAMP(1);
            if (m >= thr) {
                uint32_t pos;
                asm volatile("atom.shared.add.u32 %0, [%1], %2;" : "=r"(pos) : "r"(sb + 64), "r"(4 * ((key[0] >= thr) + (key[1] >= thr) + (key[2] >= thr) + (key[3] >= thr))) : "memory");
#pragma unroll
                for (int i = 0; i < 4; i++) if (key[i] >= thr) { sts32(list + pos, key[i]); pos += 4; }
            }
            __syncthreads();
            const uint32_t nc4 = lds32(sb + 64);
            if (nc4 != 1) WSTAMP(2);
#pragma unroll 1
            for (uint32_t j = 4 * pw; j < nc4; j += 64) {
                const uint32_t mine = lds32(list + j);
                int rank = 0;
#pragma unroll 1
                for (uint32_t i = 0; i < nc4; i += 128) rank += __popc(__ballot_sync(0xffffffffu, lds32(list + i + 4 * lane) > mine));
                if (rank < 8 && lane == 0) sts32(sb + 96 + 4 * rank, mine);
            }
            __syncthreads();
            if (tid < 8 * NTOP) st_gpu32(&p.sc->top[tid >> 3][tid & 7], lds32(sb + 96 + 4 * (tid & 7)) | (((tag + pass - 1) & 31) << 11));
            WSTAMP(3);
            if (!pass) RSTAMP(4);
        }
        WDUMP();
        return;
    }

    WSTAMP(0);
    if (pw < 8) {
        const int d = 8 * c + pw - MAIN_W0;
        if (lane == 0) asm volatile("cp.async.ca.shared.global [%0], [%1], 4;" :: "r"(sb + M_DSK + 4 * (pw - MAIN_W0)), "l"(p.Dskip + (d & ~1)) : "memory");
        asm volatile("barrier.cluster.arrive.relaxed.aligned;" ::: "memory");
        const int warp = pw - MAIN_W0;
        asm volatile("setmaxnreg.inc.sync.aligned.u32 160;");
        const int g = lane >> 2, t = lane & 3;
        const int mi = lane >> 3, r = lane & 7;
        const uint32_t TB = sb + OFF_TAB + warp * TAB_W;
        const uint32_t UB = sb + OFF_U + warp * U_CH;
        if (mi < 2) sts128(UB + mi * U_PL + r * 16, 0, 0, 0, 0);
        if (lane < 4) sts128(TB + lane * T_PL, 0, 0, 0, 0);
        sts128(sb + OFF_SCR + warp * 8192 + lane * 16, 0x3C00u, 0x3C00u, 0x3C00u, 0x3C00u);
        asm volatile("barrier.cluster.wait.acquire.aligned;" ::: "memory");
        __syncwarp();

        uint32_t cfix;
        {
            KSTAMP(4, v_la.x ^ v_ai.x ^ v_cr.x ^ v_ci.x ^ ldt16);
            const float dt = bf_round(exp_acc(__uint_as_float(ldt16 << 16)));
            float l2[4], li[4];
            {
                const uint32_t la[2] = {v_la.x, v_la.y}, ai[2] = {v_ai.x, v_ai.y};
                const float dt2 = -1.4426950408889634f * dt;
#pragma unroll
                for (int i = 0; i < 4; i++) {
                    l2[i] = bf_round(ex2f(((i & 1) ? bf_hi(la[i >> 1]) : bf_lo(la[i >> 1])) * 1.4426950408889634f)) * dt2;
                    li[i] = ((i & 1) ? bf_hi(ai[i >> 1]) : bf_lo(ai[i >> 1])) * dt;
                }
            }
            const uint32_t SX = sb + OFF_SCR + warp * 8192;
            const uint32_t sw = SX + (lane << 4);
#define PUT(buf, row, v) sts128(((sw + (row) * 512) ^ ((row) << 4)) + (buf) * 4096, v[0], v[1], v[2], v[3])
#define EMIT(bufa, rowa, bufb, rowb, xr, xi, k, kp) do { uint32_t pk[4], pd[4]; sched_fence(p.zero, __LINE__); \
                _Pragma("unroll") for (int i = 0; i < 4; i++) { pk[i] = pack_h(xr[i], xi[i]); pd[i] = hcmul(pk[i], k[i], kp[i]); } \
                PUT(bufa, rowa, pk); PUT(bufb, rowb, pd); } while (0)
#define CMUL4(orr, oi, ar, ai, br, bi) _Pragma("unroll") for (int i = 0; i < 4; i++) CMUL(orr[i], oi[i], ar[i], ai[i], br[i], bi[i])
#define CSQ4(orr, oi, ar, ai) _Pragma("unroll") for (int i = 0; i < 4; i++) CSQ(orr[i], oi[i], ar[i], ai[i])
            float z1r[4], z1i[4], z2r[4], z2i[4], z8r[4], z8i[4], z256r[4], z256i[4];
            uint32_t k4[4], k4p[4];
            float z4r[4], z4i[4];
#pragma unroll
            for (int i = 0; i < 4; i++) cexp_pow(l2[i], li[i], 1.f, z1r[i], z1i[i]);
            CSQ4(z2r, z2i, z1r, z1i);
            CSQ4(z4r, z4i, z2r, z2i);
            CSQ4(z8r, z8i, z4r, z4i);
            KSTAMP(5, __float_as_uint(z8r[3]));
            uint32_t Ya[16][4];
            float cr[4], ci[4], inv;
            {
                float w1r[4], w1i[4], ar[4], ai[4], br[4], bi[4];
                uint32_t k8[4], k8p[4];
#pragma unroll
                for (int i = 0; i < 4; i++) {
                    k8[i] = pack_h(z8r[i], -z8i[i]); k8p[i] = pack_h(z8i[i], z8r[i]);
                    CSQ(w1r[i], w1i[i], z8r[i], z8i[i]); w1i[i] = -w1i[i];
                }
                PUT(1, 0, k8);
                EMIT(0, 1, 1, 1, w1r, w1i, k8, k8p);
                CSQ4(ar, ai, w1r, w1i);            EMIT(0, 2, 1, 2, ar, ai, k8, k8p);
                CMUL4(br, bi, ar, ai, w1r, w1i);   EMIT(0, 3, 1, 3, br, bi, k8, k8p);
                CSQ4(ar, ai, ar, ai);              EMIT(0, 4, 1, 4, ar, ai, k8, k8p);
                CMUL4(ar, ai, ar, ai, w1r, w1i);   EMIT(0, 5, 1, 5, ar, ai, k8, k8p);
                CSQ4(br, bi, br, bi);              EMIT(0, 6, 1, 6, br, bi, k8, k8p);
                CMUL4(br, bi, br, bi, w1r, w1i);   EMIT(0, 7, 1, 7, br, bi, k8, k8p);
                __syncwarp();
                KSTAMP(6, 0);
                sched_fence(p.zero, 5);
                const uint32_t ab = SX + (mi & 1) * 4096 + r * 512, ax = ((mi >> 1) ^ r) << 4;
                const uint32_t vr[2] = {v_cr.x, v_cr.y}, vi[2] = {v_ci.x, v_ci.y};
                const uint32_t m2 = __vmaxu2(__vmaxu2(vr[0] & 0x7fff7fffu, vr[1] & 0x7fff7fffu), __vmaxu2(vi[0] & 0x7fff7fffu, vi[1] & 0x7fff7fffu));
                const uint32_t mx = __reduce_max_sync(0xffffffffu, max(m2, m2 << 16));
                const uint32_t e = min(max(mx >> 23, 11u), 254u);
                const float sc = __uint_as_float((264u - e) << 23);
                inv = __uint_as_float((e - 10u) << 23) * (2.f * dt);
#pragma unroll
                for (int i = 0; i < 4; i++) {
#pragma unroll
                    for (int k = 0; k < 4; k++) ldsm4(ab + (ax ^ (i << 5)) + k * 128, Ya[4 * k + i][0], Ya[4 * k + i][1], Ya[4 * k + i][2], Ya[4 * k + i][3]);
                    float tr, ti;
                    cexp_pow(l2[i], li[i], 128.f, tr, ti);
                    sts32(TB + 2176 + 256 * i + 4 * lane, pack_h(tr, ti));
                    sts32(TB + 2176 + 256 * i + 128 + 4 * (lane ^ 16), pack_h(-ti, tr));
                    k4[i] = pack_h(z4r[i], z4i[i]); k4p[i] = pack_h(-z4i[i], z4r[i]);
                    CSQ(z256r[i], z256i[i], tr, ti);
                    cr[i] = ((i & 1) ? bf_hi(vr[i >> 1]) : bf_lo(vr[i >> 1])) * sc;
                    ci[i] = ((i & 1) ? bf_hi(vi[i >> 1]) : bf_lo(vi[i >> 1])) * sc;
                    if (i < 3) sched_fence(p.zero, 8 + i);
                }
                __syncwarp();
            }
            KSTAMP(7, Ya[15][0]);
            const uint32_t ld0 = SX + r * 512 + ((mi ^ r) << 4), ld1 = ld0 ^ 64;
            float R[6][4], s1024;
            {
                float xr[4], xi[4], yr[4], yi[4];
                EMIT(0, 0, 0, 1, cr, ci, k4, k4p);
                CMUL4(yr, yi, cr, ci, z1r, z1i);        EMIT(0, 2, 0, 3, yr, yi, k4, k4p);
                CMUL4(xr, xi, cr, ci, z256r, z256i);    EMIT(1, 0, 1, 1, xr, xi, k4, k4p);
                CMUL4(yr, yi, yr, yi, z1r, z1i);        EMIT(0, 4, 0, 5, yr, yi, k4, k4p);
                CMUL4(cr, ci, yr, yi, z256r, z256i);    EMIT(1, 2, 1, 3, cr, ci, k4, k4p);
                CMUL4(yr, yi, yr, yi, z1r, z1i);        EMIT(0, 6, 0, 7, yr, yi, k4, k4p);
                CMUL4(xr, xi, xr, xi, z256r, z256i);    EMIT(1, 4, 1, 5, xr, xi, k4, k4p);
                CMUL4(xr, xi, xr, xi, z256r, z256i);    EMIT(1, 6, 1, 7, xr, xi, k4, k4p);
                CMUL4(xr, xi, xr, xi, z256r, z256i);
                s1024 = (xr[0] + xr[1]) + (xr[2] + xr[3]);
#pragma unroll
                for (int m = 0; m < 4; m++) {
                    if (m == 0) { CMUL4(xr, xi, xr, xi, z8r, z8i); } else { CMUL4(xr, xi, xr, xi, z256r, z256i); }
                    sched_fence(p.zero, 1 + m);
                    sts128(TB + m * T_PL + 16 + 16 * lane, pack_h(xr[0], xi[0]), pack_h(xr[1], xi[1]), pack_h(xr[2], xi[2]), pack_h(xr[3], xi[3]));
                }
            }
            __syncwarp();
            {
                KSTAMP(8, 0);
                uint32_t bd[2][4] = {{0, 0, 0, 0}, {0, 0, 0, 0}};
                const bool on = (g >> 1) == t;
#pragma unroll
                for (int i = 0; i < 6; i++) { R[i][0] = R[i][1] = R[i][2] = R[i][3] = 0.f; }
                uint32_t x[2][4], y[2][4], z[2][4];
                auto fetch = [&](const int k2) {
                    const int b = k2 & 1;
                    lds128_if(on, TB + 2176 + g * 128 + (k2 < 4 ? 64 : -64) * (g & 1) + 16 * k2, bd[b]);
                    ldsm4(((k2 & 1) ? ld1 : ld0) + (k2 >> 1) * 128, x[b][0], x[b][1], x[b][2], x[b][3]);
                    ldsm4(((k2 & 1) ? ld1 : ld0) + (k2 >> 1) * 128 + 4096, y[b][0], y[b][1], y[b][2], y[b][3]);
                    ldsm4(TB + (r & 3) * T_PL + 16 + 16 * mi + 64 * k2, z[b][0], z[b][1], z[b][2], z[b][3]);
                };
                fetch(0);
#pragma unroll
                for (int k2 = 0; k2 < 8; k2++) {
                    const int b = k2 & 1;
                    uint32_t a1[2][4];
                    if (k2 < 7) fetch(k2 + 1);
#pragma unroll
                    for (int u = 0; u < 2; u++) {
                        mma_hh_k8(a1[u][0], a1[u][1], Ya[2 * k2 + u][0], Ya[2 * k2 + u][1], bd[b][2 * u]);
                        mma_hh_k8(a1[u][2], a1[u][3], Ya[2 * k2 + u][2], Ya[2 * k2 + u][3], bd[b][2 * u + 1]);
                    }
#pragma unroll
                    for (int u = 0; u < 2; u++) {
                        const uint32_t(&a0)[4] = Ya[2 * k2 + u];
                        mma_h(R[0], a0[0], a0[1], a0[2], a0[3], x[b][2 * u], x[b][2 * u + 1]);
                        mma_h(R[2], a0[0], a0[1], a0[2], a0[3], y[b][2 * u], y[b][2 * u + 1]);
                        mma_h(R[4], a0[0], a0[1], a0[2], a0[3], z[b][2 * u], z[b][2 * u + 1]);
                        mma_h(R[1], a1[u][0], a1[u][1], a1[u][2], a1[u][3], x[b][2 * u], x[b][2 * u + 1]);
                        mma_h(R[3], a1[u][0], a1[u][1], a1[u][2], a1[u][3], y[b][2 * u], y[b][2 * u + 1]);
                        mma_h(R[5], a1[u][0], a1[u][1], a1[u][2], a1[u][3], z[b][2 * u], z[b][2 * u + 1]);
                    }
                }
            }
            __syncwarp();
            KSTAMP(9, __float_as_uint(R[3][0]));
            if (lane == 0) mbar_arrive(bars + 8 * B_KG + (__float_as_uint(R[0][0]) & __float_as_uint(R[2][0]) & p.zero));
            sts128(TB + 2176 + 16 * lane, 0, 0, 0, 0);
            sts128(TB + 2688 + 16 * lane, 0, 0, 0, 0);
            __syncwarp();
#undef PUT
#undef EMIT
#pragma unroll
            for (int o = 16; o > 0; o >>= 1) s1024 += __shfl_xor_sync(0xffffffffu, s1024, o);
            uint32_t w[4][4], dsk = 0;
            cp_wait_all();
            asm volatile("{\n\t.reg .pred p;\n\tsetp.eq.u32 p, %2, 0;\n\t@p ld.shared.u16 %0, [%1];\n\t}" : "+r"(dsk) : "r"(sb + M_DSK + 4 * warp + 2 * (warp & 1)), "r"(lane) : "memory");
#pragma unroll
            for (int a = 0; a < 4; a++) {
                const float v0 = (a == 0) ? fmaf(R[0][0], inv, __uint_as_float(dsk << 16)) : R[a][0] * inv;
                const float v1 = R[a][1] * inv, v2 = R[a][2] * inv, v3 = R[a][3] * inv;
                w[a][0] = pack_bf(v0, 0.f); w[a][1] = pack_bf(v1, v0); w[a][2] = pack_bf(v2, v1); w[a][3] = pack_bf(v3, v2);
            }
            const uint32_t wb = TB + 16 + 16 * g, w1 = wb + t * T_PL, w2 = wb + 256 + 2 * t * T_PL;
            const uint32_t w3 = (t == 0) ? wb + 256 + 3 * T_PL : TB + T_A + 8 * (16 * t + g);
            const uint32_t w3s = (t == 0) ? 128 : 64, w3o = (t == 0) ? 8 : 12;
            const uint32_t k512 = __shfl_sync(0xffffffffu, w[2][1], 2);
#pragma unroll
            for (int a = 0; a < 2; a++) {
                sts128(w1 + 128 * a, w[a][0], w[a][1], w[a][2], w[a][3]);
                const uint32_t(&q)[4] = w[2 + a];
                if (t < 2) sts128(w2 + 128 * a, q[0], q[1], q[2], q[3]);
                if (t == 0) { sts128(w2 + T_PL + 128 * a, q[0], q[1], q[2], q[3]); sts32(w3 + 128 * a + 4, q[2]); }
                sts32_if(t != 1 && (a == 1 || lane != 2), w3 + w3s * a, q[1]);
                sts32_if(t != 1, w3 + w3s * a + w3o, q[3]);
            }
            sts128_if(lane < 4, w1 + 512, t == 3 ? k512 : k512 >> 16, t < 2 ? k512 : t == 2 ? k512 & 0xffff0000u : k512 << 16, t < 2 ? k512 << 16 : 0u, 0);
            __syncwarp();
#pragma unroll
            for (int a = 0; a < 2; a++) {
                sts16(w1 + 128 * a + 18, w[a][3]);
                const uint32_t(&q)[4] = w[2 + a];
                if (t < 2) sts16(w2 + 128 * a + 18, q[3]);
                if (t == 0) { sts16(w2 + T_PL + 128 * a + 18, q[3]); sts16(w3 + 128 * a + 14, q[3]); }
            }
            if (t == 0) sts16(w3 + 128 - 4, w[3][0]);
            if (lane == 2 || (t == 0 && g > 0)) sts16(lane == 2 ? TB + 16 + 3 * T_PL + 4 * 127 : w3 - 4, w[2][0]);
            {
                float q[4];
#pragma unroll
                for (int i = 0; i < 4; i++) q[i] = (t < 2 ? R[4][i] : R[5][i]) * inv;
                const uint32_t b0 = pack_bf(q[0], q[2]), b1 = pack_bf(q[1], q[3]);
                const uint32_t wq = TB + T_B + 8 * (65 + 32 * (t & 1) + 4 * (t & 2) + g);
                sts32(wq, b0); sts32(wq + 12, b0); sts32(wq + 128, b1); sts32(wq + 140, b1);
            }
            cfix = pack_bf(s1024 * inv, s1024 * inv);
            if (lane == 0) sts32(TB + T_A + 8 * 64, cfix);
            __syncwarp();
        }
        WSTAMP(1);

        mbar_wait(bars + 8 * B_U);
        WSTAMP(2);

        float D[16][4];
        {
            const int x5 = g - t + 5;
            const uint32_t tabD = TB + (x5 & 3) * T_PL + (x5 & 12) + 16;
            {
                const uint32_t a1 = lds32(tabD - 8), a0 = p.zero;
#pragma unroll
                for (int jq = 0; jq < 4; jq++) {
                    uint32_t b[4];
                    ldsm4(UB + (9 + lane) * 16 + jq * 512, b[0], b[1], b[2], b[3]);
#pragma unroll
                    for (int i = 0; i < 4; i++) mma_bf_k8z(D[4 * jq + i], a0, a1, b[i]);
                }
            }
            const uint32_t ua = UB + (mi & 1) * U_PL + (8 + 8 * (mi >> 1) + r) * 16;
#pragma unroll 1
            for (int k0 = 0; k0 < 8; k0++) {
                uint32_t Uf[16][2];
#pragma unroll
                for (int jp = 0; jp < 8; jp++) ldsm4(ua + jp * 256 - k0 * 16, Uf[2 * jp][0], Uf[2 * jp][1], Uf[2 * jp + 1][0], Uf[2 * jp + 1][1]);
#pragma unroll
                for (int k1 = 0; k1 < 4; k1++) {
                    const uint32_t ta = tabD + 16 * (8 * k1 + k0);
                    const uint32_t a0 = lds32(ta), a1 = lds32(ta + 8), a2 = lds32(ta - 8), a3 = a0 ^ p.zero;
#pragma unroll
                    for (int J = k1; J < 16; J++) mma_bf(D[J], a0, a1, a2, a3, Uf[J - k1][0], Uf[J - k1][1]);
                }
                if (k0 == 0) {
                    const uint32_t ta = tabD + 16 * 32;
                    const uint32_t a0 = lds32(ta), a1 = lds32(ta + 8), a2 = lds32(ta - 8), a3 = a0 ^ p.zero;
#pragma unroll
                    for (int J = 4; J < 16; J++) mma_bf(D[J], a0, a1, a2, a3, Uf[J - 4][0], Uf[J - 4][1]);
                    const uint32_t f0 = (cfix ^ 0x80008000u) & (g == t ? 0xffffu : g == t + 4 ? 0xffff0000u : 0u);
                    const uint32_t f1 = p.zero, f2 = p.zero + p.zero, f3 = f0 ^ p.zero;
#pragma unroll
                    for (int J = 8; J < 16; J++) mma_bf(D[J], f0, f1, f2, f3, Uf[J - 8][0], Uf[J - 8][1]);
                }
            }
        }
        WSTAMP(3);
        {
            const int ch = 8 * h + warp;
            const uint32_t yo = sb + ch * 512 + ((lane ^ (((ch >> 2) << 1) | (ch & 1))) << 4);
            const uint32_t yr = mapa(yo, h ^ 1), ybr = mapa(bars + 8 * B_Y, h ^ 1);
            auto ship = [&](const int Q) {
                uint4 y[2];
#pragma unroll
                for (int hh = 0; hh < 2; hh++) {
                    const int J = 4 * Q + 2 * hh;
                    y[hh] = make_uint4(pack_bf(D[J][0], D[J][1]), pack_bf(D[J][2], D[J][3]), pack_bf(D[J + 1][0], D[J + 1][1]), pack_bf(D[J + 1][2], D[J + 1][3]));
                }
                if (!(Q & 1)) mbar_wait(bars + 8 * (B_F + (Q >> 1)));
                asm volatile("{\n\t.reg .pred p;\n\tsetp.eq.u32 p, %11, 0;\n\t"
                             "@p st.async.weak.shared::cluster.mbarrier::complete_tx::bytes.v4.b32 [%9], {%4,%5,%6,%7}, [%10];\n\t"
                             "@!p st.async.weak.shared::cluster.mbarrier::complete_tx::bytes.v4.b32 [%9], {%0,%1,%2,%3}, [%10];\n\t"
                             "@p st.shared.v4.b32 [%8], {%0,%1,%2,%3};\n\t@!p st.shared.v4.b32 [%8], {%4,%5,%6,%7};\n\t}"
                             :: "r"(y[0].x), "r"(y[0].y), "r"(y[0].z), "r"(y[0].w), "r"(y[1].x), "r"(y[1].y), "r"(y[1].z), "r"(y[1].w),
                                "r"(yo + y_off(Q)), "r"(yr + y_off(Q)), "r"(ybr + 8 * Q), "r"(h) : "memory");
                __syncwarp();
                if (lane == 0) mbar_arrive(bars + 8 * (B_Y + Q));
            };
            ship(0);
            const uint4 bA = lds128(sb + OFF_BAND + (g - t + 3) * 48), bB = lds128(sb + OFF_BAND + (g - t + 3) * 48 + 16);
            const uint2 bC = lds64(sb + OFF_BAND + (g - t + 3) * 48 + 32);
            uint2 QA[5][2], QB[8];
            const uint32_t tq = TB + 8 * (1 + g - 2 * t);
#pragma unroll
            for (int dd = 0; dd < 5; dd++) { QA[dd][0] = lds64(tq + T_A + 64 * (dd + 4)); QA[dd][1] = lds64(tq + T_A + 64 * (dd + 4) - 8); }
#pragma unroll
            for (int dd = 0; dd < 8; dd++) QB[dd] = lds64(tq + T_B + 64 * (dd + 8));
            const uint32_t u1 = UB + (mi & 1) * U_PL + (7 + r + (mi >> 1)) * 16;
            const uint32_t u2 = UB + ((mi & 1) ^ 1) * U_PL + (7 + r + (mi & 1) + 8 * (mi >> 1)) * 16;
            uint32_t n[4];
#pragma unroll
            for (int j = 0; j < 12; j++) {
                uint32_t m[4];
                ldsm4(u1 + j * 128, m[0], m[1], m[2], m[3]);
                if (!(j & 1)) ldsm4(u2 + j * 128, n[0], n[1], n[2], n[3]);
                const uint32_t n0 = n[2 * (j & 1)], n1 = n[2 * (j & 1) + 1];
                float wa[4], wb[4], wc[4], g1[4], g2[4];
                mma_bf_z(wa, bA.x, bA.y, bA.z, bA.w, m[0], m[1]);
                mma_bf_z(wb, bA.x, bA.y, bA.z, bA.w, n0, n1);
                mma_bf_z(wc, bA.x, bA.y, bA.z, bA.w, m[2], m[3]);
                if (j < 8) {
                    mma_bf_z(g1, bB.x, bB.y, bB.z, bB.w, m[0], m[1]);
                    mma_bf_z(g2, bB.x, bB.y, bB.z, bB.w, n0, n1);
                    mma_bf_k8(g1, bC.x, bC.y, m[2]);
                    mma_bf_k8(g2, bC.x, bC.y, m[3]);
                }
#pragma unroll
                for (int e = 0; e < 2; e++) {
                    const uint32_t q0 = pack_bf(wa[e], wa[e + 2]), q1 = pack_bf(wb[e], wb[e + 2]), q2 = q1 ^ p.zero, q3 = pack_bf(wc[e], wc[e + 2]);
#pragma unroll
                    for (int dd = 0; dd < 5; dd++)
                        if (j + 4 + dd < 16) mma_bf(D[j + 4 + dd], q0, q1, q2, q3, QA[dd][e].x, QA[dd][e].y);
                }
                if (j < 8) {
                    const uint32_t q0 = pack_bf(g1[0], g1[2]), q1 = pack_bf(g2[0], g2[2]), q2 = pack_bf(g1[1], g1[3]), q3 = pack_bf(g2[1], g2[3]);
#pragma unroll
                    for (int dd = 7 - j; dd >= 0; dd--) mma_bf(D[j + 8 + dd], q0, q1, q2, q3, QB[dd].x, QB[dd].y);
                }
                if ((j & 3) == 3) {
                    WSTAMP(4 + 2 * (j >> 2));
                    if (j == 11 && LATE2) ship(2);
                    if (j != 7 || !LATE2) ship((j >> 2) + 1);
                }
            }
        }
        const int warpu = __reduce_max_sync(0xffffffffu, warp);
        mix_rows<1, BULKM>(p, &tm_out, sb, sb + OFF_U + warpu * U_CH + (warpu & 1) * 64, PQ, 4, warpu, h, pr, lane);
        if (BULKM) asm volatile("cp.async.bulk.commit_group;\n\tcp.async.bulk.wait_group.read 0;" ::: "memory");
        WSTAMP(10);
        WDUMP();
    } else if ((pw & 12) == AUX_W0) {
        const int v = __reduce_max_sync(0xffffffffu, pw & 3);
        const int at = tid & 127;
        const int g = lane >> 2, t = lane & 3;
        unsigned tag;
        const bool gu = c < NGU_CTA;
        {
            const uint32_t xb = sb + (v < 2 ? OFF_XSEL : OFF_RING + 2 * 8192) + v * 8192;
            const uint32_t gws = sb + M_DPIN;
            const uint32_t row = 16 * c + 4 * v + (g >> 1);
#pragma unroll
            for (int i = 0; i < 8; i++)
                asm volatile("cp.async.ca.shared.global [%0], [%1], 4;" :: "r"((i < 4 ? sb + OFF_GP : gws) + 512 * (i & 3) + (tid & 124) * 4 + (tid & 1) * 8 + (tid & 2) * 2),
                             "l"((i < 4 ? p.wr : p.gatew) + 256 * (i & 3) + (tid & 127) * 2) : "memory");
            if ((tid & 127) < 33) cp16(sb + OFF_BAND + (tid & 127) * 16, p.band + (tid & 127));
            asm volatile("barrier.cluster.arrive.relaxed.aligned;" ::: "memory");
            tag = __reduce_max_sync(0xffffffffu, (*(volatile unsigned*)&p.sc->epoch + 1) & 0xffffu);
            if (gu) st_gpu32((uint32_t*)&p.sc->h[(tag + 1) & 1][32 * c] + at, 0);
            if (v == 2) sts32(sb + M_BMAP + lane * 4, 0);
            if (at == 0) sts32(sb + M_TAG, tag << 16);
            cp_wait_all();
            bar_sync(1, 128);
            uint2 w[16];
#pragma unroll
            for (int kb = 0; kb < 16; kb++) w[kb] = lds64((g < 4 ? sb + OFF_GP : gws) + 128 * kb + 32 * (g & 2) + 16 * t + 8 * (g & 1));
            asm volatile("barrier.cluster.wait.acquire.aligned;" ::: "memory");
            mbar_wait(bars + 8 * (B_X + v));
            WSTAMP(10);
            float dr[4][4];
#pragma unroll
            for (int kb = 0; kb < 16; kb++) {
                const uint4 x = lds128(xb + (g >> 1) * 2048 + 128 * kb + 16 * (lane & 7));
                if (kb < 4) mma_bf_z(dr[kb], x.x, x.y, x.z, x.w, w[kb].x, w[kb].y);
                else mma_bf(dr[kb & 3], x.x, x.y, x.z, x.w, w[kb].x, w[kb].y);
            }
            float rs = ((dr[0][0] + dr[0][3]) + (dr[1][0] + dr[1][3])) + ((dr[2][0] + dr[2][3]) + (dr[3][0] + dr[3][3]));
            if (lane == 0) mbar_arrive(bars + 8 * (B_XE + v) + (__float_as_uint(rs) & p.zero));
            rs += __shfl_xor_sync(0xffffffffu, rs, 5);
            const uint32_t rb = pack_bf(0.f, rs);
            if (!(lane & 7)) st_gpu32((uint32_t*)p.sc->r + row, ((rb ^ (((int)rb >> 31) | 0x80000000u)) & 0xffff0000u) | tag);
            WSTAMP(1);
            {
                const int n = 3 + (lane >> 3) + 4 * (lane & 1);
                const uint32_t so = (n & 7) * S_PL + ((lane & 6) + (n >> 3)) * 32;
                const uint32_t src[2] = {sb + OFF_S + v * S_Q + s_addr(so, h), sb + OFF_S + v * S_Q + s_addr(so + 32, h)};
                const uint32_t dst = sb + OFF_U + g * U_CH + (8 + 32 * v + 16 * h + t) * 16;
                const uint32_t rdst = mapa(dst, h ^ 1), rbar = mapa(bars + 8 * B_U, h ^ 1);
                mbar_wait(bars + 8 * (B_S + v));
                WSTAMP(9);
                uint4 a[8];
#pragma unroll
                for (int b = 0; b < 2; b++) {
#pragma unroll
                    for (int j = 0; j < 8; j++) { const int u = 4 * b + (j >> 1) + 8 * (j & 1); ldsm4t((u < 8 ? src[u & 1] ^ 16 : src[u & 1]) + ((u >> 1) & 3) * 256, a[j].x, a[j].y, a[j].z, a[j].w); }
#pragma unroll
                    for (int j = 0; j < 8; j++) {
                        const int u = 4 * b + (j >> 1) + 8 * (j & 1);
                        if (u < 8) st_async16(rdst + ((u >> 1) & 3) * 64 + (u & 1) * U_PL, a[j], rbar);
                        else sts128(dst + ((u >> 1) & 3) * 64 + (u & 1) * U_PL, a[j].x, a[j].y, a[j].z, a[j].w);
                    }
                }
                if (h && v == 3) {
                    ldsm4t((src[0] ^ 16) + 1024, a[0].x, a[0].y, a[0].z, a[0].w);
                    ldsm4t(src[0] + 1024, a[1].x, a[1].y, a[1].z, a[1].w);
                    if (t == 0) {
                        st_async16(rdst + 256, make_uint4(a[0].x, a[0].y & 0xffffu, a[0].z & 0xffffu, a[0].w & 0xffffu), rbar);
                        sts128(dst + 256, a[1].x, a[1].y & 0xffffu, a[1].z & 0xffffu, a[1].w & 0xffffu);
                    }
                }
                __syncwarp();
                if (lane == 0) mbar_arrive(bars + 8 * B_U);
            }
            if ((lane & 7) == 2) st_gpu32((uint32_t*)p.sc->g + ((row & 256) << 2) + gate_pos(row), pack_bf(sigmoid_f(__uint_as_float(rb)), 0.f) | (tag << 16));
            WSTAMP(2);
        }
        {
            const bool lane0 = pin(lane, lane) == 0;
            const uint32_t own = pin(sb + OFF_XSEL + (at ^ ((at >> 1) & 4)) * 16, lane);
            float acc[8][4];
#pragma unroll
            for (int i = 0; i < 8; i++) { acc[i][0] = acc[i][1] = acc[i][2] = acc[i][3] = 0.f; }
            const int krow = ((lane >> 1) & 8) + (lane & 7);
            const uint32_t tile0 = pin(sb + OFF_RING + krow * 64 + ((((lane >> 3) & 1) ^ ((krow >> 1) & 3)) << 4), lane);
            const uint32_t xo = pin(sb + OFF_XSEL + (lane & 7) * XS_ROW + 512 * v + 2 * (lane & 24), lane);
            const uint32_t po = pin(sb + OFF_XSEL + t * XS_ROW + (g & 3) * 128 + (g & 1) * 64 + v * 16 + (lane >> 4) * 8, lane);
            const uint32_t po1 = pin(po + 64 - (g & 1) * 128, lane);
            uint32_t* hdst = pin((uint32_t*)&p.sc->h[tag & 1][32 * c] + at, lane);
            auto signal = [&](const int k, const uint32_t dep) {
                if (lane < 2 && v < 2)
                    asm volatile("st.async.weak.shared::cluster.mbarrier::complete_tx::bytes.b32 [%0], %1, [%2];"
                                 :: "r"(mapa(sb + M_SINK, lane)), "r"(dep), "r"(mapa(bars + 8 * (B_F + k), lane)) : "memory");
            };
#pragma unroll 1
            for (int i = 0; i < 4; i++) {
                const int s = 4 * i + v;
                uint32_t a[16][4], b[2][4];
                if (gu) {
                    const uint32_t tile = tile0 + (s < 14 ? s : v) * 8192;
                    if (lane0 && i > 1) mbar_arrive(bars + 8 * (B_E + s - 4));
                    if (i == 2) signal(0, 0);
                    mbar_wait(bars + 8 * (B_W + s));
#pragma unroll
                    for (int q = 0; q < 16; q++) ldsm4t((tile ^ ((q & 1) << 5)) + ((q >> 1) & 1) * 4096 + (q >> 2) * 1024, a[q][0], a[q][1], a[q][2], a[q][3]);
                }
                if (i == 0) {
                    if (gu) {
                        uint32_t dep = p.zero;
#pragma unroll
                        for (int q = 0; q < 16; q += 2) dep &= a[q][0] & a[q + 1][0];
                        if (lane == 0) mbar_arrive(bars + 8 * (B_E + v) + dep);
                    }
                    WSTAMP(11);
                    uint32_t top;
#pragma unroll 1
                    for (int it = 0; it < (1 << 22); it++) {
                        asm volatile("ld.relaxed.gpu.global.u32 %0, [%1];" : "=r"(top) : "l"(&p.sc->top[c % NTOP][g]) : "memory");
                        if (__all_sync(0xffffffffu, ((top ^ (tag << 11)) & 0xf800u) == 0)) break;
                        if (TSLEEP) __nanosleep(TSLEEP);
                    }
                    WSTAMP(3);
                    if (gu) {
                        const uint32_t k = 4 * h + v, row = __reduce_max_sync(0xffffffffu, lane == 4 * k ? ~top & 2047 : 0);
                        asm volatile("{\n\t.reg .pred p;\n\telect.sync _|p, 0xffffffff;\n\t"
                                     "@p cp.async.bulk.shared::cluster.global.mbarrier::complete_tx::bytes.multicast::cluster [%0], [%1], 2048, [%2], %3;\n\t}"
                            :: "r"(sb + OFF_XSEL + k * XS_ROW), "l"(p.u + (size_t)row * D_), "r"(bars + 8 * B_G), "h"((unsigned short)3) : "memory");
                    }
                    if (v == 2) {
                        const uint32_t row = ~top & 2047;
                        if (t == 0 && ((row >> 8) & 1) == h)
                            asm volatile("red.shared.or.b32 [%0], %1;" :: "r"(sb + M_BMAP + (row & 7) * 16 + (row >> 9) * 4), "r"(1u << (gate_pos(row) & 31)) : "memory");
                        if (t == 0) sts32(sb + M_TOP + lane, top);
                        if (c == 0 && lane == 0) *(volatile unsigned*)&p.sc->epoch = tag;
                        __syncwarp();
                        if (lane0) mbar_arrive(bars + 8 * B_Y);
                    }
                    if (!gu) break;
                    mbar_wait(bars + 8 * B_G);
                    WSTAMP(4);
                }
                ldsm4(xo + 128 * i, b[0][0], b[0][1], b[0][2], b[0][3]);
                ldsm4(xo + 128 * i + 64, b[1][0], b[1][1], b[1][2], b[1][3]);
#pragma unroll
                for (int q = 0; q < 16; q++) mma_bf(acc[q & 7], a[q][0], a[q][1], a[q][2], a[q][3], b[q >> 3][(q >> 1) & 2], b[q >> 3][((q >> 1) & 2) + 1]);
            }
            if (gu) {
                WSTAMP(5);
                __syncwarp();
#pragma unroll
                for (int q = 0; q < 4; q++) {
                    const int ct = q >> 1, e = 2 * (q & 1);
                    sts128(own + q * XS_ROW,
                           __float_as_uint(acc[ct][e] + acc[4 + ct][e]), __float_as_uint(acc[2 + ct][e] + acc[6 + ct][e]),
                           __float_as_uint(acc[ct][e + 1] + acc[4 + ct][e + 1]), __float_as_uint(acc[2 + ct][e + 1] + acc[6 + ct][e + 1]));
                }
                bar_sync(1, 128);
                float sl[2], uv[2];
#pragma unroll
                for (int e = 0; e < 2; e++) {
                    uint2 q[4];
#pragma unroll
                    for (int i = 0; i < 4; i++) q[i] = lds64((e ? po1 : po) + 512 * i);
                    const float s0 = (__uint_as_float(q[0].x) + __uint_as_float(q[1].x)) + (__uint_as_float(q[2].x) + __uint_as_float(q[3].x));
                    const float s1 = (__uint_as_float(q[0].y) + __uint_as_float(q[1].y)) + (__uint_as_float(q[2].y) + __uint_as_float(q[3].y));
                    const float gv = bf_round(p.gu_swap ? s1 : s0);
                    uv[e] = p.gu_swap ? s0 : s1;
                    sl[e] = gv * sigmoid_f(gv);
                }
                const uint32_t hw = hmul2_bf(pack_bf(sl[0], sl[1]), pack_bf(uv[0], uv[1]));
                st_gpu32(hdst, hw ? hw : 0x80000000u);
                signal(1, hw);
            }
        }
        WSTAMP(6);
        {
            const uint32_t own = pin(sb + OFF_XSEL + at * 16, lane);
            const uint32_t hb = sb + (v < 2 ? OFF_XSEL + 7168 * v : OFF_RING + 8192 * v), hl = pin(hb + 16 * lane, lane);
            const int krow = ((lane >> 1) & 8) + (lane & 7);
            const uint32_t tile = pin(sb + OFF_RING + v * 8192 + krow * 32 + ((((lane >> 3) ^ (krow >> 2)) & 1) << 4), lane);
            float dd[4][4];
            bar_sync(1, 128);
            mbar_wait(bars + 8 * (B_W + HW));
            WSTAMP(12);
            uint4 hq[7];
#pragma unroll 1
            for (int it = 0; it < (1 << 16); it++) {
                bulk_load(hb, &p.sc->h[tag & 1][32 * (56 * h + 14 * v)], 7168, bars + 8 * (B_X + v));
                uint32_t a[14][4], mn = 0xffffffffu;
                mbar_wait(bars + 8 * (B_W + 16 + v));
#pragma unroll
                for (int j = 0; j < 14; j++) ldsm4t(tile + (v & 2) * 16384 + j * 512, a[j][0], a[j][1], a[j][2], a[j][3]);
                mbar_wait(bars + 8 * (B_X + v), ~it & 1);
                WSTAMP(7);
#pragma unroll
                for (int j = 0; j < 7; j++) {
                    const uint4 q = lds128(hl + 512 * j);
                    mn = min(mn, q.x);
#pragma unroll
                    for (int e = 0; e < 2; e++) {
                        const uint32_t(&f)[4] = a[2 * j + e];
                        if (j < 2) mma_bf_z(dd[2 * j + e], f[0], f[1], f[2], f[3], e ? q.z : q.x, e ? q.w : q.y);
                        else mma_bf(dd[(2 * j + e) & 3], f[0], f[1], f[2], f[3], e ? q.z : q.x, e ? q.w : q.y);
                    }
                }
#pragma unroll
                for (int j = 0; j < 7; j++) { hq[j] = lds128(hl + 3584 + 512 * j); mn = min(mn, hq[j].x); }
                if (__all_sync(0xffffffffu, mn != 0)) break;
            }
            mbar_wait(bars + 8 * (B_W + 20 + v));
#pragma unroll
            for (int j = 0; j < 14; j++) {
                uint32_t f[4];
                ldsm4t(tile + 65536 + j * 512, f[0], f[1], f[2], f[3]);
                mma_bf(dd[(j + 2) & 3], f[0], f[1], f[2], f[3], (j & 1) ? hq[j >> 1].z : hq[j >> 1].x, (j & 1) ? hq[j >> 1].w : hq[j >> 1].y);
            }
            WSTAMP(8);
            uint4 part;
            part.x = __float_as_uint((dd[0][0] + dd[1][0]) + (dd[2][0] + dd[3][0])); part.y = __float_as_uint((dd[0][1] + dd[1][1]) + (dd[2][1] + dd[3][1]));
            part.z = __float_as_uint((dd[0][2] + dd[1][2]) + (dd[2][2] + dd[3][2])); part.w = __float_as_uint((dd[0][3] + dd[1][3]) + (dd[2][3] + dd[3][3]));
            st_async16(mapa(own + (M_DPIN - OFF_XSEL), h ^ 1), part, mapa(bars + 8 * B_DP, h ^ 1));
            sts128(own + 14336, part.x, part.y, part.z, part.w);
            __syncwarp();
            if (lane == 0) mbar_arrive(bars + 8 * B_DP);
        }
        WDUMP();
    } else {
        asm volatile("setmaxnreg.dec.sync.aligned.u32 64;");
        const int v = __reduce_max_sync(0xffffffffu, pw - PREP_W0);
        const bool gu = c < NGU_CTA;
        const uint32_t t0 = clock();
        const uint32_t bu = bars + 8 * v;
        if (lane == 0) {
#pragma unroll
            for (int i = 0; i < 10; i++) mbar_init(bu + 32 * i, 1);
            mbar_init(bu + 8 * B_X, 1);
            mbar_init(bu + 8 * B_XE, 1);
            mbar_init(bu + 8 * B_Y, v == 0 ? 11 : 9);
            mbar_init(bu + 8 * B_DP, (0x1855 >> (4 * v)) & 15);
            mbar_init(bu + 8 * B_F, 1);
            mbar_init(bu + 8 * B_H, 1);
            asm volatile("fence.mbarrier_init.release.cluster;" ::: "memory");
            mbar_expect(bu + 8 * B_Y, 4096);
            if (v != 2) mbar_expect(bu + 8 * B_DP, v == 0 ? 2048 : (h || v == 3) ? 16384 : 16384 + 128);
            mbar_expect(bu + 8 * B_F, c < NGU_CTA ? 16 : 0);
        }
        __syncwarp();
        asm volatile("barrier.cluster.arrive.relaxed.aligned;" ::: "memory");
        bulk_load(sb + (v < 2 ? OFF_XSEL : OFF_RING + 2 * 8192) + v * 8192, p.u + (size_t)(16 * c + 4 * v) * D_, 8192, bu + 8 * B_X);
        tma3d(sb + OFF_S + v * S_Q, &tm_x, 16 * pr, 64 * v + 32 * h - 1, bars + 8 * (B_S + v), S_Q);
        WSTAMP(9);
        if (v < 3 && lane == 0) asm volatile("prefetch.tensormap [%0];" :: "l"(v == 0 ? &tm_gu : v == 1 ? &tm_down : &tm_out) : "memory");
        asm volatile("barrier.cluster.wait.acquire.aligned;" ::: "memory");
        uint32_t desc;
        {
            const int s = 6 * v + lane, i = s >> 2, w = s & 3, slot = s < 14 ? s : (s | 1) == 17 ? s - 16 : s - 12;
            const int fb = s < 4 ? B_H : (gu && s >= 14) ? B_E + slot : s < 6 ? B_XE + s - 2 : B_KG;
            desc = slot | (fb << 4) | ((i < 4 ? 256 * w + 64 * i : 1792 * h + 448 * w + 224 * (i - 4)) << 10);
            if (lane < 6) mbar_expect(bars + 8 * (B_W + s), i < 4 ? 8192 : 7168);
            if (tid == 32 * PREP_W0) mbar_arrive(bars + 8 * B_H);
        }
        if (v == 3) {
            mbar_wait(bars + 8 * B_U);
            mbar_wait(bars + 8 * (gu ? B_G : B_H + 2));
            const uint32_t tag16 = lds32(sb + M_TAG);
            uint4 q[8];
#pragma unroll 1
            for (int it = 0; it < (1 << 22); it++) {
                uint32_t bad = 0;
#pragma unroll
                for (int i = 0; i < 8; i++) q[i] = ld_gpu128(&p.sc->g[256 * h + 32 * i + lane]);
#pragma unroll
                for (int i = 0; i < 8; i++) bad |= ((q[i].x ^ tag16) | (q[i].y ^ tag16)) | ((q[i].z ^ tag16) | (q[i].w ^ tag16));
                if ((bad >> 16) == 0) break;
                __nanosleep(200);
            }
#pragma unroll
            for (int i = 0; i < 8; i++)
                asm volatile("st.shared.v2.u32 [%0], {%1, %2};" :: "r"(sb + OFF_GP + 256 * i + lane * 8),
                             "r"(__byte_perm(q[i].x, q[i].y, 0x5410)), "r"(__byte_perm(q[i].z, q[i].w, 0x5410)) : "memory");
            __syncwarp();
            if (lane == 0) mbar_arrive(bars + 8 * B_Y);
        }
        mbar_wait(bars + 8 * (B_H + v));
        {
            const int gap = v == 0 ? GAP : v == 1 ? GAP1 : v == 2 ? GAP2 : GAP3;
            uint32_t last = v ? clock() - SLACK : t0 + T0 - GAP + STAG * ((pr * 5) & 15) / 16;
#pragma unroll 1
            while ((int)(last - clock()) > 500) __nanosleep(256);
#pragma unroll 1
            for (int k = 0; k < 6; k++) {
                const uint32_t dk = __reduce_max_sync(0xffffffffu, lane == k ? desc : 0);
                const bool dn = 6 * v + k >= 16;
                mbar_wait(bars + ((dk >> 1) & 0x1f8));
                uint32_t now;
#pragma unroll 1
                while ((int)((now = clock()) - last) < gap) __nanosleep(CSLEEP);
                last = max((int)(now - last) - SLACK, gap) + last;
                WSTAMP(3 + k);
                if (gu || dn)
                    asm volatile("{\n\t.reg .pred p;\n\telect.sync _|p, 0xffffffff;\n\t"
                                 "@p cp.async.bulk.tensor.3d.shared::cluster.global.mbarrier::complete_tx::bytes [%0], [%1, {%3, %4, 0}], [%2];\n\t}"
                        :: "r"(sb + OFF_RING + (dk & 15) * 8192), "l"(dn ? &tm_down : &tm_gu), "r"(bars + 8 * (B_W + 6 * v + k)), "r"(dn ? 16 * pr : 32 * c), "r"(dk >> 10) : "memory");
                if (k < 5 && PRESLEEP) __nanosleep(PRESLEEP);
            }
            if (lane == 0 && v < 3) mbar_arrive(bars + 8 * (B_H + v + 1));
        }
        {
            WSTAMP(1);
            mix_rows<2, true>(p, &tm_out, sb, sb + OFF_TAB + v * TAB_W, 0, PQ, v, h, pr, lane);
            WSTAMP(2);
            asm volatile("cp.async.bulk.commit_group;" ::: "memory");
            const uint32_t top = lds32(sb + M_TOP + 8 * v + 4 * (lane >> 4));
            const uint32_t row = ~top & 2047, ch = lane & 15, gp = gate_pos(row);
            const bool mine = ((row >> 8) & 1) == h;
            uint32_t gfin, x16, y16 = 0;
            asm volatile("ld.shared.u16 %0, [%1];" : "=r"(gfin) : "r"(sb + OFF_GP + gp * 2) : "memory");
            asm volatile("ld.shared.u16 %0, [%1];" : "=r"(x16) : "r"(sb + OFF_S + (row >> 9) * S_Q + s_addr((row & 7) * S_PL + 32 + (row & 248) * 4, ch >> 3) + 2 * (ch & 7)) : "memory");
            const float rsel = __uint_as_float(pin(__float_as_uint(bf_round(sigmoid_f(__uint_as_float((top ^ (((int)~top >> 31) | 0x80000000u)) & 0xffff0000u)))), lane));
            const uint32_t po = pin(sb + (4 * (ch & 7) + v) * 16 + (ch >> 3) * 8 + (lane >> 4) * 4, lane);
            bf16* op = pin(p.out + (size_t)row * D_ + 16 * pr + ch, lane);
            if (mine) {
                mbar_wait(bars + 8 * (B_Y + (row >> 9)));
                asm volatile("ld.shared.u16 %0, [%1];" : "=r"(y16)
                             : "r"(sb + y_off(row >> 9) + ch * 512 + (((4 * (row & 7) + ((row >> 5) & 3)) ^ (((ch >> 2) << 1) | (ch & 1))) << 4) + 2 * row_elem(row)) : "memory");
            }
            mbar_wait(bars + 8 * B_DP);
            float q[8];
#pragma unroll
            for (int i = 0; i < 4; i++) { q[i] = ldsf(po + M_DPIN + 512 * i); q[4 + i] = ldsf(po + OFF_XSEL + 14336 + 512 * i); }
            const float tot = ((q[0] + q[1]) + (q[2] + q[3])) + ((q[4] + q[5]) + (q[6] + q[7]));
            const float b = bf_round(__uint_as_float(x16 << 16) + bf_round(bf_round(tot) * rsel));
            if (mine) *op = __float2bfloat16_rn(fmaf(bf_lo(gfin), __uint_as_float(y16 << 16), bf_round(bf_round(1.f - bf_lo(gfin)) * b)));
        }
        asm volatile("cp.async.bulk.wait_group.read 0;" ::: "memory");
        WSTAMP(10);
        WDUMP();
    }
}

typedef CUresult (*EncodeFn)(CUtensorMap*, CUtensorMapDataType, cuuint32_t, void*, const cuuint64_t*, const cuuint64_t*,
                             const cuuint32_t*, const cuuint32_t*, CUtensorMapInterleave, CUtensorMapSwizzle,
                             CUtensorMapL2promotion, CUtensorMapFloatOOBfill);

void make_map(EncodeFn f, CUtensorMap* m, const void* ptr, uint64_t cols, uint64_t rows, uint64_t pitch, uint32_t bc, uint32_t br, CUtensorMapSwizzle sw, int prom,
              uint32_t planes = 1, uint64_t plane_stride = 0, uint32_t box_planes = 0) {
    cuuint64_t dims[3] = {cols, rows, planes};
    cuuint64_t str[2] = {pitch, planes > 1 ? plane_stride : pitch * rows};
    cuuint32_t box[3] = {bc, br, box_planes ? box_planes : planes};
    cuuint32_t es[3] = {1, 1, 1};
    f(m, CU_TENSOR_MAP_DATA_TYPE_BFLOAT16, 3, (void*)ptr, dims, str, box, es, CU_TENSOR_MAP_INTERLEAVE_NONE, sw,
      (CUtensorMapL2promotion)prom, CU_TENSOR_MAP_FLOAT_OOB_FILL_NONE);
}

}

extern "C" void kernel_launch(void* const* d_in, const int* in_sizes, int n_in, void* d_out, int out_size) {
    static EncodeFn enc = nullptr;
    static void *sc = nullptr, *band = nullptr;
    if (!enc) {
        void* fn = nullptr;
        cudaDriverEntryPointQueryResult qr;
        cudaGetDriverEntryPoint("cuTensorMapEncodeTiled", &fn, cudaEnableDefault, &qr);
        enc = (EncodeFn)fn;
        cudaGetSymbolAddress(&sc, g_scratch);
        cudaGetSymbolAddress(&band, g_band);
        cudaFuncSetAttribute(fused_kernel, cudaFuncAttributeMaxDynamicSharedMemorySize, SMEM_BYTES);
    }
    CUtensorMap tg, td, tx, to;
    const char *wg = (const char*)d_in[9], *wu = (const char*)d_in[10];
    const bool swap = wu < wg;
    make_map(enc, &tg, swap ? wu : wg, F_, D_, F_ * 2, 32, 64, CU_TENSOR_MAP_SWIZZLE_64B, PROMG, 2, swap ? wg - wu : wu - wg);
    make_map(enc, &td, d_in[11], D_, F_, D_ * 2, 16, 224, CU_TENSOR_MAP_SWIZZLE_32B, PROMD);
    make_map(enc, &tx, d_in[0], D_, L_ / 8, D_ * 16, 16, 33, CU_TENSOR_MAP_SWIZZLE_32B, PROMX, 8, D_ * 2);
    make_map(enc, &to, d_out, D_, L_ / 8, D_ * 16, 16, 32, CU_TENSOR_MAP_SWIZZLE_NONE, 0, 8, D_ * 2, 1);
    Params p;
    p.u = (const bf16*)d_in[0]; p.logA = (const bf16*)d_in[1]; p.Aim = (const bf16*)d_in[2];
    p.Cre = (const bf16*)d_in[3]; p.Cim = (const bf16*)d_in[4]; p.logdt = (const bf16*)d_in[5];
    p.Dskip = (const bf16*)d_in[6]; p.wr = (const bf16*)d_in[8]; p.gatew = (const bf16*)d_in[12];
    p.out = (bf16*)d_out;
    p.sc = (Scratch*)sc; p.band = (const uint4*)band;
    p.gu_swap = swap;
    p.zero = 0;
    fused_kernel<<<NCTA, NTHREADS, SMEM_BYTES>>>(p, tg, td, tx, to);
}
```

```cpp
#include <cuda_runtime.h>
#include <cuda_bf16.h>
#include <cuda_fp16.h>
#include <cuda.h>
#include <stdint.h>

typedef __nv_bfloat16 bf16;

namespace {

constexpr int L_ = 2048, D_ = 1024, F_ = 3584;
constexpr int NCTA = 130;
constexpr int NTHREADS = 512;
#define AUXW 12
constexpr int MAIN_W0 = 0, AUX_W0 = AUXW, PREP_W0 = 20 - AUXW;
#define T0 3000
#define GAP 540
#define GAP1 530
#define GAP2 530
#define GAP3 550
#define STAG GAP
#define CSLEEP 50
#define SLACK 300
#define TSLEEP 40
#define BULKM true
#define PRESLEEP 64
#define PQ 3
#define PROMG 2
#define PROMD 1
#define PROMX 0
#define LATE2 0
#define HW 20
constexpr int NGU_CTA = 112;

constexpr int OFF_RING = 0;
constexpr int OFF_SCR  = 6 * 8192;
constexpr int S_PL     = 1056;
constexpr int S_Q      = 8 * S_PL;
constexpr int OFF_S    = 114688;
constexpr int OFF_GP   = OFF_S + 4 * S_Q;
constexpr int U_PL     = 2240;
constexpr int U_CH     = 4416;
constexpr int OFF_U    = 151552;
constexpr int TAB_W    = 3200;
constexpr int T_PL     = 544;
constexpr int T_A      = 2192 - 26 * 8;
constexpr int T_B      = 2568 - 59 * 8;
constexpr int OFF_TAB  = 186880;
constexpr int OFF_XSEL = 212480;
constexpr int XS_ROW   = 2064;
constexpr int OFF_BAND = 228992;
constexpr int OFF_MISC = 229536;
constexpr int M_BARS   = OFF_MISC;
constexpr int M_DSK    = OFF_MISC + 2736;
constexpr int M_SINK   = OFF_MISC + 512;
constexpr int M_TAG    = OFF_MISC + 516;
constexpr int M_BMAP   = OFF_MISC + 528;
constexpr int M_DPIN   = OFF_MISC + 656;
constexpr int M_TOP    = OFF_MISC + 2704;
constexpr int SMEM_BYTES = OFF_MISC + 2768;
__device__ __forceinline__ uint32_t s_addr(uint32_t o, uint32_t half) { return o + (((half ^ (o >> 7)) & 1) << 4); }
__host__ __device__ constexpr uint32_t y_off(uint32_t q) { return OFF_RING + 32768 + (q & 1) * 8192 + (q >> 1) * 65536; }

constexpr int B_W = 0;
constexpr int B_E = 24;
constexpr int B_S = 36;
constexpr int B_Y = 40;
constexpr int B_DP = 44, B_U = 45, B_KG = 46, B_G = 47;
constexpr int B_F = 48;
constexpr int B_H = 60;
constexpr int B_X = 52, B_XE = 56;

struct BandTab { uint32_t w[11][12]; };
constexpr BandTab make_band() {
    BandTab b{};
    for (int cls = 0; cls < 11; cls++)
        for (int wd = 0; wd < 10; wd++) {
            const int tau = cls + 2 - 8 * ((wd < 4 ? wd : wd - 4) >> 1);
            const int lo = (wd < 4) ? ((wd & 1) ? -2 : 3) : ((wd & 1) ? -4 : -11), wid = (wd < 4 ? 3 : 7) + 2 * (wd & 1);
            b.w[cls][wd] = ((tau >= lo && tau < lo + wid) ? 0x3F80u : 0u) | ((tau - 4 >= lo && tau - 4 < lo + wid) ? 0x3F800000u : 0u);
        }
    return b;
}
constexpr int NTOP = 32;
struct Scratch {
    uint4 r[L_ / 4];
    uint4 g[L_ / 4];
    uint4 h[2][8 * F_ / 8];
    uint32_t top[NTOP][32];
    unsigned epoch;
};
__device__ __align__(128) Scratch g_scratch;
__device__ const __align__(16) BandTab g_band = make_band();

struct Params {
    const bf16 *u, *logA, *Aim, *Cre, *Cim, *logdt, *Dskip, *wr, *gatew;
    bf16* out;
    Scratch* sc;
    const uint4* band;
    uint32_t gu_swap;
    uint32_t zero;
};

#define WSTAMP(i) do {} while (0)
#define KSTAMP(i, dep) do {} while (0)
#define WDUMP() do {} while (0)
#define RSTAMP(i) do {} while (0)

__device__ __forceinline__ uint32_t smem_u32(const void* p) { return (uint32_t)__cvta_generic_to_shared(p); }
__device__ __forceinline__ void mbar_init(uint32_t b, uint32_t c) { asm volatile("mbarrier.init.shared::cta.b64 [%0], %1;" :: "r"(b), "r"(c) : "memory"); }
__device__ __forceinline__ void mbar_expect(uint32_t b, uint32_t tx) { asm volatile("mbarrier.arrive.expect_tx.shared::cta.b64 _, [%0], %1;" :: "r"(b), "r"(tx) : "memory"); }
__device__ __forceinline__ void mbar_arrive(uint32_t b) { asm volatile("mbarrier.arrive.shared::cta.b64 _, [%0];" :: "r"(b) : "memory"); }
__device__ __forceinline__ void mbar_wait(uint32_t b, uint32_t parity = 0) {
    asm volatile("{\n\t.reg .pred p;\nW%=:\n\tmbarrier.try_wait.parity.shared::cta.b64 p, [%0], %1, 20000;\n\t@!p bra W%=;\n\t}" :: "r"(b), "r"(parity) : "memory");
}
__device__ __forceinline__ uint32_t mapa(uint32_t addr, uint32_t rank) { uint32_t r; asm("mapa.shared::cluster.u32 %0, %1, %2;" : "=r"(r) : "r"(addr), "r"(rank)); return r; }
__device__ __forceinline__ void tma3d(uint32_t dst, const CUtensorMap* tm, int c0, int c1, uint32_t bar, uint32_t bytes) {
    asm volatile("{\n\t.reg .pred p;\n\telect.sync _|p, 0xffffffff;\n\t"
                 "@p mbarrier.arrive.expect_tx.shared::cta.b64 _, [%2], %5;\n\t"
                 "@p cp.async.bulk.tensor.3d.shared::cluster.global.mbarrier::complete_tx::bytes [%0], [%1, {%3, %4, 0}], [%2];\n\t}"
        :: "r"(dst), "l"(tm), "r"(bar), "r"(c0), "r"(c1), "r"(bytes) : "memory");
}
__device__ __forceinline__ void bulk_load(uint32_t dst, const void* src, uint32_t bytes, uint32_t bar) {
    asm volatile("{\n\t.reg .pred p;\n\telect.sync _|p, 0xffffffff;\n\t"
                 "@p mbarrier.arrive.expect_tx.shared::cta.b64 _, [%2], %3;\n\t"
                 "@p cp.async.bulk.shared::cluster.global.mbarrier::complete_tx::bytes [%0], [%1], %3, [%2];\n\t}"
        :: "r"(dst), "l"(src), "r"(bar), "r"(bytes) : "memory");
}
__device__ __forceinline__ void st_async16(uint32_t dst, const uint4& v, uint32_t bar) {
    asm volatile("st.async.weak.shared::cluster.mbarrier::complete_tx::bytes.v4.b32 [%0], {%1,%2,%3,%4}, [%5];"
                 :: "r"(dst), "r"(v.x), "r"(v.y), "r"(v.z), "r"(v.w), "r"(bar) : "memory");
}
__device__ __forceinline__ void bar_sync(int id, int n) { asm volatile("bar.sync %0, %1;" :: "r"(id), "r"(n) : "memory"); }
__device__ __forceinline__ void cp16(uint32_t dst, const void* src) { asm volatile("cp.async.cg.shared.global [%0], [%1], 16;" :: "r"(dst), "l"(src) : "memory"); }
__device__ __forceinline__ void cp_wait_all() { asm volatile("cp.async.wait_all;" ::: "memory"); }
__device__ __forceinline__ uint4 ld_gpu128(const void* p) { uint4 v; asm volatile("ld.relaxed.gpu.global.v4.u32 {%0,%1,%2,%3}, [%4];" : "=r"(v.x), "=r"(v.y), "=r"(v.z), "=r"(v.w) : "l"(p) : "memory"); return v; }
__device__ __forceinline__ void st_gpu32(void* p, uint32_t v) { asm volatile("st.relaxed.gpu.global.u32 [%0], %1;" :: "l"(p), "r"(v) : "memory"); }

__device__ __forceinline__ void ldsm4(uint32_t a, uint32_t& r0, uint32_t& r1, uint32_t& r2, uint32_t& r3) {
    asm volatile("ldmatrix.sync.aligned.m8n8.x4.shared.b16 {%0,%1,%2,%3}, [%4];" : "=r"(r0), "=r"(r1), "=r"(r2), "=r"(r3) : "r"(a) : "memory");
}
__device__ __forceinline__ void ldsm4t(uint32_t a, uint32_t& r0, uint32_t& r1, uint32_t& r2, uint32_t& r3) {
    asm volatile("ldmatrix.sync.aligned.m8n8.x4.trans.shared.b16 {%0,%1,%2,%3}, [%4];" : "=r"(r0), "=r"(r1), "=r"(r2), "=r"(r3) : "r"(a) : "memory");
}
__device__ __forceinline__ uint32_t lds32(uint32_t a) { uint32_t v; asm volatile("ld.shared.u32 %0, [%1];" : "=r"(v) : "r"(a) : "memory"); return v; }
__device__ __forceinline__ uint2 lds64(uint32_t a) { uint2 v; asm volatile("ld.shared.v2.u32 {%0,%1}, [%2];" : "=r"(v.x), "=r"(v.y) : "r"(a) : "memory"); return v; }
__device__ __forceinline__ uint4 lds128(uint32_t a) { uint4 v; asm volatile("ld.shared.v4.u32 {%0,%1,%2,%3}, [%4];" : "=r"(v.x), "=r"(v.y), "=r"(v.z), "=r"(v.w) : "r"(a) : "memory"); return v; }
__device__ __forceinline__ void sts32(uint32_t a, uint32_t v) { asm volatile("st.shared.u32 [%0], %1;" :: "r"(a), "r"(v) : "memory"); }
__device__ __forceinline__ void sts16(uint32_t a, uint32_t v) { asm volatile("st.shared.u16 [%0], %1;" :: "r"(a), "h"((unsigned short)v) : "memory"); }
__device__ __forceinline__ void sts128(uint32_t a, uint32_t x, uint32_t y, uint32_t z, uint32_t w) { asm volatile("st.shared.v4.u32 [%0], {%1,%2,%3,%4};" :: "r"(a), "r"(x), "r"(y), "r"(z), "r"(w) : "memory"); }
__device__ __forceinline__ float ldsf(uint32_t a) { float v; asm volatile("ld.shared.f32 %0, [%1];" : "=f"(v) : "r"(a) : "memory"); return v; }

__device__ __forceinline__ void mma_bf(float (&d)[4], uint32_t a0, uint32_t a1, uint32_t a2, uint32_t a3, uint32_t b0, uint32_t b1) {
    asm volatile("mma.sync.aligned.m16n8k16.row.col.f32.bf16.bf16.f32 {%0,%1,%2,%3}, {%4,%5,%6,%7}, {%8,%9}, {%0,%1,%2,%3};"
        : "+f"(d[0]), "+f"(d[1]), "+f"(d[2]), "+f"(d[3]) : "r"(a0), "r"(a1), "r"(a2), "r"(a3), "r"(b0), "r"(b1));
}
__device__ __forceinline__ void mma_bf_z(float (&d)[4], uint32_t a0, uint32_t a1, uint32_t a2, uint32_t a3, uint32_t b0, uint32_t b1) {
    asm volatile("mma.sync.aligned.m16n8k16.row.col.f32.bf16.bf16.f32 {%0,%1,%2,%3}, {%4,%5,%6,%7}, {%8,%9}, {%10,%10,%10,%10};"
        : "=f"(d[0]), "=f"(d[1]), "=f"(d[2]), "=f"(d[3]) : "r"(a0), "r"(a1), "r"(a2), "r"(a3), "r"(b0), "r"(b1), "f"(0.f));
}
__device__ __forceinline__ void mma_bf_k8(float (&d)[4], uint32_t a0, uint32_t a1, uint32_t b0) {
    asm volatile("mma.sync.aligned.m16n8k8.row.col.f32.bf16.bf16.f32 {%0,%1,%2,%3}, {%4,%5}, {%6}, {%0,%1,%2,%3};"
        : "+f"(d[0]), "+f"(d[1]), "+f"(d[2]), "+f"(d[3]) : "r"(a0), "r"(a1), "r"(b0));
}
__device__ __forceinline__ void mma_h(float (&d)[4], uint32_t a0, uint32_t a1, uint32_t a2, uint32_t a3, uint32_t b0, uint32_t b1) {
    asm volatile("mma.sync.aligned.m16n8k16.row.col.f32.f16.f16.f32 {%0,%1,%2,%3}, {%4,%5,%6,%7}, {%8,%9}, {%0,%1,%2,%3};"
        : "+f"(d[0]), "+f"(d[1]), "+f"(d[2]), "+f"(d[3]) : "r"(a0), "r"(a1), "r"(a2), "r"(a3), "r"(b0), "r"(b1));
}
__device__ __forceinline__ uint32_t pack_bf(float lo, float hi) { uint32_t r; asm("cvt.rn.bf16x2.f32 %0, %1, %2;" : "=r"(r) : "f"(hi), "f"(lo)); return r; }
__device__ __forceinline__ uint32_t pack_h(float lo, float hi) { uint32_t r; asm("cvt.rn.f16x2.f32 %0, %1, %2;" : "=r"(r) : "f"(hi), "f"(lo)); return r; }
__device__ __forceinline__ float bf_lo(uint32_t v) { return __uint_as_float(v << 16); }
__device__ __forceinline__ float bf_hi(uint32_t v) { return __uint_as_float(v & 0xffff0000u); }
__device__ __forceinline__ float bf_round(float x) { return __uint_as_float(pack_bf(0.f, x)); }
__device__ __forceinline__ uint32_t hmul2_bf(uint32_t a, uint32_t b) { uint32_t r; asm("mul.rn.bf16x2 %0, %1, %2;" : "=r"(r) : "r"(a), "r"(b)); return r; }
__device__ __forceinline__ float ex2f(float x) { float r; asm("ex2.approx.ftz.f32 %0, %1;" : "=f"(r) : "f"(x)); return r; }

__device__ __forceinline__ float exp_acc(float x) {
    const float t = x * 1.4426950216293335f;
    const float r = fmaf(x, 1.4426950216293335f, -t) + x * 1.9259629911266175e-8f;
    return ex2f(t) * fmaf(r, 0.6931471805599453f, 1.f);
}
__device__ __forceinline__ float sigmoid_f(float x) { return __fdividef(1.f, 1.f + ex2f(-x * 1.4426950408889634f)); }
__device__ __forceinline__ void cexp_pow(float l2, float li, float e, float& zr, float& zi) {
    const float mag = ex2f(l2 * e);
    zr = mag * __cosf(li * e);
    zi = mag * __sinf(li * e);
}
__device__ __forceinline__ uint32_t hcmul(uint32_t a, uint32_t k, uint32_t kp) {
    const __half2 A = *reinterpret_cast<const __half2*>(&a);
    const __half2 r = __hfma2(__high2half2(A), *reinterpret_cast<const __half2*>(&kp), __hmul2(__low2half2(A), *reinterpret_cast<const __half2*>(&k)));
    return *reinterpret_cast<const uint32_t*>(&r);
}
#define CMUL(orr, oi, ar, ai, br, bi) do { float _r = (ar) * (br) - (ai) * (bi); float _i = (ar) * (bi) + (ai) * (br); orr = _r; oi = _i; } while (0)
#define CSQ(orr, oi, ar, ai) do { float _r = (ar) * (ar) - (ai) * (ai); float _i = 2.f * (ar) * (ai); orr = _r; oi = _i; } while (0)

__device__ __forceinline__ void mma_bf_k8z(float (&d)[4], uint32_t a0, uint32_t a1, uint32_t b0) {
    asm volatile("mma.sync.aligned.m16n8k8.row.col.f32.bf16.bf16.f32 {%0,%1,%2,%3}, {%4,%5}, {%6}, {%7,%7,%7,%7};"
        : "=f"(d[0]), "=f"(d[1]), "=f"(d[2]), "=f"(d[3]) : "r"(a0), "r"(a1), "r"(b0), "f"(0.f));
}
__device__ __forceinline__ void mma_hh_k8(uint32_t& d0, uint32_t& d1, uint32_t a0, uint32_t a1, uint32_t b0) {
    asm volatile("mma.sync.aligned.m16n8k8.row.col.f16.f16.f16.f16 {%0,%1}, {%2,%3}, {%4}, {%5,%5};"
        : "=r"(d0), "=r"(d1) : "r"(a0), "r"(a1), "r"(b0), "r"(0));
}
__device__ __forceinline__ void sched_fence(uint32_t zero, uint32_t id) {
    asm volatile("{\n\t.reg .pred p;\n\tsetp.eq.u32 p, %0, %1;\n\t@p exit;\n\t}" :: "r"(zero), "r"(id) : "memory");
}
__device__ __forceinline__ uint32_t pin(uint32_t x, int lane) { return __shfl_sync(0xffffffffu, x, lane); }
template <class T> __device__ __forceinline__ T* pin(T* x, int lane) { return (T*)__shfl_sync(0xffffffffu, (unsigned long long)x, lane); }
__device__ __forceinline__ void sts32_if(bool on, uint32_t a, uint32_t v) {
    asm volatile("{\n\t.reg .pred p;\n\tsetp.ne.u32 p, %2, 0;\n\t@p st.shared.u32 [%0], %1;\n\t}" :: "r"(a), "r"(v), "r"((uint32_t)on) : "memory");
}
__device__ __forceinline__ void sts128_if(bool on, uint32_t a, uint32_t x, uint32_t y, uint32_t z, uint32_t w) {
    asm volatile("{\n\t.reg .pred p;\n\tsetp.ne.u32 p, %5, 0;\n\t@p st.shared.v4.u32 [%0], {%1,%2,%3,%4};\n\t}" :: "r"(a), "r"(x), "r"(y), "r"(z), "r"(w), "r"((uint32_t)on) : "memory");
}
__device__ __forceinline__ void lds128_if(bool on, uint32_t a, uint32_t (&v)[4]) {
    asm volatile("{\n\t.reg .pred p;\n\tsetp.ne.u32 p, %5, 0;\n\t@p ld.shared.v4.u32 {%0,%1,%2,%3}, [%4];\n\t}"
        : "+r"(v[0]), "+r"(v[1]), "+r"(v[2]), "+r"(v[3]) : "r"(a), "r"((uint32_t)on) : "memory");
}
__device__ __forceinline__ uint32_t hfma2_bf(uint32_t a, uint32_t b, uint32_t c) { uint32_t r; asm("fma.rn.bf16x2 %0, %1, %2, %3;" : "=r"(r) : "r"(a), "r"(b), "r"(c)); return r; }
__device__ __forceinline__ __nv_bfloat162 bcast(uint32_t a, int hi) { const __nv_bfloat162 v = *reinterpret_cast<const __nv_bfloat162*>(&a); return hi ? __high2bfloat162(v) : __low2bfloat162(v); }
__device__ __forceinline__ uint32_t hmul2_bc(uint32_t a, int hi, uint32_t b) { const __nv_bfloat162 r = __hmul2_rn(bcast(a, hi), *reinterpret_cast<const __nv_bfloat162*>(&b)); return *reinterpret_cast<const uint32_t*>(&r); }
__device__ __forceinline__ uint32_t hfma2_bc(uint32_t a, int hi, uint32_t b, uint32_t c) {
    const __nv_bfloat162 r = __hfma2(bcast(a, hi), *reinterpret_cast<const __nv_bfloat162*>(&b), *reinterpret_cast<const __nv_bfloat162*>(&c));
    return *reinterpret_cast<const uint32_t*>(&r);
}
__device__ __forceinline__ uint32_t row_elem(uint32_t row) { return ((row >> 5) & 4) | ((row >> 2) & 2) | ((row >> 4) & 1); }
__device__ __forceinline__ uint32_t gate_pos(uint32_t row) { return ((row >> 9) << 8) | ((row & 7) << 5) | (row_elem(row) << 2) | ((row >> 5) & 3); }

template <int N, bool BULK>
__device__ __forceinline__ void mix_rows(const Params& p, const CUtensorMap* tm_out, uint32_t sb, uint32_t ob, int Q0, int Q1, int w, int h, int pr, int lane) {
    const int g = lane >> 2, t = lane & 3, mi = lane >> 3, r = lane & 7;
    const int m8 = 16 * (g >> 2) + ((g >> 1) & 1) + 2 * (g & 1);
    uint32_t yi = sb + (4 * (r >> 1) + 2 * (mi & 1) + (r & 1)) * 512 + (((4 * w + (mi >> 1)) ^ r) << 4);
    uint32_t xs = sb + OFF_S + s_addr(w * S_PL + 32 + m8 * 32, t >> 1) + ((t & 1) << 3);
    uint32_t gs = sb + OFF_GP + w * 64 + g * 8, os = ob + m8 * 32 + t * 8;
    if (N > 1) { yi = pin(yi, lane); xs = pin(xs, lane); gs = pin(gs, lane); os = pin(os, lane); }
    mbar_wait(sb + M_BARS + 8 * B_Y);
#pragma unroll 1
    for (int Q = Q0; Q < Q1; Q++) {
        uint2 xq[N][4];
        uint32_t gg[N][2], sw[N];
#pragma unroll
        for (int n = 0; n < N; n++) {
#pragma unroll
            for (int i = 0; i < 4; i++) xq[n][i] = lds64((xs ^ (((i ^ n) & 1) << 4)) + Q * S_Q + n * 4 * S_PL + i * 128);
            const uint2 gq = lds64(gs + Q * 512 + n * 256);
            sw[n] = lds32(sb + M_BMAP + w * 16 + n * 64 + Q * 4);
            gg[n][0] = gq.x; gg[n][1] = gq.y;
#pragma unroll
            for (int i = 0; i < 4; i++) {
                const uint32_t og = hfma2_bf(gg[n][i >> 1], 0xBF80BF80u, 0x3F803F80u);
                xq[n][i].x = hmul2_bc(og, i & 1, xq[n][i].x); xq[n][i].y = hmul2_bc(og, i & 1, xq[n][i].y);
            }
        }
        mbar_wait(sb + M_BARS + 8 * (B_Y + Q));
        __syncwarp();
#pragma unroll
        for (int n = 0; n < N; n++) {
#pragma unroll
            for (int x = 0; x < 2; x++) {
                uint32_t y[4];
                ldsm4t((yi ^ (x << 5)) + y_off(Q) + n * 256, y[0], y[1], y[2], y[3]);
#pragma unroll
                for (int e = 0; e < 2; e++) {
                    uint2& o = xq[n][2 * x + e];
                    o.x = hfma2_bc(gg[n][x], e, y[2 * e], o.x); o.y = hfma2_bc(gg[n][x], e, y[2 * e + 1], o.y);
                }
            }
        }
        if (BULK && (sw[0] | sw[N - 1]) == 0) {
#pragma unroll
            for (int n = 0; n < N; n++)
#pragma unroll
                for (int i = 0; i < 4; i++)
                    asm volatile("st.shared.v2.u32 [%0], {%1, %2};" :: "r"(os + Q * 1024 + n * 4 * TAB_W + i * 128), "r"(xq[n][i].x), "r"(xq[n][i].y) : "memory");
            asm volatile("fence.proxy.async.shared::cta;" ::: "memory");
            __syncwarp();
#pragma unroll
            for (int n = 0; n < N; n++)
                asm volatile("{\n\t.reg .pred p;\n\telect.sync _|p, 0xffffffff;\n\t"
                             "@p cp.async.bulk.tensor.3d.global.shared::cta.bulk_group [%1, {%2, %3, %4}], [%0];\n\t}"
                    :: "r"(ob + 4 * n * TAB_W + Q * 1024), "l"(tm_out), "r"(16 * pr), "r"(64 * Q + 32 * h), "r"(w + 4 * n) : "memory");
        } else {
            bf16* op = p.out + (size_t)(512 * Q + 256 * h + 8 * m8 + w) * D_ + 16 * pr + 4 * t;
#pragma unroll
            for (int n = 0; n < N; n++)
#pragma unroll
                for (int i = 0; i < 4; i++)
                    if (!((sw[n] >> (4 * g)) & (1u << i))) *(uint2*)(op + (size_t)(32 * i + 4 * n) * D_) = xq[n][i];
        }
    }
}

__global__ void __cluster_dims__(2, 1, 1) __launch_bounds__(NTHREADS, 1)
fused_kernel(const Params p, const __grid_constant__ CUtensorMap tm_gu, const __grid_constant__ CUtensorMap tm_down,
             const __grid_constant__ CUtensorMap tm_x, const __grid_constant__ CUtensorMap tm_out) {
    extern __shared__ __align__(1024) unsigned char smem[];
    const uint32_t sb = smem_u32(smem);
    int tid;
    asm volatile("mov.u32 %0, %%tid.x;" : "=r"(tid));
    const int pw = tid >> 5, lane = tid & 31;
    const int c = blockIdx.x, h = c & 1, pr = c >> 1;
    const uint32_t bars = sb + M_BARS;

    uint2 v_la, v_ai, v_cr, v_ci;
    uint32_t ldt16;
    {
        const uint32_t po = c * 256 + tid;
        asm volatile("{\n\t.reg .pred p;\n\t.reg .b64 a;\n\tsetp.ne.u32 p, %16, 0;\n\t"
                     "mad.wide.u32 a, %14, 8, %9;\n\t@p ld.global.nc.L1::no_allocate.v2.u32 {%0,%1}, [a];\n\t"
                     "mad.wide.u32 a, %15, 2, %13;\n\t@p ld.global.nc.u16 %8, [a];\n\t"
                     "mad.wide.u32 a, %14, 8, %10;\n\t@p ld.global.nc.L1::no_allocate.v2.u32 {%2,%3}, [a];\n\t"
                     "mad.wide.u32 a, %14, 8, %11;\n\t@p ld.global.nc.L1::no_allocate.v2.u32 {%4,%5}, [a];\n\t"
                     "mad.wide.u32 a, %14, 8, %12;\n\t@p ld.global.nc.L1::no_allocate.v2.u32 {%6,%7}, [a];\n\t}"
            : "=r"(v_la.x), "=r"(v_la.y), "=r"(v_ai.x), "=r"(v_ai.y), "=r"(v_cr.x), "=r"(v_cr.y), "=r"(v_ci.x), "=r"(v_ci.y), "=r"(ldt16)
            : "l"(p.logA), "l"(p.Aim), "l"(p.Cre), "l"(p.Cim), "l"(p.logdt), "r"(po), "r"(po >> 5), "r"((uint32_t)(tid < 256 && c < 128)));
    }

    if (c >= 128) {
        if (c != 128) return;
        RSTAMP(5);
        const unsigned tag = (*(volatile unsigned*)&p.sc->epoch + 1) & 0xffffu;
        const uint32_t list = sb + 128;
#pragma unroll 1
        for (int pass = 0; pass < 2; pass++) {
            sts128(list + 16 * tid, 0, 0, 0, 0);
            if (tid == 0) sts32(sb + 64, 0);
            uint32_t key[4] = {tag - 1, tag - 1, tag - 1, tag - 1};
#pragma unroll 1
            for (int it = 0; it < (pass << 22); it++) {
                uint32_t a[4];
                asm volatile("{\n\t.reg .b128 o, z;\n\t.reg .b64 l, u;\n\tmov.b64 l, {%5, %5};\n\tmov.b128 z, {l, l};\n\tatom.relaxed.gpu.global.exch.b128 o, [%4], z;\n\t"
                             "mov.b128 {l, u}, o;\n\tmov.b64 {%0, %1}, l;\n\tmov.b64 {%2, %3}, u;\n\t}"
                    : "=r"(a[0]), "=r"(a[1]), "=r"(a[2]), "=r"(a[3]) : "l"(&p.sc->r[tid]), "r"(tag - 1) : "memory");
#pragma unroll
                for (int i = 0; i < 4; i++) if (((a[i] ^ tag) & 0xffffu) == 0) key[i] = a[i];
                if ((((key[0] ^ tag) | (key[1] ^ tag) | (key[2] ^ tag) | (key[3] ^ tag)) & 0xffffu) == 0) break;
            }
            WSTAMP(0);
            uint32_t m = 0;
#pragma unroll
            for (int i = 0; i < 4; i++) {
                key[i] = ((pass ? key[i] : (lane + i) << 16) & 0xffff0000u) | (uint32_t)(2047 - (4 * tid + i));
                m = max(m, key[i]);
            }
            const uint32_t wm = __reduce_max_sync(0xffffffffu, m);
            if (lane == 0) sts32(sb + pw * 4, wm);
            __syncthreads();
            uint32_t thr = 0xffffffffu;
#pragma unroll
            for (int i = 0; i < 4; i++) { const uint4 q = lds128(sb + 16 * i); thr = min(thr, min(max(q.x, q.y), max(q.z, q.w))); }
            if (thr != 1) WSTAMP(1);
            if (m >= thr) {
                uint32_t pos;
                asm volatile("atom.shared.add.u32 %0, [%1], %2;" : "=r"(pos) : "r"(sb + 64), "r"(4 * ((key[0] >= thr) + (key[1] >= thr) + (key[2] >= thr) + (key[3] >= thr))) : "memory");
#pragma unroll
                for (int i = 0; i < 4; i++) if (key[i] >= thr) { sts32(list + pos, key[i]); pos += 4; }
            }
            __syncthreads();
            const uint32_t nc4 = lds32(sb + 64);
            if (nc4 != 1) WSTAMP(2);
#pragma unroll 1
            for (uint32_t j = 4 * pw; j < nc4; j += 64) {
                const uint32_t mine = lds32(list + j);
                int rank = 0;
#pragma unroll 1
                for (uint32_t i = 0; i < nc4; i += 128) rank += __popc(__ballot_sync(0xffffffffu, lds32(list + i + 4 * lane) > mine));
                if (rank < 8 && lane == 0) sts32(sb + 96 + 4 * rank, mine);
            }
            __syncthreads();
            if (tid < 8 * NTOP) st_gpu32(&p.sc->top[tid >> 3][tid & 7], lds32(sb + 96 + 4 * (tid & 7)) | (((tag + pass - 1) & 31) << 11));
            WSTAMP(3);
            if (!pass) RSTAMP(4);
        }
        WDUMP();
        return;
    }

    WSTAMP(0);
    if (pw < 8) {
        const int d = 8 * c + pw - MAIN_W0;
        if (lane == 0) asm volatile("cp.async.ca.shared.global [%0], [%1], 4;" :: "r"(sb + M_DSK + 4 * (pw - MAIN_W0)), "l"(p.Dskip + (d & ~1)) : "memory");
        asm volatile("barrier.cluster.arrive.relaxed.aligned;" ::: "memory");
        const int warp = pw - MAIN_W0;
        asm volatile("setmaxnreg.inc.sync.aligned.u32 160;");
        const int g = lane >> 2, t = lane & 3;
        const int mi = lane >> 3, r = lane & 7;
        const uint32_t TB = sb + OFF_TAB + warp * TAB_W;
        const uint32_t UB = sb + OFF_U + warp * U_CH;
        if (mi < 2) sts128(UB + mi * U_PL + r * 16, 0, 0, 0, 0);
        if (lane < 4) sts128(TB + lane * T_PL, 0, 0, 0, 0);
        sts128(sb + OFF_SCR + warp * 8192 + lane * 16, 0x3C00u, 0x3C00u, 0x3C00u, 0x3C00u);
        asm volatile("barrier.cluster.wait.acquire.aligned;" ::: "memory");
        __syncwarp();

        uint32_t cfix;
        {
            KSTAMP(4, v_la.x ^ v_ai.x ^ v_cr.x ^ v_ci.x ^ ldt16);
            const float dt = bf_round(exp_acc(__uint_as_float(ldt16 << 16)));
            float l2[4], li[4];
            {
                const uint32_t la[2] = {v_la.x, v_la.y}, ai[2] = {v_ai.x, v_ai.y};
                const float dt2 = -1.4426950408889634f * dt;
#pragma unroll
                for (int i = 0; i < 4; i++) {
                    l2[i] = bf_round(ex2f(((i & 1) ? bf_hi(la[i >> 1]) : bf_lo(la[i >> 1])) * 1.4426950408889634f)) * dt2;
                    li[i] = ((i & 1) ? bf_hi(ai[i >> 1]) : bf_lo(ai[i >> 1])) * dt;
                }
            }
            const uint32_t SX = sb + OFF_SCR + warp * 8192;
            const uint32_t sw = SX + (lane << 4);
#define PUT(buf, row, v) sts128(((sw + (row) * 512) ^ ((row) << 4)) + (buf) * 4096, v[0], v[1], v[2], v[3])
#define EMIT(bufa, rowa, bufb, rowb, xr, xi, k, kp) do { uint32_t pk[4], pd[4]; sched_fence(p.zero, __LINE__); \
                _Pragma("unroll") for (int i = 0; i < 4; i++) { pk[i] = pack_h(xr[i], xi[i]); pd[i] = hcmul(pk[i], k[i], kp[i]); } \
                PUT(bufa, rowa, pk); PUT(bufb, rowb, pd); } while (0)
#define CMUL4(orr, oi, ar, ai, br, bi) _Pragma("unroll") for (int i = 0; i < 4; i++) CMUL(orr[i], oi[i], ar[i], ai[i], br[i], bi[i])
#define CSQ4(orr, oi, ar, ai) _Pragma("unroll") for (int i = 0; i < 4; i++) CSQ(orr[i], oi[i], ar[i], ai[i])
            float z1r[4], z1i[4], z2r[4], z2i[4], z8r[4], z8i[4], z256r[4], z256i[4];
            uint32_t k4[4], k4p[4];
            float z4r[4], z4i[4];
#pragma unroll
            for (int i = 0; i < 4; i++) cexp_pow(l2[i], li[i], 1.f, z1r[i], z1i[i]);
            CSQ4(z2r, z2i, z1r, z1i);
            CSQ4(z4r, z4i, z2r, z2i);
            CSQ4(z8r, z8i, z4r, z4i);
            KSTAMP(5, __float_as_uint(z8r[3]));
            uint32_t Ya[16][4];
            float cr[4], ci[4], inv;
            {
                float w1r[4], w1i[4], ar[4], ai[4], br[4], bi[4];
                uint32_t k8[4], k8p[4];
#pragma unroll
                for (int i = 0; i < 4; i++) {
                    k8[i] = pack_h(z8r[i], -z8i[i]); k8p[i] = pack_h(z8i[i], z8r[i]);
                    CSQ(w1r[i], w1i[i], z8r[i], z8i[i]); w1i[i] = -w1i[i];
                }
                PUT(1, 0, k8);
                EMIT(0, 1, 1, 1, w1r, w1i, k8, k8p);
                CSQ4(ar, ai, w1r, w1i);            EMIT(0, 2, 1, 2, ar, ai, k8, k8p);
                CMUL4(br, bi, ar, ai, w1r, w1i);   EMIT(0, 3, 1, 3, br, bi, k8, k8p);
                CSQ4(ar, ai, ar, ai);              EMIT(0, 4, 1, 4, ar, ai, k8, k8p);
                CMUL4(ar, ai, ar, ai, w1r, w1i);   EMIT(0, 5, 1, 5, ar, ai, k8, k8p);
                CSQ4(br, bi, br, bi);              EMIT(0, 6, 1, 6, br, bi, k8, k8p);
                CMUL4(br, bi, br, bi, w1r, w1i);   EMIT(0, 7, 1, 7, br, bi, k8, k8p);
                __syncwarp();
                KSTAMP(6, 0);
                sched_fence(p.zero, 5);
                const uint32_t ab = SX + (mi & 1) * 4096 + r * 512, ax = ((mi >> 1) ^ r) << 4;
                const uint32_t vr[2] = {v_cr.x, v_cr.y}, vi[2] = {v_ci.x, v_ci.y};
                const uint32_t m2 = __vmaxu2(__vmaxu2(vr[0] & 0x7fff7fffu, vr[1] & 0x7fff7fffu), __vmaxu2(vi[0] & 0x7fff7fffu, vi[1] & 0x7fff7fffu));
                const uint32_t mx = __reduce_max_sync(0xffffffffu, max(m2, m2 << 16));
                const uint32_t e = min(max(mx >> 23, 11u), 254u);
                const float sc = __uint_as_float((264u - e) << 23);
                inv = __uint_as_float((e - 10u) << 23) * (2.f * dt);
#pragma unroll
                for (int i = 0; i < 4; i++) {
#pragma unroll
                    for (int k = 0; k < 4; k++) ldsm4(ab + (ax ^ (i << 5)) + k * 128, Ya[4 * k + i][0], Ya[4 * k + i][1], Ya[4 * k + i][2], Ya[4 * k + i][3]);
                    float tr, ti;
                    cexp_pow(l2[i], li[i], 128.f, tr, ti);
                    sts32(TB + 2176 + 256 * i + 4 * lane, pack_h(tr, ti));
                    sts32(TB + 2176 + 256 * i + 128 + 4 * (lane ^ 16), pack_h(-ti, tr));
                    k4[i] = pack_h(z4r[i], z4i[i]); k4p[i] = pack_h(-z4i[i], z4r[i]);
                    CSQ(z256r[i], z256i[i], tr, ti);
                    cr[i] = ((i & 1) ? bf_hi(vr[i >> 1]) : bf_lo(vr[i >> 1])) * sc;
                    ci[i] = ((i & 1) ? bf_hi(vi[i >> 1]) : bf_lo(vi[i >> 1])) * sc;
                    if (i < 3) sched_fence(p.zero, 8 + i);
                }
                __syncwarp();
            }
            KSTAMP(7, Ya[15][0]);
            const uint32_t ld0 = SX + r * 512 + ((mi ^ r) << 4), ld1 = ld0 ^ 64;
            float R[6][4], s1024;
            {
                float xr[4], xi[4], yr[4], yi[4];
                EMIT(0, 0, 0, 1, cr, ci, k4, k4p);
                CMUL4(yr, yi, cr, ci, z1r, z1i);        EMIT(0, 2, 0, 3, yr, yi, k4, k4p);
                CMUL4(xr, xi, cr, ci, z256r, z256i);    EMIT(1, 0, 1, 1, xr, xi, k4, k4p);
                CMUL4(yr, yi, yr, yi, z1r, z1i);        EMIT(0, 4, 0, 5, yr, yi, k4, k4p);
                CMUL4(cr, ci, yr, yi, z256r, z256i);    EMIT(1, 2, 1, 3, cr, ci, k4, k4p);
                CMUL4(yr, yi, yr, yi, z1r, z1i);        EMIT(0, 6, 0, 7, yr, yi, k4, k4p);
                CMUL4(xr, xi, xr, xi, z256r, z256i);    EMIT(1, 4, 1, 5, xr, xi, k4, k4p);
                CMUL4(xr, xi, xr, xi, z256r, z256i);    EMIT(1, 6, 1, 7, xr, xi, k4, k4p);
                CMUL4(xr, xi, xr, xi, z256r, z256i);
                s1024 = (xr[0] + xr[1]) + (xr[2] + xr[3]);
#pragma unroll
                for (int m = 0; m < 4; m++) {
                    if (m == 0) { CMUL4(xr, xi, xr, xi, z8r, z8i); } else { CMUL4(xr, xi, xr, xi, z256r, z256i); }
                    sched_fence(p.zero, 1 + m);
                    sts128(TB + m * T_PL + 16 + 16 * lane, pack_h(xr[0], xi[0]), pack_h(xr[1], xi[1]), pack_h(xr[2], xi[2]), pack_h(xr[3], xi[3]));
                }
            }
            __syncwarp();
            {
                KSTAMP(8, 0);
                uint32_t bd[2][4] = {{0, 0, 0, 0}, {0, 0, 0, 0}};
                const bool on = (g >> 1) == t;
#pragma unroll
                for (int i = 0; i < 6; i++) { R[i][0] = R[i][1] = R[i][2] = R[i][3] = 0.f; }
                uint32_t x[2][4], y[2][4], z[2][4];
                auto fetch = [&](const int k2) {
                    const int b = k2 & 1;
                    lds128_if(on, TB + 2176 + g * 128 + (k2 < 4 ? 64 : -64) * (g & 1) + 16 * k2, bd[b]);
                    ldsm4(((k2 & 1) ? ld1 : ld0) + (k2 >> 1) * 128, x[b][0], x[b][1], x[b][2], x[b][3]);
                    ldsm4(((k2 & 1) ? ld1 : ld0) + (k2 >> 1) * 128 + 4096, y[b][0], y[b][1], y[b][2], y[b][3]);
                    ldsm4(TB + (r & 3) * T_PL + 16 + 16 * mi + 64 * k2, z[b][0], z[b][1], z[b][2], z[b][3]);
                };
                fetch(0);
#pragma unroll
                for (int k2 = 0; k2 < 8; k2++) {
                    const int b = k2 & 1;
                    uint32_t a1[2][4];
                    if (k2 < 7) fetch(k2 + 1);
#pragma unroll
                    for (int u = 0; u < 2; u++) {
                        mma_hh_k8(a1[u][0], a1[u][1], Ya[2 * k2 + u][0], Ya[2 * k2 + u][1], bd[b][2 * u]);
                        mma_hh_k8(a1[u][2], a1[u][3], Ya[2 * k2 + u][2], Ya[2 * k2 + u][3], bd[b][2 * u + 1]);
                    }
#pragma unroll
                    for (int u = 0; u < 2; u++) {
                        const uint32_t(&a0)[4] = Ya[2 * k2 + u];
                        mma_h(R[0], a0[0], a0[1], a0[2], a0[3], x[b][2 * u], x[b][2 * u + 1]);
                        mma_h(R[2], a0[0], a0[1], a0[2], a0[3], y[b][2 * u], y[b][2 * u + 1]);
                        mma_h(R[4], a0[0], a0[1], a0[2], a0[3], z[b][2 * u], z[b][2 * u + 1]);
                        mma_h(R[1], a1[u][0], a1[u][1], a1[u][2], a1[u][3], x[b][2 * u], x[b][2 * u + 1]);
                        mma_h(R[3], a1[u][0], a1[u][1], a1[u][2], a1[u][3], y[b][2 * u], y[b][2 * u + 1]);
                        mma_h(R[5], a1[u][0], a1[u][1], a1[u][2], a1[u][3], z[b][2 * u], z[b][2 * u + 1]);
                    }
                }
            }
            __syncwarp();
            KSTAMP(9, __float_as_uint(R[3][0]));
            if (lane == 0) mbar_arrive(bars + 8 * B_KG + (__float_as_uint(R[0][0]) & __float_as_uint(R[2][0]) & p.zero));
            sts128(TB + 2176 + 16 * lane, 0, 0, 0, 0);
            sts128(TB + 2688 + 16 * lane, 0, 0, 0, 0);
            __syncwarp();
#undef PUT
#undef EMIT
#pragma unroll
            for (int o = 16; o > 0; o >>= 1) s1024 += __shfl_xor_sync(0xffffffffu, s1024, o);
            uint32_t w[4][4], dsk = 0;
            cp_wait_all();
            asm volatile("{\n\t.reg .pred p;\n\tsetp.eq.u32 p, %2, 0;\n\t@p ld.shared.u16 %0, [%1];\n\t}" : "+r"(dsk) : "r"(sb + M_DSK + 4 * warp + 2 * (warp & 1)), "r"(lane) : "memory");
#pragma unroll
            for (int a = 0; a < 4; a++) {
                const float v0 = (a == 0) ? fmaf(R[0][0], inv, __uint_as_float(dsk << 16)) : R[a][0] * inv;
                const float v1 = R[a][1] * inv, v2 = R[a][2] * inv, v3 = R[a][3] * inv;
                w[a][0] = pack_bf(v0, 0.f); w[a][1] = pack_bf(v1, v0); w[a][2] = pack_bf(v2, v1); w[a][3] = pack_bf(v3, v2);
            }
            const uint32_t wb = TB + 16 + 16 * g, w1 = wb + t * T_PL, w2 = wb + 256 + 2 * t * T_PL;
            const uint32_t w3 = (t == 0) ? wb + 256 + 3 * T_PL : TB + T_A + 8 * (16 * t + g);
            const uint32_t w3s = (t == 0) ? 128 : 64, w3o = (t == 0) ? 8 : 12;
            const uint32_t k512 = __shfl_sync(0xffffffffu, w[2][1], 2);
#pragma unroll
            for (int a = 0; a < 2; a++) {
                sts128(w1 + 128 * a, w[a][0], w[a][1], w[a][2], w[a][3]);
                const uint32_t(&q)[4] = w[2 + a];
                if (t < 2) sts128(w2 + 128 * a, q[0], q[1], q[2], q[3]);
                if (t == 0) { sts128(w2 + T_PL + 128 * a, q[0], q[1], q[2], q[3]); sts32(w3 + 128 * a + 4, q[2]); }
                sts32_if(t != 1 && (a == 1 || lane != 2), w3 + w3s * a, q[1]);
                sts32_if(t != 1, w3 + w3s * a + w3o, q[3]);
            }
            sts128_if(lane < 4, w1 + 512, t == 3 ? k512 : k512 >> 16, t < 2 ? k512 : t == 2 ? k512 & 0xffff0000u : k512 << 16, t < 2 ? k512 << 16 : 0u, 0);
            __syncwarp();
#pragma unroll
            for (int a = 0; a < 2; a++) {
                sts16(w1 + 128 * a + 18, w[a][3]);
                const uint32_t(&q)[4] = w[2 + a];
                if (t < 2) sts16(w2 + 128 * a + 18, q[3]);
                if (t == 0) { sts16(w2 + T_PL + 128 * a + 18, q[3]); sts16(w3 + 128 * a + 14, q[3]); }
            }
            if (t == 0) sts16(w3 + 128 - 4, w[3][0]);
            if (lane == 2 || (t == 0 && g > 0)) sts16(lane == 2 ? TB + 16 + 3 * T_PL + 4 * 127 : w3 - 4, w[2][0]);
            {
                float q[4];
#pragma unroll
                for (int i = 0; i < 4; i++) q[i] = (t < 2 ? R[4][i] : R[5][i]) * inv;
                const uint32_t b0 = pack_bf(q[0], q[2]), b1 = pack_bf(q[1], q[3]);
                const uint32_t wq = TB + T_B + 8 * (65 + 32 * (t & 1) + 4 * (t & 2) + g);
                sts32(wq, b0); sts32(wq + 12, b0); sts32(wq + 128, b1); sts32(wq + 140, b1);
            }
            cfix = pack_bf(s1024 * inv, s1024 * inv);
            if (lane == 0) sts32(TB + T_A + 8 * 64, cfix);
            __syncwarp();
        }
        WSTAMP(1);

        mbar_wait(bars + 8 * B_U);
        WSTAMP(2);

        float D[16][4];
        {
            const int x5 = g - t + 5;
            const uint32_t tabD = TB + (x5 & 3) * T_PL + (x5 & 12) + 16;
            {
                const uint32_t a1 = lds32(tabD - 8), a0 = p.zero;
#pragma unroll
                for (int jq = 0; jq < 4; jq++) {
                    uint32_t b[4];
                    ldsm4(UB + (9 + lane) * 16 + jq * 512, b[0], b[1], b[2], b[3]);
#pragma unroll
                    for (int i = 0; i < 4; i++) mma_bf_k8z(D[4 * jq + i], a0, a1, b[i]);
                }
            }
            const uint32_t ua = UB + (mi & 1) * U_PL + (8 + 8 * (mi >> 1) + r) * 16;
#pragma unroll 1
            for (int k0 = 0; k0 < 8; k0++) {
                uint32_t Uf[16][2];
#pragma unroll
                for (int jp = 0; jp < 8; jp++) ldsm4(ua + jp * 256 - k0 * 16, Uf[2 * jp][0], Uf[2 * jp][1], Uf[2 * jp + 1][0], Uf[2 * jp + 1][1]);
#pragma unroll
                for (int k1 = 0; k1 < 4; k1++) {
                    const uint32_t ta = tabD + 16 * (8 * k1 + k0);
                    const uint32_t a0 = lds32(ta), a1 = lds32(ta + 8), a2 = lds32(ta - 8), a3 = a0 ^ p.zero;
#pragma unroll
                    for (int J = k1; J < 16; J++) mma_bf(D[J], a0, a1, a2, a3, Uf[J - k1][0], Uf[J - k1][1]);
                }
                if (k0 == 0) {
                    const uint32_t ta = tabD + 16 * 32;
                    const uint32_t a0 = lds32(ta), a1 = lds32(ta + 8), a2 = lds32(ta - 8), a3 = a0 ^ p.zero;
#pragma unroll
                    for (int J = 4; J < 16; J++) mma_bf(D[J], a0, a1, a2, a3, Uf[J - 4][0], Uf[J - 4][1]);
                    const uint32_t f0 = (cfix ^ 0x80008000u) & (g == t ? 0xffffu : g == t + 4 ? 0xffff0000u : 0u);
                    const uint32_t f1 = p.zero, f2 = p.zero + p.zero, f3 = f0 ^ p.zero;
#pragma unroll
                    for (int J = 8; J < 16; J++) mma_bf(D[J], f0, f1, f2, f3, Uf[J - 8][0], Uf[J - 8][1]);
                }
            }
        }
        WSTAMP(3);
        {
            const int ch = 8 * h + warp;
            const uint32_t yo = sb + ch * 512 + ((lane ^ (((ch >> 2) << 1) | (ch & 1))) << 4);
            const uint32_t yr = mapa(yo, h ^ 1), ybr = mapa(bars + 8 * B_Y, h ^ 1);
            auto ship = [&](const int Q) {
                uint4 y[2];
#pragma unroll
                for (int hh = 0; hh < 2; hh++) {
                    const int J = 4 * Q + 2 * hh;
                    y[hh] = make_uint4(pack_bf(D[J][0], D[J][1]), pack_bf(D[J][2], D[J][3]), pack_bf(D[J + 1][0], D[J + 1][1]), pack_bf(D[J + 1][2], D[J + 1][3]));
                }
                if (!(Q & 1)) mbar_wait(bars + 8 * (B_F + (Q >> 1)));
                asm volatile("{\n\t.reg .pred p;\n\tsetp.eq.u32 p, %11, 0;\n\t"
                             "@p st.async.weak.shared::cluster.mbarrier::complete_tx::bytes.v4.b32 [%9], {%4,%5,%6,%7}, [%10];\n\t"
                             "@!p st.async.weak.shared::cluster.mbarrier::complete_tx::bytes.v4.b32 [%9], {%0,%1,%2,%3}, [%10];\n\t"
                             "@p st.shared.v4.b32 [%8], {%0,%1,%2,%3};\n\t@!p st.shared.v4.b32 [%8], {%4,%5,%6,%7};\n\t}"
                             :: "r"(y[0].x), "r"(y[0].y), "r"(y[0].z), "r"(y[0].w), "r"(y[1].x), "r"(y[1].y), "r"(y[1].z), "r"(y[1].w),
                                "r"(yo + y_off(Q)), "r"(yr + y_off(Q)), "r"(ybr + 8 * Q), "r"(h) : "memory");
                __syncwarp();
                if (lane == 0) mbar_arrive(bars + 8 * (B_Y + Q));
            };
            ship(0);
            const uint4 bA = lds128(sb + OFF_BAND + (g - t + 3) * 48), bB = lds128(sb + OFF_BAND + (g - t + 3) * 48 + 16);
            const uint2 bC = lds64(sb + OFF_BAND + (g - t + 3) * 48 + 32);
            uint2 QA[5][2], QB[8];
            const uint32_t tq = TB + 8 * (1 + g - 2 * t);
#pragma unroll
            for (int dd = 0; dd < 5; dd++) { QA[dd][0] = lds64(tq + T_A + 64 * (dd + 4)); QA[dd][1] = lds64(tq + T_A + 64 * (dd + 4) - 8); }
#pragma unroll
            for (int dd = 0; dd < 8; dd++) QB[dd] = lds64(tq + T_B + 64 * (dd + 8));
            const uint32_t u1 = UB + (mi & 1) * U_PL + (7 + r + (mi >> 1)) * 16;
            const uint32_t u2 = UB + ((mi & 1) ^ 1) * U_PL + (7 + r + (mi & 1) + 8 * (mi >> 1)) * 16;
            uint32_t n[4];
#pragma unroll
            for (int j = 0; j < 12; j++) {
                uint32_t m[4];
                ldsm4(u1 + j * 128, m[0], m[1], m[2], m[3]);
                if (!(j & 1)) ldsm4(u2 + j * 128, n[0], n[1], n[2], n[3]);
                const uint32_t n0 = n[2 * (j & 1)], n1 = n[2 * (j & 1) + 1];
                float wa[4], wb[4], wc[4], g1[4], g2[4];
                mma_bf_z(wa, bA.x, bA.y, bA.z, bA.w, m[0], m[1]);
                mma_bf_z(wb, bA.x, bA.y, bA.z, bA.w, n0, n1);
                mma_bf_z(wc, bA.x, bA.y, bA.z, bA.w, m[2], m[3]);
                if (j < 8) {
                    mma_bf_z(g1, bB.x, bB.y, bB.z, bB.w, m[0], m[1]);
                    mma_bf_z(g2, bB.x, bB.y, bB.z, bB.w, n0, n1);
                    mma_bf_k8(g1, bC.x, bC.y, m[2]);
                    mma_bf_k8(g2, bC.x, bC.y, m[3]);
                }
#pragma unroll
                for (int e = 0; e < 2; e++) {
                    const uint32_t q0 = pack_bf(wa[e], wa[e + 2]), q1 = pack_bf(wb[e], wb[e + 2]), q2 = q1 ^ p.zero, q3 = pack_bf(wc[e], wc[e + 2]);
#pragma unroll
                    for (int dd = 0; dd < 5; dd++)
                        if (j + 4 + dd < 16) mma_bf(D[j + 4 + dd], q0, q1, q2, q3, QA[dd][e].x, QA[dd][e].y);
                }
                if (j < 8) {
                    const uint32_t q0 = pack_bf(g1[0], g1[2]), q1 = pack_bf(g2[0], g2[2]), q2 = pack_bf(g1[1], g1[3]), q3 = pack_bf(g2[1], g2[3]);
#pragma unroll
                    for (int dd = 7 - j; dd >= 0; dd--) mma_bf(D[j + 8 + dd], q0, q1, q2, q3, QB[dd].x, QB[dd].y);
                }
                if ((j & 3) == 3) {
                    WSTAMP(4 + 2 * (j >> 2));
                    if (j == 11 && LATE2) ship(2);
                    if (j != 7 || !LATE2) ship((j >> 2) + 1);
                }
            }
        }
        const int warpu = __reduce_max_sync(0xffffffffu, warp);
        mix_rows<1, BULKM>(p, &tm_out, sb, sb + OFF_U + warpu * U_CH + (warpu & 1) * 64, PQ, 4, warpu, h, pr, lane);
        if (BULKM) asm volatile("cp.async.bulk.commit_group;\n\tcp.async.bulk.wait_group.read 0;" ::: "memory");
        WSTAMP(10);
        WDUMP();
    } else if ((pw & 12) == AUX_W0) {
        const int v = __reduce_max_sync(0xffffffffu, pw & 3);
        const int at = tid & 127;
        const int g = lane >> 2, t = lane & 3;
        unsigned tag;
        const bool gu = c < NGU_CTA;
        {
            const uint32_t xb = sb + (v < 2 ? OFF_XSEL : OFF_RING + 2 * 8192) + v * 8192;
            const uint32_t gws = sb + M_DPIN;
            const uint32_t row = 16 * c + 4 * v + (g >> 1);
#pragma unroll
            for (int i = 0; i < 8; i++)
                asm volatile("cp.async.ca.shared.global [%0], [%1], 4;" :: "r"((i < 4 ? sb + OFF_GP : gws) + 512 * (i & 3) + (tid & 124) * 4 + (tid & 1) * 8 + (tid & 2) * 2),
                             "l"((i < 4 ? p.wr : p.gatew) + 256 * (i & 3) + (tid & 127) * 2) : "memory");
            if ((tid & 127) < 33) cp16(sb + OFF_BAND + (tid & 127) * 16, p.band + (tid & 127));
            asm volatile("barrier.cluster.arrive.relaxed.aligned;" ::: "memory");
            tag = __reduce_max_sync(0xffffffffu, (*(volatile unsigned*)&p.sc->epoch + 1) & 0xffffu);
            if (gu) st_gpu32((uint32_t*)&p.sc->h[(tag + 1) & 1][32 * c] + at, 0);
            if (v == 2) sts32(sb + M_BMAP + lane * 4, 0);
            if (at == 0) sts32(sb + M_TAG, tag << 16);
            cp_wait_all();
            bar_sync(1, 128);
            uint2 w[16];
#pragma unroll
            for (int kb = 0; kb < 16; kb++) w[kb] = lds64((g < 4 ? sb + OFF_GP : gws) + 128 * kb + 32 * (g & 2) + 16 * t + 8 * (g & 1));
            asm volatile("barrier.cluster.wait.acquire.aligned;" ::: "memory");
            mbar_wait(bars + 8 * (B_X + v));
            WSTAMP(10);
            float dr[4][4];
#pragma unroll
            for (int kb = 0; kb < 16; kb++) {
                const uint4 x = lds128(xb + (g >> 1) * 2048 + 128 * kb + 16 * (lane & 7));
                if (kb < 4) mma_bf_z(dr[kb], x.x, x.y, x.z, x.w, w[kb].x, w[kb].y);
                else mma_bf(dr[kb & 3], x.x, x.y, x.z, x.w, w[kb].x, w[kb].y);
            }
            float rs = ((dr[0][0] + dr[0][3]) + (dr[1][0] + dr[1][3])) + ((dr[2][0] + dr[2][3]) + (dr[3][0] + dr[3][3]));
            if (lane == 0) mbar_arrive(bars + 8 * (B_XE + v) + (__float_as_uint(rs) & p.zero));
            rs += __shfl_xor_sync(0xffffffffu, rs, 5);
            const uint32_t rb = pack_bf(0.f, rs);
            if (!(lane & 7)) st_gpu32((uint32_t*)p.sc->r + row, ((rb ^ (((int)rb >> 31) | 0x80000000u)) & 0xffff0000u) | tag);
            WSTAMP(1);
            {
                const int n = 3 + (lane >> 3) + 4 * (lane & 1);
                const uint32_t so = (n & 7) * S_PL + ((lane & 6) + (n >> 3)) * 32;
                const uint32_t src[2] = {sb + OFF_S + v * S_Q + s_addr(so, h), sb + OFF_S + v * S_Q + s_addr(so + 32, h)};
                const uint32_t dst = sb + OFF_U + g * U_CH + (8 + 32 * v + 16 * h + t) * 16;
                const uint32_t rdst = mapa(dst, h ^ 1), rbar = mapa(bars + 8 * B_U, h ^ 1);
                mbar_wait(bars + 8 * (B_S + v));
                WSTAMP(9);
                uint4 a[8];
#pragma unroll
                for (int b = 0; b < 2; b++) {
#pragma unroll
                    for (int j = 0; j < 8; j++) { const int u = 4 * b + (j >> 1) + 8 * (j & 1); ldsm4t((u < 8 ? src[u & 1] ^ 16 : src[u & 1]) + ((u >> 1) & 3) * 256, a[j].x, a[j].y, a[j].z, a[j].w); }
#pragma unroll
                    for (int j = 0; j < 8; j++) {
                        const int u = 4 * b + (j >> 1) + 8 * (j & 1);
                        if (u < 8) st_async16(rdst + ((u >> 1) & 3) * 64 + (u & 1) * U_PL, a[j], rbar);
                        else sts128(dst + ((u >> 1) & 3) * 64 + (u & 1) * U_PL, a[j].x, a[j].y, a[j].z, a[j].w);
                    }
                }
                if (h && v == 3) {
                    ldsm4t((src[0] ^ 16) + 1024, a[0].x, a[0].y, a[0].z, a[0].w);
                    ldsm4t(src[0] + 1024, a[1].x, a[1].y, a[1].z, a[1].w);
                    if (t == 0) {
                        st_async16(rdst + 256, make_uint4(a[0].x, a[0].y & 0xffffu, a[0].z & 0xffffu, a[0].w & 0xffffu), rbar);
                        sts128(dst + 256, a[1].x, a[1].y & 0xffffu, a[1].z & 0xffffu, a[1].w & 0xffffu);
                    }
                }
                __syncwarp();
                if (lane == 0) mbar_arrive(bars + 8 * B_U);
            }
            if ((lane & 7) == 2) st_gpu32((uint32_t*)p.sc->g + ((row & 256) << 2) + gate_pos(row), pack_bf(sigmoid_f(__uint_as_float(rb)), 0.f) | (tag << 16));
            WSTAMP(2);
        }
        {
            const bool lane0 = pin(lane, lane) == 0;
            const uint32_t own = pin(sb + OFF_XSEL + (at ^ ((at >> 1) & 4)) * 16, lane);
            float acc[8][4];
#pragma unroll
            for (int i = 0; i < 8; i++) { acc[i][0] = acc[i][1] = acc[i][2] = acc[i][3] = 0.f; }
            const int krow = ((lane >> 1) & 8) + (lane & 7);
            const uint32_t tile0 = pin(sb + OFF_RING + krow * 64 + ((((lane >> 3) & 1) ^ ((krow >> 1) & 3)) << 4), lane);
            const uint32_t xo = pin(sb + OFF_XSEL + (lane & 7) * XS_ROW + 512 * v + 2 * (lane & 24), lane);
            const uint32_t po = pin(sb + OFF_XSEL + t * XS_ROW + (g & 3) * 128 + (g & 1) * 64 + v * 16 + (lane >> 4) * 8, lane);
            const uint32_t po1 = pin(po + 64 - (g & 1) * 128, lane);
            uint32_t* hdst = pin((uint32_t*)&p.sc->h[tag & 1][32 * c] + at, lane);
            auto signal = [&](const int k, const uint32_t dep) {
                if (lane < 2 && v < 2)
                    asm volatile("st.async.weak.shared::cluster.mbarrier::complete_tx::bytes.b32 [%0], %1, [%2];"
                                 :: "r"(mapa(sb + M_SINK, lane)), "r"(dep), "r"(mapa(bars + 8 * (B_F + k), lane)) : "memory");
            };
#pragma unroll 1
            for (int i = 0; i < 4; i++) {
                const int s = 4 * i + v;
                uint32_t a[16][4], b[2][4];
                if (gu) {
                    const uint32_t tile = tile0 + (s < 14 ? s : v) * 8192;
                    if (lane0 && i > 1) mbar_arrive(bars + 8 * (B_E + s - 4));
                    if (i == 2) signal(0, 0);
                    mbar_wait(bars + 8 * (B_W + s));
#pragma unroll
                    for (int q = 0; q < 16; q++) ldsm4t((tile ^ ((q & 1) << 5)) + ((q >> 1) & 1) * 4096 + (q >> 2) * 1024, a[q][0], a[q][1], a[q][2], a[q][3]);
                }
                if (i == 0) {
                    if (gu) {
                        uint32_t dep = p.zero;
#pragma unroll
                        for (int q = 0; q < 16; q += 2) dep &= a[q][0] & a[q + 1][0];
                        if (lane == 0) mbar_arrive(bars + 8 * (B_E + v) + dep);
                    }
                    WSTAMP(11);
                    uint32_t top;
#pragma unroll 1
                    for (int it = 0; it < (1 << 22); it++) {
                        asm volatile("ld.relaxed.gpu.global.u32 %0, [%1];" : "=r"(top) : "l"(&p.sc->top[c % NTOP][g]) : "memory");
                        if (__all_sync(0xffffffffu, ((top ^ (tag << 11)) & 0xf800u) == 0)) break;
                        if (TSLEEP) __nanosleep(TSLEEP);
                    }
                    WSTAMP(3);
                    if (gu) {
                        const uint32_t k = 4 * h + v, row = __reduce_max_sync(0xffffffffu, lane == 4 * k ? ~top & 2047 : 0);
                        asm volatile("{\n\t.reg .pred p;\n\telect.sync _|p, 0xffffffff;\n\t"
                                     "@p cp.async.bulk.shared::cluster.global.mbarrier::complete_tx::bytes.multicast::cluster [%0], [%1], 2048, [%2], %3;\n\t}"
                            :: "r"(sb + OFF_XSEL + k * XS_ROW), "l"(p.u + (size_t)row * D_), "r"(bars + 8 * B_G), "h"((unsigned short)3) : "memory");
                    }
                    if (v == 2) {
                        const uint32_t row = ~top & 2047;
                        if (t == 0 && ((row >> 8) & 1) == h)
                            asm volatile("red.shared.or.b32 [%0], %1;" :: "r"(sb + M_BMAP + (row & 7) * 16 + (row >> 9) * 4), "r"(1u << (gate_pos(row) & 31)) : "memory");
                        if (t == 0) sts32(sb + M_TOP + lane, top);
                        if (c == 0 && lane == 0) *(volatile unsigned*)&p.sc->epoch = tag;
                        __syncwarp();
                        if (lane0) mbar_arrive(bars + 8 * B_Y);
                    }
                    if (!gu) break;
                    mbar_wait(bars + 8 * B_G);
                    WSTAMP(4);
                }
                ldsm4(xo + 128 * i, b[0][0], b[0][1], b[0][2], b[0][3]);
                ldsm4(xo + 128 * i + 64, b[1][0], b[1][1], b[1][2], b[1][3]);
#pragma unroll
                for (int q = 0; q < 16; q++) mma_bf(acc[q & 7], a[q][0], a[q][1], a[q][2], a[q][3], b[q >> 3][(q >> 1) & 2], b[q >> 3][((q >> 1) & 2) + 1]);
            }
            if (gu) {
                WSTAMP(5);
                __syncwarp();
#pragma unroll
                for (int q = 0; q < 4; q++) {
                    const int ct = q >> 1, e = 2 * (q & 1);
                    sts128(own + q * XS_ROW,
                           __float_as_uint(acc[ct][e] + acc[4 + ct][e]), __float_as_uint(acc[2 + ct][e] + acc[6 + ct][e]),
                           __float_as_uint(acc[ct][e + 1] + acc[4 + ct][e + 1]), __float_as_uint(acc[2 + ct][e + 1] + acc[6 + ct][e + 1]));
                }
                bar_sync(1, 128);
                float sl[2], uv[2];
#pragma unroll
                for (int e = 0; e < 2; e++) {
                    uint2 q[4];
#pragma unroll
                    for (int i = 0; i < 4; i++) q[i] = lds64((e ? po1 : po) + 512 * i);
                    const float s0 = (__uint_as_float(q[0].x) + __uint_as_float(q[1].x)) + (__uint_as_float(q[2].x) + __uint_as_float(q[3].x));
                    const float s1 = (__uint_as_float(q[0].y) + __uint_as_float(q[1].y)) + (__uint_as_float(q[2].y) + __uint_as_float(q[3].y));
                    const float gv = bf_round(p.gu_swap ? s1 : s0);
                    uv[e] = p.gu_swap ? s0 : s1;
                    sl[e] = gv * sigmoid_f(gv);
                }
                const uint32_t hw = hmul2_bf(pack_bf(sl[0], sl[1]), pack_bf(uv[0], uv[1]));
                st_gpu32(hdst, hw ? hw : 0x80000000u);
                signal(1, hw);
            }
        }
        WSTAMP(6);
        {
            const uint32_t own = pin(sb + OFF_XSEL + at * 16, lane);
            const uint32_t hb = sb + (v < 2 ? OFF_XSEL + 7168 * v : OFF_RING + 8192 * v), hl = pin(hb + 16 * lane, lane);
            const int krow = ((lane >> 1) & 8) + (lane & 7);
            const uint32_t tile = pin(sb + OFF_RING + v * 8192 + krow * 32 + ((((lane >> 3) ^ (krow >> 2)) & 1) << 4), lane);
            float dd[4][4];
            bar_sync(1, 128);
            mbar_wait(bars + 8 * (B_W + HW));
            WSTAMP(12);
            uint4 hq[7];
#pragma unroll 1
            for (int it = 0; it < (1 << 16); it++) {
                bulk_load(hb, &p.sc->h[tag & 1][32 * (56 * h + 14 * v)], 7168, bars + 8 * (B_X + v));
                uint32_t a[14][4], mn = 0xffffffffu;
                mbar_wait(bars + 8 * (B_W + 16 + v));
#pragma unroll
                for (int j = 0; j < 14; j++) ldsm4t(tile + (v & 2) * 16384 + j * 512, a[j][0], a[j][1], a[j][2], a[j][3]);
                mbar_wait(bars + 8 * (B_X + v), ~it & 1);
                WSTAMP(7);
#pragma unroll
                for (int j = 0; j < 7; j++) {
                    const uint4 q = lds128(hl + 512 * j);
                    mn = min(mn, q.x);
#pragma unroll
                    for (int e = 0; e < 2; e++) {
                        const uint32_t(&f)[4] = a[2 * j + e];
                        if (j < 2) mma_bf_z(dd[2 * j + e], f[0], f[1], f[2], f[3], e ? q.z : q.x, e ? q.w : q.y);
                        else mma_bf(dd[(2 * j + e) & 3], f[0], f[1], f[2], f[3], e ? q.z : q.x, e ? q.w : q.y);
                    }
                }
#pragma unroll
                for (int j = 0; j < 7; j++) { hq[j] = lds128(hl + 3584 + 512 * j); mn = min(mn, hq[j].x); }
                if (__all_sync(0xffffffffu, mn != 0)) break;
            }
            mbar_wait(bars + 8 * (B_W + 20 + v));
#pragma unroll
            for (int j = 0; j < 14; j++) {
                uint32_t f[4];
                ldsm4t(tile + 65536 + j * 512, f[0], f[1], f[2], f[3]);
                mma_bf(dd[(j + 2) & 3], f[0], f[1], f[2], f[3], (j & 1) ? hq[j >> 1].z : hq[j >> 1].x, (j & 1) ? hq[j >> 1].w : hq[j >> 1].y);
            }
            WSTAMP(8);
            uint4 part;
            part.x = __float_as_uint((dd[0][0] + dd[1][0]) + (dd[2][0] + dd[3][0])); part.y = __float_as_uint((dd[0][1] + dd[1][1]) + (dd[2][1] + dd[3][1]));
            part.z = __float_as_uint((dd[0][2] + dd[1][2]) + (dd[2][2] + dd[3][2])); part.w = __float_as_uint((dd[0][3] + dd[1][3]) + (dd[2][3] + dd[3][3]));
            st_async16(mapa(own + (M_DPIN - OFF_XSEL), h ^ 1), part, mapa(bars + 8 * B_DP, h ^ 1));
            sts128(own + 14336, part.x, part.y, part.z, part.w);
            __syncwarp();
            if (lane == 0) mbar_arrive(bars + 8 * B_DP);
        }
        WDUMP();
    } else {
        asm volatile("setmaxnreg.dec.sync.aligned.u32 64;");
        const int v = __reduce_max_sync(0xffffffffu, pw - PREP_W0);
        const bool gu = c < NGU_CTA;
        const uint32_t t0 = clock();
        const uint32_t bu = bars + 8 * v;
        if (lane == 0) {
#pragma unroll
            for (int i = 0; i < 10; i++) mbar_init(bu + 32 * i, 1);
            mbar_init(bu + 8 * B_X, 1);
            mbar_init(bu + 8 * B_XE, 1);
            mbar_init(bu + 8 * B_Y, v == 0 ? 11 : 9);
            mbar_init(bu + 8 * B_DP, (0x1855 >> (4 * v)) & 15);
            mbar_init(bu + 8 * B_F, 1);
            mbar_init(bu + 8 * B_H, 1);
            asm volatile("fence.mbarrier_init.release.cluster;" ::: "memory");
            mbar_expect(bu + 8 * B_Y, 4096);
            if (v != 2) mbar_expect(bu + 8 * B_DP, v == 0 ? 2048 : (h || v == 3) ? 16384 : 16384 + 128);
            mbar_expect(bu + 8 * B_F, c < NGU_CTA ? 16 : 0);
        }
        __syncwarp();
        asm volatile("barrier.cluster.arrive.relaxed.aligned;" ::: "memory");
        bulk_load(sb + (v < 2 ? OFF_XSEL : OFF_RING + 2 * 8192) + v * 8192, p.u + (size_t)(16 * c + 4 * v) * D_, 8192, bu + 8 * B_X);
        tma3d(sb + OFF_S + v * S_Q, &tm_x, 16 * pr, 64 * v + 32 * h - 1, bars + 8 * (B_S + v), S_Q);
        WSTAMP(9);
        if (v < 3 && lane == 0) asm volatile("prefetch.tensormap [%0];" :: "l"(v == 0 ? &tm_gu : v == 1 ? &tm_down : &tm_out) : "memory");
        asm volatile("barrier.cluster.wait.acquire.aligned;" ::: "memory");
        uint32_t desc;
        {
            const int s = 6 * v + lane, i = s >> 2, w = s & 3, slot = s < 14 ? s : (s | 1) == 17 ? s - 16 : s - 12;
            const int fb = s < 4 ? B_H : (gu && s >= 14) ? B_E + slot : s < 6 ? B_XE + s - 2 : B_KG;
            desc = slot | (fb << 4) | ((i < 4 ? 256 * w + 64 * i : 1792 * h + 448 * w + 224 * (i - 4)) << 10);
            if (lane < 6) mbar_expect(bars + 8 * (B_W + s), i < 4 ? 8192 : 7168);
            if (tid == 32 * PREP_W0) mbar_arrive(bars + 8 * B_H);
        }
        if (v == 3) {
            mbar_wait(bars + 8 * B_U);
            mbar_wait(bars + 8 * (gu ? B_G : B_H + 2));
            const uint32_t tag16 = lds32(sb + M_TAG);
            uint4 q[8];
#pragma unroll 1
            for (int it = 0; it < (1 << 22); it++) {
                uint32_t bad = 0;
#pragma unroll
                for (int i = 0; i < 8; i++) q[i] = ld_gpu128(&p.sc->g[256 * h + 32 * i + lane]);
#pragma unroll
                for (int i = 0; i < 8; i++) bad |= ((q[i].x ^ tag16) | (q[i].y ^ tag16)) | ((q[i].z ^ tag16) | (q[i].w ^ tag16));
                if ((bad >> 16) == 0) break;
                __nanosleep(200);
            }
#pragma unroll
            for (int i = 0; i < 8; i++)
                asm volatile("st.shared.v2.u32 [%0], {%1, %2};" :: "r"(sb + OFF_GP + 256 * i + lane * 8),
                             "r"(__byte_perm(q[i].x, q[i].y, 0x5410)), "r"(__byte_perm(q[i].z, q[i].w, 0x5410)) : "memory");
            __syncwarp();
            if (lane == 0) mbar_arrive(bars + 8 * B_Y);
        }
        mbar_wait(bars + 8 * (B_H + v));
        {
            const int gap = v == 0 ? GAP : v == 1 ? GAP1 : v == 2 ? GAP2 : GAP3;
            uint32_t last = v ? clock() - SLACK : t0 + T0 - GAP + STAG * ((pr * 5) & 15) / 16;
#pragma unroll 1
            while ((int)(last - clock()) > 500) __nanosleep(256);
#pragma unroll 1
            for (int k = 0; k < 6; k++) {
                const uint32_t dk = __reduce_max_sync(0xffffffffu, lane == k ? desc : 0);
                const bool dn = 6 * v + k >= 16;
                mbar_wait(bars + ((dk >> 1) & 0x1f8));
                uint32_t now;
#pragma unroll 1
                while ((int)((now = clock()) - last) < gap) __nanosleep(CSLEEP);
                last = max((int)(now - last) - SLACK, gap) + last;
                WSTAMP(3 + k);
                if (gu || dn)
                    asm volatile("{\n\t.reg .pred p;\n\telect.sync _|p, 0xffffffff;\n\t"
                                 "@p cp.async.bulk.tensor.3d.shared::cluster.global.mbarrier::complete_tx::bytes [%0], [%1, {%3, %4, 0}], [%2];\n\t}"
                        :: "r"(sb + OFF_RING + (dk & 15) * 8192), "l"(dn ? &tm_down : &tm_gu), "r"(bars + 8 * (B_W + 6 * v + k)), "r"(dn ? 16 * pr : 32 * c), "r"(dk >> 10) : "memory");
                if (k < 5 && PRESLEEP) __nanosleep(PRESLEEP);
            }
            if (lane == 0 && v < 3) mbar_arrive(bars + 8 * (B_H + v + 1));
        }
        {
            WSTAMP(1);
            mix_rows<2, true>(p, &tm_out, sb, sb + OFF_TAB + v * TAB_W, 0, PQ, v, h, pr, lane);
            WSTAMP(2);
            asm volatile("cp.async.bulk.commit_group;" ::: "memory");
            const uint32_t top = lds32(sb + M_TOP + 8 * v + 4 * (lane >> 4));
            const uint32_t row = ~top & 2047, ch = lane & 15, gp = gate_pos(row);
            const bool mine = ((row >> 8) & 1) == h;
            uint32_t gfin, x16, y16 = 0;
            asm volatile("ld.shared.u16 %0, [%1];" : "=r"(gfin) : "r"(sb + OFF_GP + gp * 2) : "memory");
            asm volatile("ld.shared.u16 %0, [%1];" : "=r"(x16) : "r"(sb + OFF_S + (row >> 9) * S_Q + s_addr((row & 7) * S_PL + 32 + (row & 248) * 4, ch >> 3) + 2 * (ch & 7)) : "memory");
            const float rsel = __uint_as_float(pin(__float_as_uint(bf_round(sigmoid_f(__uint_as_float((top ^ (((int)~top >> 31) | 0x80000000u)) & 0xffff0000u)))), lane));
            const uint32_t po = pin(sb + (4 * (ch & 7) + v) * 16 + (ch >> 3) * 8 + (lane >> 4) * 4, lane);
            bf16* op = pin(p.out + (size_t)row * D_ + 16 * pr + ch, lane);
            if (mine) {
                mbar_wait(bars + 8 * (B_Y + (row >> 9)));
                asm volatile("ld.shared.u16 %0, [%1];" : "=r"(y16)
                             : "r"(sb + y_off(row >> 9) + ch * 512 + (((4 * (row & 7) + ((row >> 5) & 3)) ^ (((ch >> 2) << 1) | (ch & 1))) << 4) + 2 * row_elem(row)) : "memory");
            }
            mbar_wait(bars + 8 * B_DP);
            float q[8];
#pragma unroll
            for (int i = 0; i < 4; i++) { q[i] = ldsf(po + M_DPIN + 512 * i); q[4 + i] = ldsf(po + OFF_XSEL + 14336 + 512 * i); }
            const float tot = ((q[0] + q[1]) + (q[2] + q[3])) + ((q[4] + q[5]) + (q[6] + q[7]));
            const float b = bf_round(__uint_as_float(x16 << 16) + bf_round(bf_round(tot) * rsel));
            if (mine) *op = __float2bfloat16_rn(fmaf(bf_lo(gfin), __uint_as_float(y16 << 16), bf_round(bf_round(1.f - bf_lo(gfin)) * b)));
        }
        asm volatile("cp.async.bulk.wait_group.read 0;" ::: "memory");
        WSTAMP(10);
        WDUMP();
    }
}

typedef CUresult (*EncodeFn)(CUtensorMap*, CUtensorMapDataType, cuuint32_t, void*, const cuuint64_t*, const cuuint64_t*,
                             const cuuint32_t*, const cuuint32_t*, CUtensorMapInterleave, CUtensorMapSwizzle,
                             CUtensorMapL2promotion, CUtensorMapFloatOOBfill);

void make_map(EncodeFn f, CUtensorMap* m, const void* ptr, uint64_t cols, uint64_t rows, uint64_t pitch, uint32_t bc, uint32_t br, CUtensorMapSwizzle sw, int prom,
              uint32_t planes = 1, uint64_t plane_stride = 0, uint32_t box_planes = 0) {
    cuuint64_t dims[3] = {cols, rows, planes};
    cuuint64_t str[2] = {pitch, planes > 1 ? plane_stride : pitch * rows};
    cuuint32_t box[3] = {bc, br, box_planes ? box_planes : planes};
    cuuint32_t es[3] = {1, 1, 1};
    f(m, CU_TENSOR_MAP_DATA_TYPE_BFLOAT16, 3, (void*)ptr, dims, str, box, es, CU_TENSOR_MAP_INTERLEAVE_NONE, sw,
      (CUtensorMapL2promotion)prom, CU_TENSOR_MAP_FLOAT_OOB_FILL_NONE);
}

}

extern "C" void kernel_launch(void* const* d_in, const int* in_sizes, int n_in, void* d_out, int out_size) {
    static EncodeFn enc = nullptr;
    static void *sc = nullptr, *band = nullptr;
    if (!enc) {
        void* fn = nullptr;
        cudaDriverEntryPointQueryResult qr;
        cudaGetDriverEntryPoint("cuTensorMapEncodeTiled", &fn, cudaEnableDefault, &qr);
        enc = (EncodeFn)fn;
        cudaGetSymbolAddress(&sc, g_scratch);
        cudaGetSymbolAddress(&band, g_band);
        cudaFuncSetAttribute(fused_kernel, cudaFuncAttributeMaxDynamicSharedMemorySize, SMEM_BYTES);
    }
    CUtensorMap tg, td, tx, to;
    const char *wg = (const char*)d_in[9], *wu = (const char*)d_in[10];
    const bool swap = wu < wg;
    make_map(enc, &tg, swap ? wu : wg, F_, D_, F_ * 2, 32, 64, CU_TENSOR_MAP_SWIZZLE_64B, PROMG, 2, swap ? wg - wu : wu - wg);
    make_map(enc, &td, d_in[11], D_, F_, D_ * 2, 16, 224, CU_TENSOR_MAP_SWIZZLE_32B, PROMD);
    make_map(enc, &tx, d_in[0], D_, L_ / 8, D_ * 16, 16, 33, CU_TENSOR_MAP_SWIZZLE_32B, PROMX, 8, D_ * 2);
    make_map(enc, &to, d_out, D_, L_ / 8, D_ * 16, 16, 32, CU_TENSOR_MAP_SWIZZLE_NONE, 0, 8, D_ * 2, 1);
    Params p;
    p.u = (const bf16*)d_in[0]; p.logA = (const bf16*)d_in[1]; p.Aim = (const bf16*)d_in[2];
    p.Cre = (const bf16*)d_in[3]; p.Cim = (const bf16*)d_in[4]; p.logdt = (const bf16*)d_in[5];
    p.Dskip = (const bf16*)d_in[6]; p.wr = (const bf16*)d_in[8]; p.gatew = (const bf16*)d_in[12];
    p.out = (bf16*)d_out;
    p.sc = (Scratch*)sc; p.band = (const uint4*)band;
    p.gu_swap = swap;
    p.zero = 0;
    fused_kernel<<<NCTA, NTHREADS, SMEM_BYTES>>>(p, tg, td, tx, to);
}
```

```cpp
#include <cuda_runtime.h>
#include <cuda_bf16.h>
#include <cuda_fp16.h>
#include <cuda.h>
#include <stdint.h>

typedef __nv_bfloat16 bf16;

namespace {

constexpr int L_ = 2048, D_ = 1024, F_ = 3584;
constexpr int NCTA = 130;
constexpr int NTHREADS = 512;
constexpr int MAIN_W0 = 0, PREP_W0 = 8, AUX_W0 = 12;
#define T0 3000
#define GAP 540
#define GAP1 530
#define GAP2 530
#define GAP3 550
#define HW 20
constexpr int SLACK = 300;
constexpr int PQ = 3;
constexpr int NGU_CTA = 112;

constexpr int OFF_RING = 0;
constexpr int OFF_SCR  = 6 * 8192;
constexpr int S_PL     = 1056;
constexpr int S_Q      = 8 * S_PL;
constexpr int OFF_S    = 114688;
constexpr int OFF_GP   = OFF_S + 4 * S_Q;
constexpr int U_PL     = 2240;
constexpr int U_CH     = 4416;
constexpr int OFF_U    = 151552;
constexpr int TAB_W    = 3200;
constexpr int T_PL     = 544;
constexpr int T_A      = 2192 - 26 * 8;
constexpr int T_B      = 2568 - 59 * 8;
constexpr int OFF_TAB  = 186880;
constexpr int OFF_XSEL = 212480;
constexpr int XS_ROW   = 2064;
constexpr int OFF_BAND = 228992;
constexpr int OFF_MISC = 229536;
constexpr int M_BARS   = OFF_MISC;
constexpr int M_DSK    = OFF_MISC + 2736;
constexpr int M_SINK   = OFF_MISC + 512;
constexpr int M_TAG    = OFF_MISC + 516;
constexpr int M_BMAP   = OFF_MISC + 528;
constexpr int M_DPIN   = OFF_MISC + 656;
constexpr int M_TOP    = OFF_MISC + 2704;
constexpr int SMEM_BYTES = OFF_MISC + 2768;
__device__ __forceinline__ uint32_t s_addr(uint32_t o, uint32_t half) { return o + (((half ^ (o >> 7)) & 1) << 4); }
__host__ __device__ constexpr uint32_t y_off(uint32_t q) { return OFF_RING + 32768 + (q & 1) * 8192 + (q >> 1) * 65536; }

constexpr int B_W = 0;
constexpr int B_E = 24;
constexpr int B_S = 36;
constexpr int B_Y = 40;
constexpr int B_DP = 44, B_U = 45, B_KG = 46, B_G = 47;
constexpr int B_F = 48;
constexpr int B_H = 60;
constexpr int B_X = 52, B_XE = 56;

struct BandTab { uint32_t w[11][12]; };
constexpr BandTab make_band() {
    BandTab b{};
    for (int cls = 0; cls < 11; cls++)
        for (int wd = 0; wd < 10; wd++) {
            const int tau = cls + 2 - 8 * ((wd < 4 ? wd : wd - 4) >> 1);
            const int lo = (wd < 4) ? ((wd & 1) ? -2 : 3) : ((wd & 1) ? -4 : -11), wid = (wd < 4 ? 3 : 7) + 2 * (wd & 1);
            b.w[cls][wd] = ((tau >= lo && tau < lo + wid) ? 0x3F80u : 0u) | ((tau - 4 >= lo && tau - 4 < lo + wid) ? 0x3F800000u : 0u);
        }
    return b;
}
constexpr int NTOP = 32;
struct Scratch {
    uint4 r[L_ / 4];
    uint4 g[L_ / 4];
    uint4 h[2][8 * F_ / 8];
    uint32_t top[NTOP][32];
    unsigned epoch;
};
__device__ __align__(128) Scratch g_scratch;
__device__ const __align__(16) BandTab g_band = make_band();

struct Params {
    const bf16 *u, *logA, *Aim, *Cre, *Cim, *logdt, *Dskip, *wr, *gatew;
    bf16* out;
    Scratch* sc;
    const uint4* band;
    uint32_t gu_swap;
    uint32_t zero;
};

#define WSTAMP(i) do {} while (0)
#define KSTAMP(i, dep) do {} while (0)
#define WDUMP() do {} while (0)
#define RSTAMP(i) do {} while (0)

__device__ __forceinline__ uint32_t smem_u32(const void* p) { return (uint32_t)__cvta_generic_to_shared(p); }
__device__ __forceinline__ void mbar_init(uint32_t b, uint32_t c) { asm volatile("mbarrier.init.shared::cta.b64 [%0], %1;" :: "r"(b), "r"(c) : "memory"); }
__device__ __forceinline__ void mbar_expect(uint32_t b, uint32_t tx) { asm volatile("mbarrier.arrive.expect_tx.shared::cta.b64 _, [%0], %1;" :: "r"(b), "r"(tx) : "memory"); }
__device__ __forceinline__ void mbar_arrive(uint32_t b) { asm volatile("mbarrier.arrive.shared::cta.b64 _, [%0];" :: "r"(b) : "memory"); }
__device__ __forceinline__ void mbar_wait(uint32_t b, uint32_t parity = 0) {
    asm volatile("{\n\t.reg .pred p;\nW%=:\n\tmbarrier.try_wait.parity.shared::cta.b64 p, [%0], %1, 20000;\n\t@!p bra W%=;\n\t}" :: "r"(b), "r"(parity) : "memory");
}
__device__ __forceinline__ uint32_t mapa(uint32_t addr, uint32_t rank) { uint32_t r; asm("mapa.shared::cluster.u32 %0, %1, %2;" : "=r"(r) : "r"(addr), "r"(rank)); return r; }
__device__ __forceinline__ void tma3d(uint32_t dst, const CUtensorMap* tm, int c0, int c1, uint32_t bar, uint32_t bytes) {
    asm volatile("{\n\t.reg .pred p;\n\telect.sync _|p, 0xffffffff;\n\t"
                 "@p mbarrier.arrive.expect_tx.shared::cta.b64 _, [%2], %5;\n\t"
                 "@p cp.async.bulk.tensor.3d.shared::cluster.global.mbarrier::complete_tx::bytes [%0], [%1, {%3, %4, 0}], [%2];\n\t}"
        :: "r"(dst), "l"(tm), "r"(bar), "r"(c0), "r"(c1), "r"(bytes) : "memory");
}
__device__ __forceinline__ void bulk_load(uint32_t dst, const void* src, uint32_t bytes, uint32_t bar) {
    asm volatile("{\n\t.reg .pred p;\n\telect.sync _|p, 0xffffffff;\n\t"
                 "@p mbarrier.arrive.expect_tx.shared::cta.b64 _, [%2], %3;\n\t"
                 "@p cp.async.bulk.shared::cluster.global.mbarrier::complete_tx::bytes [%0], [%1], %3, [%2];\n\t}"
        :: "r"(dst), "l"(src), "r"(bar), "r"(bytes) : "memory");
}
__device__ __forceinline__ void st_async16(uint32_t dst, const uint4& v, uint32_t bar) {
    asm volatile("st.async.weak.shared::cluster.mbarrier::complete_tx::bytes.v4.b32 [%0], {%1,%2,%3,%4}, [%5];"
                 :: "r"(dst), "r"(v.x), "r"(v.y), "r"(v.z), "r"(v.w), "r"(bar) : "memory");
}
__device__ __forceinline__ void bar_sync(int id, int n) { asm volatile("bar.sync %0, %1;" :: "r"(id), "r"(n) : "memory"); }
__device__ __forceinline__ void cp16(uint32_t dst, const void* src) { asm volatile("cp.async.cg.shared.global [%0], [%1], 16;" :: "r"(dst), "l"(src) : "memory"); }
__device__ __forceinline__ void cp_wait_all() { asm volatile("cp.async.wait_all;" ::: "memory"); }
__device__ __forceinline__ uint4 ld_gpu128(const void* p) { uint4 v; asm volatile("ld.relaxed.gpu.global.v4.u32 {%0,%1,%2,%3}, [%4];" : "=r"(v.x), "=r"(v.y), "=r"(v.z), "=r"(v.w) : "l"(p) : "memory"); return v; }
__device__ __forceinline__ void st_gpu32(void* p, uint32_t v) { asm volatile("st.relaxed.gpu.global.u32 [%0], %1;" :: "l"(p), "r"(v) : "memory"); }

__device__ __forceinline__ void ldsm4(uint32_t a, uint32_t& r0, uint32_t& r1, uint32_t& r2, uint32_t& r3) {
    asm volatile("ldmatrix.sync.aligned.m8n8.x4.shared.b16 {%0,%1,%2,%3}, [%4];" : "=r"(r0), "=r"(r1), "=r"(r2), "=r"(r3) : "r"(a) : "memory");
}
__device__ __forceinline__ void ldsm4t(uint32_t a, uint32_t& r0, uint32_t& r1, uint32_t& r2, uint32_t& r3) {
    asm volatile("ldmatrix.sync.aligned.m8n8.x4.trans.shared.b16 {%0,%1,%2,%3}, [%4];" : "=r"(r0), "=r"(r1), "=r"(r2), "=r"(r3) : "r"(a) : "memory");
}
__device__ __forceinline__ uint32_t lds32(uint32_t a) { uint32_t v; asm volatile("ld.shared.u32 %0, [%1];" : "=r"(v) : "r"(a) : "memory"); return v; }
__device__ __forceinline__ uint2 lds64(uint32_t a) { uint2 v; asm volatile("ld.shared.v2.u32 {%0,%1}, [%2];" : "=r"(v.x), "=r"(v.y) : "r"(a) : "memory"); return v; }
__device__ __forceinline__ uint4 lds128(uint32_t a) { uint4 v; asm volatile("ld.shared.v4.u32 {%0,%1,%2,%3}, [%4];" : "=r"(v.x), "=r"(v.y), "=r"(v.z), "=r"(v.w) : "r"(a) : "memory"); return v; }
__device__ __forceinline__ void sts32(uint32_t a, uint32_t v) { asm volatile("st.shared.u32 [%0], %1;" :: "r"(a), "r"(v) : "memory"); }
__device__ __forceinline__ void sts16(uint32_t a, uint32_t v) { asm volatile("st.shared.u16 [%0], %1;" :: "r"(a), "h"((unsigned short)v) : "memory"); }
__device__ __forceinline__ void sts128(uint32_t a, uint32_t x, uint32_t y, uint32_t z, uint32_t w) { asm volatile("st.shared.v4.u32 [%0], {%1,%2,%3,%4};" :: "r"(a), "r"(x), "r"(y), "r"(z), "r"(w) : "memory"); }
__device__ __forceinline__ float ldsf(uint32_t a) { float v; asm volatile("ld.shared.f32 %0, [%1];" : "=f"(v) : "r"(a) : "memory"); return v; }

__device__ __forceinline__ void mma_bf(float (&d)[4], uint32_t a0, uint32_t a1, uint32_t a2, uint32_t a3, uint32_t b0, uint32_t b1) {
    asm volatile("mma.sync.aligned.m16n8k16.row.col.f32.bf16.bf16.f32 {%0,%1,%2,%3}, {%4,%5,%6,%7}, {%8,%9}, {%0,%1,%2,%3};"
        : "+f"(d[0]), "+f"(d[1]), "+f"(d[2]), "+f"(d[3]) : "r"(a0), "r"(a1), "r"(a2), "r"(a3), "r"(b0), "r"(b1));
}
__device__ __forceinline__ void mma_bf_z(float (&d)[4], uint32_t a0, uint32_t a1, uint32_t a2, uint32_t a3, uint32_t b0, uint32_t b1) {
    asm volatile("mma.sync.aligned.m16n8k16.row.col.f32.bf16.bf16.f32 {%0,%1,%2,%3}, {%4,%5,%6,%7}, {%8,%9}, {%10,%10,%10,%10};"
        : "=f"(d[0]), "=f"(d[1]), "=f"(d[2]), "=f"(d[3]) : "r"(a0), "r"(a1), "r"(a2), "r"(a3), "r"(b0), "r"(b1), "f"(0.f));
}
__device__ __forceinline__ void mma_bf_k8(float (&d)[4], uint32_t a0, uint32_t a1, uint32_t b0) {
    asm volatile("mma.sync.aligned.m16n8k8.row.col.f32.bf16.bf16.f32 {%0,%1,%2,%3}, {%4,%5}, {%6}, {%0,%1,%2,%3};"
        : "+f"(d[0]), "+f"(d[1]), "+f"(d[2]), "+f"(d[3]) : "r"(a0), "r"(a1), "r"(b0));
}
__device__ __forceinline__ void mma_h(float (&d)[4], uint32_t a0, uint32_t a1, uint32_t a2, uint32_t a3, uint32_t b0, uint32_t b1) {
    asm volatile("mma.sync.aligned.m16n8k16.row.col.f32.f16.f16.f32 {%0,%1,%2,%3}, {%4,%5,%6,%7}, {%8,%9}, {%0,%1,%2,%3};"
        : "+f"(d[0]), "+f"(d[1]), "+f"(d[2]), "+f"(d[3]) : "r"(a0), "r"(a1), "r"(a2), "r"(a3), "r"(b0), "r"(b1));
}
__device__ __forceinline__ uint32_t pack_bf(float lo, float hi) { uint32_t r; asm("cvt.rn.bf16x2.f32 %0, %1, %2;" : "=r"(r) : "f"(hi), "f"(lo)); return r; }
__device__ __forceinline__ uint32_t pack_h(float lo, float hi) { uint32_t r; asm("cvt.rn.f16x2.f32 %0, %1, %2;" : "=r"(r) : "f"(hi), "f"(lo)); return r; }
__device__ __forceinline__ float bf_lo(uint32_t v) { return __uint_as_float(v << 16); }
__device__ __forceinline__ float bf_hi(uint32_t v) { return __uint_as_float(v & 0xffff0000u); }
__device__ __forceinline__ float bf_round(float x) { return __uint_as_float(pack_bf(0.f, x)); }
__device__ __forceinline__ uint32_t hmul2_bf(uint32_t a, uint32_t b) { uint32_t r; asm("mul.rn.bf16x2 %0, %1, %2;" : "=r"(r) : "r"(a), "r"(b)); return r; }
__device__ __forceinline__ float ex2f(float x) { float r; asm("ex2.approx.ftz.f32 %0, %1;" : "=f"(r) : "f"(x)); return r; }

__device__ __forceinline__ float exp_acc(float x) {
    const float t = x * 1.4426950216293335f;
    const float r = fmaf(x, 1.4426950216293335f, -t) + x * 1.9259629911266175e-8f;
    return ex2f(t) * fmaf(r, 0.6931471805599453f, 1.f);
}
__device__ __forceinline__ float sigmoid_f(float x) { return __fdividef(1.f, 1.f + ex2f(-x * 1.4426950408889634f)); }
__device__ __forceinline__ void cexp_pow(float l2, float li, float e, float& zr, float& zi) {
    const float mag = ex2f(l2 * e);
    zr = mag * __cosf(li * e);
    zi = mag * __sinf(li * e);
}
__device__ __forceinline__ uint32_t hcmul(uint32_t a, uint32_t k, uint32_t kp) {
    const __half2 A = *reinterpret_cast<const __half2*>(&a);
    const __half2 r = __hfma2(__high2half2(A), *reinterpret_cast<const __half2*>(&kp), __hmul2(__low2half2(A), *reinterpret_cast<const __half2*>(&k)));
    return *reinterpret_cast<const uint32_t*>(&r);
}
#define CMUL(orr, oi, ar, ai, br, bi) do { float _r = (ar) * (br) - (ai) * (bi); float _i = (ar) * (bi) + (ai) * (br); orr = _r; oi = _i; } while (0)
#define CSQ(orr, oi, ar, ai) do { float _r = (ar) * (ar) - (ai) * (ai); float _i = 2.f * (ar) * (ai); orr = _r; oi = _i; } while (0)

__device__ __forceinline__ void mma_bf_k8z(float (&d)[4], uint32_t a0, uint32_t a1, uint32_t b0) {
    asm volatile("mma.sync.aligned.m16n8k8.row.col.f32.bf16.bf16.f32 {%0,%1,%2,%3}, {%4,%5}, {%6}, {%7,%7,%7,%7};"
        : "=f"(d[0]), "=f"(d[1]), "=f"(d[2]), "=f"(d[3]) : "r"(a0), "r"(a1), "r"(b0), "f"(0.f));
}
__device__ __forceinline__ void mma_hh_k8(uint32_t& d0, uint32_t& d1, uint32_t a0, uint32_t a1, uint32_t b0) {
    asm volatile("mma.sync.aligned.m16n8k8.row.col.f16.f16.f16.f16 {%0,%1}, {%2,%3}, {%4}, {%5,%5};"
        : "=r"(d0), "=r"(d1) : "r"(a0), "r"(a1), "r"(b0), "r"(0));
}
__device__ __forceinline__ void sched_fence(uint32_t zero, uint32_t id) {
    asm volatile("{\n\t.reg .pred p;\n\tsetp.eq.u32 p, %0, %1;\n\t@p exit;\n\t}" :: "r"(zero), "r"(id) : "memory");
}
__device__ __forceinline__ uint32_t pin(uint32_t x, int lane) { return __shfl_sync(0xffffffffu, x, lane); }
template <class T> __device__ __forceinline__ T* pin(T* x, int lane) { return (T*)__shfl_sync(0xffffffffu, (unsigned long long)x, lane); }
__device__ __forceinline__ void sts32_if(bool on, uint32_t a, uint32_t v) {
    asm volatile("{\n\t.reg .pred p;\n\tsetp.ne.u32 p, %2, 0;\n\t@p st.shared.u32 [%0], %1;\n\t}" :: "r"(a), "r"(v), "r"((uint32_t)on) : "memory");
}
__device__ __forceinline__ void sts128_if(bool on, uint32_t a, uint32_t x, uint32_t y, uint32_t z, uint32_t w) {
    asm volatile("{\n\t.reg .pred p;\n\tsetp.ne.u32 p, %5, 0;\n\t@p st.shared.v4.u32 [%0], {%1,%2,%3,%4};\n\t}" :: "r"(a), "r"(x), "r"(y), "r"(z), "r"(w), "r"((uint32_t)on) : "memory");
}
__device__ __forceinline__ void lds128_if(bool on, uint32_t a, uint32_t (&v)[4]) {
    asm volatile("{\n\t.reg .pred p;\n\tsetp.ne.u32 p, %5, 0;\n\t@p ld.shared.v4.u32 {%0,%1,%2,%3}, [%4];\n\t}"
        : "+r"(v[0]), "+r"(v[1]), "+r"(v[2]), "+r"(v[3]) : "r"(a), "r"((uint32_t)on) : "memory");
}
__device__ __forceinline__ uint32_t hfma2_bf(uint32_t a, uint32_t b, uint32_t c) { uint32_t r; asm("fma.rn.bf16x2 %0, %1, %2, %3;" : "=r"(r) : "r"(a), "r"(b), "r"(c)); return r; }
__device__ __forceinline__ __nv_bfloat162 bcast(uint32_t a, int hi) { const __nv_bfloat162 v = *reinterpret_cast<const __nv_bfloat162*>(&a); return hi ? __high2bfloat162(v) : __low2bfloat162(v); }
__device__ __forceinline__ uint32_t hmul2_bc(uint32_t a, int hi, uint32_t b) { const __nv_bfloat162 r = __hmul2_rn(bcast(a, hi), *reinterpret_cast<const __nv_bfloat162*>(&b)); return *reinterpret_cast<const uint32_t*>(&r); }
__device__ __forceinline__ uint32_t hfma2_bc(uint32_t a, int hi, uint32_t b, uint32_t c) {
    const __nv_bfloat162 r = __hfma2(bcast(a, hi), *reinterpret_cast<const __nv_bfloat162*>(&b), *reinterpret_cast<const __nv_bfloat162*>(&c));
    return *reinterpret_cast<const uint32_t*>(&r);
}
__device__ __forceinline__ uint32_t row_elem(uint32_t row) { return ((row >> 5) & 4) | ((row >> 2) & 2) | ((row >> 4) & 1); }
__device__ __forceinline__ uint32_t gate_pos(uint32_t row) { return ((row >> 9) << 8) | ((row & 7) << 5) | (row_elem(row) << 2) | ((row >> 5) & 3); }

template <int N>
__device__ __forceinline__ void mix_rows(const Params& p, const CUtensorMap* tm_out, uint32_t sb, uint32_t ob, int Q0, int Q1, int w, int h, int pr, int lane) {
    const int g = lane >> 2, t = lane & 3, mi = lane >> 3, r = lane & 7;
    const int m8 = 16 * (g >> 2) + ((g >> 1) & 1) + 2 * (g & 1);
    uint32_t yi = sb + (4 * (r >> 1) + 2 * (mi & 1) + (r & 1)) * 512 + (((4 * w + (mi >> 1)) ^ r) << 4);
    uint32_t xs = sb + OFF_S + s_addr(w * S_PL + 32 + m8 * 32, t >> 1) + ((t & 1) << 3);
    uint32_t gs = sb + OFF_GP + w * 64 + g * 8, os = ob + m8 * 32 + t * 8;
    if (N > 1) { yi = pin(yi, lane); xs = pin(xs, lane); gs = pin(gs, lane); os = pin(os, lane); }
    mbar_wait(sb + M_BARS + 8 * B_Y);
#pragma unroll 1
    for (int Q = Q0; Q < Q1; Q++) {
        uint2 xq[N][4];
        uint32_t gg[N][2], sw[N];
#pragma unroll
        for (int n = 0; n < N; n++) {
#pragma unroll
            for (int i = 0; i < 4; i++) xq[n][i] = lds64((xs ^ (((i ^ n) & 1) << 4)) + Q * S_Q + n * 4 * S_PL + i * 128);
            const uint2 gq = lds64(gs + Q * 512 + n * 256);
            sw[n] = lds32(sb + M_BMAP + w * 16 + n * 64 + Q * 4);
            gg[n][0] = gq.x; gg[n][1] = gq.y;
#pragma unroll
            for (int i = 0; i < 4; i++) {
                const uint32_t og = hfma2_bf(gg[n][i >> 1], 0xBF80BF80u, 0x3F803F80u);
                xq[n][i].x = hmul2_bc(og, i & 1, xq[n][i].x); xq[n][i].y = hmul2_bc(og, i & 1, xq[n][i].y);
            }
        }
        mbar_wait(sb + M_BARS + 8 * (B_Y + Q));
        __syncwarp();
#pragma unroll
        for (int n = 0; n < N; n++) {
#pragma unroll
            for (int x = 0; x < 2; x++) {
                uint32_t y[4];
                ldsm4t((yi ^ (x << 5)) + y_off(Q) + n * 256, y[0], y[1], y[2], y[3]);
#pragma unroll
                for (int e = 0; e < 2; e++) {
                    uint2& o = xq[n][2 * x + e];
                    o.x = hfma2_bc(gg[n][x], e, y[2 * e], o.x); o.y = hfma2_bc(gg[n][x], e, y[2 * e + 1], o.y);
                }
            }
        }
        if ((sw[0] | sw[N - 1]) == 0) {
#pragma unroll
            for (int n = 0; n < N; n++)
#pragma unroll
                for (int i = 0; i < 4; i++)
                    asm volatile("st.shared.v2.u32 [%0], {%1, %2};" :: "r"(os + Q * 1024 + n * 4 * TAB_W + i * 128), "r"(xq[n][i].x), "r"(xq[n][i].y) : "memory");
            asm volatile("fence.proxy.async.shared::cta;" ::: "memory");
            __syncwarp();
#pragma unroll
            for (int n = 0; n < N; n++)
                asm volatile("{\n\t.reg .pred p;\n\telect.sync _|p, 0xffffffff;\n\t"
                             "@p cp.async.bulk.tensor.3d.global.shared::cta.bulk_group [%1, {%2, %3, %4}], [%0];\n\t}"
                    :: "r"(ob + 4 * n * TAB_W + Q * 1024), "l"(tm_out), "r"(16 * pr), "r"(64 * Q + 32 * h), "r"(w + 4 * n) : "memory");
        } else {
            bf16* op = p.out + (size_t)(512 * Q + 256 * h + 8 * m8 + w) * D_ + 16 * pr + 4 * t;
#pragma unroll
            for (int n = 0; n < N; n++)
#pragma unroll
                for (int i = 0; i < 4; i++)
                    if (!((sw[n] >> (4 * g)) & (1u << i))) *(uint2*)(op + (size_t)(32 * i + 4 * n) * D_) = xq[n][i];
        }
    }
}

__global__ void __cluster_dims__(2, 1, 1) __launch_bounds__(NTHREADS, 1)
fused_kernel(const Params p, const __grid_constant__ CUtensorMap tm_gu, const __grid_constant__ CUtensorMap tm_down,
             const __grid_constant__ CUtensorMap tm_x, const __grid_constant__ CUtensorMap tm_out) {
    extern __shared__ __align__(1024) unsigned char smem[];
    const uint32_t sb = smem_u32(smem);
    int tid;
    asm volatile("mov.u32 %0, %%tid.x;" : "=r"(tid));
    const int pw = tid >> 5, lane = tid & 31;
    const int c = blockIdx.x, h = c & 1, pr = c >> 1;
    const uint32_t bars = sb + M_BARS;

    uint2 v_la, v_ai, v_cr, v_ci;
    uint32_t ldt16;
    {
        const uint32_t po = c * 256 + tid;
        asm volatile("{\n\t.reg .pred p;\n\t.reg .b64 a;\n\tsetp.ne.u32 p, %16, 0;\n\t"
                     "mad.wide.u32 a, %14, 8, %9;\n\t@p ld.global.nc.L1::no_allocate.v2.u32 {%0,%1}, [a];\n\t"
                     "mad.wide.u32 a, %15, 2, %13;\n\t@p ld.global.nc.u16 %8, [a];\n\t"
                     "mad.wide.u32 a, %14, 8, %10;\n\t@p ld.global.nc.L1::no_allocate.v2.u32 {%2,%3}, [a];\n\t"
                     "mad.wide.u32 a, %14, 8, %11;\n\t@p ld.global.nc.L1::no_allocate.v2.u32 {%4,%5}, [a];\n\t"
                     "mad.wide.u32 a, %14, 8, %12;\n\t@p ld.global.nc.L1::no_allocate.v2.u32 {%6,%7}, [a];\n\t}"
            : "=r"(v_la.x), "=r"(v_la.y), "=r"(v_ai.x), "=r"(v_ai.y), "=r"(v_cr.x), "=r"(v_cr.y), "=r"(v_ci.x), "=r"(v_ci.y), "=r"(ldt16)
            : "l"(p.logA), "l"(p.Aim), "l"(p.Cre), "l"(p.Cim), "l"(p.logdt), "r"(po), "r"(po >> 5), "r"((uint32_t)(tid < 256 && c < 128)));
    }

    if (c >= 128) {
        if (c != 128) return;
        RSTAMP(5);
        const unsigned tag = (*(volatile unsigned*)&p.sc->epoch + 1) & 0xffffu;
        const uint32_t list = sb + 128;
        sts128(list + 16 * tid, 0, 0, 0, 0);
        if (tid == 0) sts32(sb + 64, 0);
        uint32_t key[4] = {tag - 1, tag - 1, tag - 1, tag - 1};
#pragma unroll 1
        for (int it = 0; it < (1 << 22); it++) {
            uint32_t a[4];
            asm volatile("{\n\t.reg .b128 o, z;\n\t.reg .b64 l, u;\n\tmov.b64 l, {%5, %5};\n\tmov.b128 z, {l, l};\n\tatom.relaxed.gpu.global.exch.b128 o, [%4], z;\n\t"
                         "mov.b128 {l, u}, o;\n\tmov.b64 {%0, %1}, l;\n\tmov.b64 {%2, %3}, u;\n\t}"
                : "=r"(a[0]), "=r"(a[1]), "=r"(a[2]), "=r"(a[3]) : "l"(&p.sc->r[tid]), "r"(tag - 1) : "memory");
#pragma unroll
            for (int i = 0; i < 4; i++) if (((a[i] ^ tag) & 0xffffu) == 0) key[i] = a[i];
            if ((((key[0] ^ tag) | (key[1] ^ tag) | (key[2] ^ tag) | (key[3] ^ tag)) & 0xffffu) == 0) break;
        }
        WSTAMP(0);
        uint32_t m = 0;
#pragma unroll
        for (int i = 0; i < 4; i++) {
            key[i] = (key[i] & 0xffff0000u) | (uint32_t)(2047 - (4 * tid + i));
            m = max(m, key[i]);
        }
        const uint32_t wm = __reduce_max_sync(0xffffffffu, m);
        if (lane == 0) sts32(sb + pw * 4, wm);
        __syncthreads();
        uint32_t thr = 0xffffffffu;
#pragma unroll
        for (int i = 0; i < 4; i++) { const uint4 q = lds128(sb + 16 * i); thr = min(thr, min(max(q.x, q.y), max(q.z, q.w))); }
        if (thr != 1) WSTAMP(1);
        if (m >= thr) {
            uint32_t pos;
            asm volatile("atom.shared.add.u32 %0, [%1], %2;" : "=r"(pos) : "r"(sb + 64), "r"(4 * ((key[0] >= thr) + (key[1] >= thr) + (key[2] >= thr) + (key[3] >= thr))) : "memory");
#pragma unroll
            for (int i = 0; i < 4; i++) if (key[i] >= thr) { sts32(list + pos, key[i]); pos += 4; }
        }
        __syncthreads();
        const uint32_t nc4 = lds32(sb + 64);
        if (nc4 != 1) WSTAMP(2);
#pragma unroll 1
        for (uint32_t j = 4 * pw; j < nc4; j += 64) {
            const uint32_t mine = lds32(list + j);
            int rank = 0;
#pragma unroll 1
            for (uint32_t i = 0; i < nc4; i += 128) rank += __popc(__ballot_sync(0xffffffffu, lds32(list + i + 4 * lane) > mine));
            if (rank < 8 && lane == 0) sts32(sb + 96 + 4 * rank, mine);
        }
        __syncthreads();
        if (tid < 8 * NTOP) st_gpu32(&p.sc->top[tid >> 3][tid & 7], lds32(sb + 96 + 4 * (tid & 7)) | ((tag & 31) << 11));
        WSTAMP(3);
        WDUMP();
        return;
    }

    WSTAMP(0);
    if (pw < 8) {
        const int d = 8 * c + pw - MAIN_W0;
        if (lane == 0) asm volatile("cp.async.ca.shared.global [%0], [%1], 4;" :: "r"(sb + M_DSK + 4 * (pw - MAIN_W0)), "l"(p.Dskip + (d & ~1)) : "memory");
        asm volatile("barrier.cluster.arrive.relaxed.aligned;" ::: "memory");
        const int warp = pw - MAIN_W0;
        asm volatile("setmaxnreg.inc.sync.aligned.u32 160;");
        const int g = lane >> 2, t = lane & 3;
        const int mi = lane >> 3, r = lane & 7;
        const uint32_t TB = sb + OFF_TAB + warp * TAB_W;
        const uint32_t UB = sb + OFF_U + warp * U_CH;
        if (mi < 2) sts128(UB + mi * U_PL + r * 16, 0, 0, 0, 0);
        if (lane < 4) sts128(TB + lane * T_PL, 0, 0, 0, 0);
        sts128(sb + OFF_SCR + warp * 8192 + lane * 16, 0x3C00u, 0x3C00u, 0x3C00u, 0x3C00u);
        asm volatile("barrier.cluster.wait.acquire.aligned;" ::: "memory");
        __syncwarp();

        uint32_t cfix;
        {
            KSTAMP(4, v_la.x ^ v_ai.x ^ v_cr.x ^ v_ci.x ^ ldt16);
            const float dt = bf_round(exp_acc(__uint_as_float(ldt16 << 16)));
            float l2[4], li[4];
            {
                const uint32_t la[2] = {v_la.x, v_la.y}, ai[2] = {v_ai.x, v_ai.y};
                const float dt2 = -1.4426950408889634f * dt;
#pragma unroll
                for (int i = 0; i < 4; i++) {
                    l2[i] = bf_round(ex2f(((i & 1) ? bf_hi(la[i >> 1]) : bf_lo(la[i >> 1])) * 1.4426950408889634f)) * dt2;
                    li[i] = ((i & 1) ? bf_hi(ai[i >> 1]) : bf_lo(ai[i >> 1])) * dt;
                }
            }
            const uint32_t SX = sb + OFF_SCR + warp * 8192;
            const uint32_t sw = SX + (lane << 4);
#define PUT(buf, row, v) sts128(((sw + (row) * 512) ^ ((row) << 4)) + (buf) * 4096, v[0], v[1], v[2], v[3])
#define EMIT(bufa, rowa, bufb, rowb, xr, xi, k, kp) do { uint32_t pk[4], pd[4]; sched_fence(p.zero, __LINE__); \
                _Pragma("unroll") for (int i = 0; i < 4; i++) { pk[i] = pack_h(xr[i], xi[i]); pd[i] = hcmul(pk[i], k[i], kp[i]); } \
                PUT(bufa, rowa, pk); PUT(bufb, rowb, pd); } while (0)
#define CMUL4(orr, oi, ar, ai, br, bi) _Pragma("unroll") for (int i = 0; i < 4; i++) CMUL(orr[i], oi[i], ar[i], ai[i], br[i], bi[i])
#define CSQ4(orr, oi, ar, ai) _Pragma("unroll") for (int i = 0; i < 4; i++) CSQ(orr[i], oi[i], ar[i], ai[i])
            float z1r[4], z1i[4], z2r[4], z2i[4], z8r[4], z8i[4], z256r[4], z256i[4];
            uint32_t k4[4], k4p[4];
            float z4r[4], z4i[4];
#pragma unroll
            for (int i = 0; i < 4; i++) cexp_pow(l2[i], li[i], 1.f, z1r[i], z1i[i]);
            CSQ4(z2r, z2i, z1r, z1i);
            CSQ4(z4r, z4i, z2r, z2i);
            CSQ4(z8r, z8i, z4r, z4i);
            KSTAMP(5, __float_as_uint(z8r[3]));
            uint32_t Ya[16][4];
            float cr[4], ci[4], inv;
            {
                float w1r[4], w1i[4], ar[4], ai[4], br[4], bi[4];
                uint32_t k8[4], k8p[4];
#pragma unroll
                for (int i = 0; i < 4; i++) {
                    k8[i] = pack_h(z8r[i], -z8i[i]); k8p[i] = pack_h(z8i[i], z8r[i]);
                    CSQ(w1r[i], w1i[i], z8r[i], z8i[i]); w1i[i] = -w1i[i];
                }
                PUT(1, 0, k8);
                EMIT(0, 1, 1, 1, w1r, w1i, k8, k8p);
                CSQ4(ar, ai, w1r, w1i);            EMIT(0, 2, 1, 2, ar, ai, k8, k8p);
                CMUL4(br, bi, ar, ai, w1r, w1i);   EMIT(0, 3, 1, 3, br, bi, k8, k8p);
                CSQ4(ar, ai, ar, ai);              EMIT(0, 4, 1, 4, ar, ai, k8, k8p);
                CMUL4(ar, ai, ar, ai, w1r, w1i);   EMIT(0, 5, 1, 5, ar, ai, k8, k8p);
                CSQ4(br, bi, br, bi);              EMIT(0, 6, 1, 6, br, bi, k8, k8p);
                CMUL4(br, bi, br, bi, w1r, w1i);   EMIT(0, 7, 1, 7, br, bi, k8, k8p);
                __syncwarp();
                KSTAMP(6, 0);
                sched_fence(p.zero, 5);
                const uint32_t ab = SX + (mi & 1) * 4096 + r * 512, ax = ((mi >> 1) ^ r) << 4;
                const uint32_t vr[2] = {v_cr.x, v_cr.y}, vi[2] = {v_ci.x, v_ci.y};
                const uint32_t m2 = __vmaxu2(__vmaxu2(vr[0] & 0x7fff7fffu, vr[1] & 0x7fff7fffu), __vmaxu2(vi[0] & 0x7fff7fffu, vi[1] & 0x7fff7fffu));
                const uint32_t mx = __reduce_max_sync(0xffffffffu, max(m2, m2 << 16));
                const uint32_t e = min(max(mx >> 23, 11u), 254u);
                const float sc = __uint_as_float((264u - e) << 23);
                inv = __uint_as_float((e - 10u) << 23) * (2.f * dt);
#pragma unroll
                for (int i = 0; i < 4; i++) {
#pragma unroll
                    for (int k = 0; k < 4; k++) ldsm4(ab + (ax ^ (i << 5)) + k * 128, Ya[4 * k + i][0], Ya[4 * k + i][1], Ya[4 * k + i][2], Ya[4 * k + i][3]);
                    float tr, ti;
                    cexp_pow(l2[i], li[i], 128.f, tr, ti);
                    sts32(TB + 2176 + 256 * i + 4 * lane, pack_h(tr, ti));
                    sts32(TB + 2176 + 256 * i + 128 + 4 * (lane ^ 16), pack_h(-ti, tr));
                    k4[i] = pack_h(z4r[i], z4i[i]); k4p[i] = pack_h(-z4i[i], z4r[i]);
                    CSQ(z256r[i], z256i[i], tr, ti);
                    cr[i] = ((i & 1) ? bf_hi(vr[i >> 1]) : bf_lo(vr[i >> 1])) * sc;
                    ci[i] = ((i & 1) ? bf_hi(vi[i >> 1]) : bf_lo(vi[i >> 1])) * sc;
                    if (i < 3) sched_fence(p.zero, 8 + i);
                }
                __syncwarp();
            }
            KSTAMP(7, Ya[15][0]);
            const uint32_t ld0 = SX + r * 512 + ((mi ^ r) << 4), ld1 = ld0 ^ 64;
            float R[6][4], s1024;
            {
                float xr[4], xi[4], yr[4], yi[4];
                EMIT(0, 0, 0, 1, cr, ci, k4, k4p);
                CMUL4(yr, yi, cr, ci, z1r, z1i);        EMIT(0, 2, 0, 3, yr, yi, k4, k4p);
                CMUL4(xr, xi, cr, ci, z256r, z256i);    EMIT(1, 0, 1, 1, xr, xi, k4, k4p);
                CMUL4(yr, yi, yr, yi, z1r, z1i);        EMIT(0, 4, 0, 5, yr, yi, k4, k4p);
                CMUL4(cr, ci, yr, yi, z256r, z256i);    EMIT(1, 2, 1, 3, cr, ci, k4, k4p);
                CMUL4(yr, yi, yr, yi, z1r, z1i);        EMIT(0, 6, 0, 7, yr, yi, k4, k4p);
                CMUL4(xr, xi, xr, xi, z256r, z256i);    EMIT(1, 4, 1, 5, xr, xi, k4, k4p);
                CMUL4(xr, xi, xr, xi, z256r, z256i);    EMIT(1, 6, 1, 7, xr, xi, k4, k4p);
                CMUL4(xr, xi, xr, xi, z256r, z256i);
                s1024 = (xr[0] + xr[1]) + (xr[2] + xr[3]);
#pragma unroll
                for (int m = 0; m < 4; m++) {
                    if (m == 0) { CMUL4(xr, xi, xr, xi, z8r, z8i); } else { CMUL4(xr, xi, xr, xi, z256r, z256i); }
                    sched_fence(p.zero, 1 + m);
                    sts128(TB + m * T_PL + 16 + 16 * lane, pack_h(xr[0], xi[0]), pack_h(xr[1], xi[1]), pack_h(xr[2], xi[2]), pack_h(xr[3], xi[3]));
                }
            }
            __syncwarp();
            {
                KSTAMP(8, 0);
                uint32_t bd[2][4] = {{0, 0, 0, 0}, {0, 0, 0, 0}};
                const bool on = (g >> 1) == t;
#pragma unroll
                for (int i = 0; i < 6; i++) { R[i][0] = R[i][1] = R[i][2] = R[i][3] = 0.f; }
                uint32_t x[2][4], y[2][4], z[2][4];
                auto fetch = [&](const int k2) {
                    const int b = k2 & 1;
                    lds128_if(on, TB + 2176 + g * 128 + (k2 < 4 ? 64 : -64) * (g & 1) + 16 * k2, bd[b]);
                    ldsm4(((k2 & 1) ? ld1 : ld0) + (k2 >> 1) * 128, x[b][0], x[b][1], x[b][2], x[b][3]);
                    ldsm4(((k2 & 1) ? ld1 : ld0) + (k2 >> 1) * 128 + 4096, y[b][0], y[b][1], y[b][2], y[b][3]);
                    ldsm4(TB + (r & 3) * T_PL + 16 + 16 * mi + 64 * k2, z[b][0], z[b][1], z[b][2], z[b][3]);
                };
                fetch(0);
#pragma unroll
                for (int k2 = 0; k2 < 8; k2++) {
                    const int b = k2 & 1;
                    uint32_t a1[2][4];
                    if (k2 < 7) fetch(k2 + 1);
#pragma unroll
                    for (int u = 0; u < 2; u++) {
                        mma_hh_k8(a1[u][0], a1[u][1], Ya[2 * k2 + u][0], Ya[2 * k2 + u][1], bd[b][2 * u]);
                        mma_hh_k8(a1[u][2], a1[u][3], Ya[2 * k2 + u][2], Ya[2 * k2 + u][3], bd[b][2 * u + 1]);
                    }
#pragma unroll
                    for (int u = 0; u < 2; u++) {
                        const uint32_t(&a0)[4] = Ya[2 * k2 + u];
                        mma_h(R[0], a0[0], a0[1], a0[2], a0[3], x[b][2 * u], x[b][2 * u + 1]);
                        mma_h(R[2], a0[0], a0[1], a0[2], a0[3], y[b][2 * u], y[b][2 * u + 1]);
                        mma_h(R[4], a0[0], a0[1], a0[2], a0[3], z[b][2 * u], z[b][2 * u + 1]);
                        mma_h(R[1], a1[u][0], a1[u][1], a1[u][2], a1[u][3], x[b][2 * u], x[b][2 * u + 1]);
                        mma_h(R[3], a1[u][0], a1[u][1], a1[u][2], a1[u][3], y[b][2 * u], y[b][2 * u + 1]);
                        mma_h(R[5], a1[u][0], a1[u][1], a1[u][2], a1[u][3], z[b][2 * u], z[b][2 * u + 1]);
                    }
                }
            }
            __syncwarp();
            KSTAMP(9, __float_as_uint(R[3][0]));
            if (lane == 0) mbar_arrive(bars + 8 * B_KG + (__float_as_uint(R[0][0]) & __float_as_uint(R[2][0]) & p.zero));
            sts128(TB + 2176 + 16 * lane, 0, 0, 0, 0);
            sts128(TB + 2688 + 16 * lane, 0, 0, 0, 0);
            __syncwarp();
#undef PUT
#undef EMIT
#pragma unroll
            for (int o = 16; o > 0; o >>= 1) s1024 += __shfl_xor_sync(0xffffffffu, s1024, o);
            uint32_t w[4][4], dsk = 0;
            cp_wait_all();
            asm volatile("{\n\t.reg .pred p;\n\tsetp.eq.u32 p, %2, 0;\n\t@p ld.shared.u16 %0, [%1];\n\t}" : "+r"(dsk) : "r"(sb + M_DSK + 4 * warp + 2 * (warp & 1)), "r"(lane) : "memory");
#pragma unroll
            for (int a = 0; a < 4; a++) {
                const float v0 = (a == 0) ? fmaf(R[0][0], inv, __uint_as_float(dsk << 16)) : R[a][0] * inv;
                const float v1 = R[a][1] * inv, v2 = R[a][2] * inv, v3 = R[a][3] * inv;
                w[a][0] = pack_bf(v0, 0.f); w[a][1] = pack_bf(v1, v0); w[a][2] = pack_bf(v2, v1); w[a][3] = pack_bf(v3, v2);
            }
            const uint32_t wb = TB + 16 + 16 * g, w1 = wb + t * T_PL, w2 = wb + 256 + 2 * t * T_PL;
            const uint32_t w3 = (t == 0) ? wb + 256 + 3 * T_PL : TB + T_A + 8 * (16 * t + g);
            const uint32_t w3s = (t == 0) ? 128 : 64, w3o = (t == 0) ? 8 : 12;
            const uint32_t k512 = __shfl_sync(0xffffffffu, w[2][1], 2);
#pragma unroll
            for (int a = 0; a < 2; a++) {
                sts128(w1 + 128 * a, w[a][0], w[a][1], w[a][2], w[a][3]);
                const uint32_t(&q)[4] = w[2 + a];
                if (t < 2) sts128(w2 + 128 * a, q[0], q[1], q[2], q[3]);
                if (t == 0) { sts128(w2 + T_PL + 128 * a, q[0], q[1], q[2], q[3]); sts32(w3 + 128 * a + 4, q[2]); }
                sts32_if(t != 1 && (a == 1 || lane != 2), w3 + w3s * a, q[1]);
                sts32_if(t != 1, w3 + w3s * a + w3o, q[3]);
            }
            sts128_if(lane < 4, w1 + 512, t == 3 ? k512 : k512 >> 16, t < 2 ? k512 : t == 2 ? k512 & 0xffff0000u : k512 << 16, t < 2 ? k512 << 16 : 0u, 0);
            __syncwarp();
#pragma unroll
            for (int a = 0; a < 2; a++) {
                sts16(w1 + 128 * a + 18, w[a][3]);
                const uint32_t(&q)[4] = w[2 + a];
                if (t < 2) sts16(w2 + 128 * a + 18, q[3]);
                if (t == 0) { sts16(w2 + T_PL + 128 * a + 18, q[3]); sts16(w3 + 128 * a + 14, q[3]); }
            }
            if (t == 0) sts16(w3 + 128 - 4, w[3][0]);
            if (lane == 2 || (t == 0 && g > 0)) sts16(lane == 2 ? TB + 16 + 3 * T_PL + 4 * 127 : w3 - 4, w[2][0]);
            {
                float q[4];
#pragma unroll
                for (int i = 0; i < 4; i++) q[i] = (t < 2 ? R[4][i] : R[5][i]) * inv;
                const uint32_t b0 = pack_bf(q[0], q[2]), b1 = pack_bf(q[1], q[3]);
                const uint32_t wq = TB + T_B + 8 * (65 + 32 * (t & 1) + 4 * (t & 2) + g);
                sts32(wq, b0); sts32(wq + 12, b0); sts32(wq + 128, b1); sts32(wq + 140, b1);
            }
            cfix = pack_bf(s1024 * inv, s1024 * inv);
            if (lane == 0) sts32(TB + T_A + 8 * 64, cfix);
            __syncwarp();
        }
        WSTAMP(1);

        mbar_wait(bars + 8 * B_U);
        WSTAMP(2);

        float D[16][4];
        {
            const int x5 = g - t + 5;
            const uint32_t tabD = TB + (x5 & 3) * T_PL + (x5 & 12) + 16;
            {
                const uint32_t a1 = lds32(tabD - 8), a0 = p.zero;
#pragma unroll
                for (int jq = 0; jq < 4; jq++) {
                    uint32_t b[4];
                    ldsm4(UB + (9 + lane) * 16 + jq * 512, b[0], b[1], b[2], b[3]);
#pragma unroll
                    for (int i = 0; i < 4; i++) mma_bf_k8z(D[4 * jq + i], a0, a1, b[i]);
                }
            }
            const uint32_t ua = UB + (mi & 1) * U_PL + (8 + 8 * (mi >> 1) + r) * 16;
#pragma unroll 1
            for (int k0 = 0; k0 < 8; k0++) {
                uint32_t Uf[16][2];
#pragma unroll
                for (int jp = 0; jp < 8; jp++) ldsm4(ua + jp * 256 - k0 * 16, Uf[2 * jp][0], Uf[2 * jp][1], Uf[2 * jp + 1][0], Uf[2 * jp + 1][1]);
#pragma unroll
                for (int k1 = 0; k1 < 4; k1++) {
                    const uint32_t ta = tabD + 16 * (8 * k1 + k0);
                    const uint32_t a0 = lds32(ta), a1 = lds32(ta + 8), a2 = lds32(ta - 8), a3 = a0 ^ p.zero;
#pragma unroll
                    for (int J = k1; J < 16; J++) mma_bf(D[J], a0, a1, a2, a3, Uf[J - k1][0], Uf[J - k1][1]);
                }
                if (k0 == 0) {
                    const uint32_t ta = tabD + 16 * 32;
                    const uint32_t a0 = lds32(ta), a1 = lds32(ta + 8), a2 = lds32(ta - 8), a3 = a0 ^ p.zero;
#pragma unroll
                    for (int J = 4; J < 16; J++) mma_bf(D[J], a0, a1, a2, a3, Uf[J - 4][0], Uf[J - 4][1]);
                    const uint32_t f0 = (cfix ^ 0x80008000u) & (g == t ? 0xffffu : g == t + 4 ? 0xffff0000u : 0u);
                    const uint32_t f1 = p.zero, f2 = p.zero + p.zero, f3 = f0 ^ p.zero;
#pragma unroll
                    for (int J = 8; J < 16; J++) mma_bf(D[J], f0, f1, f2, f3, Uf[J - 8][0], Uf[J - 8][1]);
                }
            }
        }
        WSTAMP(3);
        {
            const int ch = 8 * h + warp;
            const uint32_t yo = sb + ch * 512 + ((lane ^ (((ch >> 2) << 1) | (ch & 1))) << 4);
            const uint32_t yr = mapa(yo, h ^ 1), ybr = mapa(bars + 8 * B_Y, h ^ 1);
            auto ship = [&](const int Q) {
                uint4 y[2];
#pragma unroll
                for (int hh = 0; hh < 2; hh++) {
                    const int J = 4 * Q + 2 * hh;
                    y[hh] = make_uint4(pack_bf(D[J][0], D[J][1]), pack_bf(D[J][2], D[J][3]), pack_bf(D[J + 1][0], D[J + 1][1]), pack_bf(D[J + 1][2], D[J + 1][3]));
                }
                if (!(Q & 1)) mbar_wait(bars + 8 * (B_F + (Q >> 1)));
                asm volatile("{\n\t.reg .pred p;\n\tsetp.eq.u32 p, %11, 0;\n\t"
                             "@p st.async.weak.shared::cluster.mbarrier::complete_tx::bytes.v4.b32 [%9], {%4,%5,%6,%7}, [%10];\n\t"
                             "@!p st.async.weak.shared::cluster.mbarrier::complete_tx::bytes.v4.b32 [%9], {%0,%1,%2,%3}, [%10];\n\t"
                             "@p st.shared.v4.b32 [%8], {%0,%1,%2,%3};\n\t@!p st.shared.v4.b32 [%8], {%4,%5,%6,%7};\n\t}"
                             :: "r"(y[0].x), "r"(y[0].y), "r"(y[0].z), "r"(y[0].w), "r"(y[1].x), "r"(y[1].y), "r"(y[1].z), "r"(y[1].w),
                                "r"(yo + y_off(Q)), "r"(yr + y_off(Q)), "r"(ybr + 8 * Q), "r"(h) : "memory");
                __syncwarp();
                if (lane == 0) mbar_arrive(bars + 8 * (B_Y + Q));
            };
            ship(0);
            const uint4 bA = lds128(sb + OFF_BAND + (g - t + 3) * 48), bB = lds128(sb + OFF_BAND + (g - t + 3) * 48 + 16);
            const uint2 bC = lds64(sb + OFF_BAND + (g - t + 3) * 48 + 32);
            uint2 QA[5][2], QB[8];
            const uint32_t tq = TB + 8 * (1 + g - 2 * t);
#pragma unroll
            for (int dd = 0; dd < 5; dd++) { QA[dd][0] = lds64(tq + T_A + 64 * (dd + 4)); QA[dd][1] = lds64(tq + T_A + 64 * (dd + 4) - 8); }
#pragma unroll
            for (int dd = 0; dd < 8; dd++) QB[dd] = lds64(tq + T_B + 64 * (dd + 8));
            const uint32_t u1 = UB + (mi & 1) * U_PL + (7 + r + (mi >> 1)) * 16;
            const uint32_t u2 = UB + ((mi & 1) ^ 1) * U_PL + (7 + r + (mi & 1) + 8 * (mi >> 1)) * 16;
            uint32_t n[4];
#pragma unroll
            for (int j = 0; j < 12; j++) {
                uint32_t m[4];
                ldsm4(u1 + j * 128, m[0], m[1], m[2], m[3]);
                if (!(j & 1)) ldsm4(u2 + j * 128, n[0], n[1], n[2], n[3]);
                const uint32_t n0 = n[2 * (j & 1)], n1 = n[2 * (j & 1) + 1];
                float wa[4], wb[4], wc[4], g1[4], g2[4];
                mma_bf_z(wa, bA.x, bA.y, bA.z, bA.w, m[0], m[1]);
                mma_bf_z(wb, bA.x, bA.y, bA.z, bA.w, n0, n1);
                mma_bf_z(wc, bA.x, bA.y, bA.z, bA.w, m[2], m[3]);
                if (j < 8) {
                    mma_bf_z(g1, bB.x, bB.y, bB.z, bB.w, m[0], m[1]);
                    mma_bf_z(g2, bB.x, bB.y, bB.z, bB.w, n0, n1);
                    mma_bf_k8(g1, bC.x, bC.y, m[2]);
                    mma_bf_k8(g2, bC.x, bC.y, m[3]);
                }
#pragma unroll
                for (int e = 0; e < 2; e++) {
                    const uint32_t q0 = pack_bf(wa[e], wa[e + 2]), q1 = pack_bf(wb[e], wb[e + 2]), q2 = q1 ^ p.zero, q3 = pack_bf(wc[e], wc[e + 2]);
#pragma unroll
                    for (int dd = 0; dd < 5; dd++)
                        if (j + 4 + dd < 16) mma_bf(D[j + 4 + dd], q0, q1, q2, q3, QA[dd][e].x, QA[dd][e].y);
                }
                if (j < 8) {
                    const uint32_t q0 = pack_bf(g1[0], g1[2]), q1 = pack_bf(g2[0], g2[2]), q2 = pack_bf(g1[1], g1[3]), q3 = pack_bf(g2[1], g2[3]);
#pragma unroll
                    for (int dd = 7 - j; dd >= 0; dd--) mma_bf(D[j + 8 + dd], q0, q1, q2, q3, QB[dd].x, QB[dd].y);
                }
                if ((j & 3) == 3) {
                    WSTAMP(4 + 2 * (j >> 2));
                    ship((j >> 2) + 1);
                }
            }
        }
        const int warpu = __reduce_max_sync(0xffffffffu, warp);
        mix_rows<1>(p, &tm_out, sb, sb + OFF_U + warpu * U_CH + (warpu & 1) * 64, PQ, 4, warpu, h, pr, lane);
        asm volatile("cp.async.bulk.commit_group;\n\tcp.async.bulk.wait_group.read 0;" ::: "memory");
        WSTAMP(10);
        WDUMP();
    } else if ((pw & 12) == AUX_W0) {
        const int v = __reduce_max_sync(0xffffffffu, pw & 3);
        const int at = tid & 127;
        const int g = lane >> 2, t = lane & 3;
        unsigned tag;
        const bool gu = c < NGU_CTA;
        {
            const uint32_t xb = sb + (v < 2 ? OFF_XSEL : OFF_RING + 2 * 8192) + v * 8192;
            const uint32_t gws = sb + M_DPIN;
            const uint32_t row = 16 * c + 4 * v + (g >> 1);
#pragma unroll
            for (int i = 0; i < 8; i++)
                asm volatile("cp.async.ca.shared.global [%0], [%1], 4;" :: "r"((i < 4 ? sb + OFF_GP : gws) + 512 * (i & 3) + (tid & 124) * 4 + (tid & 1) * 8 + (tid & 2) * 2),
                             "l"((i < 4 ? p.wr : p.gatew) + 256 * (i & 3) + (tid & 127) * 2) : "memory");
            if ((tid & 127) < 33) cp16(sb + OFF_BAND + (tid & 127) * 16, p.band + (tid & 127));
            asm volatile("barrier.cluster.arrive.relaxed.aligned;" ::: "memory");
            tag = __reduce_max_sync(0xffffffffu, (*(volatile unsigned*)&p.sc->epoch + 1) & 0xffffu);
            if (gu) st_gpu32((uint32_t*)&p.sc->h[(tag + 1) & 1][32 * c] + at, 0);
            if (v == 2) sts32(sb + M_BMAP + lane * 4, 0);
            if (at == 0) sts32(sb + M_TAG, tag << 16);
            cp_wait_all();
            bar_sync(1, 128);
            uint2 w[16];
#pragma unroll
            for (int kb = 0; kb < 16; kb++) w[kb] = lds64((g < 4 ? sb + OFF_GP : gws) + 128 * kb + 32 * (g & 2) + 16 * t + 8 * (g & 1));
            asm volatile("barrier.cluster.wait.acquire.aligned;" ::: "memory");
            mbar_wait(bars + 8 * (B_X + v));
            WSTAMP(10);
            float dr[4][4];
#pragma unroll
            for (int kb = 0; kb < 16; kb++) {
                const uint4 x = lds128(xb + (g >> 1) * 2048 + 128 * kb + 16 * (lane & 7));
                if (kb < 4) mma_bf_z(dr[kb], x.x, x.y, x.z, x.w, w[kb].x, w[kb].y);
                else mma_bf(dr[kb & 3], x.x, x.y, x.z, x.w, w[kb].x, w[kb].y);
            }
            float rs = ((dr[0][0] + dr[0][3]) + (dr[1][0] + dr[1][3])) + ((dr[2][0] + dr[2][3]) + (dr[3][0] + dr[3][3]));
            if (lane == 0) mbar_arrive(bars + 8 * (B_XE + v) + (__float_as_uint(rs) & p.zero));
            rs += __shfl_xor_sync(0xffffffffu, rs, 5);
            const uint32_t rb = pack_bf(0.f, rs);
            if (!(lane & 7)) st_gpu32((uint32_t*)p.sc->r + row, ((rb ^ (((int)rb >> 31) | 0x80000000u)) & 0xffff0000u) | tag);
            WSTAMP(1);
            {
                const int n = 3 + (lane >> 3) + 4 * (lane & 1);
                const uint32_t so = (n & 7) * S_PL + ((lane & 6) + (n >> 3)) * 32;
                const uint32_t src[2] = {sb + OFF_S + v * S_Q + s_addr(so, h), sb + OFF_S + v * S_Q + s_addr(so + 32, h)};
                const uint32_t dst = sb + OFF_U + g * U_CH + (8 + 32 * v + 16 * h + t) * 16;
                const uint32_t rdst = mapa(dst, h ^ 1), rbar = mapa(bars + 8 * B_U, h ^ 1);
                mbar_wait(bars + 8 * (B_S + v));
                WSTAMP(9);
                uint4 a[8];
#pragma unroll
                for (int b = 0; b < 2; b++) {
#pragma unroll
                    for (int j = 0; j < 8; j++) { const int u = 4 * b + (j >> 1) + 8 * (j & 1); ldsm4t((u < 8 ? src[u & 1] ^ 16 : src[u & 1]) + ((u >> 1) & 3) * 256, a[j].x, a[j].y, a[j].z, a[j].w); }
#pragma unroll
                    for (int j = 0; j < 8; j++) {
                        const int u = 4 * b + (j >> 1) + 8 * (j & 1);
                        if (u < 8) st_async16(rdst + ((u >> 1) & 3) * 64 + (u & 1) * U_PL, a[j], rbar);
                        else sts128(dst + ((u >> 1) & 3) * 64 + (u & 1) * U_PL, a[j].x, a[j].y, a[j].z, a[j].w);
                    }
                }
                if (h && v == 3) {
                    ldsm4t((src[0] ^ 16) + 1024, a[0].x, a[0].y, a[0].z, a[0].w);
                    ldsm4t(src[0] + 1024, a[1].x, a[1].y, a[1].z, a[1].w);
                    if (t == 0) {
                        st_async16(rdst + 256, make_uint4(a[0].x, a[0].y & 0xffffu, a[0].z & 0xffffu, a[0].w & 0xffffu), rbar);
                        sts128(dst + 256, a[1].x, a[1].y & 0xffffu, a[1].z & 0xffffu, a[1].w & 0xffffu);
                    }
                }
                __syncwarp();
                if (lane == 0) mbar_arrive(bars + 8 * B_U);
            }
            if ((lane & 7) == 2) st_gpu32((uint32_t*)p.sc->g + ((row & 256) << 2) + gate_pos(row), pack_bf(sigmoid_f(__uint_as_float(rb)), 0.f) | (tag << 16));
            WSTAMP(2);
        }
        {
            const bool lane0 = pin(lane, lane) == 0;
            const uint32_t own = pin(sb + OFF_XSEL + (at ^ ((at >> 1) & 4)) * 16, lane);
            float acc[8][4];
#pragma unroll
            for (int i = 0; i < 8; i++) { acc[i][0] = acc[i][1] = acc[i][2] = acc[i][3] = 0.f; }
            const int krow = ((lane >> 1) & 8) + (lane & 7);
            const uint32_t tile0 = pin(sb + OFF_RING + krow * 64 + ((((lane >> 3) & 1) ^ ((krow >> 1) & 3)) << 4), lane);
            const uint32_t xo = pin(sb + OFF_XSEL + (lane & 7) * XS_ROW + 512 * v + 2 * (lane & 24), lane);
            const uint32_t po = pin(sb + OFF_XSEL + t * XS_ROW + (g & 3) * 128 + (g & 1) * 64 + v * 16 + (lane >> 4) * 8, lane);
            const uint32_t po1 = pin(po + 64 - (g & 1) * 128, lane);
            uint32_t* hdst = pin((uint32_t*)&p.sc->h[tag & 1][32 * c] + at, lane);
            auto signal = [&](const int k, const uint32_t dep) {
                if (lane < 2 && v < 2)
                    asm volatile("st.async.weak.shared::cluster.mbarrier::complete_tx::bytes.b32 [%0], %1, [%2];"
                                 :: "r"(mapa(sb + M_SINK, lane)), "r"(dep), "r"(mapa(bars + 8 * (B_F + k), lane)) : "memory");
            };
#pragma unroll 1
            for (int i = 0; i < 4; i++) {
                const int s = 4 * i + v;
                uint32_t a[16][4], b[2][4];
                if (gu) {
                    const uint32_t tile = tile0 + (s < 14 ? s : v) * 8192;
                    if (lane0 && i > 1) mbar_arrive(bars + 8 * (B_E + s - 4));
                    if (i == 2) signal(0, 0);
                    mbar_wait(bars + 8 * (B_W + s));
#pragma unroll
                    for (int q = 0; q < 16; q++) ldsm4t((tile ^ ((q & 1) << 5)) + ((q >> 1) & 1) * 4096 + (q >> 2) * 1024, a[q][0], a[q][1], a[q][2], a[q][3]);
                }
                if (i == 0) {
                    if (gu) {
                        uint32_t dep = p.zero;
#pragma unroll
                        for (int q = 0; q < 16; q += 2) dep &= a[q][0] & a[q + 1][0];
                        if (lane == 0) mbar_arrive(bars + 8 * (B_E + v) + dep);
                    }
                    WSTAMP(11);
                    uint32_t top;
#pragma unroll 1
                    for (int it = 0; it < (1 << 22); it++) {
                        asm volatile("ld.relaxed.gpu.global.u32 %0, [%1];" : "=r"(top) : "l"(&p.sc->top[c % NTOP][g]) : "memory");
                        if (__all_sync(0xffffffffu, ((top ^ (tag << 11)) & 0xf800u) == 0)) break;
                        __nanosleep(40);
                    }
                    WSTAMP(3);
                    if (gu) {
                        const uint32_t k = 4 * h + v, row = __reduce_max_sync(0xffffffffu, lane == 4 * k ? ~top & 2047 : 0);
                        asm volatile("{\n\t.reg .pred p;\n\telect.sync _|p, 0xffffffff;\n\t"
                                     "@p cp.async.bulk.shared::cluster.global.mbarrier::complete_tx::bytes.multicast::cluster [%0], [%1], 2048, [%2], %3;\n\t}"
                            :: "r"(sb + OFF_XSEL + k * XS_ROW), "l"(p.u + (size_t)row * D_), "r"(bars + 8 * B_G), "h"((unsigned short)3) : "memory");
                    }
                    if (v == 2) {
                        const uint32_t row = ~top & 2047;
                        if (t == 0 && ((row >> 8) & 1) == h)
                            asm volatile("red.shared.or.b32 [%0], %1;" :: "r"(sb + M_BMAP + (row & 7) * 16 + (row >> 9) * 4), "r"(1u << (gate_pos(row) & 31)) : "memory");
                        if (t == 0) sts32(sb + M_TOP + lane, top);
                        if (c == 0 && lane == 0) *(volatile unsigned*)&p.sc->epoch = tag;
                        __syncwarp();
                        if (lane0) mbar_arrive(bars + 8 * B_Y);
                    }
                    if (!gu) break;
                    mbar_wait(bars + 8 * B_G);
                    WSTAMP(4);
                }
                ldsm4(xo + 128 * i, b[0][0], b[0][1], b[0][2], b[0][3]);
                ldsm4(xo + 128 * i + 64, b[1][0], b[1][1], b[1][2], b[1][3]);
#pragma unroll
                for (int q = 0; q < 16; q++) mma_bf(acc[q & 7], a[q][0], a[q][1], a[q][2], a[q][3], b[q >> 3][(q >> 1) & 2], b[q >> 3][((q >> 1) & 2) + 1]);
            }
            if (gu) {
                WSTAMP(5);
                __syncwarp();
#pragma unroll
                for (int q = 0; q < 4; q++) {
                    const int ct = q >> 1, e = 2 * (q & 1);
                    sts128(own + q * XS_ROW,
                           __float_as_uint(acc[ct][e] + acc[4 + ct][e]), __float_as_uint(acc[2 + ct][e] + acc[6 + ct][e]),
                           __float_as_uint(acc[ct][e + 1] + acc[4 + ct][e + 1]), __float_as_uint(acc[2 + ct][e + 1] + acc[6 + ct][e + 1]));
                }
                bar_sync(1, 128);
                float sl[2], uv[2];
#pragma unroll
                for (int e = 0; e < 2; e++) {
                    uint2 q[4];
#pragma unroll
                    for (int i = 0; i < 4; i++) q[i] = lds64((e ? po1 : po) + 512 * i);
                    const float s0 = (__uint_as_float(q[0].x) + __uint_as_float(q[1].x)) + (__uint_as_float(q[2].x) + __uint_as_float(q[3].x));
                    const float s1 = (__uint_as_float(q[0].y) + __uint_as_float(q[1].y)) + (__uint_as_float(q[2].y) + __uint_as_float(q[3].y));
                    const float gv = bf_round(p.gu_swap ? s1 : s0);
                    uv[e] = p.gu_swap ? s0 : s1;
                    sl[e] = gv * sigmoid_f(gv);
                }
                const uint32_t hw = hmul2_bf(pack_bf(sl[0], sl[1]), pack_bf(uv[0], uv[1]));
                st_gpu32(hdst, hw ? hw : 0x80000000u);
                signal(1, hw);
            }
        }
        WSTAMP(6);
        {
            const uint32_t own = pin(sb + OFF_XSEL + at * 16, lane);
            const uint32_t hb = sb + (v < 2 ? OFF_XSEL + 7168 * v : OFF_RING + 8192 * v), hl = pin(hb + 16 * lane, lane);
            const int krow = ((lane >> 1) & 8) + (lane & 7);
            const uint32_t tile = pin(sb + OFF_RING + v * 8192 + krow * 32 + ((((lane >> 3) ^ (krow >> 2)) & 1) << 4), lane);
            float dd[4][4];
            bar_sync(1, 128);
            mbar_wait(bars + 8 * (B_W + HW));
            WSTAMP(12);
            uint4 hq[7];
#pragma unroll 1
            for (int it = 0; it < (1 << 16); it++) {
                bulk_load(hb, &p.sc->h[tag & 1][32 * (56 * h + 14 * v)], 7168, bars + 8 * (B_X + v));
                uint32_t a[14][4], mn = 0xffffffffu;
                mbar_wait(bars + 8 * (B_W + 16 + v));
#pragma unroll
                for (int j = 0; j < 14; j++) ldsm4t(tile + (v & 2) * 16384 + j * 512, a[j][0], a[j][1], a[j][2], a[j][3]);
                mbar_wait(bars + 8 * (B_X + v), ~it & 1);
                WSTAMP(7);
#pragma unroll
                for (int j = 0; j < 7; j++) {
                    const uint4 q = lds128(hl + 512 * j);
                    mn = min(mn, q.x);
#pragma unroll
                    for (int e = 0; e < 2; e++) {
                        const uint32_t(&f)[4] = a[2 * j + e];
                        if (j < 2) mma_bf_z(dd[2 * j + e], f[0], f[1], f[2], f[3], e ? q.z : q.x, e ? q.w : q.y);
                        else mma_bf(dd[(2 * j + e) & 3], f[0], f[1], f[2], f[3], e ? q.z : q.x, e ? q.w : q.y);
                    }
                }
#pragma unroll
                for (int j = 0; j < 7; j++) { hq[j] = lds128(hl + 3584 + 512 * j); mn = min(mn, hq[j].x); }
                if (__all_sync(0xffffffffu, mn != 0)) break;
            }
            mbar_wait(bars + 8 * (B_W + 20 + v));
#pragma unroll
            for (int j = 0; j < 14; j++) {
                uint32_t f[4];
                ldsm4t(tile + 65536 + j * 512, f[0], f[1], f[2], f[3]);
                mma_bf(dd[(j + 2) & 3], f[0], f[1], f[2], f[3], (j & 1) ? hq[j >> 1].z : hq[j >> 1].x, (j & 1) ? hq[j >> 1].w : hq[j >> 1].y);
            }
            WSTAMP(8);
            uint4 part;
            part.x = __float_as_uint((dd[0][0] + dd[1][0]) + (dd[2][0] + dd[3][0])); part.y = __float_as_uint((dd[0][1] + dd[1][1]) + (dd[2][1] + dd[3][1]));
            part.z = __float_as_uint((dd[0][2] + dd[1][2]) + (dd[2][2] + dd[3][2])); part.w = __float_as_uint((dd[0][3] + dd[1][3]) + (dd[2][3] + dd[3][3]));
            st_async16(mapa(own + (M_DPIN - OFF_XSEL), h ^ 1), part, mapa(bars + 8 * B_DP, h ^ 1));
            sts128(own + 14336, part.x, part.y, part.z, part.w);
            __syncwarp();
            if (lane == 0) mbar_arrive(bars + 8 * B_DP);
        }
        WDUMP();
    } else {
        asm volatile("setmaxnreg.dec.sync.aligned.u32 64;");
        const int v = __reduce_max_sync(0xffffffffu, pw - PREP_W0);
        const bool gu = c < NGU_CTA;
        const uint32_t t0 = clock();
        const uint32_t bu = bars + 8 * v;
        if (lane == 0) {
#pragma unroll
            for (int i = 0; i < 10; i++) mbar_init(bu + 32 * i, 1);
            mbar_init(bu + 8 * B_X, 1);
            mbar_init(bu + 8 * B_XE, 1);
            mbar_init(bu + 8 * B_Y, v == 0 ? 11 : 9);
            mbar_init(bu + 8 * B_DP, (0x1855 >> (4 * v)) & 15);
            mbar_init(bu + 8 * B_F, 1);
            mbar_init(bu + 8 * B_H, 1);
            asm volatile("fence.mbarrier_init.release.cluster;" ::: "memory");
            mbar_expect(bu + 8 * B_Y, 4096);
            if (v != 2) mbar_expect(bu + 8 * B_DP, v == 0 ? 2048 : (h || v == 3) ? 16384 : 16384 + 128);
            mbar_expect(bu + 8 * B_F, c < NGU_CTA ? 16 : 0);
        }
        __syncwarp();
        asm volatile("barrier.cluster.arrive.relaxed.aligned;" ::: "memory");
        bulk_load(sb + (v < 2 ? OFF_XSEL : OFF_RING + 2 * 8192) + v * 8192, p.u + (size_t)(16 * c + 4 * v) * D_, 8192, bu + 8 * B_X);
        tma3d(sb + OFF_S + v * S_Q, &tm_x, 16 * pr, 64 * v + 32 * h - 1, bars + 8 * (B_S + v), S_Q);
        WSTAMP(9);
        if (v < 3 && lane == 0) asm volatile("prefetch.tensormap [%0];" :: "l"(v == 0 ? &tm_gu : v == 1 ? &tm_down : &tm_out) : "memory");
        asm volatile("barrier.cluster.wait.acquire.aligned;" ::: "memory");
        uint32_t desc;
        {
            const int s = 6 * v + lane, i = s >> 2, w = s & 3, slot = s < 14 ? s : (s | 1) == 17 ? s - 16 : s - 12;
            const int fb = s < 4 ? B_H : (gu && s >= 14) ? B_E + slot : s < 6 ? B_XE + s - 2 : B_KG;
            desc = slot | (fb << 4) | ((i < 4 ? 256 * w + 64 * i : 1792 * h + 448 * w + 224 * (i - 4)) << 10);
            if (lane < 6) mbar_expect(bars + 8 * (B_W + s), i < 4 ? 8192 : 7168);
            if (tid == 32 * PREP_W0) mbar_arrive(bars + 8 * B_H);
        }
        if (v == 3) {
            mbar_wait(bars + 8 * B_U);
            mbar_wait(bars + 8 * (gu ? B_G : B_H + 2));
            const uint32_t tag16 = lds32(sb + M_TAG);
            uint4 q[8];
#pragma unroll 1
            for (int it = 0; it < (1 << 22); it++) {
                uint32_t bad = 0;
#pragma unroll
                for (int i = 0; i < 8; i++) q[i] = ld_gpu128(&p.sc->g[256 * h + 32 * i + lane]);
#pragma unroll
                for (int i = 0; i < 8; i++) bad |= ((q[i].x ^ tag16) | (q[i].y ^ tag16)) | ((q[i].z ^ tag16) | (q[i].w ^ tag16));
                if ((bad >> 16) == 0) break;
                __nanosleep(200);
            }
#pragma unroll
            for (int i = 0; i < 8; i++)
                asm volatile("st.shared.v2.u32 [%0], {%1, %2};" :: "r"(sb + OFF_GP + 256 * i + lane * 8),
                             "r"(__byte_perm(q[i].x, q[i].y, 0x5410)), "r"(__byte_perm(q[i].z, q[i].w, 0x5410)) : "memory");
            __syncwarp();
            if (lane == 0) mbar_arrive(bars + 8 * B_Y);
        }
        mbar_wait(bars + 8 * (B_H + v));
        {
            const int gap = v == 0 ? GAP : v == 1 ? GAP1 : v == 2 ? GAP2 : GAP3;
            uint32_t last = v ? clock() - SLACK : t0 + T0 - GAP + GAP * ((pr * 5) & 15) / 16;
#pragma unroll 1
            while ((int)(last - clock()) > 500) __nanosleep(256);
#pragma unroll 1
            for (int k = 0; k < 6; k++) {
                const uint32_t dk = __reduce_max_sync(0xffffffffu, lane == k ? desc : 0);
                const bool dn = 6 * v + k >= 16;
                mbar_wait(bars + ((dk >> 1) & 0x1f8));
                uint32_t now;
#pragma unroll 1
                while ((int)((now = clock()) - last) < gap) __nanosleep(50);
                last = max((int)(now - last) - SLACK, gap) + last;
                WSTAMP(3 + k);
                if (gu || dn)
                    asm volatile("{\n\t.reg .pred p;\n\telect.sync _|p, 0xffffffff;\n\t"
                                 "@p cp.async.bulk.tensor.3d.shared::cluster.global.mbarrier::complete_tx::bytes [%0], [%1, {%3, %4, 0}], [%2];\n\t}"
                        :: "r"(sb + OFF_RING + (dk & 15) * 8192), "l"(dn ? &tm_down : &tm_gu), "r"(bars + 8 * (B_W + 6 * v + k)), "r"(dn ? 16 * pr : 32 * c), "r"(dk >> 10) : "memory");
                if (k < 5) __nanosleep(64);
            }
            if (lane == 0 && v < 3) mbar_arrive(bars + 8 * (B_H + v + 1));
        }
        {
            WSTAMP(1);
            mix_rows<2>(p, &tm_out, sb, sb + OFF_TAB + v * TAB_W, 0, PQ, v, h, pr, lane);
            WSTAMP(2);
            asm volatile("cp.async.bulk.commit_group;" ::: "memory");
            const uint32_t top = lds32(sb + M_TOP + 8 * v + 4 * (lane >> 4));
            const uint32_t row = ~top & 2047, ch = lane & 15, gp = gate_pos(row);
            const bool mine = ((row >> 8) & 1) == h;
            uint32_t gfin, x16, y16 = 0;
            asm volatile("ld.shared.u16 %0, [%1];" : "=r"(gfin) : "r"(sb + OFF_GP + gp * 2) : "memory");
            asm volatile("ld.shared.u16 %0, [%1];" : "=r"(x16) : "r"(sb + OFF_S + (row >> 9) * S_Q + s_addr((row & 7) * S_PL + 32 + (row & 248) * 4, ch >> 3) + 2 * (ch & 7)) : "memory");
            const float rsel = __uint_as_float(pin(__float_as_uint(bf_round(sigmoid_f(__uint_as_float((top ^ (((int)~top >> 31) | 0x80000000u)) & 0xffff0000u)))), lane));
            const uint32_t po = pin(sb + (4 * (ch & 7) + v) * 16 + (ch >> 3) * 8 + (lane >> 4) * 4, lane);
            bf16* op = pin(p.out + (size_t)row * D_ + 16 * pr + ch, lane);
            if (mine) {
                mbar_wait(bars + 8 * (B_Y + (row >> 9)));
                asm volatile("ld.shared.u16 %0, [%1];" : "=r"(y16)
                             : "r"(sb + y_off(row >> 9) + ch * 512 + (((4 * (row & 7) + ((row >> 5) & 3)) ^ (((ch >> 2) << 1) | (ch & 1))) << 4) + 2 * row_elem(row)) : "memory");
            }
            mbar_wait(bars + 8 * B_DP);
            float q[8];
#pragma unroll
            for (int i = 0; i < 4; i++) { q[i] = ldsf(po + M_DPIN + 512 * i); q[4 + i] = ldsf(po + OFF_XSEL + 14336 + 512 * i); }
            const float tot = ((q[0] + q[1]) + (q[2] + q[3])) + ((q[4] + q[5]) + (q[6] + q[7]));
            const float b = bf_round(__uint_as_float(x16 << 16) + bf_round(bf_round(tot) * rsel));
            if (mine) *op = __float2bfloat16_rn(fmaf(bf_lo(gfin), __uint_as_float(y16 << 16), bf_round(bf_round(1.f - bf_lo(gfin)) * b)));
        }
        asm volatile("cp.async.bulk.wait_group.read 0;" ::: "memory");
        WSTAMP(10);
        WDUMP();
    }
}

typedef CUresult (*EncodeFn)(CUtensorMap*, CUtensorMapDataType, cuuint32_t, void*, const cuuint64_t*, const cuuint64_t*,
                             const cuuint32_t*, const cuuint32_t*, CUtensorMapInterleave, CUtensorMapSwizzle,
                             CUtensorMapL2promotion, CUtensorMapFloatOOBfill);

void make_map(EncodeFn f, CUtensorMap* m, const void* ptr, uint64_t cols, uint64_t rows, uint64_t pitch, uint32_t bc, uint32_t br, CUtensorMapSwizzle sw, CUtensorMapL2promotion prom,
              uint32_t planes = 1, uint64_t plane_stride = 0, uint32_t box_planes = 0) {
    cuuint64_t dims[3] = {cols, rows, planes};
    cuuint64_t str[2] = {pitch, planes > 1 ? plane_stride : pitch * rows};
    cuuint32_t box[3] = {bc, br, box_planes ? box_planes : planes};
    cuuint32_t es[3] = {1, 1, 1};
    f(m, CU_TENSOR_MAP_DATA_TYPE_BFLOAT16, 3, (void*)ptr, dims, str, box, es, CU_TENSOR_MAP_INTERLEAVE_NONE, sw,
      prom, CU_TENSOR_MAP_FLOAT_OOB_FILL_NONE);
}

}

extern "C" void kernel_launch(void* const* d_in, const int* in_sizes, int n_in, void* d_out, int out_size) {
    static EncodeFn enc = nullptr;
    static void *sc = nullptr, *band = nullptr;
    if (!enc) {
        void* fn = nullptr;
        cudaDriverEntryPointQueryResult qr;
        cudaGetDriverEntryPoint("cuTensorMapEncodeTiled", &fn, cudaEnableDefault, &qr);
        enc = (EncodeFn)fn;
        cudaGetSymbolAddress(&sc, g_scratch);
        cudaGetSymbolAddress(&band, g_band);
        cudaFuncSetAttribute(fused_kernel, cudaFuncAttributeMaxDynamicSharedMemorySize, SMEM_BYTES);
    }
    CUtensorMap tg, td, tx, to;
    const char *wg = (const char*)d_in[9], *wu = (const char*)d_in[10];
    const bool swap = wu < wg;
    make_map(enc, &tg, swap ? wu : wg, F_, D_, F_ * 2, 32, 64, CU_TENSOR_MAP_SWIZZLE_64B, CU_TENSOR_MAP_L2_PROMOTION_L2_128B, 2, swap ? wg - wu : wu - wg);
    make_map(enc, &td, d_in[11], D_, F_, D_ * 2, 16, 224, CU_TENSOR_MAP_SWIZZLE_32B, CU_TENSOR_MAP_L2_PROMOTION_L2_64B);
    make_map(enc, &tx, d_in[0], D_, L_ / 8, D_ * 16, 16, 33, CU_TENSOR_MAP_SWIZZLE_32B, CU_TENSOR_MAP_L2_PROMOTION_NONE, 8, D_ * 2);
    make_map(enc, &to, d_out, D_, L_ / 8, D_ * 16, 16, 32, CU_TENSOR_MAP_SWIZZLE_NONE, CU_TENSOR_MAP_L2_PROMOTION_NONE, 8, D_ * 2, 1);
    Params p;
    p.u = (const bf16*)d_in[0]; p.logA = (const bf16*)d_in[1]; p.Aim = (const bf16*)d_in[2];
    p.Cre = (const bf16*)d_in[3]; p.Cim = (const bf16*)d_in[4]; p.logdt = (const bf16*)d_in[5];
    p.Dskip = (const bf16*)d_in[6]; p.wr = (const bf16*)d_in[8]; p.gatew = (const bf16*)d_in[12];
    p.out = (bf16*)d_out;
    p.sc = (Scratch*)sc; p.band = (const uint4*)band;
    p.gu_swap = swap;
    p.zero = 0;
    fused_kernel<<<NCTA, NTHREADS, SMEM_BYTES>>>(p, tg, td, tx, to);
}
```

```cpp
#include <cuda_runtime.h>
#include <cuda_bf16.h>
#include <cuda_fp16.h>
#include <cuda.h>
#include <stdint.h>

typedef __nv_bfloat16 bf16;

namespace {

constexpr int L_ = 2048, D_ = 1024, F_ = 3584;
constexpr int NCTA = 130;
constexpr int NTHREADS = 512;
constexpr int MAIN_W0 = 0, PREP_W0 = 8, AUX_W0 = 12;
#define T0 3000
#define GAP 540
#define GAP1 530
#define GAP2 530
#define GAP3 550
#define HW 20
constexpr int SLACK = 300;
constexpr int PQ = 3;
constexpr int NGU_CTA = 112;

constexpr int OFF_RING = 0;
constexpr int OFF_SCR  = 6 * 8192;
constexpr int S_PL     = 1056;
constexpr int S_Q      = 8 * S_PL;
constexpr int OFF_S    = 114688;
constexpr int OFF_GP   = OFF_S + 4 * S_Q;
constexpr int U_PL     = 2240;
constexpr int U_CH     = 4416;
constexpr int OFF_U    = 151552;
constexpr int TAB_W    = 3200;
constexpr int T_PL     = 544;
constexpr int T_A      = 2192 - 26 * 8;
constexpr int T_B      = 2568 - 59 * 8;
constexpr int OFF_TAB  = 186880;
constexpr int OFF_XSEL = 212480;
constexpr int XS_ROW   = 2064;
constexpr int OFF_BAND = 228992;
constexpr int OFF_MISC = 229536;
constexpr int M_BARS   = OFF_MISC;
constexpr int M_DSK    = OFF_MISC + 2736;
constexpr int M_SINK   = OFF_MISC + 512;
constexpr int M_TAG    = OFF_MISC + 516;
constexpr int M_BMAP   = OFF_MISC + 528;
constexpr int M_DPIN   = OFF_MISC + 656;
constexpr int M_TOP    = OFF_MISC + 2704;
constexpr int SMEM_BYTES = OFF_MISC + 2768;
__device__ __forceinline__ uint32_t s_addr(uint32_t o, uint32_t half) { return o + (((half ^ (o >> 7)) & 1) << 4); }
__host__ __device__ constexpr uint32_t y_off(uint32_t q) { return OFF_RING + 32768 + (q & 1) * 8192 + (q >> 1) * 65536; }

constexpr int B_W = 0;
constexpr int B_E = 24;
constexpr int B_S = 36;
constexpr int B_Y = 40;
constexpr int B_DP = 44, B_U = 45, B_KG = 46, B_G = 47;
constexpr int B_F = 48;
constexpr int B_H = 60;
constexpr int B_X = 52, B_XE = 56;

struct BandTab { uint32_t w[11][12]; };
constexpr BandTab make_band() {
    BandTab b{};
    for (int cls = 0; cls < 11; cls++)
        for (int wd = 0; wd < 10; wd++) {
            const int tau = cls + 2 - 8 * ((wd < 4 ? wd : wd - 4) >> 1);
            const int lo = (wd < 4) ? ((wd & 1) ? -2 : 3) : ((wd & 1) ? -4 : -11), wid = (wd < 4 ? 3 : 7) + 2 * (wd & 1);
            b.w[cls][wd] = ((tau >= lo && tau < lo + wid) ? 0x3F80u : 0u) | ((tau - 4 >= lo && tau - 4 < lo + wid) ? 0x3F800000u : 0u);
        }
    return b;
}
constexpr int NTOP = 32;
struct Scratch {
    uint4 r[L_ / 4];
    uint4 g[L_ / 4];
    uint4 h[2][8 * F_ / 8];
    uint32_t top[NTOP][32];
    unsigned epoch;
};
__device__ __align__(128) Scratch g_scratch;
__device__ const __align__(16) BandTab g_band = make_band();

struct Params {
    const bf16 *u, *logA, *Aim, *Cre, *Cim, *logdt, *Dskip, *wr, *gatew;
    bf16* out;
    Scratch* sc;
    const uint4* band;
    uint32_t gu_swap;
    uint32_t zero;
};

#define WSTAMP(i) do {} while (0)
#define KSTAMP(i, dep) do {} while (0)
#define WDUMP() do {} while (0)
#define RSTAMP(i) do {} while (0)

__device__ __forceinline__ uint32_t smem_u32(const void* p) { return (uint32_t)__cvta_generic_to_shared(p); }
__device__ __forceinline__ void mbar_init(uint32_t b, uint32_t c) { asm volatile("mbarrier.init.shared::cta.b64 [%0], %1;" :: "r"(b), "r"(c) : "memory"); }
__device__ __forceinline__ void mbar_expect(uint32_t b, uint32_t tx) { asm volatile("mbarrier.arrive.expect_tx.shared::cta.b64 _, [%0], %1;" :: "r"(b), "r"(tx) : "memory"); }
__device__ __forceinline__ void mbar_arrive(uint32_t b) { asm volatile("mbarrier.arrive.shared::cta.b64 _, [%0];" :: "r"(b) : "memory"); }
__device__ __forceinline__ void mbar_wait(uint32_t b, uint32_t parity = 0) {
    asm volatile("{\n\t.reg .pred p;\nW%=:\n\tmbarrier.try_wait.parity.shared::cta.b64 p, [%0], %1, 20000;\n\t@!p bra W%=;\n\t}" :: "r"(b), "r"(parity) : "memory");
}
__device__ __forceinline__ uint32_t mapa(uint32_t addr, uint32_t rank) { uint32_t r; asm("mapa.shared::cluster.u32 %0, %1, %2;" : "=r"(r) : "r"(addr), "r"(rank)); return r; }
__device__ __forceinline__ void tma3d(uint32_t dst, const CUtensorMap* tm, int c0, int c1, uint32_t bar, uint32_t bytes) {
    asm volatile("{\n\t.reg .pred p;\n\telect.sync _|p, 0xffffffff;\n\t"
                 "@p mbarrier.arrive.expect_tx.shared::cta.b64 _, [%2], %5;\n\t"
                 "@p cp.async.bulk.tensor.3d.shared::cluster.global.mbarrier::complete_tx::bytes [%0], [%1, {%3, %4, 0}], [%2];\n\t}"
        :: "r"(dst), "l"(tm), "r"(bar), "r"(c0), "r"(c1), "r"(bytes) : "memory");
}
__device__ __forceinline__ void bulk_load(uint32_t dst, const void* src, uint32_t bytes, uint32_t bar) {
    asm volatile("{\n\t.reg .pred p;\n\telect.sync _|p, 0xffffffff;\n\t"
                 "@p mbarrier.arrive.expect_tx.shared::cta.b64 _, [%2], %3;\n\t"
                 "@p cp.async.bulk.shared::cluster.global.mbarrier::complete_tx::bytes [%0], [%1], %3, [%2];\n\t}"
        :: "r"(dst), "l"(src), "r"(bar), "r"(bytes) : "memory");
}
__device__ __forceinline__ void st_async16(uint32_t dst, const uint4& v, uint32_t bar) {
    asm volatile("st.async.weak.shared::cluster.mbarrier::complete_tx::bytes.v4.b32 [%0], {%1,%2,%3,%4}, [%5];"
                 :: "r"(dst), "r"(v.x), "r"(v.y), "r"(v.z), "r"(v.w), "r"(bar) : "memory");
}
__device__ __forceinline__ void bar_sync(int id, int n) { asm volatile("bar.sync %0, %1;" :: "r"(id), "r"(n) : "memory"); }
__device__ __forceinline__ void cp16(uint32_t dst, const void* src) { asm volatile("cp.async.cg.shared.global [%0], [%1], 16;" :: "r"(dst), "l"(src) : "memory"); }
__device__ __forceinline__ void cp_wait_all() { asm volatile("cp.async.wait_all;" ::: "memory"); }
__device__ __forceinline__ uint4 ld_gpu128(const void* p) { uint4 v; asm volatile("ld.relaxed.gpu.global.v4.u32 {%0,%1,%2,%3}, [%4];" : "=r"(v.x), "=r"(v.y), "=r"(v.z), "=r"(v.w) : "l"(p) : "memory"); return v; }
__device__ __forceinline__ void st_gpu32(void* p, uint32_t v) { asm volatile("st.relaxed.gpu.global.u32 [%0], %1;" :: "l"(p), "r"(v) : "memory"); }

__device__ __forceinline__ void ldsm4(uint32_t a, uint32_t& r0, uint32_t& r1, uint32_t& r2, uint32_t& r3) {
    asm volatile("ldmatrix.sync.aligned.m8n8.x4.shared.b16 {%0,%1,%2,%3}, [%4];" : "=r"(r0), "=r"(r1), "=r"(r2), "=r"(r3) : "r"(a) : "memory");
}
__device__ __forceinline__ void ldsm4t(uint32_t a, uint32_t& r0, uint32_t& r1, uint32_t& r2, uint32_t& r3) {
    asm volatile("ldmatrix.sync.aligned.m8n8.x4.trans.shared.b16 {%0,%1,%2,%3}, [%4];" : "=r"(r0), "=r"(r1), "=r"(r2), "=r"(r3) : "r"(a) : "memory");
}
__device__ __forceinline__ uint32_t lds32(uint32_t a) { uint32_t v; asm volatile("ld.shared.u32 %0, [%1];" : "=r"(v) : "r"(a) : "memory"); return v; }
__device__ __forceinline__ uint2 lds64(uint32_t a) { uint2 v; asm volatile("ld.shared.v2.u32 {%0,%1}, [%2];" : "=r"(v.x), "=r"(v.y) : "r"(a) : "memory"); return v; }
__device__ __forceinline__ uint4 lds128(uint32_t a) { uint4 v; asm volatile("ld.shared.v4.u32 {%0,%1,%2,%3}, [%4];" : "=r"(v.x), "=r"(v.y), "=r"(v.z), "=r"(v.w) : "r"(a) : "memory"); return v; }
__device__ __forceinline__ void sts32(uint32_t a, uint32_t v) { asm volatile("st.shared.u32 [%0], %1;" :: "r"(a), "r"(v) : "memory"); }
__device__ __forceinline__ void sts16(uint32_t a, uint32_t v) { asm volatile("st.shared.u16 [%0], %1;" :: "r"(a), "h"((unsigned short)v) : "memory"); }
__device__ __forceinline__ void sts128(uint32_t a, uint32_t x, uint32_t y, uint32_t z, uint32_t w) { asm volatile("st.shared.v4.u32 [%0], {%1,%2,%3,%4};" :: "r"(a), "r"(x), "r"(y), "r"(z), "r"(w) : "memory"); }
__device__ __forceinline__ float ldsf(uint32_t a) { float v; asm volatile("ld.shared.f32 %0, [%1];" : "=f"(v) : "r"(a) : "memory"); return v; }

__device__ __forceinline__ void mma_bf(float (&d)[4], uint32_t a0, uint32_t a1, uint32_t a2, uint32_t a3, uint32_t b0, uint32_t b1) {
    asm volatile("mma.sync.aligned.m16n8k16.row.col.f32.bf16.bf16.f32 {%0,%1,%2,%3}, {%4,%5,%6,%7}, {%8,%9}, {%0,%1,%2,%3};"
        : "+f"(d[0]), "+f"(d[1]), "+f"(d[2]), "+f"(d[3]) : "r"(a0), "r"(a1), "r"(a2), "r"(a3), "r"(b0), "r"(b1));
}
__device__ __forceinline__ void mma_bf_z(float (&d)[4], uint32_t a0, uint32_t a1, uint32_t a2, uint32_t a3, uint32_t b0, uint32_t b1) {
    asm volatile("mma.sync.aligned.m16n8k16.row.col.f32.bf16.bf16.f32 {%0,%1,%2,%3}, {%4,%5,%6,%7}, {%8,%9}, {%10,%10,%10,%10};"
        : "=f"(d[0]), "=f"(d[1]), "=f"(d[2]), "=f"(d[3]) : "r"(a0), "r"(a1), "r"(a2), "r"(a3), "r"(b0), "r"(b1), "f"(0.f));
}
__device__ __forceinline__ void mma_bf_k8(float (&d)[4], uint32_t a0, uint32_t a1, uint32_t b0) {
    asm volatile("mma.sync.aligned.m16n8k8.row.col.f32.bf16.bf16.f32 {%0,%1,%2,%3}, {%4,%5}, {%6}, {%0,%1,%2,%3};"
        : "+f"(d[0]), "+f"(d[1]), "+f"(d[2]), "+f"(d[3]) : "r"(a0), "r"(a1), "r"(b0));
}
__device__ __forceinline__ void mma_h(float (&d)[4], uint32_t a0, uint32_t a1, uint32_t a2, uint32_t a3, uint32_t b0, uint32_t b1) {
    asm volatile("mma.sync.aligned.m16n8k16.row.col.f32.f16.f16.f32 {%0,%1,%2,%3}, {%4,%5,%6,%7}, {%8,%9}, {%0,%1,%2,%3};"
        : "+f"(d[0]), "+f"(d[1]), "+f"(d[2]), "+f"(d[3]) : "r"(a0), "r"(a1), "r"(a2), "r"(a3), "r"(b0), "r"(b1));
}
__device__ __forceinline__ uint32_t pack_bf(float lo, float hi) { uint32_t r; asm("cvt.rn.bf16x2.f32 %0, %1, %2;" : "=r"(r) : "f"(hi), "f"(lo)); return r; }
__device__ __forceinline__ uint32_t pack_h(float lo, float hi) { uint32_t r; asm("cvt.rn.f16x2.f32 %0, %1, %2;" : "=r"(r) : "f"(hi), "f"(lo)); return r; }
__device__ __forceinline__ float bf_lo(uint32_t v) { return __uint_as_float(v << 16); }
__device__ __forceinline__ float bf_hi(uint32_t v) { return __uint_as_float(v & 0xffff0000u); }
__device__ __forceinline__ float bf_round(float x) { return __uint_as_float(pack_bf(0.f, x)); }
__device__ __forceinline__ uint32_t hmul2_bf(uint32_t a, uint32_t b) { uint32_t r; asm("mul.rn.bf16x2 %0, %1, %2;" : "=r"(r) : "r"(a), "r"(b)); return r; }
__device__ __forceinline__ float ex2f(float x) { float r; asm("ex2.approx.ftz.f32 %0, %1;" : "=f"(r) : "f"(x)); return r; }

__device__ __forceinline__ float exp_acc(float x) {
    const float t = x * 1.4426950216293335f;
    const float r = fmaf(x, 1.4426950216293335f, -t) + x * 1.9259629911266175e-8f;
    return ex2f(t) * fmaf(r, 0.6931471805599453f, 1.f);
}
__device__ __forceinline__ float sigmoid_f(float x) { return __fdividef(1.f, 1.f + ex2f(-x * 1.4426950408889634f)); }
__device__ __forceinline__ void cexp_pow(float l2, float li, float e, float& zr, float& zi) {
    const float mag = ex2f(l2 * e);
    zr = mag * __cosf(li * e);
    zi = mag * __sinf(li * e);
}
__device__ __forceinline__ uint32_t hcmul(uint32_t a, uint32_t k, uint32_t kp) {
    const __half2 A = *reinterpret_cast<const __half2*>(&a);
    const __half2 r = __hfma2(__high2half2(A), *reinterpret_cast<const __half2*>(&kp), __hmul2(__low2half2(A), *reinterpret_cast<const __half2*>(&k)));
    return *reinterpret_cast<const uint32_t*>(&r);
}
#define CMUL(orr, oi, ar, ai, br, bi) do { float _r = (ar) * (br) - (ai) * (bi); float _i = (ar) * (bi) + (ai) * (br); orr = _r; oi = _i; } while (0)
#define CSQ(orr, oi, ar, ai) do { float _r = (ar) * (ar) - (ai) * (ai); float _i = 2.f * (ar) * (ai); orr = _r; oi = _i; } while (0)

__device__ __forceinline__ void mma_bf_k8z(float (&d)[4], uint32_t a0, uint32_t a1, uint32_t b0) {
    asm volatile("mma.sync.aligned.m16n8k8.row.col.f32.bf16.bf16.f32 {%0,%1,%2,%3}, {%4,%5}, {%6}, {%7,%7,%7,%7};"
        : "=f"(d[0]), "=f"(d[1]), "=f"(d[2]), "=f"(d[3]) : "r"(a0), "r"(a1), "r"(b0), "f"(0.f));
}
__device__ __forceinline__ void mma_hh_k8(uint32_t& d0, uint32_t& d1, uint32_t a0, uint32_t a1, uint32_t b0) {
    asm volatile("mma.sync.aligned.m16n8k8.row.col.f16.f16.f16.f16 {%0,%1}, {%2,%3}, {%4}, {%5,%5};"
        : "=r"(d0), "=r"(d1) : "r"(a0), "r"(a1), "r"(b0), "r"(0));
}
__device__ __forceinline__ void sched_fence() { asm volatile("pmevent 0;" ::: "memory"); }
__device__ __forceinline__ uint32_t pin(uint32_t x, int lane) { return __shfl_sync(0xffffffffu, x, lane); }
template <class T> __device__ __forceinline__ T* pin(T* x, int lane) { return (T*)__shfl_sync(0xffffffffu, (unsigned long long)x, lane); }
__device__ __forceinline__ void sts32_if(bool on, uint32_t a, uint32_t v) {
    asm volatile("{\n\t.reg .pred p;\n\tsetp.ne.u32 p, %2, 0;\n\t@p st.shared.u32 [%0], %1;\n\t}" :: "r"(a), "r"(v), "r"((uint32_t)on) : "memory");
}
__device__ __forceinline__ void sts128_if(bool on, uint32_t a, uint32_t x, uint32_t y, uint32_t z, uint32_t w) {
    asm volatile("{\n\t.reg .pred p;\n\tsetp.ne.u32 p, %5, 0;\n\t@p st.shared.v4.u32 [%0], {%1,%2,%3,%4};\n\t}" :: "r"(a), "r"(x), "r"(y), "r"(z), "r"(w), "r"((uint32_t)on) : "memory");
}
__device__ __forceinline__ void lds128_if(bool on, uint32_t a, uint32_t (&v)[4]) {
    asm volatile("{\n\t.reg .pred p;\n\tsetp.ne.u32 p, %5, 0;\n\t@p ld.shared.v4.u32 {%0,%1,%2,%3}, [%4];\n\t}"
        : "+r"(v[0]), "+r"(v[1]), "+r"(v[2]), "+r"(v[3]) : "r"(a), "r"((uint32_t)on) : "memory");
}
__device__ __forceinline__ uint32_t hfma2_bf(uint32_t a, uint32_t b, uint32_t c) { uint32_t r; asm("fma.rn.bf16x2 %0, %1, %2, %3;" : "=r"(r) : "r"(a), "r"(b), "r"(c)); return r; }
__device__ __forceinline__ __nv_bfloat162 bcast(uint32_t a, int hi) { const __nv_bfloat162 v = *reinterpret_cast<const __nv_bfloat162*>(&a); return hi ? __high2bfloat162(v) : __low2bfloat162(v); }
__device__ __forceinline__ uint32_t hmul2_bc(uint32_t a, int hi, uint32_t b) { const __nv_bfloat162 r = __hmul2_rn(bcast(a, hi), *reinterpret_cast<const __nv_bfloat162*>(&b)); return *reinterpret_cast<const uint32_t*>(&r); }
__device__ __forceinline__ uint32_t hfma2_bc(uint32_t a, int hi, uint32_t b, uint32_t c) {
    const __nv_bfloat162 r = __hfma2(bcast(a, hi), *reinterpret_cast<const __nv_bfloat162*>(&b), *reinterpret_cast<const __nv_bfloat162*>(&c));
    return *reinterpret_cast<const uint32_t*>(&r);
}
__device__ __forceinline__ uint32_t row_elem(uint32_t row) { return ((row >> 5) & 4) | ((row >> 2) & 2) | ((row >> 4) & 1); }
__device__ __forceinline__ uint32_t gate_pos(uint32_t row) { return ((row >> 9) << 8) | ((row & 7) << 5) | (row_elem(row) << 2) | ((row >> 5) & 3); }

template <int N>
__device__ __forceinline__ void mix_rows(const Params& p, const CUtensorMap* tm_out, uint32_t sb, uint32_t ob, int Q0, int Q1, int w, int h, int pr, int lane) {
    const int g = lane >> 2, t = lane & 3, mi = lane >> 3, r = lane & 7;
    const int m8 = 16 * (g >> 2) + ((g >> 1) & 1) + 2 * (g & 1);
    uint32_t yi = sb + (4 * (r >> 1) + 2 * (mi & 1) + (r & 1)) * 512 + (((4 * w + (mi >> 1)) ^ r) << 4);
    uint32_t xs = sb + OFF_S + s_addr(w * S_PL + 32 + m8 * 32, t >> 1) + ((t & 1) << 3);
    uint32_t gs = sb + OFF_GP + w * 64 + g * 8, os = ob + m8 * 32 + t * 8;
    if (N > 1) { yi = pin(yi, lane); xs = pin(xs, lane); gs = pin(gs, lane); os = pin(os, lane); }
    mbar_wait(sb + M_BARS + 8 * B_Y);
#pragma unroll 1
    for (int Q = Q0; Q < Q1; Q++) {
        uint2 xq[N][4];
        uint32_t gg[N][2], sw[N];
#pragma unroll
        for (int n = 0; n < N; n++) {
#pragma unroll
            for (int i = 0; i < 4; i++) xq[n][i] = lds64((xs ^ (((i ^ n) & 1) << 4)) + Q * S_Q + n * 4 * S_PL + i * 128);
            const uint2 gq = lds64(gs + Q * 512 + n * 256);
            sw[n] = lds32(sb + M_BMAP + w * 16 + n * 64 + Q * 4);
            gg[n][0] = gq.x; gg[n][1] = gq.y;
#pragma unroll
            for (int i = 0; i < 4; i++) {
                const uint32_t og = hfma2_bf(gg[n][i >> 1], 0xBF80BF80u, 0x3F803F80u);
                xq[n][i].x = hmul2_bc(og, i & 1, xq[n][i].x); xq[n][i].y = hmul2_bc(og, i & 1, xq[n][i].y);
            }
        }
        mbar_wait(sb + M_BARS + 8 * (B_Y + Q));
        __syncwarp();
#pragma unroll
        for (int n = 0; n < N; n++) {
#pragma unroll
            for (int x = 0; x < 2; x++) {
                uint32_t y[4];
                ldsm4t((yi ^ (x << 5)) + y_off(Q) + n * 256, y[0], y[1], y[2], y[3]);
#pragma unroll
                for (int e = 0; e < 2; e++) {
                    uint2& o = xq[n][2 * x + e];
                    o.x = hfma2_bc(gg[n][x], e, y[2 * e], o.x); o.y = hfma2_bc(gg[n][x], e, y[2 * e + 1], o.y);
                }
            }
        }
        if ((sw[0] | sw[N - 1]) == 0) {
#pragma unroll
            for (int n = 0; n < N; n++)
#pragma unroll
                for (int i = 0; i < 4; i++)
                    asm volatile("st.shared.v2.u32 [%0], {%1, %2};" :: "r"(os + Q * 1024 + n * 4 * TAB_W + i * 128), "r"(xq[n][i].x), "r"(xq[n][i].y) : "memory");
            asm volatile("fence.proxy.async.shared::cta;" ::: "memory");
            __syncwarp();
#pragma unroll
            for (int n = 0; n < N; n++)
                asm volatile("{\n\t.reg .pred p;\n\telect.sync _|p, 0xffffffff;\n\t"
                             "@p cp.async.bulk.tensor.3d.global.shared::cta.bulk_group [%1, {%2, %3, %4}], [%0];\n\t}"
                    :: "r"(ob + 4 * n * TAB_W + Q * 1024), "l"(tm_out), "r"(16 * pr), "r"(64 * Q + 32 * h), "r"(w + 4 * n) : "memory");
        } else {
            bf16* op = p.out + (size_t)(512 * Q + 256 * h + 8 * m8 + w) * D_ + 16 * pr + 4 * t;
#pragma unroll
            for (int n = 0; n < N; n++)
#pragma unroll
                for (int i = 0; i < 4; i++)
                    if (!((sw[n] >> (4 * g)) & (1u << i))) *(uint2*)(op + (size_t)(32 * i + 4 * n) * D_) = xq[n][i];
        }
    }
}

__global__ void __cluster_dims__(2, 1, 1) __launch_bounds__(NTHREADS, 1)
fused_kernel(const Params p, const __grid_constant__ CUtensorMap tm_gu, const __grid_constant__ CUtensorMap tm_down,
             const __grid_constant__ CUtensorMap tm_x, const __grid_constant__ CUtensorMap tm_out) {
    extern __shared__ __align__(1024) unsigned char smem[];
    const uint32_t sb = smem_u32(smem);
    int tid;
    asm volatile("mov.u32 %0, %%tid.x;" : "=r"(tid));
    const int pw = tid >> 5, lane = tid & 31;
    const int c = blockIdx.x, h = c & 1, pr = c >> 1;
    const uint32_t bars = sb + M_BARS;

    uint2 v_la, v_ai, v_cr, v_ci;
    uint32_t ldt16;
    {
        const uint32_t po = c * 256 + tid;
        asm volatile("{\n\t.reg .pred p;\n\t.reg .b64 a;\n\tsetp.ne.u32 p, %16, 0;\n\t"
                     "mad.wide.u32 a, %14, 8, %9;\n\t@p ld.global.nc.L1::no_allocate.v2.u32 {%0,%1}, [a];\n\t"
                     "mad.wide.u32 a, %15, 2, %13;\n\t@p ld.global.nc.u16 %8, [a];\n\t"
                     "mad.wide.u32 a, %14, 8, %10;\n\t@p ld.global.nc.L1::no_allocate.v2.u32 {%2,%3}, [a];\n\t"
                     "mad.wide.u32 a, %14, 8, %11;\n\t@p ld.global.nc.L1::no_allocate.v2.u32 {%4,%5}, [a];\n\t"
                     "mad.wide.u32 a, %14, 8, %12;\n\t@p ld.global.nc.L1::no_allocate.v2.u32 {%6,%7}, [a];\n\t}"
            : "=r"(v_la.x), "=r"(v_la.y), "=r"(v_ai.x), "=r"(v_ai.y), "=r"(v_cr.x), "=r"(v_cr.y), "=r"(v_ci.x), "=r"(v_ci.y), "=r"(ldt16)
            : "l"(p.logA), "l"(p.Aim), "l"(p.Cre), "l"(p.Cim), "l"(p.logdt), "r"(po), "r"(po >> 5), "r"((uint32_t)(tid < 256 && c < 128)));
    }

    if (c >= 128) {
        if (c != 128) return;
        RSTAMP(5);
        const unsigned tag = (*(volatile unsigned*)&p.sc->epoch + 1) & 0xffffu;
        const uint32_t list = sb + 128;
        sts128(list + 16 * tid, 0, 0, 0, 0);
        if (tid == 0) sts32(sb + 64, 0);
        uint32_t key[4] = {tag - 1, tag - 1, tag - 1, tag - 1};
#pragma unroll 1
        for (int it = 0; it < (1 << 22); it++) {
            uint32_t a[4];
            asm volatile("{\n\t.reg .b128 o, z;\n\t.reg .b64 l, u;\n\tmov.b64 l, {%5, %5};\n\tmov.b128 z, {l, l};\n\tatom.relaxed.gpu.global.exch.b128 o, [%4], z;\n\t"
                         "mov.b128 {l, u}, o;\n\tmov.b64 {%0, %1}, l;\n\tmov.b64 {%2, %3}, u;\n\t}"
                : "=r"(a[0]), "=r"(a[1]), "=r"(a[2]), "=r"(a[3]) : "l"(&p.sc->r[tid]), "r"(tag - 1) : "memory");
#pragma unroll
            for (int i = 0; i < 4; i++) if (((a[i] ^ tag) & 0xffffu) == 0) key[i] = a[i];
            if ((((key[0] ^ tag) | (key[1] ^ tag) | (key[2] ^ tag) | (key[3] ^ tag)) & 0xffffu) == 0) break;
        }
        WSTAMP(0);
        uint32_t m = 0;
#pragma unroll
        for (int i = 0; i < 4; i++) {
            key[i] = (key[i] & 0xffff0000u) | (uint32_t)(2047 - (4 * tid + i));
            m = max(m, key[i]);
        }
        const uint32_t wm = __reduce_max_sync(0xffffffffu, m);
        if (lane == 0) sts32(sb + pw * 4, wm);
        __syncthreads();
        uint32_t thr = 0xffffffffu;
#pragma unroll
        for (int i = 0; i < 4; i++) { const uint4 q = lds128(sb + 16 * i); thr = min(thr, min(max(q.x, q.y), max(q.z, q.w))); }
        if (thr != 1) WSTAMP(1);
        if (m >= thr) {
            uint32_t pos;
            asm volatile("atom.shared.add.u32 %0, [%1], %2;" : "=r"(pos) : "r"(sb + 64), "r"(4 * ((key[0] >= thr) + (key[1] >= thr) + (key[2] >= thr) + (key[3] >= thr))) : "memory");
#pragma unroll
            for (int i = 0; i < 4; i++) if (key[i] >= thr) { sts32(list + pos, key[i]); pos += 4; }
        }
        __syncthreads();
        const uint32_t nc4 = lds32(sb + 64);
        if (nc4 != 1) WSTAMP(2);
#pragma unroll 1
        for (uint32_t j = 4 * pw; j < nc4; j += 64) {
            const uint32_t mine = lds32(list + j);
            int rank = 0;
#pragma unroll 1
            for (uint32_t i = 0; i < nc4; i += 128) rank += __popc(__ballot_sync(0xffffffffu, lds32(list + i + 4 * lane) > mine));
            if (rank < 8 && lane == 0) sts32(sb + 96 + 4 * rank, mine);
        }
        __syncthreads();
        if (tid < 8 * NTOP) st_gpu32(&p.sc->top[tid >> 3][tid & 7], lds32(sb + 96 + 4 * (tid & 7)) | ((tag & 31) << 11));
        WSTAMP(3);
        WDUMP();
        return;
    }

    WSTAMP(0);
    if (pw < 8) {
        const int d = 8 * c + pw - MAIN_W0;
        if (lane == 0) asm volatile("cp.async.ca.shared.global [%0], [%1], 4;" :: "r"(sb + M_DSK + 4 * (pw - MAIN_W0)), "l"(p.Dskip + (d & ~1)) : "memory");
        asm volatile("barrier.cluster.arrive.relaxed.aligned;" ::: "memory");
        const int warp = pw - MAIN_W0;
        asm volatile("setmaxnreg.inc.sync.aligned.u32 160;");
        const int g = lane >> 2, t = lane & 3;
        const int mi = lane >> 3, r = lane & 7;
        const uint32_t TB = sb + OFF_TAB + warp * TAB_W;
        const uint32_t UB = sb + OFF_U + warp * U_CH;
        if (mi < 2) sts128(UB + mi * U_PL + r * 16, 0, 0, 0, 0);
        if (lane < 4) sts128(TB + lane * T_PL, 0, 0, 0, 0);
        sts128(sb + OFF_SCR + warp * 8192 + lane * 16, 0x3C00u, 0x3C00u, 0x3C00u, 0x3C00u);
        asm volatile("barrier.cluster.wait.acquire.aligned;" ::: "memory");
        __syncwarp();

        uint32_t cfix;
        {
            KSTAMP(4, v_la.x ^ v_ai.x ^ v_cr.x ^ v_ci.x ^ ldt16);
            const float dt = bf_round(exp_acc(__uint_as_float(ldt16 << 16)));
            float l2[4], li[4];
            {
                const uint32_t la[2] = {v_la.x, v_la.y}, ai[2] = {v_ai.x, v_ai.y};
                const float dt2 = -1.4426950408889634f * dt;
#pragma unroll
                for (int i = 0; i < 4; i++) {
                    l2[i] = bf_round(ex2f(((i & 1) ? bf_hi(la[i >> 1]) : bf_lo(la[i >> 1])) * 1.4426950408889634f)) * dt2;
                    li[i] = ((i & 1) ? bf_hi(ai[i >> 1]) : bf_lo(ai[i >> 1])) * dt;
                }
            }
            const uint32_t SX = sb + OFF_SCR + warp * 8192;
            const uint32_t sw = SX + (lane << 4);
#define PUT(buf, row, v) sts128(((sw + (row) * 512) ^ ((row) << 4)) + (buf) * 4096, v[0], v[1], v[2], v[3])
#define EMIT(bufa, rowa, bufb, rowb, xr, xi, k, kp) do { uint32_t pk[4], pd[4]; sched_fence(); \
                _Pragma("unroll") for (int i = 0; i < 4; i++) { pk[i] = pack_h(xr[i], xi[i]); pd[i] = hcmul(pk[i], k[i], kp[i]); } \
                PUT(bufa, rowa, pk); PUT(bufb, rowb, pd); } while (0)
#define CMUL4(orr, oi, ar, ai, br, bi) _Pragma("unroll") for (int i = 0; i < 4; i++) CMUL(orr[i], oi[i], ar[i], ai[i], br[i], bi[i])
#define CSQ4(orr, oi, ar, ai) _Pragma("unroll") for (int i = 0; i < 4; i++) CSQ(orr[i], oi[i], ar[i], ai[i])
            float z1r[4], z1i[4], z2r[4], z2i[4], z8r[4], z8i[4], z256r[4], z256i[4];
            uint32_t k4[4], k4p[4];
            float z4r[4], z4i[4];
#pragma unroll
            for (int i = 0; i < 4; i++) cexp_pow(l2[i], li[i], 1.f, z1r[i], z1i[i]);
            CSQ4(z2r, z2i, z1r, z1i);
            CSQ4(z4r, z4i, z2r, z2i);
            CSQ4(z8r, z8i, z4r, z4i);
            KSTAMP(5, __float_as_uint(z8r[3]));
            uint32_t Ya[16][4];
            float cr[4], ci[4], inv;
            {
                float w1r[4], w1i[4], ar[4], ai[4], br[4], bi[4];
                uint32_t k8[4], k8p[4];
#pragma unroll
                for (int i = 0; i < 4; i++) {
                    k8[i] = pack_h(z8r[i], -z8i[i]); k8p[i] = pack_h(z8i[i], z8r[i]);
                    CSQ(w1r[i], w1i[i], z8r[i], z8i[i]); w1i[i] = -w1i[i];
                }
                PUT(1, 0, k8);
                EMIT(0, 1, 1, 1, w1r, w1i, k8, k8p);
                CSQ4(ar, ai, w1r, w1i);            EMIT(0, 2, 1, 2, ar, ai, k8, k8p);
                CMUL4(br, bi, ar, ai, w1r, w1i);   EMIT(0, 3, 1, 3, br, bi, k8, k8p);
                CSQ4(ar, ai, ar, ai);              EMIT(0, 4, 1, 4, ar, ai, k8, k8p);
                CMUL4(ar, ai, ar, ai, w1r, w1i);   EMIT(0, 5, 1, 5, ar, ai, k8, k8p);
                CSQ4(br, bi, br, bi);              EMIT(0, 6, 1, 6, br, bi, k8, k8p);
                CMUL4(br, bi, br, bi, w1r, w1i);   EMIT(0, 7, 1, 7, br, bi, k8, k8p);
                __syncwarp();
                KSTAMP(6, 0);
                sched_fence();
                const uint32_t ab = SX + (mi & 1) * 4096 + r * 512, ax = ((mi >> 1) ^ r) << 4;
                const uint32_t vr[2] = {v_cr.x, v_cr.y}, vi[2] = {v_ci.x, v_ci.y};
                const uint32_t m2 = __vmaxu2(__vmaxu2(vr[0] & 0x7fff7fffu, vr[1] & 0x7fff7fffu), __vmaxu2(vi[0] & 0x7fff7fffu, vi[1] & 0x7fff7fffu));
                const uint32_t mx = __reduce_max_sync(0xffffffffu, max(m2, m2 << 16));
                const uint32_t e = min(max(mx >> 23, 11u), 254u);
                const float sc = __uint_as_float((264u - e) << 23);
                inv = __uint_as_float((e - 10u) << 23) * (2.f * dt);
#pragma unroll
                for (int i = 0; i < 4; i++) {
#pragma unroll
                    for (int k = 0; k < 4; k++) ldsm4(ab + (ax ^ (i << 5)) + k * 128, Ya[4 * k + i][0], Ya[4 * k + i][1], Ya[4 * k + i][2], Ya[4 * k + i][3]);
                    float tr, ti;
                    cexp_pow(l2[i], li[i], 128.f, tr, ti);
                    sts32(TB + 2176 + 256 * i + 4 * lane, pack_h(tr, ti));
                    sts32(TB + 2176 + 256 * i + 128 + 4 * (lane ^ 16), pack_h(-ti, tr));
                    k4[i] = pack_h(z4r[i], z4i[i]); k4p[i] = pack_h(-z4i[i], z4r[i]);
                    CSQ(z256r[i], z256i[i], tr, ti);
                    cr[i] = ((i & 1) ? bf_hi(vr[i >> 1]) : bf_lo(vr[i >> 1])) * sc;
                    ci[i] = ((i & 1) ? bf_hi(vi[i >> 1]) : bf_lo(vi[i >> 1])) * sc;
                    if (i < 3) sched_fence();
                }
                __syncwarp();
            }
            KSTAMP(7, Ya[15][0]);
            const uint32_t ld0 = SX + r * 512 + ((mi ^ r) << 4), ld1 = ld0 ^ 64;
            float R[6][4], s1024;
            {
                float xr[4], xi[4], yr[4], yi[4];
                EMIT(0, 0, 0, 1, cr, ci, k4, k4p);
                CMUL4(yr, yi, cr, ci, z1r, z1i);        EMIT(0, 2, 0, 3, yr, yi, k4, k4p);
                CMUL4(xr, xi, cr, ci, z256r, z256i);    EMIT(1, 0, 1, 1, xr, xi, k4, k4p);
                CMUL4(yr, yi, yr, yi, z1r, z1i);        EMIT(0, 4, 0, 5, yr, yi, k4, k4p);
                CMUL4(cr, ci, yr, yi, z256r, z256i);    EMIT(1, 2, 1, 3, cr, ci, k4, k4p);
                CMUL4(yr, yi, yr, yi, z1r, z1i);        EMIT(0, 6, 0, 7, yr, yi, k4, k4p);
                CMUL4(xr, xi, xr, xi, z256r, z256i);    EMIT(1, 4, 1, 5, xr, xi, k4, k4p);
                CMUL4(xr, xi, xr, xi, z256r, z256i);    EMIT(1, 6, 1, 7, xr, xi, k4, k4p);
                CMUL4(xr, xi, xr, xi, z256r, z256i);
                s1024 = (xr[0] + xr[1]) + (xr[2] + xr[3]);
#pragma unroll
                for (int m = 0; m < 4; m++) {
                    if (m == 0) { CMUL4(xr, xi, xr, xi, z8r, z8i); } else { CMUL4(xr, xi, xr, xi, z256r, z256i); }
                    sched_fence();
                    sts128(TB + m * T_PL + 16 + 16 * lane, pack_h(xr[0], xi[0]), pack_h(xr[1], xi[1]), pack_h(xr[2], xi[2]), pack_h(xr[3], xi[3]));
                }
            }
            __syncwarp();
            {
                KSTAMP(8, 0);
                uint32_t bd[2][4] = {{0, 0, 0, 0}, {0, 0, 0, 0}};
                const bool on = (g >> 1) == t;
#pragma unroll
                for (int i = 0; i < 6; i++) { R[i][0] = R[i][1] = R[i][2] = R[i][3] = 0.f; }
                uint32_t x[2][4], y[2][4], z[2][4];
                auto fetch = [&](const int k2) {
                    const int b = k2 & 1;
                    lds128_if(on, TB + 2176 + g * 128 + (k2 < 4 ? 64 : -64) * (g & 1) + 16 * k2, bd[b]);
                    ldsm4(((k2 & 1) ? ld1 : ld0) + (k2 >> 1) * 128, x[b][0], x[b][1], x[b][2], x[b][3]);
                    ldsm4(((k2 & 1) ? ld1 : ld0) + (k2 >> 1) * 128 + 4096, y[b][0], y[b][1], y[b][2], y[b][3]);
                    ldsm4(TB + (r & 3) * T_PL + 16 + 16 * mi + 64 * k2, z[b][0], z[b][1], z[b][2], z[b][3]);
                };
                fetch(0);
#pragma unroll
                for (int k2 = 0; k2 < 8; k2++) {
                    const int b = k2 & 1;
                    uint32_t a1[2][4];
                    if (k2 < 7) fetch(k2 + 1);
#pragma unroll
                    for (int u = 0; u < 2; u++) {
                        mma_hh_k8(a1[u][0], a1[u][1], Ya[2 * k2 + u][0], Ya[2 * k2 + u][1], bd[b][2 * u]);
                        mma_hh_k8(a1[u][2], a1[u][3], Ya[2 * k2 + u][2], Ya[2 * k2 + u][3], bd[b][2 * u + 1]);
                    }
#pragma unroll
                    for (int u = 0; u < 2; u++) {
                        const uint32_t(&a0)[4] = Ya[2 * k2 + u];
                        mma_h(R[0], a0[0], a0[1], a0[2], a0[3], x[b][2 * u], x[b][2 * u + 1]);
                        mma_h(R[2], a0[0], a0[1], a0[2], a0[3], y[b][2 * u], y[b][2 * u + 1]);
                        mma_h(R[4], a0[0], a0[1], a0[2], a0[3], z[b][2 * u], z[b][2 * u + 1]);
                        mma_h(R[1], a1[u][0], a1[u][1], a1[u][2], a1[u][3], x[b][2 * u], x[b][2 * u + 1]);
                        mma_h(R[3], a1[u][0], a1[u][1], a1[u][2], a1[u][3], y[b][2 * u], y[b][2 * u + 1]);
                        mma_h(R[5], a1[u][0], a1[u][1], a1[u][2], a1[u][3], z[b][2 * u], z[b][2 * u + 1]);
                    }
                }
            }
            __syncwarp();
            KSTAMP(9, __float_as_uint(R[3][0]));
            if (lane == 0) mbar_arrive(bars + 8 * B_KG + (__float_as_uint(R[0][0]) & __float_as_uint(R[2][0]) & p.zero));
            sts128(TB + 2176 + 16 * lane, 0, 0, 0, 0);
            sts128(TB + 2688 + 16 * lane, 0, 0, 0, 0);
            __syncwarp();
#undef PUT
#undef EMIT
#pragma unroll
            for (int o = 16; o > 0; o >>= 1) s1024 += __shfl_xor_sync(0xffffffffu, s1024, o);
            uint32_t w[4][4], dsk = 0;
            cp_wait_all();
            asm volatile("{\n\t.reg .pred p;\n\tsetp.eq.u32 p, %2, 0;\n\t@p ld.shared.u16 %0, [%1];\n\t}" : "+r"(dsk) : "r"(sb + M_DSK + 4 * warp + 2 * (warp & 1)), "r"(lane) : "memory");
#pragma unroll
            for (int a = 0; a < 4; a++) {
                const float v0 = (a == 0) ? fmaf(R[0][0], inv, __uint_as_float(dsk << 16)) : R[a][0] * inv;
                const float v1 = R[a][1] * inv, v2 = R[a][2] * inv, v3 = R[a][3] * inv;
                w[a][0] = pack_bf(v0, 0.f); w[a][1] = pack_bf(v1, v0); w[a][2] = pack_bf(v2, v1); w[a][3] = pack_bf(v3, v2);
            }
            const uint32_t wb = TB + 16 + 16 * g, w1 = wb + t * T_PL, w2 = wb + 256 + 2 * t * T_PL;
            const uint32_t w3 = (t == 0) ? wb + 256 + 3 * T_PL : TB + T_A + 8 * (16 * t + g);
            const uint32_t w3s = (t == 0) ? 128 : 64, w3o = (t == 0) ? 8 : 12;
            const uint32_t k512 = __shfl_sync(0xffffffffu, w[2][1], 2);
#pragma unroll
            for (int a = 0; a < 2; a++) {
                sts128(w1 + 128 * a, w[a][0], w[a][1], w[a][2], w[a][3]);
                const uint32_t(&q)[4] = w[2 + a];
                if (t < 2) sts128(w2 + 128 * a, q[0], q[1], q[2], q[3]);
                if (t == 0) { sts128(w2 + T_PL + 128 * a, q[0], q[1], q[2], q[3]); sts32(w3 + 128 * a + 4, q[2]); }
                sts32_if(t != 1 && (a == 1 || lane != 2), w3 + w3s * a, q[1]);
                sts32_if(t != 1, w3 + w3s * a + w3o, q[3]);
            }
            sts128_if(lane < 4, w1 + 512, t == 3 ? k512 : k512 >> 16, t < 2 ? k512 : t == 2 ? k512 & 0xffff0000u : k512 << 16, t < 2 ? k512 << 16 : 0u, 0);
            __syncwarp();
#pragma unroll
            for (int a = 0; a < 2; a++) {
                sts16(w1 + 128 * a + 18, w[a][3]);
                const uint32_t(&q)[4] = w[2 + a];
                if (t < 2) sts16(w2 + 128 * a + 18, q[3]);
                if (t == 0) { sts16(w2 + T_PL + 128 * a + 18, q[3]); sts16(w3 + 128 * a + 14, q[3]); }
            }
            if (t == 0) sts16(w3 + 128 - 4, w[3][0]);
            if (lane == 2 || (t == 0 && g > 0)) sts16(lane == 2 ? TB + 16 + 3 * T_PL + 4 * 127 : w3 - 4, w[2][0]);
            {
                float q[4];
#pragma unroll
                for (int i = 0; i < 4; i++) q[i] = (t < 2 ? R[4][i] : R[5][i]) * inv;
                const uint32_t b0 = pack_bf(q[0], q[2]), b1 = pack_bf(q[1], q[3]);
                const uint32_t wq = TB + T_B + 8 * (65 + 32 * (t & 1) + 4 * (t & 2) + g);
                sts32(wq, b0); sts32(wq + 12, b0); sts32(wq + 128, b1); sts32(wq + 140, b1);
            }
            cfix = pack_bf(s1024 * inv, s1024 * inv);
            if (lane == 0) sts32(TB + T_A + 8 * 64, cfix);
            __syncwarp();
        }
        WSTAMP(1);

        mbar_wait(bars + 8 * B_U);
        WSTAMP(2);

        float D[16][4];
        {
            const int x5 = g - t + 5;
            const uint32_t tabD = TB + (x5 & 3) * T_PL + (x5 & 12) + 16;
            {
                const uint32_t a1 = lds32(tabD - 8), a0 = p.zero;
#pragma unroll
                for (int jq = 0; jq < 4; jq++) {
                    uint32_t b[4];
                    ldsm4(UB + (9 + lane) * 16 + jq * 512, b[0], b[1], b[2], b[3]);
#pragma unroll
                    for (int i = 0; i < 4; i++) mma_bf_k8z(D[4 * jq + i], a0, a1, b[i]);
                }
            }
            const uint32_t ua = UB + (mi & 1) * U_PL + (8 + 8 * (mi >> 1) + r) * 16;
#pragma unroll 1
            for (int k0 = 0; k0 < 8; k0++) {
                uint32_t Uf[16][2];
#pragma unroll
                for (int jp = 0; jp < 8; jp++) ldsm4(ua + jp * 256 - k0 * 16, Uf[2 * jp][0], Uf[2 * jp][1], Uf[2 * jp + 1][0], Uf[2 * jp + 1][1]);
#pragma unroll
                for (int k1 = 0; k1 < 4; k1++) {
                    const uint32_t ta = tabD + 16 * (8 * k1 + k0);
                    const uint32_t a0 = lds32(ta), a1 = lds32(ta + 8), a2 = lds32(ta - 8), a3 = a0 ^ p.zero;
#pragma unroll
                    for (int J = k1; J < 16; J++) mma_bf(D[J], a0, a1, a2, a3, Uf[J - k1][0], Uf[J - k1][1]);
                }
                if (k0 == 0) {
                    const uint32_t ta = tabD + 16 * 32;
                    const uint32_t a0 = lds32(ta), a1 = lds32(ta + 8), a2 = lds32(ta - 8), a3 = a0 ^ p.zero;
#pragma unroll
                    for (int J = 4; J < 16; J++) mma_bf(D[J], a0, a1, a2, a3, Uf[J - 4][0], Uf[J - 4][1]);
                    const uint32_t f0 = (cfix ^ 0x80008000u) & (g == t ? 0xffffu : g == t + 4 ? 0xffff0000u : 0u);
                    const uint32_t f1 = p.zero, f2 = p.zero + p.zero, f3 = f0 ^ p.zero;
#pragma unroll
                    for (int J = 8; J < 16; J++) mma_bf(D[J], f0, f1, f2, f3, Uf[J - 8][0], Uf[J - 8][1]);
                }
            }
        }
        WSTAMP(3);
        {
            const int ch = 8 * h + warp;
            const uint32_t yo = sb + ch * 512 + ((lane ^ (((ch >> 2) << 1) | (ch & 1))) << 4);
            const uint32_t yr = mapa(yo, h ^ 1), ybr = mapa(bars + 8 * B_Y, h ^ 1);
            auto ship = [&](const int Q) {
                uint4 y[2];
#pragma unroll
                for (int hh = 0; hh < 2; hh++) {
                    const int J = 4 * Q + 2 * hh;
                    y[hh] = make_uint4(pack_bf(D[J][0], D[J][1]), pack_bf(D[J][2], D[J][3]), pack_bf(D[J + 1][0], D[J + 1][1]), pack_bf(D[J + 1][2], D[J + 1][3]));
                }
                if (!(Q & 1)) mbar_wait(bars + 8 * (B_F + (Q >> 1)));
                asm volatile("{\n\t.reg .pred p;\n\tsetp.eq.u32 p, %11, 0;\n\t"
                             "@p st.async.weak.shared::cluster.mbarrier::complete_tx::bytes.v4.b32 [%9], {%4,%5,%6,%7}, [%10];\n\t"
                             "@!p st.async.weak.shared::cluster.mbarrier::complete_tx::bytes.v4.b32 [%9], {%0,%1,%2,%3}, [%10];\n\t"
                             "@p st.shared.v4.b32 [%8], {%0,%1,%2,%3};\n\t@!p st.shared.v4.b32 [%8], {%4,%5,%6,%7};\n\t}"
                             :: "r"(y[0].x), "r"(y[0].y), "r"(y[0].z), "r"(y[0].w), "r"(y[1].x), "r"(y[1].y), "r"(y[1].z), "r"(y[1].w),
                                "r"(yo + y_off(Q)), "r"(yr + y_off(Q)), "r"(ybr + 8 * Q), "r"(h) : "memory");
                __syncwarp();
                if (lane == 0) mbar_arrive(bars + 8 * (B_Y + Q));
            };
            ship(0);
            const uint4 bA = lds128(sb + OFF_BAND + (g - t + 3) * 48), bB = lds128(sb + OFF_BAND + (g - t + 3) * 48 + 16);
            const uint2 bC = lds64(sb + OFF_BAND + (g - t + 3) * 48 + 32);
            uint2 QA[5][2], QB[8];
            const uint32_t tq = TB + 8 * (1 + g - 2 * t);
#pragma unroll
            for (int dd = 0; dd < 5; dd++) { QA[dd][0] = lds64(tq + T_A + 64 * (dd + 4)); QA[dd][1] = lds64(tq + T_A + 64 * (dd + 4) - 8); }
#pragma unroll
            for (int dd = 0; dd < 8; dd++) QB[dd] = lds64(tq + T_B + 64 * (dd + 8));
            const uint32_t u1 = UB + (mi & 1) * U_PL + (7 + r + (mi >> 1)) * 16;
            const uint32_t u2 = UB + ((mi & 1) ^ 1) * U_PL + (7 + r + (mi & 1) + 8 * (mi >> 1)) * 16;
            uint32_t n[4];
#pragma unroll
            for (int j = 0; j < 12; j++) {
                uint32_t m[4];
                ldsm4(u1 + j * 128, m[0], m[1], m[2], m[3]);
                if (!(j & 1)) ldsm4(u2 + j * 128, n[0], n[1], n[2], n[3]);
                const uint32_t n0 = n[2 * (j & 1)], n1 = n[2 * (j & 1) + 1];
                float wa[4], wb[4], wc[4], g1[4], g2[4];
                mma_bf_z(wa, bA.x, bA.y, bA.z, bA.w, m[0], m[1]);
                mma_bf_z(wb, bA.x, bA.y, bA.z, bA.w, n0, n1);
                mma_bf_z(wc, bA.x, bA.y, bA.z, bA.w, m[2], m[3]);
                if (j < 8) {
                    mma_bf_z(g1, bB.x, bB.y, bB.z, bB.w, m[0], m[1]);
                    mma_bf_z(g2, bB.x, bB.y, bB.z, bB.w, n0, n1);
                    mma_bf_k8(g1, bC.x, bC.y, m[2]);
                    mma_bf_k8(g2, bC.x, bC.y, m[3]);
                }
#pragma unroll
                for (int e = 0; e < 2; e++) {
                    const uint32_t q0 = pack_bf(wa[e], wa[e + 2]), q1 = pack_bf(wb[e], wb[e + 2]), q2 = q1 ^ p.zero, q3 = pack_bf(wc[e], wc[e + 2]);
#pragma unroll
                    for (int dd = 0; dd < 5; dd++)
                        if (j + 4 + dd < 16) mma_bf(D[j + 4 + dd], q0, q1, q2, q3, QA[dd][e].x, QA[dd][e].y);
                }
                if (j < 8) {
                    const uint32_t q0 = pack_bf(g1[0], g1[2]), q1 = pack_bf(g2[0], g2[2]), q2 = pack_bf(g1[1], g1[3]), q3 = pack_bf(g2[1], g2[3]);
#pragma unroll
                    for (int dd = 7 - j; dd >= 0; dd--) mma_bf(D[j + 8 + dd], q0, q1, q2, q3, QB[dd].x, QB[dd].y);
                }
                if ((j & 3) == 3) {
                    WSTAMP(4 + 2 * (j >> 2));
                    ship((j >> 2) + 1);
                }
            }
        }
        const int warpu = __reduce_max_sync(0xffffffffu, warp);
        mix_rows<1>(p, &tm_out, sb, sb + OFF_U + warpu * U_CH + (warpu & 1) * 64, PQ, 4, warpu, h, pr, lane);
        asm volatile("cp.async.bulk.commit_group;\n\tcp.async.bulk.wait_group.read 0;" ::: "memory");
        WSTAMP(10);
        WDUMP();
    } else if ((pw & 12) == AUX_W0) {
        const int v = __reduce_max_sync(0xffffffffu, pw & 3);
        const int at = tid & 127;
        const int g = lane >> 2, t = lane & 3;
        unsigned tag;
        const bool gu = c < NGU_CTA;
        {
            const uint32_t xb = sb + (v < 2 ? OFF_XSEL : OFF_RING + 2 * 8192) + v * 8192;
            const uint32_t gws = sb + M_DPIN;
            const uint32_t row = 16 * c + 4 * v + (g >> 1);
#pragma unroll
            for (int i = 0; i < 8; i++)
                asm volatile("cp.async.ca.shared.global [%0], [%1], 4;" :: "r"((i < 4 ? sb + OFF_GP : gws) + 512 * (i & 3) + (tid & 124) * 4 + (tid & 1) * 8 + (tid & 2) * 2),
                             "l"((i < 4 ? p.wr : p.gatew) + 256 * (i & 3) + (tid & 127) * 2) : "memory");
            if ((tid & 127) < 33) cp16(sb + OFF_BAND + (tid & 127) * 16, p.band + (tid & 127));
            asm volatile("barrier.cluster.arrive.relaxed.aligned;" ::: "memory");
            tag = __reduce_max_sync(0xffffffffu, (*(volatile unsigned*)&p.sc->epoch + 1) & 0xffffu);
            if (gu) st_gpu32((uint32_t*)&p.sc->h[(tag + 1) & 1][32 * c] + at, 0);
            if (v == 2) sts32(sb + M_BMAP + lane * 4, 0);
            if (at == 0) sts32(sb + M_TAG, tag << 16);
            cp_wait_all();
            bar_sync(1, 128);
            uint2 w[16];
#pragma unroll
            for (int kb = 0; kb < 16; kb++) w[kb] = lds64((g < 4 ? sb + OFF_GP : gws) + 128 * kb + 32 * (g & 2) + 16 * t + 8 * (g & 1));
            asm volatile("barrier.cluster.wait.acquire.aligned;" ::: "memory");
            mbar_wait(bars + 8 * (B_X + v));
            WSTAMP(10);
            float dr[4][4];
#pragma unroll
            for (int kb = 0; kb < 16; kb++) {
                const uint4 x = lds128(xb + (g >> 1) * 2048 + 128 * kb + 16 * (lane & 7));
                if (kb < 4) mma_bf_z(dr[kb], x.x, x.y, x.z, x.w, w[kb].x, w[kb].y);
                else mma_bf(dr[kb & 3], x.x, x.y, x.z, x.w, w[kb].x, w[kb].y);
            }
            float rs = ((dr[0][0] + dr[0][3]) + (dr[1][0] + dr[1][3])) + ((dr[2][0] + dr[2][3]) + (dr[3][0] + dr[3][3]));
            if (lane == 0) mbar_arrive(bars + 8 * (B_XE + v) + (__float_as_uint(rs) & p.zero));
            rs += __shfl_xor_sync(0xffffffffu, rs, 5);
            const uint32_t rb = pack_bf(0.f, rs);
            if (!(lane & 7)) st_gpu32((uint32_t*)p.sc->r + row, ((rb ^ (((int)rb >> 31) | 0x80000000u)) & 0xffff0000u) | tag);
            WSTAMP(1);
            {
                const int n = 3 + (lane >> 3) + 4 * (lane & 1);
                const uint32_t so = (n & 7) * S_PL + ((lane & 6) + (n >> 3)) * 32;
                const uint32_t src[2] = {sb + OFF_S + v * S_Q + s_addr(so, h), sb + OFF_S + v * S_Q + s_addr(so + 32, h)};
                const uint32_t dst = sb + OFF_U + g * U_CH + (8 + 32 * v + 16 * h + t) * 16;
                const uint32_t rdst = mapa(dst, h ^ 1), rbar = mapa(bars + 8 * B_U, h ^ 1);
                mbar_wait(bars + 8 * (B_S + v));
                WSTAMP(9);
                uint4 a[8];
#pragma unroll
                for (int b = 0; b < 2; b++) {
#pragma unroll
                    for (int j = 0; j < 8; j++) { const int u = 4 * b + (j >> 1) + 8 * (j & 1); ldsm4t((u < 8 ? src[u & 1] ^ 16 : src[u & 1]) + ((u >> 1) & 3) * 256, a[j].x, a[j].y, a[j].z, a[j].w); }
#pragma unroll
                    for (int j = 0; j < 8; j++) {
                        const int u = 4 * b + (j >> 1) + 8 * (j & 1);
                        if (u < 8) st_async16(rdst + ((u >> 1) & 3) * 64 + (u & 1) * U_PL, a[j], rbar);
                        else sts128(dst + ((u >> 1) & 3) * 64 + (u & 1) * U_PL, a[j].x, a[j].y, a[j].z, a[j].w);
                    }
                }
                if (h && v == 3) {
                    ldsm4t((src[0] ^ 16) + 1024, a[0].x, a[0].y, a[0].z, a[0].w);
                    ldsm4t(src[0] + 1024, a[1].x, a[1].y, a[1].z, a[1].w);
                    if (t == 0) {
                        st_async16(rdst + 256, make_uint4(a[0].x, a[0].y & 0xffffu, a[0].z & 0xffffu, a[0].w & 0xffffu), rbar);
                        sts128(dst + 256, a[1].x, a[1].y & 0xffffu, a[1].z & 0xffffu, a[1].w & 0xffffu);
                    }
                }
                __syncwarp();
                if (lane == 0) mbar_arrive(bars + 8 * B_U);
            }
            if ((lane & 7) == 2) st_gpu32((uint32_t*)p.sc->g + ((row & 256) << 2) + gate_pos(row), pack_bf(sigmoid_f(__uint_as_float(rb)), 0.f) | (tag << 16));
            WSTAMP(2);
        }
        {
            const bool lane0 = pin(lane, lane) == 0;
            const uint32_t own = pin(sb + OFF_XSEL + (at ^ ((at >> 1) & 4)) * 16, lane);
            float acc[8][4];
#pragma unroll
            for (int i = 0; i < 8; i++) { acc[i][0] = acc[i][1] = acc[i][2] = acc[i][3] = 0.f; }
            const int krow = ((lane >> 1) & 8) + (lane & 7);
            const uint32_t tile0 = pin(sb + OFF_RING + krow * 64 + ((((lane >> 3) & 1) ^ ((krow >> 1) & 3)) << 4), lane);
            const uint32_t xo = pin(sb + OFF_XSEL + (lane & 7) * XS_ROW + 512 * v + 2 * (lane & 24), lane);
            const uint32_t po = pin(sb + OFF_XSEL + t * XS_ROW + (g & 3) * 128 + (g & 1) * 64 + v * 16 + (lane >> 4) * 8, lane);
            const uint32_t po1 = pin(po + 64 - (g & 1) * 128, lane);
            uint32_t* hdst = pin((uint32_t*)&p.sc->h[tag & 1][32 * c] + at, lane);
            auto signal = [&](const int k, const uint32_t dep) {
                if (lane < 2 && v < 2)
                    asm volatile("st.async.weak.shared::cluster.mbarrier::complete_tx::bytes.b32 [%0], %1, [%2];"
                                 :: "r"(mapa(sb + M_SINK, lane)), "r"(dep), "r"(mapa(bars + 8 * (B_F + k), lane)) : "memory");
            };
#pragma unroll 1
            for (int i = 0; i < 4; i++) {
                const int s = 4 * i + v;
                uint32_t a[16][4], b[2][4];
                if (gu) {
                    const uint32_t tile = tile0 + (s < 14 ? s : v) * 8192;
                    if (lane0 && i > 1) mbar_arrive(bars + 8 * (B_E + s - 4));
                    if (i == 2) signal(0, 0);
                    mbar_wait(bars + 8 * (B_W + s));
#pragma unroll
                    for (int q = 0; q < 16; q++) ldsm4t((tile ^ ((q & 1) << 5)) + ((q >> 1) & 1) * 4096 + (q >> 2) * 1024, a[q][0], a[q][1], a[q][2], a[q][3]);
                }
                if (i == 0) {
                    if (gu) {
                        uint32_t dep = p.zero;
#pragma unroll
                        for (int q = 0; q < 16; q += 2) dep &= a[q][0] & a[q + 1][0];
                        if (lane == 0) mbar_arrive(bars + 8 * (B_E + v) + dep);
                    }
                    WSTAMP(11);
                    uint32_t top;
#pragma unroll 1
                    for (int it = 0; it < (1 << 22); it++) {
                        asm volatile("ld.relaxed.gpu.global.u32 %0, [%1];" : "=r"(top) : "l"(&p.sc->top[c % NTOP][g]) : "memory");
                        if (__all_sync(0xffffffffu, ((top ^ (tag << 11)) & 0xf800u) == 0)) break;
                        __nanosleep(40);
                    }
                    WSTAMP(3);
                    if (gu) {
                        const uint32_t k = 4 * h + v, row = __reduce_max_sync(0xffffffffu, lane == 4 * k ? ~top & 2047 : 0);
                        asm volatile("{\n\t.reg .pred p;\n\telect.sync _|p, 0xffffffff;\n\t"
                                     "@p cp.async.bulk.shared::cluster.global.mbarrier::complete_tx::bytes.multicast::cluster [%0], [%1], 2048, [%2], %3;\n\t}"
                            :: "r"(sb + OFF_XSEL + k * XS_ROW), "l"(p.u + (size_t)row * D_), "r"(bars + 8 * B_G), "h"((unsigned short)3) : "memory");
                    }
                    if (v == 2) {
                        const uint32_t row = ~top & 2047;
                        if (t == 0 && ((row >> 8) & 1) == h)
                            asm volatile("red.shared.or.b32 [%0], %1;" :: "r"(sb + M_BMAP + (row & 7) * 16 + (row >> 9) * 4), "r"(1u << (gate_pos(row) & 31)) : "memory");
                        if (t == 0) sts32(sb + M_TOP + lane, top);
                        if (c == 0 && lane == 0) *(volatile unsigned*)&p.sc->epoch = tag;
                        __syncwarp();
                        if (lane0) mbar_arrive(bars + 8 * B_Y);
                    }
                    if (!gu) break;
                    mbar_wait(bars + 8 * B_G);
                    WSTAMP(4);
                }
                ldsm4(xo + 128 * i, b[0][0], b[0][1], b[0][2], b[0][3]);
                ldsm4(xo + 128 * i + 64, b[1][0], b[1][1], b[1][2], b[1][3]);
#pragma unroll
                for (int q = 0; q < 16; q++) mma_bf(acc[q & 7], a[q][0], a[q][1], a[q][2], a[q][3], b[q >> 3][(q >> 1) & 2], b[q >> 3][((q >> 1) & 2) + 1]);
            }
            if (gu) {
                WSTAMP(5);
                __syncwarp();
#pragma unroll
                for (int q = 0; q < 4; q++) {
                    const int ct = q >> 1, e = 2 * (q & 1);
                    sts128(own + q * XS_ROW,
                           __float_as_uint(acc[ct][e] + acc[4 + ct][e]), __float_as_uint(acc[2 + ct][e] + acc[6 + ct][e]),
                           __float_as_uint(acc[ct][e + 1] + acc[4 + ct][e + 1]), __float_as_uint(acc[2 + ct][e + 1] + acc[6 + ct][e + 1]));
                }
                bar_sync(1, 128);
                float sl[2], uv[2];
#pragma unroll
                for (int e = 0; e < 2; e++) {
                    uint2 q[4];
#pragma unroll
                    for (int i = 0; i < 4; i++) q[i] = lds64((e ? po1 : po) + 512 * i);
                    const float s0 = (__uint_as_float(q[0].x) + __uint_as_float(q[1].x)) + (__uint_as_float(q[2].x) + __uint_as_float(q[3].x));
                    const float s1 = (__uint_as_float(q[0].y) + __uint_as_float(q[1].y)) + (__uint_as_float(q[2].y) + __uint_as_float(q[3].y));
                    const float gv = bf_round(p.gu_swap ? s1 : s0);
                    uv[e] = p.gu_swap ? s0 : s1;
                    sl[e] = gv * sigmoid_f(gv);
                }
                const uint32_t hw = hmul2_bf(pack_bf(sl[0], sl[1]), pack_bf(uv[0], uv[1]));
                st_gpu32(hdst, hw ? hw : 0x80000000u);
                signal(1, hw);
            }
        }
        WSTAMP(6);
        {
            const uint32_t own = pin(sb + OFF_XSEL + at * 16, lane);
            const uint32_t hb = sb + (v < 2 ? OFF_XSEL + 7168 * v : OFF_RING + 8192 * v), hl = pin(hb + 16 * lane, lane);
            const int krow = ((lane >> 1) & 8) + (lane & 7);
            const uint32_t tile = pin(sb + OFF_RING + v * 8192 + krow * 32 + ((((lane >> 3) ^ (krow >> 2)) & 1) << 4), lane);
            float dd[4][4];
            bar_sync(1, 128);
            mbar_wait(bars + 8 * (B_W + HW));
            WSTAMP(12);
            uint4 hq[7];
#pragma unroll 1
            for (int it = 0; it < (1 << 16); it++) {
                bulk_load(hb, &p.sc->h[tag & 1][32 * (56 * h + 14 * v)], 7168, bars + 8 * (B_X + v));
                uint32_t a[14][4], mn = 0xffffffffu;
                mbar_wait(bars + 8 * (B_W + 16 + v));
#pragma unroll
                for (int j = 0; j < 14; j++) ldsm4t(tile + (v & 2) * 16384 + j * 512, a[j][0], a[j][1], a[j][2], a[j][3]);
                mbar_wait(bars + 8 * (B_X + v), ~it & 1);
                WSTAMP(7);
#pragma unroll
                for (int j = 0; j < 7; j++) {
                    const uint4 q = lds128(hl + 512 * j);
                    mn = min(mn, q.x);
#pragma unroll
                    for (int e = 0; e < 2; e++) {
                        const uint32_t(&f)[4] = a[2 * j + e];
                        if (j < 2) mma_bf_z(dd[2 * j + e], f[0], f[1], f[2], f[3], e ? q.z : q.x, e ? q.w : q.y);
                        else mma_bf(dd[(2 * j + e) & 3], f[0], f[1], f[2], f[3], e ? q.z : q.x, e ? q.w : q.y);
                    }
                }
#pragma unroll
                for (int j = 0; j < 7; j++) { hq[j] = lds128(hl + 3584 + 512 * j); mn = min(mn, hq[j].x); }
                if (__all_sync(0xffffffffu, mn != 0)) break;
            }
            mbar_wait(bars + 8 * (B_W + 20 + v));
#pragma unroll
            for (int j = 0; j < 14; j++) {
                uint32_t f[4];
                ldsm4t(tile + 65536 + j * 512, f[0], f[1], f[2], f[3]);
                mma_bf(dd[(j + 2) & 3], f[0], f[1], f[2], f[3], (j & 1) ? hq[j >> 1].z : hq[j >> 1].x, (j & 1) ? hq[j >> 1].w : hq[j >> 1].y);
            }
            WSTAMP(8);
            uint4 part;
            part.x = __float_as_uint((dd[0][0] + dd[1][0]) + (dd[2][0] + dd[3][0])); part.y = __float_as_uint((dd[0][1] + dd[1][1]) + (dd[2][1] + dd[3][1]));
            part.z = __float_as_uint((dd[0][2] + dd[1][2]) + (dd[2][2] + dd[3][2])); part.w = __float_as_uint((dd[0][3] + dd[1][3]) + (dd[2][3] + dd[3][3]));
            st_async16(mapa(own + (M_DPIN - OFF_XSEL), h ^ 1), part, mapa(bars + 8 * B_DP, h ^ 1));
            sts128(own + 14336, part.x, part.y, part.z, part.w);
            __syncwarp();
            if (lane == 0) mbar_arrive(bars + 8 * B_DP);
        }
        WDUMP();
    } else {
        asm volatile("setmaxnreg.dec.sync.aligned.u32 64;");
        const int v = __reduce_max_sync(0xffffffffu, pw - PREP_W0);
        const bool gu = c < NGU_CTA;
        const uint32_t t0 = clock();
        const uint32_t bu = bars + 8 * v;
        if (lane == 0) {
#pragma unroll
            for (int i = 0; i < 10; i++) mbar_init(bu + 32 * i, 1);
            mbar_init(bu + 8 * B_X, 1);
            mbar_init(bu + 8 * B_XE, 1);
            mbar_init(bu + 8 * B_Y, v == 0 ? 11 : 9);
            mbar_init(bu + 8 * B_DP, (0x1855 >> (4 * v)) & 15);
            mbar_init(bu + 8 * B_F, 1);
            mbar_init(bu + 8 * B_H, 1);
            asm volatile("fence.mbarrier_init.release.cluster;" ::: "memory");
            mbar_expect(bu + 8 * B_Y, 4096);
            if (v != 2) mbar_expect(bu + 8 * B_DP, v == 0 ? 2048 : (h || v == 3) ? 16384 : 16384 + 128);
            mbar_expect(bu + 8 * B_F, c < NGU_CTA ? 16 : 0);
        }
        __syncwarp();
        asm volatile("barrier.cluster.arrive.relaxed.aligned;" ::: "memory");
        bulk_load(sb + (v < 2 ? OFF_XSEL : OFF_RING + 2 * 8192) + v * 8192, p.u + (size_t)(16 * c + 4 * v) * D_, 8192, bu + 8 * B_X);
        tma3d(sb + OFF_S + v * S_Q, &tm_x, 16 * pr, 64 * v + 32 * h - 1, bars + 8 * (B_S + v), S_Q);
        WSTAMP(9);
        if (v < 3 && lane == 0) asm volatile("prefetch.tensormap [%0];" :: "l"(v == 0 ? &tm_gu : v == 1 ? &tm_down : &tm_out) : "memory");
        asm volatile("barrier.cluster.wait.acquire.aligned;" ::: "memory");
        uint32_t desc;
        {
            const int s = 6 * v + lane, i = s >> 2, w = s & 3, slot = s < 14 ? s : (s | 1) == 17 ? s - 16 : s - 12;
            const int fb = s < 4 ? B_H : (gu && s >= 14) ? B_E + slot : s < 6 ? B_XE + s - 2 : B_KG;
            desc = slot | (fb << 4) | ((i < 4 ? 256 * w + 64 * i : 1792 * h + 448 * w + 224 * (i - 4)) << 10);
            if (lane < 6) mbar_expect(bars + 8 * (B_W + s), i < 4 ? 8192 : 7168);
            if (tid == 32 * PREP_W0) mbar_arrive(bars + 8 * B_H);
        }
        if (v == 3) {
            mbar_wait(bars + 8 * B_U);
            mbar_wait(bars + 8 * (gu ? B_G : B_H + 2));
            const uint32_t tag16 = lds32(sb + M_TAG);
            uint4 q[8];
#pragma unroll 1
            for (int it = 0; it < (1 << 22); it++) {
                uint32_t bad = 0;
#pragma unroll
                for (int i = 0; i < 8; i++) q[i] = ld_gpu128(&p.sc->g[256 * h + 32 * i + lane]);
#pragma unroll
                for (int i = 0; i < 8; i++) bad |= ((q[i].x ^ tag16) | (q[i].y ^ tag16)) | ((q[i].z ^ tag16) | (q[i].w ^ tag16));
                if ((bad >> 16) == 0) break;
                __nanosleep(200);
            }
#pragma unroll
            for (int i = 0; i < 8; i++)
                asm volatile("st.shared.v2.u32 [%0], {%1, %2};" :: "r"(sb + OFF_GP + 256 * i + lane * 8),
                             "r"(__byte_perm(q[i].x, q[i].y, 0x5410)), "r"(__byte_perm(q[i].z, q[i].w, 0x5410)) : "memory");
            __syncwarp();
            if (lane == 0) mbar_arrive(bars + 8 * B_Y);
        }
        mbar_wait(bars + 8 * (B_H + v));
        {
            const int gap = v == 0 ? GAP : v == 1 ? GAP1 : v == 2 ? GAP2 : GAP3;
            uint32_t last = v ? clock() - SLACK : t0 + T0 - GAP + GAP * ((pr * 5) & 15) / 16;
#pragma unroll 1
            while ((int)(last - clock()) > 500) __nanosleep(256);
#pragma unroll 1
            for (int k = 0; k < 6; k++) {
                const uint32_t dk = __reduce_max_sync(0xffffffffu, lane == k ? desc : 0);
                const bool dn = 6 * v + k >= 16;
                mbar_wait(bars + ((dk >> 1) & 0x1f8));
                uint32_t now;
#pragma unroll 1
                while ((int)((now = clock()) - last) < gap) __nanosleep(50);
                last = max((int)(now - last) - SLACK, gap) + last;
                WSTAMP(3 + k);
                if (gu || dn)
                    asm volatile("{\n\t.reg .pred p;\n\telect.sync _|p, 0xffffffff;\n\t"
                                 "@p cp.async.bulk.tensor.3d.shared::cluster.global.mbarrier::complete_tx::bytes [%0], [%1, {%3, %4, 0}], [%2];\n\t}"
                        :: "r"(sb + OFF_RING + (dk & 15) * 8192), "l"(dn ? &tm_down : &tm_gu), "r"(bars + 8 * (B_W + 6 * v + k)), "r"(dn ? 16 * pr : 32 * c), "r"(dk >> 10) : "memory");
                if (k < 5) __nanosleep(64);
            }
            if (lane == 0 && v < 3) mbar_arrive(bars + 8 * (B_H + v + 1));
        }
        {
            WSTAMP(1);
            mix_rows<2>(p, &tm_out, sb, sb + OFF_TAB + v * TAB_W, 0, PQ, v, h, pr, lane);
            WSTAMP(2);
            asm volatile("cp.async.bulk.commit_group;" ::: "memory");
            const uint32_t top = lds32(sb + M_TOP + 8 * v + 4 * (lane >> 4));
            const uint32_t row = ~top & 2047, ch = lane & 15, gp = gate_pos(row);
            const bool mine = ((row >> 8) & 1) == h;
            uint32_t gfin, x16, y16 = 0;
            asm volatile("ld.shared.u16 %0, [%1];" : "=r"(gfin) : "r"(sb + OFF_GP + gp * 2) : "memory");
            asm volatile("ld.shared.u16 %0, [%1];" : "=r"(x16) : "r"(sb + OFF_S + (row >> 9) * S_Q + s_addr((row & 7) * S_PL + 32 + (row & 248) * 4, ch >> 3) + 2 * (ch & 7)) : "memory");
            const float rsel = __uint_as_float(pin(__float_as_uint(bf_round(sigmoid_f(__uint_as_float((top ^ (((int)~top >> 31) | 0x80000000u)) & 0xffff0000u)))), lane));
            const uint32_t po = pin(sb + (4 * (ch & 7) + v) * 16 + (ch >> 3) * 8 + (lane >> 4) * 4, lane);
            bf16* op = pin(p.out + (size_t)row * D_ + 16 * pr + ch, lane);
            if (mine) {
                mbar_wait(bars + 8 * (B_Y + (row >> 9)));
                asm volatile("ld.shared.u16 %0, [%1];" : "=r"(y16)
                             : "r"(sb + y_off(row >> 9) + ch * 512 + (((4 * (row & 7) + ((row >> 5) & 3)) ^ (((ch >> 2) << 1) | (ch & 1))) << 4) + 2 * row_elem(row)) : "memory");
            }
            mbar_wait(bars + 8 * B_DP);
            float q[8];
#pragma unroll
            for (int i = 0; i < 4; i++) { q[i] = ldsf(po + M_DPIN + 512 * i); q[4 + i] = ldsf(po + OFF_XSEL + 14336 + 512 * i); }
            const float tot = ((q[0] + q[1]) + (q[2] + q[3])) + ((q[4] + q[5]) + (q[6] + q[7]));
            const float b = bf_round(__uint_as_float(x16 << 16) + bf_round(bf_round(tot) * rsel));
            if (mine) *op = __float2bfloat16_rn(fmaf(bf_lo(gfin), __uint_as_float(y16 << 16), bf_round(bf_round(1.f - bf_lo(gfin)) * b)));
        }
        asm volatile("cp.async.bulk.wait_group.read 0;" ::: "memory");
        WSTAMP(10);
        WDUMP();
    }
}

typedef CUresult (*EncodeFn)(CUtensorMap*, CUtensorMapDataType, cuuint32_t, void*, const cuuint64_t*, const cuuint64_t*,
                             const cuuint32_t*, const cuuint32_t*, CUtensorMapInterleave, CUtensorMapSwizzle,
                             CUtensorMapL2promotion, CUtensorMapFloatOOBfill);

void make_map(EncodeFn f, CUtensorMap* m, const void* ptr, uint64_t cols, uint64_t rows, uint64_t pitch, uint32_t bc, uint32_t br, CUtensorMapSwizzle sw, CUtensorMapL2promotion prom,
              uint32_t planes = 1, uint64_t plane_stride = 0, uint32_t box_planes = 0) {
    cuuint64_t dims[3] = {cols, rows, planes};
    cuuint64_t str[2] = {pitch, planes > 1 ? plane_stride : pitch * rows};
    cuuint32_t box[3] = {bc, br, box_planes ? box_planes : planes};
    cuuint32_t es[3] = {1, 1, 1};
    f(m, CU_TENSOR_MAP_DATA_TYPE_BFLOAT16, 3, (void*)ptr, dims, str, box, es, CU_TENSOR_MAP_INTERLEAVE_NONE, sw,
      prom, CU_TENSOR_MAP_FLOAT_OOB_FILL_NONE);
}

}

extern "C" void kernel_launch(void* const* d_in, const int* in_sizes, int n_in, void* d_out, int out_size) {
    static EncodeFn enc = nullptr;
    static void *sc = nullptr, *band = nullptr;
    if (!enc) {
        void* fn = nullptr;
        cudaDriverEntryPointQueryResult qr;
        cudaGetDriverEntryPoint("cuTensorMapEncodeTiled", &fn, cudaEnableDefault, &qr);
        enc = (EncodeFn)fn;
        cudaGetSymbolAddress(&sc, g_scratch);
        cudaGetSymbolAddress(&band, g_band);
        cudaFuncSetAttribute(fused_kernel, cudaFuncAttributeMaxDynamicSharedMemorySize, SMEM_BYTES);
    }
    CUtensorMap tg, td, tx, to;
    const char *wg = (const char*)d_in[9], *wu = (const char*)d_in[10];
    const bool swap = wu < wg;
    make_map(enc, &tg, swap ? wu : wg, F_, D_, F_ * 2, 32, 64, CU_TENSOR_MAP_SWIZZLE_64B, CU_TENSOR_MAP_L2_PROMOTION_L2_128B, 2, swap ? wg - wu : wu - wg);
    make_map(enc, &td, d_in[11], D_, F_, D_ * 2, 16, 224, CU_TENSOR_MAP_SWIZZLE_32B, CU_TENSOR_MAP_L2_PROMOTION_L2_64B);
    make_map(enc, &tx, d_in[0], D_, L_ / 8, D_ * 16, 16, 33, CU_TENSOR_MAP_SWIZZLE_32B, CU_TENSOR_MAP_L2_PROMOTION_NONE, 8, D_ * 2);
    make_map(enc, &to, d_out, D_, L_ / 8, D_ * 16, 16, 32, CU_TENSOR_MAP_SWIZZLE_NONE, CU_TENSOR_MAP_L2_PROMOTION_NONE, 8, D_ * 2, 1);
    Params p;
    p.u = (const bf16*)d_in[0]; p.logA = (const bf16*)d_in[1]; p.Aim = (const bf16*)d_in[2];
    p.Cre = (const bf16*)d_in[3]; p.Cim = (const bf16*)d_in[4]; p.logdt = (const bf16*)d_in[5];
    p.Dskip = (const bf16*)d_in[6]; p.wr = (const bf16*)d_in[8]; p.gatew = (const bf16*)d_in[12];
    p.out = (bf16*)d_out;
    p.sc = (Scratch*)sc; p.band = (const uint4*)band;
    p.gu_swap = swap;
    p.zero = 0;
    fused_kernel<<<NCTA, NTHREADS, SMEM_BYTES>>>(p, tg, td, tx, to);
}
```

```cpp
#include <cuda_runtime.h>
#include <cuda_bf16.h>
#include <cuda_fp16.h>
#include <cuda.h>
#include <stdint.h>

typedef __nv_bfloat16 bf16;

namespace {

constexpr int L_ = 2048, D_ = 1024, F_ = 3584;
constexpr int NCTA = 130;
constexpr int NTHREADS = 512;
constexpr int MAIN_W0 = 0, PREP_W0 = 8, AUX_W0 = 12;
#define T0 3150
#define GAP 510
#define GAP1 515
#define GAP2 515
#define GAP3 560
#define HW 20
constexpr int SLACK = 300;
constexpr int PQ = 3;
constexpr int NGU_CTA = 112;

constexpr int OFF_RING = 0;
constexpr int OFF_SCR  = 6 * 8192;
constexpr int S_PL     = 1056;
constexpr int S_Q      = 8 * S_PL;
constexpr int OFF_S    = 114688;
constexpr int OFF_GP   = OFF_S + 4 * S_Q;
constexpr int U_PL     = 2240;
constexpr int U_CH     = 4416;
constexpr int OFF_U    = 151552;
constexpr int TAB_W    = 3200;
constexpr int T_PL     = 544;
constexpr int T_A      = 2192 - 26 * 8;
constexpr int T_B      = 2568 - 59 * 8;
constexpr int OFF_TAB  = 186880;
constexpr int OFF_XSEL = 212480;
constexpr int XS_ROW   = 2064;
constexpr int OFF_BAND = 228992;
constexpr int OFF_MISC = 229536;
constexpr int M_BARS   = OFF_MISC;
constexpr int M_DSK    = OFF_MISC + 2736;
constexpr int M_SINK   = OFF_MISC + 512;
constexpr int M_TAG    = OFF_MISC + 516;
constexpr int M_BMAP   = OFF_MISC + 528;
constexpr int M_DPIN   = OFF_MISC + 656;
constexpr int M_TOP    = OFF_MISC + 2704;
constexpr int SMEM_BYTES = OFF_MISC + 2768;
__device__ __forceinline__ uint32_t s_addr(uint32_t o, uint32_t half) { return o + (((half ^ (o >> 7)) & 1) << 4); }
__host__ __device__ constexpr uint32_t y_off(uint32_t q) { return OFF_RING + 32768 + (q & 1) * 8192 + (q >> 1) * 65536; }

constexpr int B_W = 0;
constexpr int B_E = 24;
constexpr int B_S = 36;
constexpr int B_Y = 40;
constexpr int B_DP = 44, B_U = 45, B_KG = 46, B_G = 47;
constexpr int B_F = 48;
constexpr int B_H = 60;
constexpr int B_X = 52, B_XE = 56;

struct BandTab { uint32_t w[11][12]; };
constexpr BandTab make_band() {
    BandTab b{};
    for (int cls = 0; cls < 11; cls++)
        for (int wd = 0; wd < 10; wd++) {
            const int tau = cls + 2 - 8 * ((wd < 4 ? wd : wd - 4) >> 1);
            const int lo = (wd < 4) ? ((wd & 1) ? -2 : 3) : ((wd & 1) ? -4 : -11), wid = (wd < 4 ? 3 : 7) + 2 * (wd & 1);
            b.w[cls][wd] = ((tau >= lo && tau < lo + wid) ? 0x3F80u : 0u) | ((tau - 4 >= lo && tau - 4 < lo + wid) ? 0x3F800000u : 0u);
        }
    return b;
}
constexpr int NTOP = 32;
struct Scratch {
    uint4 r[L_ / 4];
    uint4 g[L_ / 4];
    uint4 h[2][8 * F_ / 8];
    uint32_t top[NTOP][32];
    unsigned epoch;
};
__device__ __align__(128) Scratch g_scratch;
__device__ const __align__(16) BandTab g_band = make_band();

struct Params {
    const bf16 *u, *logA, *Aim, *Cre, *Cim, *logdt, *Dskip, *wr, *gatew;
    bf16* out;
    Scratch* sc;
    const uint4* band;
    uint32_t gu_swap;
    uint32_t zero;
};

#define WSTAMP(i) do {} while (0)
#define KSTAMP(i, dep) do {} while (0)
#define WDUMP() do {} while (0)
#define RSTAMP(i) do {} while (0)

__device__ __forceinline__ uint32_t smem_u32(const void* p) { return (uint32_t)__cvta_generic_to_shared(p); }
__device__ __forceinline__ void mbar_init(uint32_t b, uint32_t c) { asm volatile("mbarrier.init.shared::cta.b64 [%0], %1;" :: "r"(b), "r"(c) : "memory"); }
__device__ __forceinline__ void mbar_expect(uint32_t b, uint32_t tx) { asm volatile("mbarrier.arrive.expect_tx.shared::cta.b64 _, [%0], %1;" :: "r"(b), "r"(tx) : "memory"); }
__device__ __forceinline__ void mbar_arrive(uint32_t b) { asm volatile("mbarrier.arrive.shared::cta.b64 _, [%0];" :: "r"(b) : "memory"); }
__device__ __forceinline__ void mbar_wait(uint32_t b, uint32_t parity = 0) {
    asm volatile("{\n\t.reg .pred p;\nW%=:\n\tmbarrier.try_wait.parity.shared::cta.b64 p, [%0], %1, 20000;\n\t@!p bra W%=;\n\t}" :: "r"(b), "r"(parity) : "memory");
}
__device__ __forceinline__ uint32_t mapa(uint32_t addr, uint32_t rank) { uint32_t r; asm("mapa.shared::cluster.u32 %0, %1, %2;" : "=r"(r) : "r"(addr), "r"(rank)); return r; }
__device__ __forceinline__ void tma3d(uint32_t dst, const CUtensorMap* tm, int c0, int c1, uint32_t bar, uint32_t bytes) {
    asm volatile("{\n\t.reg .pred p;\n\telect.sync _|p, 0xffffffff;\n\t"
                 "@p mbarrier.arrive.expect_tx.shared::cta.b64 _, [%2], %5;\n\t"
                 "@p cp.async.bulk.tensor.3d.shared::cluster.global.mbarrier::complete_tx::bytes [%0], [%1, {%3, %4, 0}], [%2];\n\t}"
        :: "r"(dst), "l"(tm), "r"(bar), "r"(c0), "r"(c1), "r"(bytes) : "memory");
}
__device__ __forceinline__ void bulk_load(uint32_t dst, const void* src, uint32_t bytes, uint32_t bar) {
    asm volatile("{\n\t.reg .pred p;\n\telect.sync _|p, 0xffffffff;\n\t"
                 "@p mbarrier.arrive.expect_tx.shared::cta.b64 _, [%2], %3;\n\t"
                 "@p cp.async.bulk.shared::cluster.global.mbarrier::complete_tx::bytes [%0], [%1], %3, [%2];\n\t}"
        :: "r"(dst), "l"(src), "r"(bar), "r"(bytes) : "memory");
}
__device__ __forceinline__ void st_async16(uint32_t dst, const uint4& v, uint32_t bar) {
    asm volatile("st.async.weak.shared::cluster.mbarrier::complete_tx::bytes.v4.b32 [%0], {%1,%2,%3,%4}, [%5];"
                 :: "r"(dst), "r"(v.x), "r"(v.y), "r"(v.z), "r"(v.w), "r"(bar) : "memory");
}
__device__ __forceinline__ void bar_sync(int id, int n) { asm volatile("bar.sync %0, %1;" :: "r"(id), "r"(n) : "memory"); }
__device__ __forceinline__ void cp16(uint32_t dst, const void* src) { asm volatile("cp.async.cg.shared.global [%0], [%1], 16;" :: "r"(dst), "l"(src) : "memory"); }
__device__ __forceinline__ void cp_wait_all() { asm volatile("cp.async.wait_all;" ::: "memory"); }
__device__ __forceinline__ uint4 ld_gpu128(const void* p) { uint4 v; asm volatile("ld.relaxed.gpu.global.v4.u32 {%0,%1,%2,%3}, [%4];" : "=r"(v.x), "=r"(v.y), "=r"(v.z), "=r"(v.w) : "l"(p) : "memory"); return v; }
__device__ __forceinline__ void st_gpu32(void* p, uint32_t v) { asm volatile("st.relaxed.gpu.global.u32 [%0], %1;" :: "l"(p), "r"(v) : "memory"); }

__device__ __forceinline__ void ldsm4(uint32_t a, uint32_t& r0, uint32_t& r1, uint32_t& r2, uint32_t& r3) {
    asm volatile("ldmatrix.sync.aligned.m8n8.x4.shared.b16 {%0,%1,%2,%3}, [%4];" : "=r"(r0), "=r"(r1), "=r"(r2), "=r"(r3) : "r"(a) : "memory");
}
__device__ __forceinline__ void ldsm4t(uint32_t a, uint32_t& r0, uint32_t& r1, uint32_t& r2, uint32_t& r3) {
    asm volatile("ldmatrix.sync.aligned.m8n8.x4.trans.shared.b16 {%0,%1,%2,%3}, [%4];" : "=r"(r0), "=r"(r1), "=r"(r2), "=r"(r3) : "r"(a) : "memory");
}
__device__ __forceinline__ uint32_t lds32(uint32_t a) { uint32_t v; asm volatile("ld.shared.u32 %0, [%1];" : "=r"(v) : "r"(a) : "memory"); return v; }
__device__ __forceinline__ uint2 lds64(uint32_t a) { uint2 v; asm volatile("ld.shared.v2.u32 {%0,%1}, [%2];" : "=r"(v.x), "=r"(v.y) : "r"(a) : "memory"); return v; }
__device__ __forceinline__ uint4 lds128(uint32_t a) { uint4 v; asm volatile("ld.shared.v4.u32 {%0,%1,%2,%3}, [%4];" : "=r"(v.x), "=r"(v.y), "=r"(v.z), "=r"(v.w) : "r"(a) : "memory"); return v; }
__device__ __forceinline__ void sts32(uint32_t a, uint32_t v) { asm volatile("st.shared.u32 [%0], %1;" :: "r"(a), "r"(v) : "memory"); }
__device__ __forceinline__ void sts16(uint32_t a, uint32_t v) { asm volatile("st.shared.u16 [%0], %1;" :: "r"(a), "h"((unsigned short)v) : "memory"); }
__device__ __forceinline__ void sts128(uint32_t a, uint32_t x, uint32_t y, uint32_t z, uint32_t w) { asm volatile("st.shared.v4.u32 [%0], {%1,%2,%3,%4};" :: "r"(a), "r"(x), "r"(y), "r"(z), "r"(w) : "memory"); }
__device__ __forceinline__ float ldsf(uint32_t a) { float v; asm volatile("ld.shared.f32 %0, [%1];" : "=f"(v) : "r"(a) : "memory"); return v; }

__device__ __forceinline__ void mma_bf(float (&d)[4], uint32_t a0, uint32_t a1, uint32_t a2, uint32_t a3, uint32_t b0, uint32_t b1) {
    asm volatile("mma.sync.aligned.m16n8k16.row.col.f32.bf16.bf16.f32 {%0,%1,%2,%3}, {%4,%5,%6,%7}, {%8,%9}, {%0,%1,%2,%3};"
        : "+f"(d[0]), "+f"(d[1]), "+f"(d[2]), "+f"(d[3]) : "r"(a0), "r"(a1), "r"(a2), "r"(a3), "r"(b0), "r"(b1));
}
__device__ __forceinline__ void mma_bf_z(float (&d)[4], uint32_t a0, uint32_t a1, uint32_t a2, uint32_t a3, uint32_t b0, uint32_t b1) {
    asm volatile("mma.sync.aligned.m16n8k16.row.col.f32.bf16.bf16.f32 {%0,%1,%2,%3}, {%4,%5,%6,%7}, {%8,%9}, {%10,%10,%10,%10};"
        : "=f"(d[0]), "=f"(d[1]), "=f"(d[2]), "=f"(d[3]) : "r"(a0), "r"(a1), "r"(a2), "r"(a3), "r"(b0), "r"(b1), "f"(0.f));
}
__device__ __forceinline__ void mma_bf_k8(float (&d)[4], uint32_t a0, uint32_t a1, uint32_t b0) {
    asm volatile("mma.sync.aligned.m16n8k8.row.col.f32.bf16.bf16.f32 {%0,%1,%2,%3}, {%4,%5}, {%6}, {%0,%1,%2,%3};"
        : "+f"(d[0]), "+f"(d[1]), "+f"(d[2]), "+f"(d[3]) : "r"(a0), "r"(a1), "r"(b0));
}
__device__ __forceinline__ void mma_h(float (&d)[4], uint32_t a0, uint32_t a1, uint32_t a2, uint32_t a3, uint32_t b0, uint32_t b1) {
    asm volatile("mma.sync.aligned.m16n8k16.row.col.f32.f16.f16.f32 {%0,%1,%2,%3}, {%4,%5,%6,%7}, {%8,%9}, {%0,%1,%2,%3};"
        : "+f"(d[0]), "+f"(d[1]), "+f"(d[2]), "+f"(d[3]) : "r"(a0), "r"(a1), "r"(a2), "r"(a3), "r"(b0), "r"(b1));
}
__device__ __forceinline__ uint32_t pack_bf(float lo, float hi) { uint32_t r; asm("cvt.rn.bf16x2.f32 %0, %1, %2;" : "=r"(r) : "f"(hi), "f"(lo)); return r; }
__device__ __forceinline__ uint32_t pack_h(float lo, float hi) { uint32_t r; asm("cvt.rn.f16x2.f32 %0, %1, %2;" : "=r"(r) : "f"(hi), "f"(lo)); return r; }
__device__ __forceinline__ float bf_lo(uint32_t v) { return __uint_as_float(v << 16); }
__device__ __forceinline__ float bf_hi(uint32_t v) { return __uint_as_float(v & 0xffff0000u); }
__device__ __forceinline__ float bf_round(float x) { return __uint_as_float(pack_bf(0.f, x)); }
__device__ __forceinline__ uint32_t hmul2_bf(uint32_t a, uint32_t b) { uint32_t r; asm("mul.rn.bf16x2 %0, %1, %2;" : "=r"(r) : "r"(a), "r"(b)); return r; }
__device__ __forceinline__ float ex2f(float x) { float r; asm("ex2.approx.ftz.f32 %0, %1;" : "=f"(r) : "f"(x)); return r; }

__device__ __forceinline__ float exp_acc(float x) {
    const float t = x * 1.4426950216293335f;
    const float r = fmaf(x, 1.4426950216293335f, -t) + x * 1.9259629911266175e-8f;
    return ex2f(t) * fmaf(r, 0.6931471805599453f, 1.f);
}
__device__ __forceinline__ float sigmoid_f(float x) { return __fdividef(1.f, 1.f + ex2f(-x * 1.4426950408889634f)); }
__device__ __forceinline__ void cexp_pow(float l2, float li, float e, float& zr, float& zi) {
    const float mag = ex2f(l2 * e);
    zr = mag * __cosf(li * e);
    zi = mag * __sinf(li * e);
}
__device__ __forceinline__ uint32_t hcmul(uint32_t a, uint32_t k, uint32_t kp) {
    const __half2 A = *reinterpret_cast<const __half2*>(&a);
    const __half2 r = __hfma2(__high2half2(A), *reinterpret_cast<const __half2*>(&kp), __hmul2(__low2half2(A), *reinterpret_cast<const __half2*>(&k)));
    return *reinterpret_cast<const uint32_t*>(&r);
}
#define CMUL(orr, oi, ar, ai, br, bi) do { float _r = (ar) * (br) - (ai) * (bi); float _i = (ar) * (bi) + (ai) * (br); orr = _r; oi = _i; } while (0)
#define CSQ(orr, oi, ar, ai) do { float _r = (ar) * (ar) - (ai) * (ai); float _i = 2.f * (ar) * (ai); orr = _r; oi = _i; } while (0)

__device__ __forceinline__ void mma_bf_k8z(float (&d)[4], uint32_t a0, uint32_t a1, uint32_t b0) {
    asm volatile("mma.sync.aligned.m16n8k8.row.col.f32.bf16.bf16.f32 {%0,%1,%2,%3}, {%4,%5}, {%6}, {%7,%7,%7,%7};"
        : "=f"(d[0]), "=f"(d[1]), "=f"(d[2]), "=f"(d[3]) : "r"(a0), "r"(a1), "r"(b0), "f"(0.f));
}
__device__ __forceinline__ void mma_hh_k8(uint32_t& d0, uint32_t& d1, uint32_t a0, uint32_t a1, uint32_t b0) {
    asm volatile("mma.sync.aligned.m16n8k8.row.col.f16.f16.f16.f16 {%0,%1}, {%2,%3}, {%4}, {%5,%5};"
        : "=r"(d0), "=r"(d1) : "r"(a0), "r"(a1), "r"(b0), "r"(0));
}
__device__ __forceinline__ void sched_fence() { asm volatile("pmevent 0;" ::: "memory"); }
__device__ __forceinline__ uint32_t pin(uint32_t x, int lane) { return __shfl_sync(0xffffffffu, x, lane); }
template <class T> __device__ __forceinline__ T* pin(T* x, int lane) { return (T*)__shfl_sync(0xffffffffu, (unsigned long long)x, lane); }
__device__ __forceinline__ void sts32_if(bool on, uint32_t a, uint32_t v) {
    asm volatile("{\n\t.reg .pred p;\n\tsetp.ne.u32 p, %2, 0;\n\t@p st.shared.u32 [%0], %1;\n\t}" :: "r"(a), "r"(v), "r"((uint32_t)on) : "memory");
}
__device__ __forceinline__ void sts128_if(bool on, uint32_t a, uint32_t x, uint32_t y, uint32_t z, uint32_t w) {
    asm volatile("{\n\t.reg .pred p;\n\tsetp.ne.u32 p, %5, 0;\n\t@p st.shared.v4.u32 [%0], {%1,%2,%3,%4};\n\t}" :: "r"(a), "r"(x), "r"(y), "r"(z), "r"(w), "r"((uint32_t)on) : "memory");
}
__device__ __forceinline__ void lds128_if(bool on, uint32_t a, uint32_t (&v)[4]) {
    asm volatile("{\n\t.reg .pred p;\n\tsetp.ne.u32 p, %5, 0;\n\t@p ld.shared.v4.u32 {%0,%1,%2,%3}, [%4];\n\t}"
        : "+r"(v[0]), "+r"(v[1]), "+r"(v[2]), "+r"(v[3]) : "r"(a), "r"((uint32_t)on) : "memory");
}
__device__ __forceinline__ uint32_t hfma2_bf(uint32_t a, uint32_t b, uint32_t c) { uint32_t r; asm("fma.rn.bf16x2 %0, %1, %2, %3;" : "=r"(r) : "r"(a), "r"(b), "r"(c)); return r; }
__device__ __forceinline__ __nv_bfloat162 bcast(uint32_t a, int hi) { const __nv_bfloat162 v = *reinterpret_cast<const __nv_bfloat162*>(&a); return hi ? __high2bfloat162(v) : __low2bfloat162(v); }
__device__ __forceinline__ uint32_t hmul2_bc(uint32_t a, int hi, uint32_t b) { const __nv_bfloat162 r = __hmul2_rn(bcast(a, hi), *reinterpret_cast<const __nv_bfloat162*>(&b)); return *reinterpret_cast<const uint32_t*>(&r); }
__device__ __forceinline__ uint32_t hfma2_bc(uint32_t a, int hi, uint32_t b, uint32_t c) {
    const __nv_bfloat162 r = __hfma2(bcast(a, hi), *reinterpret_cast<const __nv_bfloat162*>(&b), *reinterpret_cast<const __nv_bfloat162*>(&c));
    return *reinterpret_cast<const uint32_t*>(&r);
}
__device__ __forceinline__ uint32_t row_elem(uint32_t row) { return ((row >> 5) & 4) | ((row >> 2) & 2) | ((row >> 4) & 1); }
__device__ __forceinline__ uint32_t gate_pos(uint32_t row) { return ((row >> 9) << 8) | ((row & 7) << 5) | (row_elem(row) << 2) | ((row >> 5) & 3); }

template <int N>
__device__ __forceinline__ void mix_rows(const Params& p, const CUtensorMap* tm_out, uint32_t sb, uint32_t ob, int Q0, int Q1, int w, int h, int pr, int lane) {
    const int g = lane >> 2, t = lane & 3, mi = lane >> 3, r = lane & 7;
    const int m8 = 16 * (g >> 2) + ((g >> 1) & 1) + 2 * (g & 1);
    uint32_t yi = sb + (4 * (r >> 1) + 2 * (mi & 1) + (r & 1)) * 512 + (((4 * w + (mi >> 1)) ^ r) << 4);
    uint32_t xs = sb + OFF_S + s_addr(w * S_PL + 32 + m8 * 32, t >> 1) + ((t & 1) << 3);
    uint32_t gs = sb + OFF_GP + w * 64 + g * 8, os = ob + m8 * 32 + t * 8;
    if (N > 1) { yi = pin(yi, lane); xs = pin(xs, lane); gs = pin(gs, lane); os = pin(os, lane); }
    mbar_wait(sb + M_BARS + 8 * B_Y);
#pragma unroll 1
    for (int Q = Q0; Q < Q1; Q++) {
        uint2 xq[N][4];
        uint32_t gg[N][2], sw[N];
#pragma unroll
        for (int n = 0; n < N; n++) {
#pragma unroll
            for (int i = 0; i < 4; i++) xq[n][i] = lds64((xs ^ (((i ^ n) & 1) << 4)) + Q * S_Q + n * 4 * S_PL + i * 128);
            const uint2 gq = lds64(gs + Q * 512 + n * 256);
            sw[n] = lds32(sb + M_BMAP + w * 16 + n * 64 + Q * 4);
            gg[n][0] = gq.x; gg[n][1] = gq.y;
#pragma unroll
            for (int i = 0; i < 4; i++) {
                const uint32_t og = hfma2_bf(gg[n][i >> 1], 0xBF80BF80u, 0x3F803F80u);
                xq[n][i].x = hmul2_bc(og, i & 1, xq[n][i].x); xq[n][i].y = hmul2_bc(og, i & 1, xq[n][i].y);
            }
        }
        mbar_wait(sb + M_BARS + 8 * (B_Y + Q));
        __syncwarp();
#pragma unroll
        for (int n = 0; n < N; n++) {
#pragma unroll
            for (int x = 0; x < 2; x++) {
                uint32_t y[4];
                ldsm4t((yi ^ (x << 5)) + y_off(Q) + n * 256, y[0], y[1], y[2], y[3]);
#pragma unroll
                for (int e = 0; e < 2; e++) {
                    uint2& o = xq[n][2 * x + e];
                    o.x = hfma2_bc(gg[n][x], e, y[2 * e], o.x); o.y = hfma2_bc(gg[n][x], e, y[2 * e + 1], o.y);
                }
            }
        }
        if ((sw[0] | sw[N - 1]) == 0) {
#pragma unroll
            for (int n = 0; n < N; n++)
#pragma unroll
                for (int i = 0; i < 4; i++)
                    asm volatile("st.shared.v2.u32 [%0], {%1, %2};" :: "r"(os + Q * 1024 + n * 4 * TAB_W + i * 128), "r"(xq[n][i].x), "r"(xq[n][i].y) : "memory");
            asm volatile("fence.proxy.async.shared::cta;" ::: "memory");
            __syncwarp();
#pragma unroll
            for (int n = 0; n < N; n++)
                asm volatile("{\n\t.reg .pred p;\n\telect.sync _|p, 0xffffffff;\n\t"
                             "@p cp.async.bulk.tensor.3d.global.shared::cta.bulk_group [%1, {%2, %3, %4}], [%0];\n\t}"
                    :: "r"(ob + 4 * n * TAB_W + Q * 1024), "l"(tm_out), "r"(16 * pr), "r"(64 * Q + 32 * h), "r"(w + 4 * n) : "memory");
        } else {
            bf16* op = p.out + (size_t)(512 * Q + 256 * h + 8 * m8 + w) * D_ + 16 * pr + 4 * t;
#pragma unroll
            for (int n = 0; n < N; n++)
#pragma unroll
                for (int i = 0; i < 4; i++)
                    if (!((sw[n] >> (4 * g)) & (1u << i))) *(uint2*)(op + (size_t)(32 * i + 4 * n) * D_) = xq[n][i];
        }
    }
}

__global__ void __cluster_dims__(2, 1, 1) __launch_bounds__(NTHREADS, 1)
fused_kernel(const Params p, const __grid_constant__ CUtensorMap tm_gu, const __grid_constant__ CUtensorMap tm_down,
             const __grid_constant__ CUtensorMap tm_x, const __grid_constant__ CUtensorMap tm_out) {
    extern __shared__ __align__(1024) unsigned char smem[];
    const uint32_t sb = smem_u32(smem);
    int tid;
    asm volatile("mov.u32 %0, %%tid.x;" : "=r"(tid));
    const int pw = tid >> 5, lane = tid & 31;
    const int c = blockIdx.x, h = c & 1, pr = c >> 1;
    const uint32_t bars = sb + M_BARS;

    uint2 v_la, v_ai, v_cr, v_ci;
    uint32_t ldt16;
    {
        const uint32_t po = c * 256 + tid;
        asm volatile("{\n\t.reg .pred p;\n\t.reg .b64 a;\n\tsetp.ne.u32 p, %16, 0;\n\t"
                     "mad.wide.u32 a, %14, 8, %9;\n\t@p ld.global.nc.L1::no_allocate.v2.u32 {%0,%1}, [a];\n\t"
                     "mad.wide.u32 a, %15, 2, %13;\n\t@p ld.global.nc.u16 %8, [a];\n\t"
                     "mad.wide.u32 a, %14, 8, %10;\n\t@p ld.global.nc.L1::no_allocate.v2.u32 {%2,%3}, [a];\n\t"
                     "mad.wide.u32 a, %14, 8, %11;\n\t@p ld.global.nc.L1::no_allocate.v2.u32 {%4,%5}, [a];\n\t"
                     "mad.wide.u32 a, %14, 8, %12;\n\t@p ld.global.nc.L1::no_allocate.v2.u32 {%6,%7}, [a];\n\t}"
            : "=r"(v_la.x), "=r"(v_la.y), "=r"(v_ai.x), "=r"(v_ai.y), "=r"(v_cr.x), "=r"(v_cr.y), "=r"(v_ci.x), "=r"(v_ci.y), "=r"(ldt16)
            : "l"(p.logA), "l"(p.Aim), "l"(p.Cre), "l"(p.Cim), "l"(p.logdt), "r"(po), "r"(po >> 5), "r"((uint32_t)(tid < 256 && c < 128)));
    }

    if (c >= 128) {
        if (c != 128) return;
        RSTAMP(5);
        const unsigned tag = (*(volatile unsigned*)&p.sc->epoch + 1) & 0xffffu;
        const uint32_t list = sb + 128;
        sts128(list + 16 * tid, 0, 0, 0, 0);
        if (tid == 0) sts32(sb + 64, 0);
        uint32_t key[4] = {tag - 1, tag - 1, tag - 1, tag - 1};
#pragma unroll 1
        for (int it = 0; it < (1 << 22); it++) {
            uint32_t a[4];
            asm volatile("{\n\t.reg .b128 o, z;\n\t.reg .b64 l, u;\n\tmov.b64 l, {%5, %5};\n\tmov.b128 z, {l, l};\n\tatom.relaxed.gpu.global.exch.b128 o, [%4], z;\n\t"
                         "mov.b128 {l, u}, o;\n\tmov.b64 {%0, %1}, l;\n\tmov.b64 {%2, %3}, u;\n\t}"
                : "=r"(a[0]), "=r"(a[1]), "=r"(a[2]), "=r"(a[3]) : "l"(&p.sc->r[tid]), "r"(tag - 1) : "memory");
#pragma unroll
            for (int i = 0; i < 4; i++) if (((a[i] ^ tag) & 0xffffu) == 0) key[i] = a[i];
            if ((((key[0] ^ tag) | (key[1] ^ tag) | (key[2] ^ tag) | (key[3] ^ tag)) & 0xffffu) == 0) break;
        }
        WSTAMP(0);
        uint32_t m = 0;
#pragma unroll
        for (int i = 0; i < 4; i++) {
            key[i] = (key[i] & 0xffff0000u) | (uint32_t)(2047 - (4 * tid + i));
            m = max(m, key[i]);
        }
        const uint32_t wm = __reduce_max_sync(0xffffffffu, m);
        if (lane == 0) sts32(sb + pw * 4, wm);
        __syncthreads();
        uint32_t thr = 0xffffffffu;
#pragma unroll
        for (int i = 0; i < 4; i++) { const uint4 q = lds128(sb + 16 * i); thr = min(thr, min(max(q.x, q.y), max(q.z, q.w))); }
        if (thr != 1) WSTAMP(1);
        if (m >= thr) {
            uint32_t pos;
            asm volatile("atom.shared.add.u32 %0, [%1], %2;" : "=r"(pos) : "r"(sb + 64), "r"(4 * ((key[0] >= thr) + (key[1] >= thr) + (key[2] >= thr) + (key[3] >= thr))) : "memory");
#pragma unroll
            for (int i = 0; i < 4; i++) if (key[i] >= thr) { sts32(list + pos, key[i]); pos += 4; }
        }
        __syncthreads();
        const uint32_t nc4 = lds32(sb + 64);
        if (nc4 != 1) WSTAMP(2);
#pragma unroll 1
        for (uint32_t j = 4 * pw; j < nc4; j += 64) {
            const uint32_t mine = lds32(list + j);
            int rank = 0;
#pragma unroll 1
            for (uint32_t i = 0; i < nc4; i += 128) rank += __popc(__ballot_sync(0xffffffffu, lds32(list + i + 4 * lane) > mine));
            if (rank < 8 && lane == 0) sts32(sb + 96 + 4 * rank, mine);
        }
        __syncthreads();
        if (tid < 8 * NTOP) st_gpu32(&p.sc->top[tid >> 3][tid & 7], lds32(sb + 96 + 4 * (tid & 7)) | ((tag & 31) << 11));
        WSTAMP(3);
        WDUMP();
        return;
    }

    WSTAMP(0);
    if (pw < 8) {
        const int d = 8 * c + pw - MAIN_W0;
        if (lane == 0) asm volatile("cp.async.ca.shared.global [%0], [%1], 4;" :: "r"(sb + M_DSK + 4 * (pw - MAIN_W0)), "l"(p.Dskip + (d & ~1)) : "memory");
        asm volatile("barrier.cluster.arrive.relaxed.aligned;" ::: "memory");
        const int warp = pw - MAIN_W0;
        asm volatile("setmaxnreg.inc.sync.aligned.u32 160;");
        const int g = lane >> 2, t = lane & 3;
        const int mi = lane >> 3, r = lane & 7;
        const uint32_t TB = sb + OFF_TAB + warp * TAB_W;
        const uint32_t UB = sb + OFF_U + warp * U_CH;
        if (mi < 2) sts128(UB + mi * U_PL + r * 16, 0, 0, 0, 0);
        if (lane < 4) sts128(TB + lane * T_PL, 0, 0, 0, 0);
        sts128(sb + OFF_SCR + warp * 8192 + lane * 16, 0x3C00u, 0x3C00u, 0x3C00u, 0x3C00u);
        asm volatile("barrier.cluster.wait.acquire.aligned;" ::: "memory");
        __syncwarp();

        uint32_t cfix;
        {
            KSTAMP(4, v_la.x ^ v_ai.x ^ v_cr.x ^ v_ci.x ^ ldt16);
            const float dt = bf_round(exp_acc(__uint_as_float(ldt16 << 16)));
            float l2[4], li[4];
            {
                const uint32_t la[2] = {v_la.x, v_la.y}, ai[2] = {v_ai.x, v_ai.y};
                const float dt2 = -1.4426950408889634f * dt;
#pragma unroll
                for (int i = 0; i < 4; i++) {
                    l2[i] = bf_round(ex2f(((i & 1) ? bf_hi(la[i >> 1]) : bf_lo(la[i >> 1])) * 1.4426950408889634f)) * dt2;
                    li[i] = ((i & 1) ? bf_hi(ai[i >> 1]) : bf_lo(ai[i >> 1])) * dt;
                }
            }
            const uint32_t SX = sb + OFF_SCR + warp * 8192;
            const uint32_t sw = SX + (lane << 4);
#define PUT(buf, row, v) sts128(((sw + (row) * 512) ^ ((row) << 4)) + (buf) * 4096, v[0], v[1], v[2], v[3])
#define EMIT(bufa, rowa, bufb, rowb, xr, xi, k, kp) do { uint32_t pk[4], pd[4]; sched_fence(); \
                _Pragma("unroll") for (int i = 0; i < 4; i++) { pk[i] = pack_h(xr[i], xi[i]); pd[i] = hcmul(pk[i], k[i], kp[i]); } \
                PUT(bufa, rowa, pk); PUT(bufb, rowb, pd); } while (0)
#define CMUL4(orr, oi, ar, ai, br, bi) _Pragma("unroll") for (int i = 0; i < 4; i++) CMUL(orr[i], oi[i], ar[i], ai[i], br[i], bi[i])
#define CSQ4(orr, oi, ar, ai) _Pragma("unroll") for (int i = 0; i < 4; i++) CSQ(orr[i], oi[i], ar[i], ai[i])
            float z1r[4], z1i[4], z2r[4], z2i[4], z8r[4], z8i[4], z256r[4], z256i[4];
            uint32_t k4[4], k4p[4];
            float z4r[4], z4i[4];
#pragma unroll
            for (int i = 0; i < 4; i++) cexp_pow(l2[i], li[i], 1.f, z1r[i], z1i[i]);
            CSQ4(z2r, z2i, z1r, z1i);
            CSQ4(z4r, z4i, z2r, z2i);
            CSQ4(z8r, z8i, z4r, z4i);
            KSTAMP(5, __float_as_uint(z8r[3]));
            uint32_t Ya[16][4];
            float cr[4], ci[4], inv;
            {
                float w1r[4], w1i[4], ar[4], ai[4], br[4], bi[4];
                uint32_t k8[4], k8p[4];
#pragma unroll
                for (int i = 0; i < 4; i++) {
                    k8[i] = pack_h(z8r[i], -z8i[i]); k8p[i] = pack_h(z8i[i], z8r[i]);
                    CSQ(w1r[i], w1i[i], z8r[i], z8i[i]); w1i[i] = -w1i[i];
                }
                PUT(1, 0, k8);
                EMIT(0, 1, 1, 1, w1r, w1i, k8, k8p);
                CSQ4(ar, ai, w1r, w1i);            EMIT(0, 2, 1, 2, ar, ai, k8, k8p);
                CMUL4(br, bi, ar, ai, w1r, w1i);   EMIT(0, 3, 1, 3, br, bi, k8, k8p);
                CSQ4(ar, ai, ar, ai);              EMIT(0, 4, 1, 4, ar, ai, k8, k8p);
                CMUL4(ar, ai, ar, ai, w1r, w1i);   EMIT(0, 5, 1, 5, ar, ai, k8, k8p);
                CSQ4(br, bi, br, bi);              EMIT(0, 6, 1, 6, br, bi, k8, k8p);
                CMUL4(br, bi, br, bi, w1r, w1i);   EMIT(0, 7, 1, 7, br, bi, k8, k8p);
                __syncwarp();
                KSTAMP(6, 0);
                sched_fence();
                const uint32_t ab = SX + (mi & 1) * 4096 + r * 512, ax = ((mi >> 1) ^ r) << 4;
                const uint32_t vr[2] = {v_cr.x, v_cr.y}, vi[2] = {v_ci.x, v_ci.y};
                const uint32_t m2 = __vmaxu2(__vmaxu2(vr[0] & 0x7fff7fffu, vr[1] & 0x7fff7fffu), __vmaxu2(vi[0] & 0x7fff7fffu, vi[1] & 0x7fff7fffu));
                const uint32_t mx = __reduce_max_sync(0xffffffffu, max(m2, m2 << 16));
                const uint32_t e = min(max(mx >> 23, 11u), 254u);
                const float sc = __uint_as_float((264u - e) << 23);
                inv = __uint_as_float((e - 10u) << 23) * (2.f * dt);
#pragma unroll
                for (int i = 0; i < 4; i++) {
#pragma unroll
                    for (int k = 0; k < 4; k++) ldsm4(ab + (ax ^ (i << 5)) + k * 128, Ya[4 * k + i][0], Ya[4 * k + i][1], Ya[4 * k + i][2], Ya[4 * k + i][3]);
                    float tr, ti;
                    cexp_pow(l2[i], li[i], 128.f, tr, ti);
                    sts32(TB + 2176 + 256 * i + 4 * lane, pack_h(tr, ti));
                    sts32(TB + 2176 + 256 * i + 128 + 4 * (lane ^ 16), pack_h(-ti, tr));
                    k4[i] = pack_h(z4r[i], z4i[i]); k4p[i] = pack_h(-z4i[i], z4r[i]);
                    CSQ(z256r[i], z256i[i], tr, ti);
                    cr[i] = ((i & 1) ? bf_hi(vr[i >> 1]) : bf_lo(vr[i >> 1])) * sc;
                    ci[i] = ((i & 1) ? bf_hi(vi[i >> 1]) : bf_lo(vi[i >> 1])) * sc;
                    if (i < 3) sched_fence();
                }
                __syncwarp();
            }
            KSTAMP(7, Ya[15][0]);
            const uint32_t ld0 = SX + r * 512 + ((mi ^ r) << 4), ld1 = ld0 ^ 64;
            float R[6][4], s1024;
            {
                float xr[4], xi[4], yr[4], yi[4];
                EMIT(0, 0, 0, 1, cr, ci, k4, k4p);
                CMUL4(yr, yi, cr, ci, z1r, z1i);        EMIT(0, 2, 0, 3, yr, yi, k4, k4p);
                CMUL4(xr, xi, cr, ci, z256r, z256i);    EMIT(1, 0, 1, 1, xr, xi, k4, k4p);
                CMUL4(yr, yi, yr, yi, z1r, z1i);        EMIT(0, 4, 0, 5, yr, yi, k4, k4p);
                CMUL4(cr, ci, yr, yi, z256r, z256i);    EMIT(1, 2, 1, 3, cr, ci, k4, k4p);
                CMUL4(yr, yi, yr, yi, z1r, z1i);        EMIT(0, 6, 0, 7, yr, yi, k4, k4p);
                CMUL4(xr, xi, xr, xi, z256r, z256i);    EMIT(1, 4, 1, 5, xr, xi, k4, k4p);
                CMUL4(xr, xi, xr, xi, z256r, z256i);    EMIT(1, 6, 1, 7, xr, xi, k4, k4p);
                CMUL4(xr, xi, xr, xi, z256r, z256i);
                s1024 = (xr[0] + xr[1]) + (xr[2] + xr[3]);
#pragma unroll
                for (int m = 0; m < 4; m++) {
                    if (m == 0) { CMUL4(xr, xi, xr, xi, z8r, z8i); } else { CMUL4(xr, xi, xr, xi, z256r, z256i); }
                    sched_fence();
                    sts128(TB + m * T_PL + 16 + 16 * lane, pack_h(xr[0], xi[0]), pack_h(xr[1], xi[1]), pack_h(xr[2], xi[2]), pack_h(xr[3], xi[3]));
                }
            }
            __syncwarp();
            {
                KSTAMP(8, 0);
                uint32_t bd[2][4] = {{0, 0, 0, 0}, {0, 0, 0, 0}};
                const bool on = (g >> 1) == t;
#pragma unroll
                for (int i = 0; i < 6; i++) { R[i][0] = R[i][1] = R[i][2] = R[i][3] = 0.f; }
                uint32_t x[2][4], y[2][4], z[2][4];
                auto fetch = [&](const int k2) {
                    const int b = k2 & 1;
                    lds128_if(on, TB + 2176 + g * 128 + (k2 < 4 ? 64 : -64) * (g & 1) + 16 * k2, bd[b]);
                    ldsm4(((k2 & 1) ? ld1 : ld0) + (k2 >> 1) * 128, x[b][0], x[b][1], x[b][2], x[b][3]);
                    ldsm4(((k2 & 1) ? ld1 : ld0) + (k2 >> 1) * 128 + 4096, y[b][0], y[b][1], y[b][2], y[b][3]);
                    ldsm4(TB + (r & 3) * T_PL + 16 + 16 * mi + 64 * k2, z[b][0], z[b][1], z[b][2], z[b][3]);
                };
                fetch(0);
#pragma unroll
                for (int k2 = 0; k2 < 8; k2++) {
                    const int b = k2 & 1;
                    uint32_t a1[2][4];
                    if (k2 < 7) fetch(k2 + 1);
#pragma unroll
                    for (int u = 0; u < 2; u++) {
                        mma_hh_k8(a1[u][0], a1[u][1], Ya[2 * k2 + u][0], Ya[2 * k2 + u][1], bd[b][2 * u]);
                        mma_hh_k8(a1[u][2], a1[u][3], Ya[2 * k2 + u][2], Ya[2 * k2 + u][3], bd[b][2 * u + 1]);
                    }
#pragma unroll
                    for (int u = 0; u < 2; u++) {
                        const uint32_t(&a0)[4] = Ya[2 * k2 + u];
                        mma_h(R[0], a0[0], a0[1], a0[2], a0[3], x[b][2 * u], x[b][2 * u + 1]);
                        mma_h(R[2], a0[0], a0[1], a0[2], a0[3], y[b][2 * u], y[b][2 * u + 1]);
                        mma_h(R[4], a0[0], a0[1], a0[2], a0[3], z[b][2 * u], z[b][2 * u + 1]);
                        mma_h(R[1], a1[u][0], a1[u][1], a1[u][2], a1[u][3], x[b][2 * u], x[b][2 * u + 1]);
                        mma_h(R[3], a1[u][0], a1[u][1], a1[u][2], a1[u][3], y[b][2 * u], y[b][2 * u + 1]);
                        mma_h(R[5], a1[u][0], a1[u][1], a1[u][2], a1[u][3], z[b][2 * u], z[b][2 * u + 1]);
                    }
                }
            }
            __syncwarp();
            KSTAMP(9, __float_as_uint(R[3][0]));
            if (lane == 0) mbar_arrive(bars + 8 * B_KG + (__float_as_uint(R[0][0]) & __float_as_uint(R[2][0]) & p.zero));
            sts128(TB + 2176 + 16 * lane, 0, 0, 0, 0);
            sts128(TB + 2688 + 16 * lane, 0, 0, 0, 0);
            __syncwarp();
#undef PUT
#undef EMIT
#pragma unroll
            for (int o = 16; o > 0; o >>= 1) s1024 += __shfl_xor_sync(0xffffffffu, s1024, o);
            uint32_t w[4][4], dsk = 0;
            cp_wait_all();
            asm volatile("{\n\t.reg .pred p;\n\tsetp.eq.u32 p, %2, 0;\n\t@p ld.shared.u16 %0, [%1];\n\t}" : "+r"(dsk) : "r"(sb + M_DSK + 4 * warp + 2 * (warp & 1)), "r"(lane) : "memory");
#pragma unroll
            for (int a = 0; a < 4; a++) {
                const float v0 = (a == 0) ? fmaf(R[0][0], inv, __uint_as_float(dsk << 16)) : R[a][0] * inv;
                const float v1 = R[a][1] * inv, v2 = R[a][2] * inv, v3 = R[a][3] * inv;
                w[a][0] = pack_bf(v0, 0.f); w[a][1] = pack_bf(v1, v0); w[a][2] = pack_bf(v2, v1); w[a][3] = pack_bf(v3, v2);
            }
            const uint32_t wb = TB + 16 + 16 * g, w1 = wb + t * T_PL, w2 = wb + 256 + 2 * t * T_PL;
            const uint32_t w3 = (t == 0) ? wb + 256 + 3 * T_PL : TB + T_A + 8 * (16 * t + g);
            const uint32_t w3s = (t == 0) ? 128 : 64, w3o = (t == 0) ? 8 : 12;
            const uint32_t k512 = __shfl_sync(0xffffffffu, w[2][1], 2);
#pragma unroll
            for (int a = 0; a < 2; a++) {
                sts128(w1 + 128 * a, w[a][0], w[a][1], w[a][2], w[a][3]);
                const uint32_t(&q)[4] = w[2 + a];
                if (t < 2) sts128(w2 + 128 * a, q[0], q[1], q[2], q[3]);
                if (t == 0) { sts128(w2 + T_PL + 128 * a, q[0], q[1], q[2], q[3]); sts32(w3 + 128 * a + 4, q[2]); }
                sts32_if(t != 1 && (a == 1 || lane != 2), w3 + w3s * a, q[1]);
                sts32_if(t != 1, w3 + w3s * a + w3o, q[3]);
            }
            sts128_if(lane < 4, w1 + 512, t == 3 ? k512 : k512 >> 16, t < 2 ? k512 : t == 2 ? k512 & 0xffff0000u : k512 << 16, t < 2 ? k512 << 16 : 0u, 0);
            __syncwarp();
#pragma unroll
            for (int a = 0; a < 2; a++) {
                sts16(w1 + 128 * a + 18, w[a][3]);
                const uint32_t(&q)[4] = w[2 + a];
                if (t < 2) sts16(w2 + 128 * a + 18, q[3]);
                if (t == 0) { sts16(w2 + T_PL + 128 * a + 18, q[3]); sts16(w3 + 128 * a + 14, q[3]); }
            }
            if (t == 0) sts16(w3 + 128 - 4, w[3][0]);
            if (lane == 2 || (t == 0 && g > 0)) sts16(lane == 2 ? TB + 16 + 3 * T_PL + 4 * 127 : w3 - 4, w[2][0]);
            {
                float q[4];
#pragma unroll
                for (int i = 0; i < 4; i++) q[i] = (t < 2 ? R[4][i] : R[5][i]) * inv;
                const uint32_t b0 = pack_bf(q[0], q[2]), b1 = pack_bf(q[1], q[3]);
                const uint32_t wq = TB + T_B + 8 * (65 + 32 * (t & 1) + 4 * (t & 2) + g);
                sts32(wq, b0); sts32(wq + 12, b0); sts32(wq + 128, b1); sts32(wq + 140, b1);
            }
            cfix = pack_bf(s1024 * inv, s1024 * inv);
            if (lane == 0) sts32(TB + T_A + 8 * 64, cfix);
            __syncwarp();
        }
        WSTAMP(1);

        mbar_wait(bars + 8 * B_U);
        WSTAMP(2);

        float D[16][4];
        {
            const int x5 = g - t + 5;
            const uint32_t tabD = TB + (x5 & 3) * T_PL + (x5 & 12) + 16;
            {
                const uint32_t a1 = lds32(tabD - 8), a0 = p.zero;
#pragma unroll
                for (int jq = 0; jq < 4; jq++) {
                    uint32_t b[4];
                    ldsm4(UB + (9 + lane) * 16 + jq * 512, b[0], b[1], b[2], b[3]);
#pragma unroll
                    for (int i = 0; i < 4; i++) mma_bf_k8z(D[4 * jq + i], a0, a1, b[i]);
                }
            }
            const uint32_t ua = UB + (mi & 1) * U_PL + (8 + 8 * (mi >> 1) + r) * 16;
#pragma unroll 1
            for (int k0 = 0; k0 < 8; k0++) {
                uint32_t Uf[16][2];
#pragma unroll
                for (int jp = 0; jp < 8; jp++) ldsm4(ua + jp * 256 - k0 * 16, Uf[2 * jp][0], Uf[2 * jp][1], Uf[2 * jp + 1][0], Uf[2 * jp + 1][1]);
#pragma unroll
                for (int k1 = 0; k1 < 4; k1++) {
                    const uint32_t ta = tabD + 16 * (8 * k1 + k0);
                    const uint32_t a0 = lds32(ta), a1 = lds32(ta + 8), a2 = lds32(ta - 8), a3 = a0 ^ p.zero;
#pragma unroll
                    for (int J = k1; J < 16; J++) mma_bf(D[J], a0, a1, a2, a3, Uf[J - k1][0], Uf[J - k1][1]);
                }
                if (k0 == 0) {
                    const uint32_t ta = tabD + 16 * 32;
                    const uint32_t a0 = lds32(ta), a1 = lds32(ta + 8), a2 = lds32(ta - 8), a3 = a0 ^ p.zero;
#pragma unroll
                    for (int J = 4; J < 16; J++) mma_bf(D[J], a0, a1, a2, a3, Uf[J - 4][0], Uf[J - 4][1]);
                    const uint32_t f0 = (cfix ^ 0x80008000u) & (g == t ? 0xffffu : g == t + 4 ? 0xffff0000u : 0u);
                    const uint32_t f1 = p.zero, f2 = p.zero + p.zero, f3 = f0 ^ p.zero;
#pragma unroll
                    for (int J = 8; J < 16; J++) mma_bf(D[J], f0, f1, f2, f3, Uf[J - 8][0], Uf[J - 8][1]);
                }
            }
        }
        WSTAMP(3);
        {
            const int ch = 8 * h + warp;
            const uint32_t yo = sb + ch * 512 + ((lane ^ (((ch >> 2) << 1) | (ch & 1))) << 4);
            const uint32_t yr = mapa(yo, h ^ 1), ybr = mapa(bars + 8 * B_Y, h ^ 1);
            auto ship = [&](const int Q) {
                uint4 y[2];
#pragma unroll
                for (int hh = 0; hh < 2; hh++) {
                    const int J = 4 * Q + 2 * hh;
                    y[hh] = make_uint4(pack_bf(D[J][0], D[J][1]), pack_bf(D[J][2], D[J][3]), pack_bf(D[J + 1][0], D[J + 1][1]), pack_bf(D[J + 1][2], D[J + 1][3]));
                }
                if (!(Q & 1)) mbar_wait(bars + 8 * (B_F + (Q >> 1)));
                asm volatile("{\n\t.reg .pred p;\n\tsetp.eq.u32 p, %11, 0;\n\t"
                             "@p st.async.weak.shared::cluster.mbarrier::complete_tx::bytes.v4.b32 [%9], {%4,%5,%6,%7}, [%10];\n\t"
                             "@!p st.async.weak.shared::cluster.mbarrier::complete_tx::bytes.v4.b32 [%9], {%0,%1,%2,%3}, [%10];\n\t"
                             "@p st.shared.v4.b32 [%8], {%0,%1,%2,%3};\n\t@!p st.shared.v4.b32 [%8], {%4,%5,%6,%7};\n\t}"
                             :: "r"(y[0].x), "r"(y[0].y), "r"(y[0].z), "r"(y[0].w), "r"(y[1].x), "r"(y[1].y), "r"(y[1].z), "r"(y[1].w),
                                "r"(yo + y_off(Q)), "r"(yr + y_off(Q)), "r"(ybr + 8 * Q), "r"(h) : "memory");
                __syncwarp();
                if (lane == 0) mbar_arrive(bars + 8 * (B_Y + Q));
            };
            ship(0);
            const uint4 bA = lds128(sb + OFF_BAND + (g - t + 3) * 48), bB = lds128(sb + OFF_BAND + (g - t + 3) * 48 + 16);
            const uint2 bC = lds64(sb + OFF_BAND + (g - t + 3) * 48 + 32);
            uint2 QA[5][2], QB[8];
            const uint32_t tq = TB + 8 * (1 + g - 2 * t);
#pragma unroll
            for (int dd = 0; dd < 5; dd++) { QA[dd][0] = lds64(tq + T_A + 64 * (dd + 4)); QA[dd][1] = lds64(tq + T_A + 64 * (dd + 4) - 8); }
#pragma unroll
            for (int dd = 0; dd < 8; dd++) QB[dd] = lds64(tq + T_B + 64 * (dd + 8));
            const uint32_t u1 = UB + (mi & 1) * U_PL + (7 + r + (mi >> 1)) * 16;
            const uint32_t u2 = UB + ((mi & 1) ^ 1) * U_PL + (7 + r + (mi & 1) + 8 * (mi >> 1)) * 16;
            uint32_t n[4];
#pragma unroll
            for (int j = 0; j < 12; j++) {
                uint32_t m[4];
                ldsm4(u1 + j * 128, m[0], m[1], m[2], m[3]);
                if (!(j & 1)) ldsm4(u2 + j * 128, n[0], n[1], n[2], n[3]);
                const uint32_t n0 = n[2 * (j & 1)], n1 = n[2 * (j & 1) + 1];
                float wa[4], wb[4], wc[4], g1[4], g2[4];
                mma_bf_z(wa, bA.x, bA.y, bA.z, bA.w, m[0], m[1]);
                mma_bf_z(wb, bA.x, bA.y, bA.z, bA.w, n0, n1);
                mma_bf_z(wc, bA.x, bA.y, bA.z, bA.w, m[2], m[3]);
                if (j < 8) {
                    mma_bf_z(g1, bB.x, bB.y, bB.z, bB.w, m[0], m[1]);
                    mma_bf_z(g2, bB.x, bB.y, bB.z, bB.w, n0, n1);
                    mma_bf_k8(g1, bC.x, bC.y, m[2]);
                    mma_bf_k8(g2, bC.x, bC.y, m[3]);
                }
#pragma unroll
                for (int e = 0; e < 2; e++) {
                    const uint32_t q0 = pack_bf(wa[e], wa[e + 2]), q1 = pack_bf(wb[e], wb[e + 2]), q2 = q1 ^ p.zero, q3 = pack_bf(wc[e], wc[e + 2]);
#pragma unroll
                    for (int dd = 0; dd < 5; dd++)
                        if (j + 4 + dd < 16) mma_bf(D[j + 4 + dd], q0, q1, q2, q3, QA[dd][e].x, QA[dd][e].y);
                }
                if (j < 8) {
                    const uint32_t q0 = pack_bf(g1[0], g1[2]), q1 = pack_bf(g2[0], g2[2]), q2 = pack_bf(g1[1], g1[3]), q3 = pack_bf(g2[1], g2[3]);
#pragma unroll
                    for (int dd = 7 - j; dd >= 0; dd--) mma_bf(D[j + 8 + dd], q0, q1, q2, q3, QB[dd].x, QB[dd].y);
                }
                if ((j & 3) == 3) {
                    WSTAMP(4 + 2 * (j >> 2));
                    ship((j >> 2) + 1);
                }
            }
        }
        const int warpu = __reduce_max_sync(0xffffffffu, warp);
        mix_rows<1>(p, &tm_out, sb, sb + OFF_U + warpu * U_CH + (warpu & 1) * 64, PQ, 4, warpu, h, pr, lane);
        asm volatile("cp.async.bulk.commit_group;\n\tcp.async.bulk.wait_group.read 0;" ::: "memory");
        WSTAMP(10);
        WDUMP();
    } else if ((pw & 12) == AUX_W0) {
        const int v = __reduce_max_sync(0xffffffffu, pw & 3);
        const int at = tid & 127;
        const int g = lane >> 2, t = lane & 3;
        unsigned tag;
        const bool gu = c < NGU_CTA;
        {
            const uint32_t xb = sb + (v < 2 ? OFF_XSEL : OFF_RING + 2 * 8192) + v * 8192;
            const uint32_t gws = sb + M_DPIN;
            const uint32_t row = 16 * c + 4 * v + (g >> 1);
#pragma unroll
            for (int i = 0; i < 8; i++)
                asm volatile("cp.async.ca.shared.global [%0], [%1], 4;" :: "r"((i < 4 ? sb + OFF_GP : gws) + 512 * (i & 3) + (tid & 124) * 4 + (tid & 1) * 8 + (tid & 2) * 2),
                             "l"((i < 4 ? p.wr : p.gatew) + 256 * (i & 3) + (tid & 127) * 2) : "memory");
            if ((tid & 127) < 33) cp16(sb + OFF_BAND + (tid & 127) * 16, p.band + (tid & 127));
            asm volatile("barrier.cluster.arrive.relaxed.aligned;" ::: "memory");
            tag = __reduce_max_sync(0xffffffffu, (*(volatile unsigned*)&p.sc->epoch + 1) & 0xffffu);
            if (gu) st_gpu32((uint32_t*)&p.sc->h[(tag + 1) & 1][32 * c] + at, 0);
            if (v == 2) sts32(sb + M_BMAP + lane * 4, 0);
            if (at == 0) sts32(sb + M_TAG, tag << 16);
            cp_wait_all();
            bar_sync(1, 128);
            uint2 w[16];
#pragma unroll
            for (int kb = 0; kb < 16; kb++) w[kb] = lds64((g < 4 ? sb + OFF_GP : gws) + 128 * kb + 32 * (g & 2) + 16 * t + 8 * (g & 1));
            asm volatile("barrier.cluster.wait.acquire.aligned;" ::: "memory");
            mbar_wait(bars + 8 * (B_X + v));
            WSTAMP(10);
            float dr[4][4];
#pragma unroll
            for (int kb = 0; kb < 16; kb++) {
                const uint4 x = lds128(xb + (g >> 1) * 2048 + 128 * kb + 16 * (lane & 7));
                if (kb < 4) mma_bf_z(dr[kb], x.x, x.y, x.z, x.w, w[kb].x, w[kb].y);
                else mma_bf(dr[kb & 3], x.x, x.y, x.z, x.w, w[kb].x, w[kb].y);
            }
            float rs = ((dr[0][0] + dr[0][3]) + (dr[1][0] + dr[1][3])) + ((dr[2][0] + dr[2][3]) + (dr[3][0] + dr[3][3]));
            if (lane == 0) mbar_arrive(bars + 8 * (B_XE + v) + (__float_as_uint(rs) & p.zero));
            rs += __shfl_xor_sync(0xffffffffu, rs, 5);
            const uint32_t rb = pack_bf(0.f, rs);
            if (!(lane & 7)) st_gpu32((uint32_t*)p.sc->r + row, ((rb ^ (((int)rb >> 31) | 0x80000000u)) & 0xffff0000u) | tag);
            WSTAMP(1);
            {
                const int n = 3 + (lane >> 3) + 4 * (lane & 1);
                const uint32_t so = (n & 7) * S_PL + ((lane & 6) + (n >> 3)) * 32;
                const uint32_t src[2] = {sb + OFF_S + v * S_Q + s_addr(so, h), sb + OFF_S + v * S_Q + s_addr(so + 32, h)};
                const uint32_t dst = sb + OFF_U + g * U_CH + (8 + 32 * v + 16 * h + t) * 16;
                const uint32_t rdst = mapa(dst, h ^ 1), rbar = mapa(bars + 8 * B_U, h ^ 1);
                mbar_wait(bars + 8 * (B_S + v));
                WSTAMP(9);
                uint4 a[8];
#pragma unroll
                for (int b = 0; b < 2; b++) {
#pragma unroll
                    for (int j = 0; j < 8; j++) { const int u = 4 * b + (j >> 1) + 8 * (j & 1); ldsm4t((u < 8 ? src[u & 1] ^ 16 : src[u & 1]) + ((u >> 1) & 3) * 256, a[j].x, a[j].y, a[j].z, a[j].w); }
#pragma unroll
                    for (int j = 0; j < 8; j++) {
                        const int u = 4 * b + (j >> 1) + 8 * (j & 1);
                        if (u < 8) st_async16(rdst + ((u >> 1) & 3) * 64 + (u & 1) * U_PL, a[j], rbar);
                        else sts128(dst + ((u >> 1) & 3) * 64 + (u & 1) * U_PL, a[j].x, a[j].y, a[j].z, a[j].w);
                    }
                }
                if (h && v == 3) {
                    ldsm4t((src[0] ^ 16) + 1024, a[0].x, a[0].y, a[0].z, a[0].w);
                    ldsm4t(src[0] + 1024, a[1].x, a[1].y, a[1].z, a[1].w);
                    if (t == 0) {
                        st_async16(rdst + 256, make_uint4(a[0].x, a[0].y & 0xffffu, a[0].z & 0xffffu, a[0].w & 0xffffu), rbar);
                        sts128(dst + 256, a[1].x, a[1].y & 0xffffu, a[1].z & 0xffffu, a[1].w & 0xffffu);
                    }
                }
                __syncwarp();
                if (lane == 0) mbar_arrive(bars + 8 * B_U);
            }
            if ((lane & 7) == 2) st_gpu32((uint32_t*)p.sc->g + ((row & 256) << 2) + gate_pos(row), pack_bf(sigmoid_f(__uint_as_float(rb)), 0.f) | (tag << 16));
            WSTAMP(2);
        }
        {
            const bool lane0 = pin(lane, lane) == 0;
            const uint32_t own = pin(sb + OFF_XSEL + (at ^ ((at >> 1) & 4)) * 16, lane);
            float acc[8][4];
#pragma unroll
            for (int i = 0; i < 8; i++) { acc[i][0] = acc[i][1] = acc[i][2] = acc[i][3] = 0.f; }
            const int krow = ((lane >> 1) & 8) + (lane & 7);
            const uint32_t tile0 = pin(sb + OFF_RING + krow * 64 + ((((lane >> 3) & 1) ^ ((krow >> 1) & 3)) << 4), lane);
            const uint32_t xo = pin(sb + OFF_XSEL + (lane & 7) * XS_ROW + 512 * v + 2 * (lane & 24), lane);
            const uint32_t po = pin(sb + OFF_XSEL + t * XS_ROW + (g & 3) * 128 + (g & 1) * 64 + v * 16 + (lane >> 4) * 8, lane);
            const uint32_t po1 = pin(po + 64 - (g & 1) * 128, lane);
            uint32_t* hdst = pin((uint32_t*)&p.sc->h[tag & 1][32 * c] + at, lane);
            auto signal = [&](const int k, const uint32_t dep) {
                if (lane < 2 && v < 2)
                    asm volatile("st.async.weak.shared::cluster.mbarrier::complete_tx::bytes.b32 [%0], %1, [%2];"
                                 :: "r"(mapa(sb + M_SINK, lane)), "r"(dep), "r"(mapa(bars + 8 * (B_F + k), lane)) : "memory");
            };
#pragma unroll 1
            for (int i = 0; i < 4; i++) {
                const int s = 4 * i + v;
                uint32_t a[16][4], b[2][4];
                if (gu) {
                    const uint32_t tile = tile0 + (s < 14 ? s : v) * 8192;
                    if (lane0 && i > 1) mbar_arrive(bars + 8 * (B_E + s - 4));
                    if (i == 2) signal(0, 0);
                    mbar_wait(bars + 8 * (B_W + s));
#pragma unroll
                    for (int q = 0; q < 16; q++) ldsm4t((tile ^ ((q & 1) << 5)) + ((q >> 1) & 1) * 4096 + (q >> 2) * 1024, a[q][0], a[q][1], a[q][2], a[q][3]);
                }
                if (i == 0) {
                    if (gu) {
                        uint32_t dep = p.zero;
#pragma unroll
                        for (int q = 0; q < 16; q += 2) dep &= a[q][0] & a[q + 1][0];
                        if (lane == 0) mbar_arrive(bars + 8 * (B_E + v) + dep);
                    }
                    WSTAMP(11);
                    uint32_t top;
#pragma unroll 1
                    for (int it = 0; it < (1 << 22); it++) {
                        asm volatile("ld.relaxed.gpu.global.u32 %0, [%1];" : "=r"(top) : "l"(&p.sc->top[c % NTOP][g]) : "memory");
                        if (__all_sync(0xffffffffu, ((top ^ (tag << 11)) & 0xf800u) == 0)) break;
                        __nanosleep(40);
                    }
                    WSTAMP(3);
                    if (gu) {
                        const uint32_t k = 4 * h + v, row = __reduce_max_sync(0xffffffffu, lane == 4 * k ? ~top & 2047 : 0);
                        asm volatile("{\n\t.reg .pred p;\n\telect.sync _|p, 0xffffffff;\n\t"
                                     "@p cp.async.bulk.shared::cluster.global.mbarrier::complete_tx::bytes.multicast::cluster [%0], [%1], 2048, [%2], %3;\n\t}"
                            :: "r"(sb + OFF_XSEL + k * XS_ROW), "l"(p.u + (size_t)row * D_), "r"(bars + 8 * B_G), "h"((unsigned short)3) : "memory");
                    }
                    if (v == 2) {
                        const uint32_t row = ~top & 2047;
                        if (t == 0 && ((row >> 8) & 1) == h)
                            asm volatile("red.shared.or.b32 [%0], %1;" :: "r"(sb + M_BMAP + (row & 7) * 16 + (row >> 9) * 4), "r"(1u << (gate_pos(row) & 31)) : "memory");
                        if (t == 0) sts32(sb + M_TOP + lane, top);
                        if (c == 0 && lane == 0) *(volatile unsigned*)&p.sc->epoch = tag;
                        __syncwarp();
                        if (lane0) mbar_arrive(bars + 8 * B_Y);
                    }
                    if (!gu) break;
                    mbar_wait(bars + 8 * B_G);
                    WSTAMP(4);
                }
                ldsm4(xo + 128 * i, b[0][0], b[0][1], b[0][2], b[0][3]);
                ldsm4(xo + 128 * i + 64, b[1][0], b[1][1], b[1][2], b[1][3]);
#pragma unroll
                for (int q = 0; q < 16; q++) mma_bf(acc[q & 7], a[q][0], a[q][1], a[q][2], a[q][3], b[q >> 3][(q >> 1) & 2], b[q >> 3][((q >> 1) & 2) + 1]);
            }
            if (gu) {
                WSTAMP(5);
                __syncwarp();
#pragma unroll
                for (int q = 0; q < 4; q++) {
                    const int ct = q >> 1, e = 2 * (q & 1);
                    sts128(own + q * XS_ROW,
                           __float_as_uint(acc[ct][e] + acc[4 + ct][e]), __float_as_uint(acc[2 + ct][e] + acc[6 + ct][e]),
                           __float_as_uint(acc[ct][e + 1] + acc[4 + ct][e + 1]), __float_as_uint(acc[2 + ct][e + 1] + acc[6 + ct][e + 1]));
                }
                bar_sync(1, 128);
                float sl[2], uv[2];
#pragma unroll
                for (int e = 0; e < 2; e++) {
                    uint2 q[4];
#pragma unroll
                    for (int i = 0; i < 4; i++) q[i] = lds64((e ? po1 : po) + 512 * i);
                    const float s0 = (__uint_as_float(q[0].x) + __uint_as_float(q[1].x)) + (__uint_as_float(q[2].x) + __uint_as_float(q[3].x));
                    const float s1 = (__uint_as_float(q[0].y) + __uint_as_float(q[1].y)) + (__uint_as_float(q[2].y) + __uint_as_float(q[3].y));
                    const float gv = bf_round(p.gu_swap ? s1 : s0);
                    uv[e] = p.gu_swap ? s0 : s1;
                    sl[e] = gv * sigmoid_f(gv);
                }
                const uint32_t hw = hmul2_bf(pack_bf(sl[0], sl[1]), pack_bf(uv[0], uv[1]));
                st_gpu32(hdst, hw ? hw : 0x80000000u);
                signal(1, hw);
            }
        }
        WSTAMP(6);
        {
            const uint32_t own = pin(sb + OFF_XSEL + at * 16, lane);
            const uint32_t hb = sb + (v < 2 ? OFF_XSEL + 7168 * v : OFF_RING + 8192 * v), hl = pin(hb + 16 * lane, lane);
            const int krow = ((lane >> 1) & 8) + (lane & 7);
            const uint32_t tile = pin(sb + OFF_RING + v * 8192 + krow * 32 + ((((lane >> 3) ^ (krow >> 2)) & 1) << 4), lane);
            float dd[4][4];
            bar_sync(1, 128);
            mbar_wait(bars + 8 * (B_W + HW));
            WSTAMP(12);
            uint4 hq[7];
            {
                const uint4* hs = &p.sc->h[tag & 1][32 * (56 * h + 14 * v)];
                bulk_load(hb, hs, 3584, bars + 8 * (B_X + v));
                bulk_load(hb + 3584, hs + 224, 3584, bars + 8 * (B_XE + v));
                uint32_t a[14][4];
                mbar_wait(bars + 8 * (B_W + 16 + v));
#pragma unroll
                for (int j = 0; j < 14; j++) ldsm4t(tile + (v & 2) * 16384 + j * 512, a[j][0], a[j][1], a[j][2], a[j][3]);
#pragma unroll
                for (int k = 0; k < 2; k++) {
                    mbar_wait(bars + 8 * ((k ? B_XE : B_X) + v), 1);
                    if (!k) WSTAMP(7);
                    uint32_t mn = 0xffffffffu;
#pragma unroll
                    for (int j = 0; j < 7; j++) { hq[j] = lds128(hl + 3584 * k + 512 * j); mn = min(mn, hq[j].x); }
#pragma unroll 1
                    for (int it = 0; it < (1 << 20) && !__all_sync(0xffffffffu, mn != 0); it++) {
                        mn = 0xffffffffu;
#pragma unroll
                        for (int j = 0; j < 7; j++)
                            asm volatile("{\n\t.reg .pred p;\n\tsetp.eq.u32 p, %0, 0;\n\t@p ld.relaxed.gpu.global.v4.u32 {%0,%1,%2,%3}, [%4];\n\t}"
                                         : "+r"(hq[j].x), "+r"(hq[j].y), "+r"(hq[j].z), "+r"(hq[j].w) : "l"(hs + 224 * k + 32 * j + lane) : "memory");
#pragma unroll
                        for (int j = 0; j < 7; j++) mn = min(mn, hq[j].x);
                    }
                    if (!k) {
#pragma unroll
                        for (int j = 0; j < 14; j++) {
                            const uint4& q = hq[j >> 1];
                            if (j < 4) mma_bf_z(dd[j], a[j][0], a[j][1], a[j][2], a[j][3], (j & 1) ? q.z : q.x, (j & 1) ? q.w : q.y);
                            else mma_bf(dd[j & 3], a[j][0], a[j][1], a[j][2], a[j][3], (j & 1) ? q.z : q.x, (j & 1) ? q.w : q.y);
                        }
                    }
                }
            }
            mbar_wait(bars + 8 * (B_W + 20 + v));
#pragma unroll
            for (int j = 0; j < 14; j++) {
                uint32_t f[4];
                ldsm4t(tile + 65536 + j * 512, f[0], f[1], f[2], f[3]);
                mma_bf(dd[(j + 2) & 3], f[0], f[1], f[2], f[3], (j & 1) ? hq[j >> 1].z : hq[j >> 1].x, (j & 1) ? hq[j >> 1].w : hq[j >> 1].y);
            }
            WSTAMP(8);
            uint4 part;
            part.x = __float_as_uint((dd[0][0] + dd[1][0]) + (dd[2][0] + dd[3][0])); part.y = __float_as_uint((dd[0][1] + dd[1][1]) + (dd[2][1] + dd[3][1]));
            part.z = __float_as_uint((dd[0][2] + dd[1][2]) + (dd[2][2] + dd[3][2])); part.w = __float_as_uint((dd[0][3] + dd[1][3]) + (dd[2][3] + dd[3][3]));
            st_async16(mapa(own + (M_DPIN - OFF_XSEL), h ^ 1), part, mapa(bars + 8 * B_DP, h ^ 1));
            sts128(own + 14336, part.x, part.y, part.z, part.w);
            __syncwarp();
            if (lane == 0) mbar_arrive(bars + 8 * B_DP);
        }
        WDUMP();
    } else {
        asm volatile("setmaxnreg.dec.sync.aligned.u32 64;");
        const int v = __reduce_max_sync(0xffffffffu, pw - PREP_W0);
        const bool gu = c < NGU_CTA;
        const uint32_t t0 = clock();
        const uint32_t bu = bars + 8 * v;
        if (lane == 0) {
#pragma unroll
            for (int i = 0; i < 10; i++) mbar_init(bu + 32 * i, 1);
            mbar_init(bu + 8 * B_X, 1);
            mbar_init(bu + 8 * B_XE, 1);
            mbar_init(bu + 8 * B_Y, v == 0 ? 11 : 9);
            mbar_init(bu + 8 * B_DP, (0x1855 >> (4 * v)) & 15);
            mbar_init(bu + 8 * B_F, 1);
            mbar_init(bu + 8 * B_H, 1);
            asm volatile("fence.mbarrier_init.release.cluster;" ::: "memory");
            mbar_expect(bu + 8 * B_Y, 4096);
            if (v != 2) mbar_expect(bu + 8 * B_DP, v == 0 ? 2048 : (h || v == 3) ? 16384 : 16384 + 128);
            mbar_expect(bu + 8 * B_F, c < NGU_CTA ? 16 : 0);
        }
        __syncwarp();
        asm volatile("barrier.cluster.arrive.relaxed.aligned;" ::: "memory");
        bulk_load(sb + (v < 2 ? OFF_XSEL : OFF_RING + 2 * 8192) + v * 8192, p.u + (size_t)(16 * c + 4 * v) * D_, 8192, bu + 8 * B_X);
        tma3d(sb + OFF_S + v * S_Q, &tm_x, 16 * pr, 64 * v + 32 * h - 1, bars + 8 * (B_S + v), S_Q);
        WSTAMP(9);
        if (v < 3 && lane == 0) asm volatile("prefetch.tensormap [%0];" :: "l"(v == 0 ? &tm_gu : v == 1 ? &tm_down : &tm_out) : "memory");
        asm volatile("barrier.cluster.wait.acquire.aligned;" ::: "memory");
        uint32_t desc;
        {
            const int s = 6 * v + lane, i = s >> 2, w = s & 3, slot = s < 14 ? s : (s | 1) == 17 ? s - 16 : s - 12;
            const int fb = s < 4 ? B_H : (gu && s >= 14) ? B_E + slot : s < 6 ? B_XE + s - 2 : B_KG;
            desc = slot | (fb << 4) | ((i < 4 ? 256 * w + 64 * i : 1792 * h + 448 * w + 224 * (i - 4)) << 10);
            if (lane < 6) mbar_expect(bars + 8 * (B_W + s), i < 4 ? 8192 : 7168);
            if (tid == 32 * PREP_W0) mbar_arrive(bars + 8 * B_H);
        }
        if (v == 3) {
            mbar_wait(bars + 8 * B_U);
            mbar_wait(bars + 8 * (gu ? B_G : B_H + 2));
            const uint32_t tag16 = lds32(sb + M_TAG);
            uint4 q[8];
#pragma unroll 1
            for (int it = 0; it < (1 << 22); it++) {
                uint32_t bad = 0;
#pragma unroll
                for (int i = 0; i < 8; i++) q[i] = ld_gpu128(&p.sc->g[256 * h + 32 * i + lane]);
#pragma unroll
                for (int i = 0; i < 8; i++) bad |= ((q[i].x ^ tag16) | (q[i].y ^ tag16)) | ((q[i].z ^ tag16) | (q[i].w ^ tag16));
                if ((bad >> 16) == 0) break;
                __nanosleep(200);
            }
#pragma unroll
            for (int i = 0; i < 8; i++)
                asm volatile("st.shared.v2.u32 [%0], {%1, %2};" :: "r"(sb + OFF_GP + 256 * i + lane * 8),
                             "r"(__byte_perm(q[i].x, q[i].y, 0x5410)), "r"(__byte_perm(q[i].z, q[i].w, 0x5410)) : "memory");
            __syncwarp();
            if (lane == 0) mbar_arrive(bars + 8 * B_Y);
        }
        mbar_wait(bars + 8 * (B_H + v));
        {
            const int gap = v == 0 ? GAP : v == 1 ? GAP1 : v == 2 ? GAP2 : GAP3;
            uint32_t last = v ? clock() - SLACK : t0 + T0 - GAP + GAP * ((pr * 5) & 15) / 16;
#pragma unroll 1
            for (int k = 0; k < 6; k++) {
                const uint32_t dk = __reduce_max_sync(0xffffffffu, lane == k ? desc : 0);
                const bool dn = 6 * v + k >= 16;
                const uint32_t dst = sb + OFF_RING + (dk & 15) * 8192, bar = bars + 8 * (B_W + 6 * v + k), c0 = dn ? 16 * pr : 32 * c, c1 = dk >> 10;
                const CUtensorMap* tm = dn ? &tm_down : &tm_gu;
                mbar_wait(bars + ((dk >> 1) & 0x1f8));
                int late;
#pragma unroll 1
                while ((late = (int)(clock() - last) - gap) < 0) __nanosleep(max(-late >> 2, 32));
                WSTAMP(3 + k);
                if (gu || dn)
                    asm volatile("{\n\t.reg .pred p;\n\telect.sync _|p, 0xffffffff;\n\t"
                                 "@p cp.async.bulk.tensor.3d.shared::cluster.global.mbarrier::complete_tx::bytes [%0], [%1, {%3, %4, 0}], [%2];\n\t}"
                        :: "r"(dst), "l"(tm), "r"(bar), "r"(c0), "r"(c1) : "memory");
                last += gap + max(late - SLACK, 0);
            }
            if (lane == 0 && v < 3) mbar_arrive(bars + 8 * (B_H + v + 1));
        }
        {
            WSTAMP(1);
            mix_rows<2>(p, &tm_out, sb, sb + OFF_TAB + v * TAB_W, 0, PQ, v, h, pr, lane);
            WSTAMP(2);
            asm volatile("cp.async.bulk.commit_group;" ::: "memory");
            const uint32_t top = lds32(sb + M_TOP + 8 * v + 4 * (lane >> 4));
            const uint32_t row = ~top & 2047, ch = lane & 15, gp = gate_pos(row);
            const bool mine = ((row >> 8) & 1) == h;
            uint32_t gfin, x16, y16 = 0;
            asm volatile("ld.shared.u16 %0, [%1];" : "=r"(gfin) : "r"(sb + OFF_GP + gp * 2) : "memory");
            asm volatile("ld.shared.u16 %0, [%1];" : "=r"(x16) : "r"(sb + OFF_S + (row >> 9) * S_Q + s_addr((row & 7) * S_PL + 32 + (row & 248) * 4, ch >> 3) + 2 * (ch & 7)) : "memory");
            const float rsel = __uint_as_float(pin(__float_as_uint(bf_round(sigmoid_f(__uint_as_float((top ^ (((int)~top >> 31) | 0x80000000u)) & 0xffff0000u)))), lane));
            const uint32_t po = pin(sb + (4 * (ch & 7) + v) * 16 + (ch >> 3) * 8 + (lane >> 4) * 4, lane);
            bf16* op = pin(p.out + (size_t)row * D_ + 16 * pr + ch, lane);
            if (mine) {
                mbar_wait(bars + 8 * (B_Y + (row >> 9)));
                asm volatile("ld.shared.u16 %0, [%1];" : "=r"(y16)
                             : "r"(sb + y_off(row >> 9) + ch * 512 + (((4 * (row & 7) + ((row >> 5) & 3)) ^ (((ch >> 2) << 1) | (ch & 1))) << 4) + 2 * row_elem(row)) : "memory");
            }
            mbar_wait(bars + 8 * B_DP);
            float q[8];
#pragma unroll
            for (int i = 0; i < 4; i++) { q[i] = ldsf(po + M_DPIN + 512 * i); q[4 + i] = ldsf(po + OFF_XSEL + 14336 + 512 * i); }
            const float tot = ((q[0] + q[1]) + (q[2] + q[3])) + ((q[4] + q[5]) + (q[6] + q[7]));
            const float b = bf_round(__uint_as_float(x16 << 16) + bf_round(bf_round(tot) * rsel));
            if (mine) *op = __float2bfloat16_rn(fmaf(bf_lo(gfin), __uint_as_float(y16 << 16), bf_round(bf_round(1.f - bf_lo(gfin)) * b)));
        }
        asm volatile("cp.async.bulk.wait_group.read 0;" ::: "memory");
        WSTAMP(10);
        WDUMP();
    }
}

typedef CUresult (*EncodeFn)(CUtensorMap*, CUtensorMapDataType, cuuint32_t, void*, const cuuint64_t*, const cuuint64_t*,
                             const cuuint32_t*, const cuuint32_t*, CUtensorMapInterleave, CUtensorMapSwizzle,
                             CUtensorMapL2promotion, CUtensorMapFloatOOBfill);

void make_map(EncodeFn f, CUtensorMap* m, const void* ptr, uint64_t cols, uint64_t rows, uint64_t pitch, uint32_t bc, uint32_t br, CUtensorMapSwizzle sw, CUtensorMapL2promotion prom,
              uint32_t planes = 1, uint64_t plane_stride = 0, uint32_t box_planes = 0) {
    cuuint64_t dims[3] = {cols, rows, planes};
    cuuint64_t str[2] = {pitch, planes > 1 ? plane_stride : pitch * rows};
    cuuint32_t box[3] = {bc, br, box_planes ? box_planes : planes};
    cuuint32_t es[3] = {1, 1, 1};
    f(m, CU_TENSOR_MAP_DATA_TYPE_BFLOAT16, 3, (void*)ptr, dims, str, box, es, CU_TENSOR_MAP_INTERLEAVE_NONE, sw,
      prom, CU_TENSOR_MAP_FLOAT_OOB_FILL_NONE);
}

}

extern "C" void kernel_launch(void* const* d_in, const int* in_sizes, int n_in, void* d_out, int out_size) {
    static EncodeFn enc = nullptr;
    static void *sc = nullptr, *band = nullptr;
    if (!enc) {
        void* fn = nullptr;
        cudaDriverEntryPointQueryResult qr;
        cudaGetDriverEntryPoint("cuTensorMapEncodeTiled", &fn, cudaEnableDefault, &qr);
        enc = (EncodeFn)fn;
        cudaGetSymbolAddress(&sc, g_scratch);
        cudaGetSymbolAddress(&band, g_band);
        cudaFuncSetAttribute(fused_kernel, cudaFuncAttributeMaxDynamicSharedMemorySize, SMEM_BYTES);
    }
    CUtensorMap tg, td, tx, to;
    const char *wg = (const char*)d_in[9], *wu = (const char*)d_in[10];
    const bool swap = wu < wg;
    make_map(enc, &tg, swap ? wu : wg, F_, D_, F_ * 2, 32, 64, CU_TENSOR_MAP_SWIZZLE_64B, CU_TENSOR_MAP_L2_PROMOTION_L2_128B, 2, swap ? wg - wu : wu - wg);
    make_map(enc, &td, d_in[11], D_, F_, D_ * 2, 16, 224, CU_TENSOR_MAP_SWIZZLE_32B, CU_TENSOR_MAP_L2_PROMOTION_L2_64B);
    make_map(enc, &tx, d_in[0], D_, L_ / 8, D_ * 16, 16, 33, CU_TENSOR_MAP_SWIZZLE_32B, CU_TENSOR_MAP_L2_PROMOTION_NONE, 8, D_ * 2);
    make_map(enc, &to, d_out, D_, L_ / 8, D_ * 16, 16, 32, CU_TENSOR_MAP_SWIZZLE_NONE, CU_TENSOR_MAP_L2_PROMOTION_NONE, 8, D_ * 2, 1);
    Params p;
    p.u = (const bf16*)d_in[0]; p.logA = (const bf16*)d_in[1]; p.Aim = (const bf16*)d_in[2];
    p.Cre = (const bf16*)d_in[3]; p.Cim = (const bf16*)d_in[4]; p.logdt = (const bf16*)d_in[5];
    p.Dskip = (const bf16*)d_in[6]; p.wr = (const bf16*)d_in[8]; p.gatew = (const bf16*)d_in[12];
    p.out = (bf16*)d_out;
    p.sc = (Scratch*)sc; p.band = (const uint4*)band;
    p.gu_swap = swap;
    p.zero = 0;
    fused_kernel<<<NCTA, NTHREADS, SMEM_BYTES>>>(p, tg, td, tx, to);
}
```

```cpp
#include <cuda_runtime.h>
#include <cuda_bf16.h>
#include <cuda_fp16.h>
#include <cuda.h>
#include <stdint.h>

typedef __nv_bfloat16 bf16;

namespace {

constexpr int L_ = 2048, D_ = 1024, F_ = 3584;
constexpr int NCTA = 130;
constexpr int NTHREADS = 512;
constexpr int MAIN_W0 = 0, PREP_W0 = 8, AUX_W0 = 12;
#define T0 3150
#define GAP 510
#define GAP1 515
#define GAP2 515
#define GAP3 560
#define HW 20
constexpr int SLACK = 300;
constexpr int PQ = 3;
constexpr int NGU_CTA = 112;

constexpr int OFF_RING = 0;
constexpr int OFF_SCR  = 6 * 8192;
constexpr int S_PL     = 1056;
constexpr int S_Q      = 8 * S_PL;
constexpr int OFF_S    = 114688;
constexpr int OFF_GP   = OFF_S + 4 * S_Q;
constexpr int U_PL     = 2240;
constexpr int U_CH     = 4416;
constexpr int OFF_U    = 151552;
constexpr int TAB_W    = 3200;
constexpr int T_PL     = 544;
constexpr int T_A      = 2192 - 26 * 8;
constexpr int T_B      = 2568 - 59 * 8;
constexpr int OFF_TAB  = 186880;
constexpr int OFF_XSEL = 212480;
constexpr int XS_ROW   = 2064;
constexpr int OFF_BAND = 228992;
constexpr int OFF_MISC = 229536;
constexpr int M_BARS   = OFF_MISC;
constexpr int M_DSK    = OFF_MISC + 2736;
constexpr int M_SINK   = OFF_MISC + 512;
constexpr int M_TAG    = OFF_MISC + 516;
constexpr int M_BMAP   = OFF_MISC + 528;
constexpr int M_DPIN   = OFF_MISC + 656;
constexpr int M_TOP    = OFF_MISC + 2704;
constexpr int SMEM_BYTES = OFF_MISC + 2768;
__device__ __forceinline__ uint32_t s_addr(uint32_t o, uint32_t half) { return o + (((half ^ (o >> 7)) & 1) << 4); }
__host__ __device__ constexpr uint32_t y_off(uint32_t q) { return OFF_RING + 32768 + (q & 1) * 8192 + (q >> 1) * 65536; }

constexpr int B_W = 0;
constexpr int B_E = 24;
constexpr int B_S = 36;
constexpr int B_Y = 40;
constexpr int B_DP = 44, B_U = 45, B_KG = 46, B_G = 47;
constexpr int B_F = 48;
constexpr int B_H = 60;
constexpr int B_X = 52, B_XE = 56;

struct BandTab { uint32_t w[11][12]; };
constexpr BandTab make_band() {
    BandTab b{};
    for (int cls = 0; cls < 11; cls++)
        for (int wd = 0; wd < 10; wd++) {
            const int tau = cls + 2 - 8 * ((wd < 4 ? wd : wd - 4) >> 1);
            const int lo = (wd < 4) ? ((wd & 1) ? -2 : 3) : ((wd & 1) ? -4 : -11), wid = (wd < 4 ? 3 : 7) + 2 * (wd & 1);
            b.w[cls][wd] = ((tau >= lo && tau < lo + wid) ? 0x3F80u : 0u) | ((tau - 4 >= lo && tau - 4 < lo + wid) ? 0x3F800000u : 0u);
        }
    return b;
}
constexpr int NTOP = 32;
struct Scratch {
    uint4 r[L_ / 4];
    uint4 g[L_ / 4];
    uint4 h[2][8 * F_ / 8];
    uint32_t top[NTOP][32];
    unsigned epoch;
};
__device__ __align__(128) Scratch g_scratch;
__device__ const __align__(16) BandTab g_band = make_band();

struct Params {
    const bf16 *u, *logA, *Aim, *Cre, *Cim, *logdt, *Dskip, *wr, *gatew;
    bf16* out;
    Scratch* sc;
    const uint4* band;
    uint32_t gu_swap;
    uint32_t zero;
};

#define WSTAMP(i) do {} while (0)
#define KSTAMP(i, dep) do {} while (0)
#define WDUMP() do {} while (0)
#define RSTAMP(i) do {} while (0)

__device__ __forceinline__ uint32_t smem_u32(const void* p) { return (uint32_t)__cvta_generic_to_shared(p); }
__device__ __forceinline__ void mbar_init(uint32_t b, uint32_t c) { asm volatile("mbarrier.init.shared::cta.b64 [%0], %1;" :: "r"(b), "r"(c) : "memory"); }
__device__ __forceinline__ void mbar_expect(uint32_t b, uint32_t tx) { asm volatile("mbarrier.arrive.expect_tx.shared::cta.b64 _, [%0], %1;" :: "r"(b), "r"(tx) : "memory"); }
__device__ __forceinline__ void mbar_arrive(uint32_t b) { asm volatile("mbarrier.arrive.shared::cta.b64 _, [%0];" :: "r"(b) : "memory"); }
__device__ __forceinline__ void mbar_wait(uint32_t b, uint32_t parity = 0) {
    asm volatile("{\n\t.reg .pred p;\nW%=:\n\tmbarrier.try_wait.parity.shared::cta.b64 p, [%0], %1, 20000;\n\t@!p bra W%=;\n\t}" :: "r"(b), "r"(parity) : "memory");
}
__device__ __forceinline__ uint32_t mapa(uint32_t addr, uint32_t rank) { uint32_t r; asm("mapa.shared::cluster.u32 %0, %1, %2;" : "=r"(r) : "r"(addr), "r"(rank)); return r; }
__device__ __forceinline__ void tma3d(uint32_t dst, const CUtensorMap* tm, int c0, int c1, uint32_t bar, uint32_t bytes) {
    asm volatile("{\n\t.reg .pred p;\n\telect.sync _|p, 0xffffffff;\n\t"
                 "@p mbarrier.arrive.expect_tx.shared::cta.b64 _, [%2], %5;\n\t"
                 "@p cp.async.bulk.tensor.3d.shared::cluster.global.mbarrier::complete_tx::bytes [%0], [%1, {%3, %4, 0}], [%2];\n\t}"
        :: "r"(dst), "l"(tm), "r"(bar), "r"(c0), "r"(c1), "r"(bytes) : "memory");
}
__device__ __forceinline__ void bulk_load(uint32_t dst, const void* src, uint32_t bytes, uint32_t bar) {
    asm volatile("{\n\t.reg .pred p;\n\telect.sync _|p, 0xffffffff;\n\t"
                 "@p mbarrier.arrive.expect_tx.shared::cta.b64 _, [%2], %3;\n\t"
                 "@p cp.async.bulk.shared::cluster.global.mbarrier::complete_tx::bytes [%0], [%1], %3, [%2];\n\t}"
        :: "r"(dst), "l"(src), "r"(bar), "r"(bytes) : "memory");
}
__device__ __forceinline__ void st_async16(uint32_t dst, const uint4& v, uint32_t bar) {
    asm volatile("st.async.weak.shared::cluster.mbarrier::complete_tx::bytes.v4.b32 [%0], {%1,%2,%3,%4}, [%5];"
                 :: "r"(dst), "r"(v.x), "r"(v.y), "r"(v.z), "r"(v.w), "r"(bar) : "memory");
}
__device__ __forceinline__ void bar_sync(int id, int n) { asm volatile("bar.sync %0, %1;" :: "r"(id), "r"(n) : "memory"); }
__device__ __forceinline__ void cp16(uint32_t dst, const void* src) { asm volatile("cp.async.cg.shared.global [%0], [%1], 16;" :: "r"(dst), "l"(src) : "memory"); }
__device__ __forceinline__ void cp_wait_all() { asm volatile("cp.async.wait_all;" ::: "memory"); }
__device__ __forceinline__ uint4 ld_gpu128(const void* p) { uint4 v; asm volatile("ld.relaxed.gpu.global.v4.u32 {%0,%1,%2,%3}, [%4];" : "=r"(v.x), "=r"(v.y), "=r"(v.z), "=r"(v.w) : "l"(p) : "memory"); return v; }
__device__ __forceinline__ void st_gpu32(void* p, uint32_t v) { asm volatile("st.relaxed.gpu.global.u32 [%0], %1;" :: "l"(p), "r"(v) : "memory"); }

__device__ __forceinline__ void ldsm4(uint32_t a, uint32_t& r0, uint32_t& r1, uint32_t& r2, uint32_t& r3) {
    asm volatile("ldmatrix.sync.aligned.m8n8.x4.shared.b16 {%0,%1,%2,%3}, [%4];" : "=r"(r0), "=r"(r1), "=r"(r2), "=r"(r3) : "r"(a) : "memory");
}
__device__ __forceinline__ void ldsm4t(uint32_t a, uint32_t& r0, uint32_t& r1, uint32_t& r2, uint32_t& r3) {
    asm volatile("ldmatrix.sync.aligned.m8n8.x4.trans.shared.b16 {%0,%1,%2,%3}, [%4];" : "=r"(r0), "=r"(r1), "=r"(r2), "=r"(r3) : "r"(a) : "memory");
}
__device__ __forceinline__ uint32_t lds32(uint32_t a) { uint32_t v; asm volatile("ld.shared.u32 %0, [%1];" : "=r"(v) : "r"(a) : "memory"); return v; }
__device__ __forceinline__ uint2 lds64(uint32_t a) { uint2 v; asm volatile("ld.shared.v2.u32 {%0,%1}, [%2];" : "=r"(v.x), "=r"(v.y) : "r"(a) : "memory"); return v; }
__device__ __forceinline__ uint4 lds128(uint32_t a) { uint4 v; asm volatile("ld.shared.v4.u32 {%0,%1,%2,%3}, [%4];" : "=r"(v.x), "=r"(v.y), "=r"(v.z), "=r"(v.w) : "r"(a) : "memory"); return v; }
__device__ __forceinline__ void sts32(uint32_t a, uint32_t v) { asm volatile("st.shared.u32 [%0], %1;" :: "r"(a), "r"(v) : "memory"); }
__device__ __forceinline__ void sts16(uint32_t a, uint32_t v) { asm volatile("st.shared.u16 [%0], %1;" :: "r"(a), "h"((unsigned short)v) : "memory"); }
__device__ __forceinline__ void sts128(uint32_t a, uint32_t x, uint32_t y, uint32_t z, uint32_t w) { asm volatile("st.shared.v4.u32 [%0], {%1,%2,%3,%4};" :: "r"(a), "r"(x), "r"(y), "r"(z), "r"(w) : "memory"); }
__device__ __forceinline__ float ldsf(uint32_t a) { float v; asm volatile("ld.shared.f32 %0, [%1];" : "=f"(v) : "r"(a) : "memory"); return v; }

__device__ __forceinline__ void mma_bf(float (&d)[4], uint32_t a0, uint32_t a1, uint32_t a2, uint32_t a3, uint32_t b0, uint32_t b1) {
    asm volatile("mma.sync.aligned.m16n8k16.row.col.f32.bf16.bf16.f32 {%0,%1,%2,%3}, {%4,%5,%6,%7}, {%8,%9}, {%0,%1,%2,%3};"
        : "+f"(d[0]), "+f"(d[1]), "+f"(d[2]), "+f"(d[3]) : "r"(a0), "r"(a1), "r"(a2), "r"(a3), "r"(b0), "r"(b1));
}
__device__ __forceinline__ void mma_bf_z(float (&d)[4], uint32_t a0, uint32_t a1, uint32_t a2, uint32_t a3, uint32_t b0, uint32_t b1) {
    asm volatile("mma.sync.aligned.m16n8k16.row.col.f32.bf16.bf16.f32 {%0,%1,%2,%3}, {%4,%5,%6,%7}, {%8,%9}, {%10,%10,%10,%10};"
        : "=f"(d[0]), "=f"(d[1]), "=f"(d[2]), "=f"(d[3]) : "r"(a0), "r"(a1), "r"(a2), "r"(a3), "r"(b0), "r"(b1), "f"(0.f));
}
__device__ __forceinline__ void mma_bf_k8(float (&d)[4], uint32_t a0, uint32_t a1, uint32_t b0) {
    asm volatile("mma.sync.aligned.m16n8k8.row.col.f32.bf16.bf16.f32 {%0,%1,%2,%3}, {%4,%5}, {%6}, {%0,%1,%2,%3};"
        : "+f"(d[0]), "+f"(d[1]), "+f"(d[2]), "+f"(d[3]) : "r"(a0), "r"(a1), "r"(b0));
}
__device__ __forceinline__ void mma_h(float (&d)[4], uint32_t a0, uint32_t a1, uint32_t a2, uint32_t a3, uint32_t b0, uint32_t b1) {
    asm volatile("mma.sync.aligned.m16n8k16.row.col.f32.f16.f16.f32 {%0,%1,%2,%3}, {%4,%5,%6,%7}, {%8,%9}, {%0,%1,%2,%3};"
        : "+f"(d[0]), "+f"(d[1]), "+f"(d[2]), "+f"(d[3]) : "r"(a0), "r"(a1), "r"(a2), "r"(a3), "r"(b0), "r"(b1));
}
__device__ __forceinline__ uint32_t pack_bf(float lo, float hi) { uint32_t r; asm("cvt.rn.bf16x2.f32 %0, %1, %2;" : "=r"(r) : "f"(hi), "f"(lo)); return r; }
__device__ __forceinline__ uint32_t pack_h(float lo, float hi) { uint32_t r; asm("cvt.rn.f16x2.f32 %0, %1, %2;" : "=r"(r) : "f"(hi), "f"(lo)); return r; }
__device__ __forceinline__ float bf_lo(uint32_t v) { return __uint_as_float(v << 16); }
__device__ __forceinline__ float bf_hi(uint32_t v) { return __uint_as_float(v & 0xffff0000u); }
__device__ __forceinline__ float bf_round(float x) { return __uint_as_float(pack_bf(0.f, x)); }
__device__ __forceinline__ uint32_t hmul2_bf(uint32_t a, uint32_t b) { uint32_t r; asm("mul.rn.bf16x2 %0, %1, %2;" : "=r"(r) : "r"(a), "r"(b)); return r; }
__device__ __forceinline__ float ex2f(float x) { float r; asm("ex2.approx.ftz.f32 %0, %1;" : "=f"(r) : "f"(x)); return r; }

__device__ __forceinline__ float exp_acc(float x) {
    const float t = x * 1.4426950216293335f;
    const float r = fmaf(x, 1.4426950216293335f, -t) + x * 1.9259629911266175e-8f;
    return ex2f(t) * fmaf(r, 0.6931471805599453f, 1.f);
}
__device__ __forceinline__ float sigmoid_f(float x) { return __fdividef(1.f, 1.f + ex2f(-x * 1.4426950408889634f)); }
__device__ __forceinline__ void cexp_pow(float l2, float li, float e, float& zr, float& zi) {
    const float mag = ex2f(l2 * e);
    zr = mag * __cosf(li * e);
    zi = mag * __sinf(li * e);
}
__device__ __forceinline__ uint32_t hcmul(uint32_t a, uint32_t k, uint32_t kp) {
    const __half2 A = *reinterpret_cast<const __half2*>(&a);
    const __half2 r = __hfma2(__high2half2(A), *reinterpret_cast<const __half2*>(&kp), __hmul2(__low2half2(A), *reinterpret_cast<const __half2*>(&k)));
    return *reinterpret_cast<const uint32_t*>(&r);
}
#define CMUL(orr, oi, ar, ai, br, bi) do { float _r = (ar) * (br) - (ai) * (bi); float _i = (ar) * (bi) + (ai) * (br); orr = _r; oi = _i; } while (0)
#define CSQ(orr, oi, ar, ai) do { float _r = (ar) * (ar) - (ai) * (ai); float _i = 2.f * (ar) * (ai); orr = _r; oi = _i; } while (0)

__device__ __forceinline__ void mma_bf_k8z(float (&d)[4], uint32_t a0, uint32_t a1, uint32_t b0) {
    asm volatile("mma.sync.aligned.m16n8k8.row.col.f32.bf16.bf16.f32 {%0,%1,%2,%3}, {%4,%5}, {%6}, {%7,%7,%7,%7};"
        : "=f"(d[0]), "=f"(d[1]), "=f"(d[2]), "=f"(d[3]) : "r"(a0), "r"(a1), "r"(b0), "f"(0.f));
}
__device__ __forceinline__ void mma_hh_k8(uint32_t& d0, uint32_t& d1, uint32_t a0, uint32_t a1, uint32_t b0) {
    asm volatile("mma.sync.aligned.m16n8k8.row.col.f16.f16.f16.f16 {%0,%1}, {%2,%3}, {%4}, {%5,%5};"
        : "=r"(d0), "=r"(d1) : "r"(a0), "r"(a1), "r"(b0), "r"(0));
}
__device__ __forceinline__ void sched_fence() { asm volatile("pmevent 0;" ::: "memory"); }
__device__ __forceinline__ uint32_t pin(uint32_t x, int lane) { return __shfl_sync(0xffffffffu, x, lane); }
template <class T> __device__ __forceinline__ T* pin(T* x, int lane) { return (T*)__shfl_sync(0xffffffffu, (unsigned long long)x, lane); }
__device__ __forceinline__ void sts32_if(bool on, uint32_t a, uint32_t v) {
    asm volatile("{\n\t.reg .pred p;\n\tsetp.ne.u32 p, %2, 0;\n\t@p st.shared.u32 [%0], %1;\n\t}" :: "r"(a), "r"(v), "r"((uint32_t)on) : "memory");
}
__device__ __forceinline__ void sts128_if(bool on, uint32_t a, uint32_t x, uint32_t y, uint32_t z, uint32_t w) {
    asm volatile("{\n\t.reg .pred p;\n\tsetp.ne.u32 p, %5, 0;\n\t@p st.shared.v4.u32 [%0], {%1,%2,%3,%4};\n\t}" :: "r"(a), "r"(x), "r"(y), "r"(z), "r"(w), "r"((uint32_t)on) : "memory");
}
__device__ __forceinline__ void lds128_if(bool on, uint32_t a, uint32_t (&v)[4]) {
    asm volatile("{\n\t.reg .pred p;\n\tsetp.ne.u32 p, %5, 0;\n\t@p ld.shared.v4.u32 {%0,%1,%2,%3}, [%4];\n\t}"
        : "+r"(v[0]), "+r"(v[1]), "+r"(v[2]), "+r"(v[3]) : "r"(a), "r"((uint32_t)on) : "memory");
}
__device__ __forceinline__ uint32_t hfma2_bf(uint32_t a, uint32_t b, uint32_t c) { uint32_t r; asm("fma.rn.bf16x2 %0, %1, %2, %3;" : "=r"(r) : "r"(a), "r"(b), "r"(c)); return r; }
__device__ __forceinline__ __nv_bfloat162 bcast(uint32_t a, int hi) { const __nv_bfloat162 v = *reinterpret_cast<const __nv_bfloat162*>(&a); return hi ? __high2bfloat162(v) : __low2bfloat162(v); }
__device__ __forceinline__ uint32_t hmul2_bc(uint32_t a, int hi, uint32_t b) { const __nv_bfloat162 r = __hmul2_rn(bcast(a, hi), *reinterpret_cast<const __nv_bfloat162*>(&b)); return *reinterpret_cast<const uint32_t*>(&r); }
__device__ __forceinline__ uint32_t hfma2_bc(uint32_t a, int hi, uint32_t b, uint32_t c) {
    const __nv_bfloat162 r = __hfma2(bcast(a, hi), *reinterpret_cast<const __nv_bfloat162*>(&b), *reinterpret_cast<const __nv_bfloat162*>(&c));
    return *reinterpret_cast<const uint32_t*>(&r);
}
__device__ __forceinline__ uint32_t row_elem(uint32_t row) { return ((row >> 5) & 4) | ((row >> 2) & 2) | ((row >> 4) & 1); }
__device__ __forceinline__ uint32_t gate_pos(uint32_t row) { return ((row >> 9) << 8) | ((row & 7) << 5) | (row_elem(row) << 2) | ((row >> 5) & 3); }

template <int N>
__device__ __forceinline__ void mix_rows(const Params& p, const CUtensorMap* tm_out, uint32_t sb, uint32_t ob, int Q0, int Q1, int w, int h, int pr, int lane) {
    const int g = lane >> 2, t = lane & 3, mi = lane >> 3, r = lane & 7;
    const int m8 = 16 * (g >> 2) + ((g >> 1) & 1) + 2 * (g & 1);
    uint32_t yi = sb + (4 * (r >> 1) + 2 * (mi & 1) + (r & 1)) * 512 + (((4 * w + (mi >> 1)) ^ r) << 4);
    uint32_t xs = sb + OFF_S + s_addr(w * S_PL + 32 + m8 * 32, t >> 1) + ((t & 1) << 3);
    uint32_t gs = sb + OFF_GP + w * 64 + g * 8, os = ob + m8 * 32 + t * 8;
    if (N > 1) { yi = pin(yi, lane); xs = pin(xs, lane); gs = pin(gs, lane); os = pin(os, lane); }
    mbar_wait(sb + M_BARS + 8 * B_Y);
#pragma unroll 1
    for (int Q = Q0; Q < Q1; Q++) {
        uint2 xq[N][4];
        uint32_t gg[N][2], sw[N];
#pragma unroll
        for (int n = 0; n < N; n++) {
#pragma unroll
            for (int i = 0; i < 4; i++) xq[n][i] = lds64((xs ^ (((i ^ n) & 1) << 4)) + Q * S_Q + n * 4 * S_PL + i * 128);
            const uint2 gq = lds64(gs + Q * 512 + n * 256);
            sw[n] = lds32(sb + M_BMAP + w * 16 + n * 64 + Q * 4);
            gg[n][0] = gq.x; gg[n][1] = gq.y;
#pragma unroll
            for (int i = 0; i < 4; i++) {
                const uint32_t og = hfma2_bf(gg[n][i >> 1], 0xBF80BF80u, 0x3F803F80u);
                xq[n][i].x = hmul2_bc(og, i & 1, xq[n][i].x); xq[n][i].y = hmul2_bc(og, i & 1, xq[n][i].y);
            }
        }
        mbar_wait(sb + M_BARS + 8 * (B_Y + Q));
        __syncwarp();
#pragma unroll
        for (int n = 0; n < N; n++) {
#pragma unroll
            for (int x = 0; x < 2; x++) {
                uint32_t y[4];
                ldsm4t((yi ^ (x << 5)) + y_off(Q) + n * 256, y[0], y[1], y[2], y[3]);
#pragma unroll
                for (int e = 0; e < 2; e++) {
                    uint2& o = xq[n][2 * x + e];
                    o.x = hfma2_bc(gg[n][x], e, y[2 * e], o.x); o.y = hfma2_bc(gg[n][x], e, y[2 * e + 1], o.y);
                }
            }
        }
        if ((sw[0] | sw[N - 1]) == 0) {
#pragma unroll
            for (int n = 0; n < N; n++)
#pragma unroll
                for (int i = 0; i < 4; i++)
                    asm volatile("st.shared.v2.u32 [%0], {%1, %2};" :: "r"(os + Q * 1024 + n * 4 * TAB_W + i * 128), "r"(xq[n][i].x), "r"(xq[n][i].y) : "memory");
            asm volatile("fence.proxy.async.shared::cta;" ::: "memory");
            __syncwarp();
#pragma unroll
            for (int n = 0; n < N; n++)
                asm volatile("{\n\t.reg .pred p;\n\telect.sync _|p, 0xffffffff;\n\t"
                             "@p cp.async.bulk.tensor.3d.global.shared::cta.bulk_group [%1, {%2, %3, %4}], [%0];\n\t}"
                    :: "r"(ob + 4 * n * TAB_W + Q * 1024), "l"(tm_out), "r"(16 * pr), "r"(64 * Q + 32 * h), "r"(w + 4 * n) : "memory");
        } else {
            bf16* op = p.out + (size_t)(512 * Q + 256 * h + 8 * m8 + w) * D_ + 16 * pr + 4 * t;
#pragma unroll
            for (int n = 0; n < N; n++)
#pragma unroll
                for (int i = 0; i < 4; i++)
                    if (!((sw[n] >> (4 * g)) & (1u << i))) *(uint2*)(op + (size_t)(32 * i + 4 * n) * D_) = xq[n][i];
        }
    }
}

__global__ void __cluster_dims__(2, 1, 1) __launch_bounds__(NTHREADS, 1)
fused_kernel(const Params p, const __grid_constant__ CUtensorMap tm_gu, const __grid_constant__ CUtensorMap tm_down,
             const __grid_constant__ CUtensorMap tm_x, const __grid_constant__ CUtensorMap tm_out) {
    extern __shared__ __align__(1024) unsigned char smem[];
    const uint32_t sb = smem_u32(smem);
    int tid;
    asm volatile("mov.u32 %0, %%tid.x;" : "=r"(tid));
    const int pw = tid >> 5, lane = tid & 31;
    const int c = blockIdx.x, h = c & 1, pr = c >> 1;
    const uint32_t bars = sb + M_BARS;

    uint2 v_la, v_ai, v_cr, v_ci;
    uint32_t ldt16;
    {
        const uint32_t po = c * 256 + tid;
        asm volatile("{\n\t.reg .pred p;\n\t.reg .b64 a;\n\tsetp.ne.u32 p, %16, 0;\n\t"
                     "mad.wide.u32 a, %14, 8, %9;\n\t@p ld.global.nc.L1::no_allocate.v2.u32 {%0,%1}, [a];\n\t"
                     "mad.wide.u32 a, %15, 2, %13;\n\t@p ld.global.nc.u16 %8, [a];\n\t"
                     "mad.wide.u32 a, %14, 8, %10;\n\t@p ld.global.nc.L1::no_allocate.v2.u32 {%2,%3}, [a];\n\t"
                     "mad.wide.u32 a, %14, 8, %11;\n\t@p ld.global.nc.L1::no_allocate.v2.u32 {%4,%5}, [a];\n\t"
                     "mad.wide.u32 a, %14, 8, %12;\n\t@p ld.global.nc.L1::no_allocate.v2.u32 {%6,%7}, [a];\n\t}"
            : "=r"(v_la.x), "=r"(v_la.y), "=r"(v_ai.x), "=r"(v_ai.y), "=r"(v_cr.x), "=r"(v_cr.y), "=r"(v_ci.x), "=r"(v_ci.y), "=r"(ldt16)
            : "l"(p.logA), "l"(p.Aim), "l"(p.Cre), "l"(p.Cim), "l"(p.logdt), "r"(po), "r"(po >> 5), "r"((uint32_t)(tid < 256 && c < 128)));
    }

    if (c >= 128) {
        if (c != 128) return;
        RSTAMP(5);
        const unsigned tag = (*(volatile unsigned*)&p.sc->epoch + 1) & 0xffffu;
        const uint32_t list = sb + 128;
        sts128(list + 16 * tid, 0, 0, 0, 0);
        if (tid == 0) sts32(sb + 64, 0);
        uint32_t key[4] = {tag - 1, tag - 1, tag - 1, tag - 1};
#pragma unroll 1
        for (int it = 0; it < (1 << 22); it++) {
            uint32_t a[4];
            asm volatile("{\n\t.reg .b128 o, z;\n\t.reg .b64 l, u;\n\tmov.b64 l, {%5, %5};\n\tmov.b128 z, {l, l};\n\tatom.relaxed.gpu.global.exch.b128 o, [%4], z;\n\t"
                         "mov.b128 {l, u}, o;\n\tmov.b64 {%0, %1}, l;\n\tmov.b64 {%2, %3}, u;\n\t}"
                : "=r"(a[0]), "=r"(a[1]), "=r"(a[2]), "=r"(a[3]) : "l"(&p.sc->r[tid]), "r"(tag - 1) : "memory");
#pragma unroll
            for (int i = 0; i < 4; i++) if (((a[i] ^ tag) & 0xffffu) == 0) key[i] = a[i];
            if ((((key[0] ^ tag) | (key[1] ^ tag) | (key[2] ^ tag) | (key[3] ^ tag)) & 0xffffu) == 0) break;
        }
        WSTAMP(0);
        uint32_t m = 0;
#pragma unroll
        for (int i = 0; i < 4; i++) {
            key[i] = (key[i] & 0xffff0000u) | (uint32_t)(2047 - (4 * tid + i));
            m = max(m, key[i]);
        }
        const uint32_t wm = __reduce_max_sync(0xffffffffu, m);
        if (lane == 0) sts32(sb + pw * 4, wm);
        __syncthreads();
        uint32_t thr = 0xffffffffu;
#pragma unroll
        for (int i = 0; i < 4; i++) { const uint4 q = lds128(sb + 16 * i); thr = min(thr, min(max(q.x, q.y), max(q.z, q.w))); }
        if (thr != 1) WSTAMP(1);
        if (m >= thr) {
            uint32_t pos;
            asm volatile("atom.shared.add.u32 %0, [%1], %2;" : "=r"(pos) : "r"(sb + 64), "r"(4 * ((key[0] >= thr) + (key[1] >= thr) + (key[2] >= thr) + (key[3] >= thr))) : "memory");
#pragma unroll
            for (int i = 0; i < 4; i++) if (key[i] >= thr) { sts32(list + pos, key[i]); pos += 4; }
        }
        __syncthreads();
        const uint32_t nc4 = lds32(sb + 64);
        if (nc4 != 1) WSTAMP(2);
#pragma unroll 1
        for (uint32_t j = 4 * pw; j < nc4; j += 64) {
            const uint32_t mine = lds32(list + j);
            int rank = 0;
#pragma unroll 1
            for (uint32_t i = 0; i < nc4; i += 128) rank += __popc(__ballot_sync(0xffffffffu, lds32(list + i + 4 * lane) > mine));
            if (rank < 8 && lane == 0) sts32(sb + 96 + 4 * rank, mine);
        }
        __syncthreads();
        if (tid < 8 * NTOP) st_gpu32(&p.sc->top[tid >> 3][tid & 7], lds32(sb + 96 + 4 * (tid & 7)) | ((tag & 31) << 11));
        WSTAMP(3);
        WDUMP();
        return;
    }

    WSTAMP(0);
    if (pw < 8) {
        const int d = 8 * c + pw - MAIN_W0;
        if (lane == 0) asm volatile("cp.async.ca.shared.global [%0], [%1], 4;" :: "r"(sb + M_DSK + 4 * (pw - MAIN_W0)), "l"(p.Dskip + (d & ~1)) : "memory");
        asm volatile("barrier.cluster.arrive.relaxed.aligned;" ::: "memory");
        const int warp = pw - MAIN_W0;
        asm volatile("setmaxnreg.inc.sync.aligned.u32 160;");
        const int g = lane >> 2, t = lane & 3;
        const int mi = lane >> 3, r = lane & 7;
        const uint32_t TB = sb + OFF_TAB + warp * TAB_W;
        const uint32_t UB = sb + OFF_U + warp * U_CH;
        if (mi < 2) sts128(UB + mi * U_PL + r * 16, 0, 0, 0, 0);
        if (lane < 4) sts128(TB + lane * T_PL, 0, 0, 0, 0);
        sts128(sb + OFF_SCR + warp * 8192 + lane * 16, 0x3C00u, 0x3C00u, 0x3C00u, 0x3C00u);
        asm volatile("barrier.cluster.wait.acquire.aligned;" ::: "memory");
        __syncwarp();

        uint32_t cfix;
        {
            KSTAMP(4, v_la.x ^ v_ai.x ^ v_cr.x ^ v_ci.x ^ ldt16);
            const float dt = bf_round(exp_acc(__uint_as_float(ldt16 << 16)));
            float l2[4], li[4];
            {
                const uint32_t la[2] = {v_la.x, v_la.y}, ai[2] = {v_ai.x, v_ai.y};
                const float dt2 = -1.4426950408889634f * dt;
#pragma unroll
                for (int i = 0; i < 4; i++) {
                    l2[i] = bf_round(ex2f(((i & 1) ? bf_hi(la[i >> 1]) : bf_lo(la[i >> 1])) * 1.4426950408889634f)) * dt2;
                    li[i] = ((i & 1) ? bf_hi(ai[i >> 1]) : bf_lo(ai[i >> 1])) * dt;
                }
            }
            const uint32_t SX = sb + OFF_SCR + warp * 8192;
            const uint32_t sw = SX + (lane << 4);
#define PUT(buf, row, v) sts128(((sw + (row) * 512) ^ ((row) << 4)) + (buf) * 4096, v[0], v[1], v[2], v[3])
#define EMIT(bufa, rowa, bufb, rowb, xr, xi, k, kp) do { uint32_t pk[4], pd[4]; sched_fence(); \
                _Pragma("unroll") for (int i = 0; i < 4; i++) { pk[i] = pack_h(xr[i], xi[i]); pd[i] = hcmul(pk[i], k[i], kp[i]); } \
                PUT(bufa, rowa, pk); PUT(bufb, rowb, pd); } while (0)
#define CMUL4(orr, oi, ar, ai, br, bi) _Pragma("unroll") for (int i = 0; i < 4; i++) CMUL(orr[i], oi[i], ar[i], ai[i], br[i], bi[i])
#define CSQ4(orr, oi, ar, ai) _Pragma("unroll") for (int i = 0; i < 4; i++) CSQ(orr[i], oi[i], ar[i], ai[i])
            float z1r[4], z1i[4], z2r[4], z2i[4], z8r[4], z8i[4], z256r[4], z256i[4];
            uint32_t k4[4], k4p[4];
            float z4r[4], z4i[4];
#pragma unroll
            for (int i = 0; i < 4; i++) cexp_pow(l2[i], li[i], 1.f, z1r[i], z1i[i]);
            CSQ4(z2r, z2i, z1r, z1i);
            CSQ4(z4r, z4i, z2r, z2i);
            CSQ4(z8r, z8i, z4r, z4i);
            KSTAMP(5, __float_as_uint(z8r[3]));
            uint32_t Ya[16][4];
            float cr[4], ci[4], inv;
            {
                float w1r[4], w1i[4], ar[4], ai[4], br[4], bi[4];
                uint32_t k8[4], k8p[4];
#pragma unroll
                for (int i = 0; i < 4; i++) {
                    k8[i] = pack_h(z8r[i], -z8i[i]); k8p[i] = pack_h(z8i[i], z8r[i]);
                    CSQ(w1r[i], w1i[i], z8r[i], z8i[i]); w1i[i] = -w1i[i];
                }
                PUT(1, 0, k8);
                EMIT(0, 1, 1, 1, w1r, w1i, k8, k8p);
                CSQ4(ar, ai, w1r, w1i);            EMIT(0, 2, 1, 2, ar, ai, k8, k8p);
                CMUL4(br, bi, ar, ai, w1r, w1i);   EMIT(0, 3, 1, 3, br, bi, k8, k8p);
                CSQ4(ar, ai, ar, ai);              EMIT(0, 4, 1, 4, ar, ai, k8, k8p);
                CMUL4(ar, ai, ar, ai, w1r, w1i);   EMIT(0, 5, 1, 5, ar, ai, k8, k8p);
                CSQ4(br, bi, br, bi);              EMIT(0, 6, 1, 6, br, bi, k8, k8p);
                CMUL4(br, bi, br, bi, w1r, w1i);   EMIT(0, 7, 1, 7, br, bi, k8, k8p);
                __syncwarp();
                KSTAMP(6, 0);
                sched_fence();
                const uint32_t ab = SX + (mi & 1) * 4096 + r * 512, ax = ((mi >> 1) ^ r) << 4;
                const uint32_t vr[2] = {v_cr.x, v_cr.y}, vi[2] = {v_ci.x, v_ci.y};
                const uint32_t m2 = __vmaxu2(__vmaxu2(vr[0] & 0x7fff7fffu, vr[1] & 0x7fff7fffu), __vmaxu2(vi[0] & 0x7fff7fffu, vi[1] & 0x7fff7fffu));
                const uint32_t mx = __reduce_max_sync(0xffffffffu, max(m2, m2 << 16));
                const uint32_t e = min(max(mx >> 23, 11u), 254u);
                const float sc = __uint_as_float((264u - e) << 23);
                inv = __uint_as_float((e - 10u) << 23) * (2.f * dt);
#pragma unroll
                for (int i = 0; i < 4; i++) {
#pragma unroll
                    for (int k = 0; k < 4; k++) ldsm4(ab + (ax ^ (i << 5)) + k * 128, Ya[4 * k + i][0], Ya[4 * k + i][1], Ya[4 * k + i][2], Ya[4 * k + i][3]);
                    float tr, ti;
                    cexp_pow(l2[i], li[i], 128.f, tr, ti);
                    sts32(TB + 2176 + 256 * i + 4 * lane, pack_h(tr, ti));
                    sts32(TB + 2176 + 256 * i + 128 + 4 * (lane ^ 16), pack_h(-ti, tr));
                    k4[i] = pack_h(z4r[i], z4i[i]); k4p[i] = pack_h(-z4i[i], z4r[i]);
                    CSQ(z256r[i], z256i[i], tr, ti);
                    cr[i] = ((i & 1) ? bf_hi(vr[i >> 1]) : bf_lo(vr[i >> 1])) * sc;
                    ci[i] = ((i & 1) ? bf_hi(vi[i >> 1]) : bf_lo(vi[i >> 1])) * sc;
                    if (i < 3) sched_fence();
                }
                __syncwarp();
            }
            KSTAMP(7, Ya[15][0]);
            const uint32_t ld0 = SX + r * 512 + ((mi ^ r) << 4), ld1 = ld0 ^ 64;
            float R[6][4], s1024;
            {
                float xr[4], xi[4], yr[4], yi[4];
                EMIT(0, 0, 0, 1, cr, ci, k4, k4p);
                CMUL4(yr, yi, cr, ci, z1r, z1i);        EMIT(0, 2, 0, 3, yr, yi, k4, k4p);
                CMUL4(xr, xi, cr, ci, z256r, z256i);    EMIT(1, 0, 1, 1, xr, xi, k4, k4p);
                CMUL4(yr, yi, yr, yi, z1r, z1i);        EMIT(0, 4, 0, 5, yr, yi, k4, k4p);
                CMUL4(cr, ci, yr, yi, z256r, z256i);    EMIT(1, 2, 1, 3, cr, ci, k4, k4p);
                CMUL4(yr, yi, yr, yi, z1r, z1i);        EMIT(0, 6, 0, 7, yr, yi, k4, k4p);
                CMUL4(xr, xi, xr, xi, z256r, z256i);    EMIT(1, 4, 1, 5, xr, xi, k4, k4p);
                CMUL4(xr, xi, xr, xi, z256r, z256i);    EMIT(1, 6, 1, 7, xr, xi, k4, k4p);
                CMUL4(xr, xi, xr, xi, z256r, z256i);
                s1024 = (xr[0] + xr[1]) + (xr[2] + xr[3]);
#pragma unroll
                for (int m = 0; m < 4; m++) {
                    if (m == 0) { CMUL4(xr, xi, xr, xi, z8r, z8i); } else { CMUL4(xr, xi, xr, xi, z256r, z256i); }
                    sched_fence();
                    sts128(TB + m * T_PL + 16 + 16 * lane, pack_h(xr[0], xi[0]), pack_h(xr[1], xi[1]), pack_h(xr[2], xi[2]), pack_h(xr[3], xi[3]));
                }
            }
            __syncwarp();
            {
                KSTAMP(8, 0);
                uint32_t bd[2][4] = {{0, 0, 0, 0}, {0, 0, 0, 0}};
                const bool on = (g >> 1) == t;
#pragma unroll
                for (int i = 0; i < 6; i++) { R[i][0] = R[i][1] = R[i][2] = R[i][3] = 0.f; }
                uint32_t x[2][4], y[2][4], z[2][4];
                auto fetch = [&](const int k2) {
                    const int b = k2 & 1;
                    lds128_if(on, TB + 2176 + g * 128 + (k2 < 4 ? 64 : -64) * (g & 1) + 16 * k2, bd[b]);
                    ldsm4(((k2 & 1) ? ld1 : ld0) + (k2 >> 1) * 128, x[b][0], x[b][1], x[b][2], x[b][3]);
                    ldsm4(((k2 & 1) ? ld1 : ld0) + (k2 >> 1) * 128 + 4096, y[b][0], y[b][1], y[b][2], y[b][3]);
                    ldsm4(TB + (r & 3) * T_PL + 16 + 16 * mi + 64 * k2, z[b][0], z[b][1], z[b][2], z[b][3]);
                };
                fetch(0);
#pragma unroll
                for (int k2 = 0; k2 < 8; k2++) {
                    const int b = k2 & 1;
                    uint32_t a1[2][4];
                    if (k2 < 7) fetch(k2 + 1);
#pragma unroll
                    for (int u = 0; u < 2; u++) {
                        mma_hh_k8(a1[u][0], a1[u][1], Ya[2 * k2 + u][0], Ya[2 * k2 + u][1], bd[b][2 * u]);
                        mma_hh_k8(a1[u][2], a1[u][3], Ya[2 * k2 + u][2], Ya[2 * k2 + u][3], bd[b][2 * u + 1]);
                    }
#pragma unroll
                    for (int u = 0; u < 2; u++) {
                        const uint32_t(&a0)[4] = Ya[2 * k2 + u];
                        mma_h(R[0], a0[0], a0[1], a0[2], a0[3], x[b][2 * u], x[b][2 * u + 1]);
                        mma_h(R[2], a0[0], a0[1], a0[2], a0[3], y[b][2 * u], y[b][2 * u + 1]);
                        mma_h(R[4], a0[0], a0[1], a0[2], a0[3], z[b][2 * u], z[b][2 * u + 1]);
                        mma_h(R[1], a1[u][0], a1[u][1], a1[u][2], a1[u][3], x[b][2 * u], x[b][2 * u + 1]);
                        mma_h(R[3], a1[u][0], a1[u][1], a1[u][2], a1[u][3], y[b][2 * u], y[b][2 * u + 1]);
                        mma_h(R[5], a1[u][0], a1[u][1], a1[u][2], a1[u][3], z[b][2 * u], z[b][2 * u + 1]);
                    }
                }
            }
            __syncwarp();
            KSTAMP(9, __float_as_uint(R[3][0]));
            if (lane == 0) mbar_arrive(bars + 8 * B_KG + (__float_as_uint(R[0][0]) & __float_as_uint(R[2][0]) & p.zero));
            sts128(TB + 2176 + 16 * lane, 0, 0, 0, 0);
            sts128(TB + 2688 + 16 * lane, 0, 0, 0, 0);
            __syncwarp();
#undef PUT
#undef EMIT
#pragma unroll
            for (int o = 16; o > 0; o >>= 1) s1024 += __shfl_xor_sync(0xffffffffu, s1024, o);
            uint32_t w[4][4], dsk = 0;
            cp_wait_all();
            asm volatile("{\n\t.reg .pred p;\n\tsetp.eq.u32 p, %2, 0;\n\t@p ld.shared.u16 %0, [%1];\n\t}" : "+r"(dsk) : "r"(sb + M_DSK + 4 * warp + 2 * (warp & 1)), "r"(lane) : "memory");
#pragma unroll
            for (int a = 0; a < 4; a++) {
                const float v0 = (a == 0) ? fmaf(R[0][0], inv, __uint_as_float(dsk << 16)) : R[a][0] * inv;
                const float v1 = R[a][1] * inv, v2 = R[a][2] * inv, v3 = R[a][3] * inv;
                w[a][0] = pack_bf(v0, 0.f); w[a][1] = pack_bf(v1, v0); w[a][2] = pack_bf(v2, v1); w[a][3] = pack_bf(v3, v2);
            }
            const uint32_t wb = TB + 16 + 16 * g, w1 = wb + t * T_PL, w2 = wb + 256 + 2 * t * T_PL;
            const uint32_t w3 = (t == 0) ? wb + 256 + 3 * T_PL : TB + T_A + 8 * (16 * t + g);
            const uint32_t w3s = (t == 0) ? 128 : 64, w3o = (t == 0) ? 8 : 12;
            const uint32_t k512 = __shfl_sync(0xffffffffu, w[2][1], 2);
#pragma unroll
            for (int a = 0; a < 2; a++) {
                sts128(w1 + 128 * a, w[a][0], w[a][1], w[a][2], w[a][3]);
                const uint32_t(&q)[4] = w[2 + a];
                if (t < 2) sts128(w2 + 128 * a, q[0], q[1], q[2], q[3]);
                if (t == 0) { sts128(w2 + T_PL + 128 * a, q[0], q[1], q[2], q[3]); sts32(w3 + 128 * a + 4, q[2]); }
                sts32_if(t != 1 && (a == 1 || lane != 2), w3 + w3s * a, q[1]);
                sts32_if(t != 1, w3 + w3s * a + w3o, q[3]);
            }
            sts128_if(lane < 4, w1 + 512, t == 3 ? k512 : k512 >> 16, t < 2 ? k512 : t == 2 ? k512 & 0xffff0000u : k512 << 16, t < 2 ? k512 << 16 : 0u, 0);
            __syncwarp();
#pragma unroll
            for (int a = 0; a < 2; a++) {
                sts16(w1 + 128 * a + 18, w[a][3]);
                const uint32_t(&q)[4] = w[2 + a];
                if (t < 2) sts16(w2 + 128 * a + 18, q[3]);
                if (t == 0) { sts16(w2 + T_PL + 128 * a + 18, q[3]); sts16(w3 + 128 * a + 14, q[3]); }
            }
            if (t == 0) sts16(w3 + 128 - 4, w[3][0]);
            if (lane == 2 || (t == 0 && g > 0)) sts16(lane == 2 ? TB + 16 + 3 * T_PL + 4 * 127 : w3 - 4, w[2][0]);
            {
                float q[4];
#pragma unroll
                for (int i = 0; i < 4; i++) q[i] = (t < 2 ? R[4][i] : R[5][i]) * inv;
                const uint32_t b0 = pack_bf(q[0], q[2]), b1 = pack_bf(q[1], q[3]);
                const uint32_t wq = TB + T_B + 8 * (65 + 32 * (t & 1) + 4 * (t & 2) + g);
                sts32(wq, b0); sts32(wq + 12, b0); sts32(wq + 128, b1); sts32(wq + 140, b1);
            }
            cfix = pack_bf(s1024 * inv, s1024 * inv);
            if (lane == 0) sts32(TB + T_A + 8 * 64, cfix);
            __syncwarp();
        }
        WSTAMP(1);

        mbar_wait(bars + 8 * B_U);
        WSTAMP(2);

        float D[16][4];
        {
            const int x5 = g - t + 5;
            const uint32_t tabD = TB + (x5 & 3) * T_PL + (x5 & 12) + 16;
            {
                const uint32_t a1 = lds32(tabD - 8), a0 = p.zero;
#pragma unroll
                for (int jq = 0; jq < 4; jq++) {
                    uint32_t b[4];
                    ldsm4(UB + (9 + lane) * 16 + jq * 512, b[0], b[1], b[2], b[3]);
#pragma unroll
                    for (int i = 0; i < 4; i++) mma_bf_k8z(D[4 * jq + i], a0, a1, b[i]);
                }
            }
            const uint32_t ua = UB + (mi & 1) * U_PL + (8 + 8 * (mi >> 1) + r) * 16;
#pragma unroll 1
            for (int k0 = 0; k0 < 8; k0++) {
                uint32_t Uf[16][2];
#pragma unroll
                for (int jp = 0; jp < 8; jp++) ldsm4(ua + jp * 256 - k0 * 16, Uf[2 * jp][0], Uf[2 * jp][1], Uf[2 * jp + 1][0], Uf[2 * jp + 1][1]);
#pragma unroll
                for (int k1 = 0; k1 < 4; k1++) {
                    const uint32_t ta = tabD + 16 * (8 * k1 + k0);
                    const uint32_t a0 = lds32(ta), a1 = lds32(ta + 8), a2 = lds32(ta - 8), a3 = a0 ^ p.zero;
#pragma unroll
                    for (int J = k1; J < 16; J++) mma_bf(D[J], a0, a1, a2, a3, Uf[J - k1][0], Uf[J - k1][1]);
                }
                if (k0 == 0) {
                    const uint32_t ta = tabD + 16 * 32;
                    const uint32_t a0 = lds32(ta), a1 = lds32(ta + 8), a2 = lds32(ta - 8), a3 = a0 ^ p.zero;
#pragma unroll
                    for (int J = 4; J < 16; J++) mma_bf(D[J], a0, a1, a2, a3, Uf[J - 4][0], Uf[J - 4][1]);
                    const uint32_t f0 = (cfix ^ 0x80008000u) & (g == t ? 0xffffu : g == t + 4 ? 0xffff0000u : 0u);
                    const uint32_t f1 = p.zero, f2 = p.zero + p.zero, f3 = f0 ^ p.zero;
#pragma unroll
                    for (int J = 8; J < 16; J++) mma_bf(D[J], f0, f1, f2, f3, Uf[J - 8][0], Uf[J - 8][1]);
                }
            }
        }
        WSTAMP(3);
        {
            const int ch = 8 * h + warp;
            const uint32_t yo = sb + ch * 512 + ((lane ^ (((ch >> 2) << 1) | (ch & 1))) << 4);
            const uint32_t yr = mapa(yo, h ^ 1), ybr = mapa(bars + 8 * B_Y, h ^ 1);
            auto ship = [&](const int Q) {
                uint4 y[2];
#pragma unroll
                for (int hh = 0; hh < 2; hh++) {
                    const int J = 4 * Q + 2 * hh;
                    y[hh] = make_uint4(pack_bf(D[J][0], D[J][1]), pack_bf(D[J][2], D[J][3]), pack_bf(D[J + 1][0], D[J + 1][1]), pack_bf(D[J + 1][2], D[J + 1][3]));
                }
                if (!(Q & 1)) mbar_wait(bars + 8 * (B_F + (Q >> 1)));
                asm volatile("{\n\t.reg .pred p;\n\tsetp.eq.u32 p, %11, 0;\n\t"
                             "@p st.async.weak.shared::cluster.mbarrier::complete_tx::bytes.v4.b32 [%9], {%4,%5,%6,%7}, [%10];\n\t"
                             "@!p st.async.weak.shared::cluster.mbarrier::complete_tx::bytes.v4.b32 [%9], {%0,%1,%2,%3}, [%10];\n\t"
                             "@p st.shared.v4.b32 [%8], {%0,%1,%2,%3};\n\t@!p st.shared.v4.b32 [%8], {%4,%5,%6,%7};\n\t}"
                             :: "r"(y[0].x), "r"(y[0].y), "r"(y[0].z), "r"(y[0].w), "r"(y[1].x), "r"(y[1].y), "r"(y[1].z), "r"(y[1].w),
                                "r"(yo + y_off(Q)), "r"(yr + y_off(Q)), "r"(ybr + 8 * Q), "r"(h) : "memory");
                __syncwarp();
                if (lane == 0) mbar_arrive(bars + 8 * (B_Y + Q));
            };
            ship(0);
            const uint4 bA = lds128(sb + OFF_BAND + (g - t + 3) * 48), bB = lds128(sb + OFF_BAND + (g - t + 3) * 48 + 16);
            const uint2 bC = lds64(sb + OFF_BAND + (g - t + 3) * 48 + 32);
            uint2 QA[5][2], QB[8];
            const uint32_t tq = TB + 8 * (1 + g - 2 * t);
#pragma unroll
            for (int dd = 0; dd < 5; dd++) { QA[dd][0] = lds64(tq + T_A + 64 * (dd + 4)); QA[dd][1] = lds64(tq + T_A + 64 * (dd + 4) - 8); }
#pragma unroll
            for (int dd = 0; dd < 8; dd++) QB[dd] = lds64(tq + T_B + 64 * (dd + 8));
            const uint32_t u1 = UB + (mi & 1) * U_PL + (7 + r + (mi >> 1)) * 16;
            const uint32_t u2 = UB + ((mi & 1) ^ 1) * U_PL + (7 + r + (mi & 1) + 8 * (mi >> 1)) * 16;
            uint32_t n[4];
#pragma unroll
            for (int j = 0; j < 12; j++) {
                uint32_t m[4];
                ldsm4(u1 + j * 128, m[0], m[1], m[2], m[3]);
                if (!(j & 1)) ldsm4(u2 + j * 128, n[0], n[1], n[2], n[3]);
                const uint32_t n0 = n[2 * (j & 1)], n1 = n[2 * (j & 1) + 1];
                float wa[4], wb[4], wc[4], g1[4], g2[4];
                mma_bf_z(wa, bA.x, bA.y, bA.z, bA.w, m[0], m[1]);
                mma_bf_z(wb, bA.x, bA.y, bA.z, bA.w, n0, n1);
                mma_bf_z(wc, bA.x, bA.y, bA.z, bA.w, m[2], m[3]);
                if (j < 8) {
                    mma_bf_z(g1, bB.x, bB.y, bB.z, bB.w, m[0], m[1]);
                    mma_bf_z(g2, bB.x, bB.y, bB.z, bB.w, n0, n1);
                    mma_bf_k8(g1, bC.x, bC.y, m[2]);
                    mma_bf_k8(g2, bC.x, bC.y, m[3]);
                }
#pragma unroll
                for (int e = 0; e < 2; e++) {
                    const uint32_t q0 = pack_bf(wa[e], wa[e + 2]), q1 = pack_bf(wb[e], wb[e + 2]), q2 = q1 ^ p.zero, q3 = pack_bf(wc[e], wc[e + 2]);
#pragma unroll
                    for (int dd = 0; dd < 5; dd++)
                        if (j + 4 + dd < 16) mma_bf(D[j + 4 + dd], q0, q1, q2, q3, QA[dd][e].x, QA[dd][e].y);
                }
                if (j < 8) {
                    const uint32_t q0 = pack_bf(g1[0], g1[2]), q1 = pack_bf(g2[0], g2[2]), q2 = pack_bf(g1[1], g1[3]), q3 = pack_bf(g2[1], g2[3]);
#pragma unroll
                    for (int dd = 7 - j; dd >= 0; dd--) mma_bf(D[j + 8 + dd], q0, q1, q2, q3, QB[dd].x, QB[dd].y);
                }
                if ((j & 3) == 3) {
                    WSTAMP(4 + 2 * (j >> 2));
                    ship((j >> 2) + 1);
                }
            }
        }
        const int warpu = __reduce_max_sync(0xffffffffu, warp);
        mix_rows<1>(p, &tm_out, sb, sb + OFF_U + warpu * U_CH + (warpu & 1) * 64, PQ, 4, warpu, h, pr, lane);
        asm volatile("cp.async.bulk.commit_group;\n\tcp.async.bulk.wait_group.read 0;" ::: "memory");
        WSTAMP(10);
        WDUMP();
    } else if ((pw & 12) == AUX_W0) {
        const int v = __reduce_max_sync(0xffffffffu, pw & 3);
        const int at = tid & 127;
        const int g = lane >> 2, t = lane & 3;
        unsigned tag;
        const bool gu = c < NGU_CTA;
        {
            const uint32_t xb = sb + (v < 2 ? OFF_XSEL : OFF_RING + 2 * 8192) + v * 8192;
            const uint32_t gws = sb + M_DPIN;
            const uint32_t row = 16 * c + 4 * v + (g >> 1);
#pragma unroll
            for (int i = 0; i < 8; i++)
                asm volatile("cp.async.ca.shared.global [%0], [%1], 4;" :: "r"((i < 4 ? sb + OFF_GP : gws) + 512 * (i & 3) + (tid & 124) * 4 + (tid & 1) * 8 + (tid & 2) * 2),
                             "l"((i < 4 ? p.wr : p.gatew) + 256 * (i & 3) + (tid & 127) * 2) : "memory");
            if ((tid & 127) < 33) cp16(sb + OFF_BAND + (tid & 127) * 16, p.band + (tid & 127));
            asm volatile("barrier.cluster.arrive.relaxed.aligned;" ::: "memory");
            tag = __reduce_max_sync(0xffffffffu, (*(volatile unsigned*)&p.sc->epoch + 1) & 0xffffu);
            if (gu) st_gpu32((uint32_t*)&p.sc->h[(tag + 1) & 1][32 * c] + at, 0);
            if (v == 2) sts32(sb + M_BMAP + lane * 4, 0);
            if (at == 0) sts32(sb + M_TAG, tag << 16);
            cp_wait_all();
            bar_sync(1, 128);
            uint2 w[16];
#pragma unroll
            for (int kb = 0; kb < 16; kb++) w[kb] = lds64((g < 4 ? sb + OFF_GP : gws) + 128 * kb + 32 * (g & 2) + 16 * t + 8 * (g & 1));
            asm volatile("barrier.cluster.wait.acquire.aligned;" ::: "memory");
            mbar_wait(bars + 8 * (B_X + v));
            WSTAMP(10);
            float dr[4][4];
#pragma unroll
            for (int kb = 0; kb < 16; kb++) {
                const uint4 x = lds128(xb + (g >> 1) * 2048 + 128 * kb + 16 * (lane & 7));
                if (kb < 4) mma_bf_z(dr[kb], x.x, x.y, x.z, x.w, w[kb].x, w[kb].y);
                else mma_bf(dr[kb & 3], x.x, x.y, x.z, x.w, w[kb].x, w[kb].y);
            }
            float rs = ((dr[0][0] + dr[0][3]) + (dr[1][0] + dr[1][3])) + ((dr[2][0] + dr[2][3]) + (dr[3][0] + dr[3][3]));
            if (lane == 0) mbar_arrive(bars + 8 * (B_XE + v) + (__float_as_uint(rs) & p.zero));
            rs += __shfl_xor_sync(0xffffffffu, rs, 5);
            const uint32_t rb = pack_bf(0.f, rs);
            if (!(lane & 7)) st_gpu32((uint32_t*)p.sc->r + row, ((rb ^ (((int)rb >> 31) | 0x80000000u)) & 0xffff0000u) | tag);
            WSTAMP(1);
            {
                const int n = 3 + (lane >> 3) + 4 * (lane & 1);
                const uint32_t so = (n & 7) * S_PL + ((lane & 6) + (n >> 3)) * 32;
                const uint32_t src[2] = {sb + OFF_S + v * S_Q + s_addr(so, h), sb + OFF_S + v * S_Q + s_addr(so + 32, h)};
                const uint32_t dst = sb + OFF_U + g * U_CH + (8 + 32 * v + 16 * h + t) * 16;
                const uint32_t rdst = mapa(dst, h ^ 1), rbar = mapa(bars + 8 * B_U, h ^ 1);
                mbar_wait(bars + 8 * (B_S + v));
                WSTAMP(9);
                uint4 a[8];
#pragma unroll
                for (int b = 0; b < 2; b++) {
#pragma unroll
                    for (int j = 0; j < 8; j++) { const int u = 4 * b + (j >> 1) + 8 * (j & 1); ldsm4t((u < 8 ? src[u & 1] ^ 16 : src[u & 1]) + ((u >> 1) & 3) * 256, a[j].x, a[j].y, a[j].z, a[j].w); }
#pragma unroll
                    for (int j = 0; j < 8; j++) {
                        const int u = 4 * b + (j >> 1) + 8 * (j & 1);
                        if (u < 8) st_async16(rdst + ((u >> 1) & 3) * 64 + (u & 1) * U_PL, a[j], rbar);
                        else sts128(dst + ((u >> 1) & 3) * 64 + (u & 1) * U_PL, a[j].x, a[j].y, a[j].z, a[j].w);
                    }
                }
                if (h && v == 3) {
                    ldsm4t((src[0] ^ 16) + 1024, a[0].x, a[0].y, a[0].z, a[0].w);
                    ldsm4t(src[0] + 1024, a[1].x, a[1].y, a[1].z, a[1].w);
                    if (t == 0) {
                        st_async16(rdst + 256, make_uint4(a[0].x, a[0].y & 0xffffu, a[0].z & 0xffffu, a[0].w & 0xffffu), rbar);
                        sts128(dst + 256, a[1].x, a[1].y & 0xffffu, a[1].z & 0xffffu, a[1].w & 0xffffu);
                    }
                }
                __syncwarp();
                if (lane == 0) mbar_arrive(bars + 8 * B_U);
            }
            if ((lane & 7) == 2) st_gpu32((uint32_t*)p.sc->g + ((row & 256) << 2) + gate_pos(row), pack_bf(sigmoid_f(__uint_as_float(rb)), 0.f) | (tag << 16));
            WSTAMP(2);
        }
        {
            const bool lane0 = pin(lane, lane) == 0;
            const uint32_t own = pin(sb + OFF_XSEL + (at ^ ((at >> 1) & 4)) * 16, lane);
            float acc[8][4];
            const int krow = ((lane >> 1) & 8) + (lane & 7);
            const uint32_t tile0 = pin(sb + OFF_RING + v * 8192 + krow * 64 + ((((lane >> 3) & 1) ^ ((krow >> 1) & 3)) << 4), lane);
            const uint32_t xo = pin(sb + OFF_XSEL + (lane & 7) * XS_ROW + 512 * v + 2 * (lane & 24), lane);
            const uint32_t po = pin(sb + OFF_XSEL + t * XS_ROW + (g & 3) * 128 + (g & 1) * 64 + v * 16 + (lane >> 4) * 8, lane);
            const uint32_t po1 = pin(po + 64 - (g & 1) * 128, lane);
            uint32_t* hdst = pin((uint32_t*)&p.sc->h[tag & 1][32 * c] + at, lane);
            auto signal = [&](const int k, const uint32_t dep) {
                if (lane < 2 && v < 2)
                    asm volatile("st.async.weak.shared::cluster.mbarrier::complete_tx::bytes.b32 [%0], %1, [%2];"
                                 :: "r"(mapa(sb + M_SINK, lane)), "r"(dep), "r"(mapa(bars + 8 * (B_F + k), lane)) : "memory");
            };
            uint32_t a[16][4], b[2][4];
            auto load_a = [&](const uint32_t tile) {
#pragma unroll
                for (int q = 0; q < 16; q++) ldsm4t((tile ^ ((q & 1) << 5)) + ((q >> 1) & 1) * 4096 + (q >> 2) * 1024, a[q][0], a[q][1], a[q][2], a[q][3]);
            };
            auto load_b = [&](const uint32_t x) { ldsm4(x, b[0][0], b[0][1], b[0][2], b[0][3]); ldsm4(x + 64, b[1][0], b[1][1], b[1][2], b[1][3]); };
            auto burst = [&](const bool first) {
#pragma unroll
                for (int q = 0; q < 16; q++) {
                    if (first && q < 8) mma_bf_z(acc[q], a[q][0], a[q][1], a[q][2], a[q][3], b[0][(q >> 1) & 2], b[0][((q >> 1) & 2) + 1]);
                    else mma_bf(acc[q & 7], a[q][0], a[q][1], a[q][2], a[q][3], b[q >> 3][(q >> 1) & 2], b[q >> 3][((q >> 1) & 2) + 1]);
                }
            };
            if (gu) {
                mbar_wait(bars + 8 * (B_W + v));
                load_a(tile0);
                uint32_t dep = p.zero;
#pragma unroll
                for (int q = 0; q < 16; q += 2) dep &= a[q][0] & a[q + 1][0];
                if (lane == 0) mbar_arrive(bars + 8 * (B_E + v) + dep);
            }
            WSTAMP(11);
            uint32_t top;
#pragma unroll 1
            for (int it = 0; it < (1 << 22); it++) {
                asm volatile("ld.relaxed.gpu.global.u32 %0, [%1];" : "=r"(top) : "l"(&p.sc->top[c % NTOP][g]) : "memory");
                if (__all_sync(0xffffffffu, ((top ^ (tag << 11)) & 0xf800u) == 0)) break;
                __nanosleep(40);
            }
            WSTAMP(3);
            if (gu) {
                const uint32_t k = 4 * h + v, row = __reduce_max_sync(0xffffffffu, lane == 4 * k ? ~top & 2047 : 0);
                asm volatile("{\n\t.reg .pred p;\n\telect.sync _|p, 0xffffffff;\n\t"
                             "@p cp.async.bulk.shared::cluster.global.mbarrier::complete_tx::bytes.multicast::cluster [%0], [%1], 2048, [%2], %3;\n\t}"
                    :: "r"(sb + OFF_XSEL + k * XS_ROW), "l"(p.u + (size_t)row * D_), "r"(bars + 8 * B_G), "h"((unsigned short)3) : "memory");
            }
            if (v == 2) {
                const uint32_t row = ~top & 2047;
                if (t == 0 && ((row >> 8) & 1) == h)
                    asm volatile("red.shared.or.b32 [%0], %1;" :: "r"(sb + M_BMAP + (row & 7) * 16 + (row >> 9) * 4), "r"(1u << (gate_pos(row) & 31)) : "memory");
                if (t == 0) sts32(sb + M_TOP + lane, top);
                if (c == 0 && lane == 0) *(volatile unsigned*)&p.sc->epoch = tag;
                __syncwarp();
                if (lane0) mbar_arrive(bars + 8 * B_Y);
            }
            if (gu) {
                mbar_wait(bars + 8 * B_G);
                WSTAMP(4);
                load_b(xo);
                burst(true);
#pragma unroll
                for (int i = 1; i < 4; i++) {
                    mbar_wait(bars + 8 * (B_W + 4 * i + v));
                    load_b(xo + 128 * i);
                    load_a(tile0 + (4 * i + v < 14 ? i : 0) * 32768);
                    if (lane0 && i > 1) mbar_arrive(bars + 8 * (B_E + 4 * i - 4 + v));
                    if (i == 2) signal(0, 0);
                    sched_fence();
                    burst(false);
                    sched_fence();
                }
                WSTAMP(5);
                __syncwarp();
#pragma unroll
                for (int q = 0; q < 4; q++) {
                    const int ct = q >> 1, e = 2 * (q & 1);
                    sts128(own + q * XS_ROW,
                           __float_as_uint(acc[ct][e] + acc[4 + ct][e]), __float_as_uint(acc[2 + ct][e] + acc[6 + ct][e]),
                           __float_as_uint(acc[ct][e + 1] + acc[4 + ct][e + 1]), __float_as_uint(acc[2 + ct][e + 1] + acc[6 + ct][e + 1]));
                }
                bar_sync(1, 128);
                float sl[2], uv[2];
#pragma unroll
                for (int e = 0; e < 2; e++) {
                    uint2 q[4];
#pragma unroll
                    for (int i = 0; i < 4; i++) q[i] = lds64((e ? po1 : po) + 512 * i);
                    const float s0 = (__uint_as_float(q[0].x) + __uint_as_float(q[1].x)) + (__uint_as_float(q[2].x) + __uint_as_float(q[3].x));
                    const float s1 = (__uint_as_float(q[0].y) + __uint_as_float(q[1].y)) + (__uint_as_float(q[2].y) + __uint_as_float(q[3].y));
                    const float gv = bf_round(p.gu_swap ? s1 : s0);
                    uv[e] = p.gu_swap ? s0 : s1;
                    sl[e] = gv * sigmoid_f(gv);
                }
                const uint32_t hw = hmul2_bf(pack_bf(sl[0], sl[1]), pack_bf(uv[0], uv[1]));
                st_gpu32(hdst, hw ? hw : 0x80000000u);
                signal(1, hw);
            }
        }
        WSTAMP(6);
        {
            const uint32_t own = pin(sb + OFF_XSEL + at * 16, lane);
            const uint32_t hb = sb + (v < 2 ? OFF_XSEL + 7168 * v : OFF_RING + 8192 * v), hl = pin(hb + 16 * lane, lane);
            const int krow = ((lane >> 1) & 8) + (lane & 7);
            const uint32_t tile = pin(sb + OFF_RING + v * 8192 + krow * 32 + ((((lane >> 3) ^ (krow >> 2)) & 1) << 4), lane);
            float dd[4][4];
            bar_sync(1, 128);
            mbar_wait(bars + 8 * (B_W + HW));
            WSTAMP(12);
            uint4 hq[7];
            {
                const uint4* hs = &p.sc->h[tag & 1][32 * (56 * h + 14 * v)];
                bulk_load(hb, hs, 3584, bars + 8 * (B_X + v));
                bulk_load(hb + 3584, hs + 224, 3584, bars + 8 * (B_XE + v));
                uint32_t a[14][4];
                mbar_wait(bars + 8 * (B_W + 16 + v));
#pragma unroll
                for (int j = 0; j < 14; j++) ldsm4t(tile + (v & 2) * 16384 + j * 512, a[j][0], a[j][1], a[j][2], a[j][3]);
#pragma unroll
                for (int k = 0; k < 2; k++) {
                    mbar_wait(bars + 8 * ((k ? B_XE : B_X) + v), 1);
                    if (!k) WSTAMP(7);
                    uint32_t mn = 0xffffffffu;
#pragma unroll
                    for (int j = 0; j < 7; j++) { hq[j] = lds128(hl + 3584 * k + 512 * j); mn = min(mn, hq[j].x); }
#pragma unroll 1
                    for (int it = 0; it < (1 << 20) && !__all_sync(0xffffffffu, mn != 0); it++) {
                        mn = 0xffffffffu;
#pragma unroll
                        for (int j = 0; j < 7; j++)
                            asm volatile("{\n\t.reg .pred p;\n\tsetp.eq.u32 p, %0, 0;\n\t@p ld.relaxed.gpu.global.v4.u32 {%0,%1,%2,%3}, [%4];\n\t}"
                                         : "+r"(hq[j].x), "+r"(hq[j].y), "+r"(hq[j].z), "+r"(hq[j].w) : "l"(hs + 224 * k + 32 * j + lane) : "memory");
#pragma unroll
                        for (int j = 0; j < 7; j++) mn = min(mn, hq[j].x);
                    }
                    if (!k) {
#pragma unroll
                        for (int j = 0; j < 14; j++) {
                            const uint4& q = hq[j >> 1];
                            if (j < 4) mma_bf_z(dd[j], a[j][0], a[j][1], a[j][2], a[j][3], (j & 1) ? q.z : q.x, (j & 1) ? q.w : q.y);
                            else mma_bf(dd[j & 3], a[j][0], a[j][1], a[j][2], a[j][3], (j & 1) ? q.z : q.x, (j & 1) ? q.w : q.y);
                        }
                    }
                }
            }
            mbar_wait(bars + 8 * (B_W + 20 + v));
#pragma unroll
            for (int j = 0; j < 14; j++) {
                uint32_t f[4];
                ldsm4t(tile + 65536 + j * 512, f[0], f[1], f[2], f[3]);
                mma_bf(dd[(j + 2) & 3], f[0], f[1], f[2], f[3], (j & 1) ? hq[j >> 1].z : hq[j >> 1].x, (j & 1) ? hq[j >> 1].w : hq[j >> 1].y);
            }
            WSTAMP(8);
            uint4 part;
            part.x = __float_as_uint((dd[0][0] + dd[1][0]) + (dd[2][0] + dd[3][0])); part.y = __float_as_uint((dd[0][1] + dd[1][1]) + (dd[2][1] + dd[3][1]));
            part.z = __float_as_uint((dd[0][2] + dd[1][2]) + (dd[2][2] + dd[3][2])); part.w = __float_as_uint((dd[0][3] + dd[1][3]) + (dd[2][3] + dd[3][3]));
            st_async16(mapa(own + (M_DPIN - OFF_XSEL), h ^ 1), part, mapa(bars + 8 * B_DP, h ^ 1));
            sts128(own + 14336, part.x, part.y, part.z, part.w);
            __syncwarp();
            if (lane == 0) mbar_arrive(bars + 8 * B_DP);
        }
        WDUMP();
    } else {
        asm volatile("setmaxnreg.dec.sync.aligned.u32 64;");
        const int v = __reduce_max_sync(0xffffffffu, pw - PREP_W0);
        const bool gu = c < NGU_CTA;
        const uint32_t t0 = clock();
        const uint32_t bu = bars + 8 * v;
        if (lane == 0) {
#pragma unroll
            for (int i = 0; i < 10; i++) mbar_init(bu + 32 * i, 1);
            mbar_init(bu + 8 * B_X, 1);
            mbar_init(bu + 8 * B_XE, 1);
            mbar_init(bu + 8 * B_Y, v == 0 ? 11 : 9);
            mbar_init(bu + 8 * B_DP, (0x1855 >> (4 * v)) & 15);
            mbar_init(bu + 8 * B_F, 1);
            mbar_init(bu + 8 * B_H, 1);
            asm volatile("fence.mbarrier_init.release.cluster;" ::: "memory");
            mbar_expect(bu + 8 * B_Y, 4096);
            if (v != 2) mbar_expect(bu + 8 * B_DP, v == 0 ? 2048 : (h || v == 3) ? 16384 : 16384 + 128);
            mbar_expect(bu + 8 * B_F, c < NGU_CTA ? 16 : 0);
        }
        __syncwarp();
        asm volatile("barrier.cluster.arrive.relaxed.aligned;" ::: "memory");
        bulk_load(sb + (v < 2 ? OFF_XSEL : OFF_RING + 2 * 8192) + v * 8192, p.u + (size_t)(16 * c + 4 * v) * D_, 8192, bu + 8 * B_X);
        tma3d(sb + OFF_S + v * S_Q, &tm_x, 16 * pr, 64 * v + 32 * h - 1, bars + 8 * (B_S + v), S_Q);
        WSTAMP(9);
        if (v < 3 && lane == 0) asm volatile("prefetch.tensormap [%0];" :: "l"(v == 0 ? &tm_gu : v == 1 ? &tm_down : &tm_out) : "memory");
        asm volatile("barrier.cluster.wait.acquire.aligned;" ::: "memory");
        uint32_t desc;
        {
            const int s = 6 * v + lane, i = s >> 2, w = s & 3, slot = s < 14 ? s : (s | 1) == 17 ? s - 16 : s - 12;
            const int fb = s < 4 ? B_H : (gu && s >= 14) ? B_E + slot : s < 6 ? B_XE + s - 2 : B_KG;
            desc = slot | (fb << 4) | ((i < 4 ? 256 * w + 64 * i : 1792 * h + 448 * w + 224 * (i - 4)) << 10);
            if (lane < 6) mbar_expect(bars + 8 * (B_W + s), i < 4 ? 8192 : 7168);
            if (tid == 32 * PREP_W0) mbar_arrive(bars + 8 * B_H);
        }
        if (v == 3) {
            mbar_wait(bars + 8 * B_U);
            mbar_wait(bars + 8 * (gu ? B_G : B_H + 2));
            const uint32_t tag16 = lds32(sb + M_TAG);
            uint4 q[8];
#pragma unroll 1
            for (int it = 0; it < (1 << 22); it++) {
                uint32_t bad = 0;
#pragma unroll
                for (int i = 0; i < 8; i++) q[i] = ld_gpu128(&p.sc->g[256 * h + 32 * i + lane]);
#pragma unroll
                for (int i = 0; i < 8; i++) bad |= ((q[i].x ^ tag16) | (q[i].y ^ tag16)) | ((q[i].z ^ tag16) | (q[i].w ^ tag16));
                if ((bad >> 16) == 0) break;
                __nanosleep(200);
            }
#pragma unroll
            for (int i = 0; i < 8; i++)
                asm volatile("st.shared.v2.u32 [%0], {%1, %2};" :: "r"(sb + OFF_GP + 256 * i + lane * 8),
                             "r"(__byte_perm(q[i].x, q[i].y, 0x5410)), "r"(__byte_perm(q[i].z, q[i].w, 0x5410)) : "memory");
            __syncwarp();
            if (lane == 0) mbar_arrive(bars + 8 * B_Y);
        }
        mbar_wait(bars + 8 * (B_H + v));
        {
            const int gap = v == 0 ? GAP : v == 1 ? GAP1 : v == 2 ? GAP2 : GAP3;
            uint32_t last = v ? clock() - SLACK : t0 + T0 - GAP + GAP * ((pr * 5) & 15) / 16;
#pragma unroll 1
            for (int k = 0; k < 6; k++) {
                const uint32_t dk = __reduce_max_sync(0xffffffffu, lane == k ? desc : 0);
                const bool dn = 6 * v + k >= 16;
                const uint32_t dst = sb + OFF_RING + (dk & 15) * 8192, bar = bars + 8 * (B_W + 6 * v + k), c0 = dn ? 16 * pr : 32 * c, c1 = dk >> 10;
                const CUtensorMap* tm = dn ? &tm_down : &tm_gu;
                mbar_wait(bars + ((dk >> 1) & 0x1f8));
                int late;
#pragma unroll 1
                while ((late = (int)(clock() - last) - gap) < 0) __nanosleep(max(-late >> 2, 32));
                WSTAMP(3 + k);
                if (gu || dn)
                    asm volatile("{\n\t.reg .pred p;\n\telect.sync _|p, 0xffffffff;\n\t"
                                 "@p cp.async.bulk.tensor.3d.shared::cluster.global.mbarrier::complete_tx::bytes [%0], [%1, {%3, %4, 0}], [%2];\n\t}"
                        :: "r"(dst), "l"(tm), "r"(bar), "r"(c0), "r"(c1) : "memory");
                last += gap + max(late - SLACK, 0);
            }
            if (lane == 0 && v < 3) mbar_arrive(bars + 8 * (B_H + v + 1));
        }
        {
            WSTAMP(1);
            mix_rows<2>(p, &tm_out, sb, sb + OFF_TAB + v * TAB_W, 0, PQ, v, h, pr, lane);
            WSTAMP(2);
            asm volatile("cp.async.bulk.commit_group;" ::: "memory");
            const uint32_t top = lds32(sb + M_TOP + 8 * v + 4 * (lane >> 4));
            const uint32_t row = ~top & 2047, ch = lane & 15, gp = gate_pos(row);
            const bool mine = ((row >> 8) & 1) == h;
            uint32_t gfin, x16, y16 = 0;
            asm volatile("ld.shared.u16 %0, [%1];" : "=r"(gfin) : "r"(sb + OFF_GP + gp * 2) : "memory");
            asm volatile("ld.shared.u16 %0, [%1];" : "=r"(x16) : "r"(sb + OFF_S + (row >> 9) * S_Q + s_addr((row & 7) * S_PL + 32 + (row & 248) * 4, ch >> 3) + 2 * (ch & 7)) : "memory");
            const float rsel = __uint_as_float(pin(__float_as_uint(bf_round(sigmoid_f(__uint_as_float((top ^ (((int)~top >> 31) | 0x80000000u)) & 0xffff0000u)))), lane));
            const uint32_t po = pin(sb + (4 * (ch & 7) + v) * 16 + (ch >> 3) * 8 + (lane >> 4) * 4, lane);
            bf16* op = pin(p.out + (size_t)row * D_ + 16 * pr + ch, lane);
            if (mine) {
                mbar_wait(bars + 8 * (B_Y + (row >> 9)));
                asm volatile("ld.shared.u16 %0, [%1];" : "=r"(y16)
                             : "r"(sb + y_off(row >> 9) + ch * 512 + (((4 * (row & 7) + ((row >> 5) & 3)) ^ (((ch >> 2) << 1) | (ch & 1))) << 4) + 2 * row_elem(row)) : "memory");
            }
            mbar_wait(bars + 8 * B_DP);
            float q[8];
#pragma unroll
            for (int i = 0; i < 4; i++) { q[i] = ldsf(po + M_DPIN + 512 * i); q[4 + i] = ldsf(po + OFF_XSEL + 14336 + 512 * i); }
            const float tot = ((q[0] + q[1]) + (q[2] + q[3])) + ((q[4] + q[5]) + (q[6] + q[7]));
            const float b = bf_round(__uint_as_float(x16 << 16) + bf_round(bf_round(tot) * rsel));
            if (mine) *op = __float2bfloat16_rn(fmaf(bf_lo(gfin), __uint_as_float(y16 << 16), bf_round(bf_round(1.f - bf_lo(gfin)) * b)));
        }
        asm volatile("cp.async.bulk.wait_group.read 0;" ::: "memory");
        WSTAMP(10);
        WDUMP();
    }
}

typedef CUresult (*EncodeFn)(CUtensorMap*, CUtensorMapDataType, cuuint32_t, void*, const cuuint64_t*, const cuuint64_t*,
                             const cuuint32_t*, const cuuint32_t*, CUtensorMapInterleave, CUtensorMapSwizzle,
                             CUtensorMapL2promotion, CUtensorMapFloatOOBfill);

void make_map(EncodeFn f, CUtensorMap* m, const void* ptr, uint64_t cols, uint64_t rows, uint64_t pitch, uint32_t bc, uint32_t br, CUtensorMapSwizzle sw, CUtensorMapL2promotion prom,
              uint32_t planes = 1, uint64_t plane_stride = 0, uint32_t box_planes = 0) {
    cuuint64_t dims[3] = {cols, rows, planes};
    cuuint64_t str[2] = {pitch, planes > 1 ? plane_stride : pitch * rows};
    cuuint32_t box[3] = {bc, br, box_planes ? box_planes : planes};
    cuuint32_t es[3] = {1, 1, 1};
    f(m, CU_TENSOR_MAP_DATA_TYPE_BFLOAT16, 3, (void*)ptr, dims, str, box, es, CU_TENSOR_MAP_INTERLEAVE_NONE, sw,
      prom, CU_TENSOR_MAP_FLOAT_OOB_FILL_NONE);
}

}

extern "C" void kernel_launch(void* const* d_in, const int* in_sizes, int n_in, void* d_out, int out_size) {
    static EncodeFn enc = nullptr;
    static void *sc = nullptr, *band = nullptr;
    if (!enc) {
        void* fn = nullptr;
        cudaDriverEntryPointQueryResult qr;
        cudaGetDriverEntryPoint("cuTensorMapEncodeTiled", &fn, cudaEnableDefault, &qr);
        enc = (EncodeFn)fn;
        cudaGetSymbolAddress(&sc, g_scratch);
        cudaGetSymbolAddress(&band, g_band);
        cudaFuncSetAttribute(fused_kernel, cudaFuncAttributeMaxDynamicSharedMemorySize, SMEM_BYTES);
    }
    CUtensorMap tg, td, tx, to;
    const char *wg = (const char*)d_in[9], *wu = (const char*)d_in[10];
    const bool swap = wu < wg;
    make_map(enc, &tg, swap ? wu : wg, F_, D_, F_ * 2, 32, 64, CU_TENSOR_MAP_SWIZZLE_64B, CU_TENSOR_MAP_L2_PROMOTION_L2_128B, 2, swap ? wg - wu : wu - wg);
    make_map(enc, &td, d_in[11], D_, F_, D_ * 2, 16, 224, CU_TENSOR_MAP_SWIZZLE_32B, CU_TENSOR_MAP_L2_PROMOTION_L2_64B);
    make_map(enc, &tx, d_in[0], D_, L_ / 8, D_ * 16, 16, 33, CU_TENSOR_MAP_SWIZZLE_32B, CU_TENSOR_MAP_L2_PROMOTION_NONE, 8, D_ * 2);
    make_map(enc, &to, d_out, D_, L_ / 8, D_ * 16, 16, 32, CU_TENSOR_MAP_SWIZZLE_NONE, CU_TENSOR_MAP_L2_PROMOTION_NONE, 8, D_ * 2, 1);
    Params p;
    p.u = (const bf16*)d_in[0]; p.logA = (const bf16*)d_in[1]; p.Aim = (const bf16*)d_in[2];
    p.Cre = (const bf16*)d_in[3]; p.Cim = (const bf16*)d_in[4]; p.logdt = (const bf16*)d_in[5];
    p.Dskip = (const bf16*)d_in[6]; p.wr = (const bf16*)d_in[8]; p.gatew = (const bf16*)d_in[12];
    p.out = (bf16*)d_out;
    p.sc = (Scratch*)sc; p.band = (const uint4*)band;
    p.gu_swap = swap;
    p.zero = 0;
    fused_kernel<<<NCTA, NTHREADS, SMEM_BYTES>>>(p, tg, td, tx, to);
}
```

```cpp
#include <cuda_runtime.h>
#include <cuda_bf16.h>
#include <cuda_fp16.h>
#include <cuda.h>
#include <stdint.h>

typedef __nv_bfloat16 bf16;

namespace {

constexpr int L_ = 2048, D_ = 1024, F_ = 3584;
constexpr int NCTA = 130;
constexpr int NTHREADS = 512;
constexpr int MAIN_W0 = 0, PREP_W0 = 8, AUX_W0 = 12;
#define TX 150
#define T0 3050
#define GAP 510
#define GAP1 515
#define GAP2 515
#define GAP3 560
#define HW 20
constexpr int SLACK = 300;
constexpr int PQ = 3;
constexpr int NGU_CTA = 112;

constexpr int OFF_RING = 0;
constexpr int OFF_SCR  = 6 * 8192;
constexpr int S_PL     = 1056;
constexpr int S_Q      = 8 * S_PL;
constexpr int OFF_S    = 114688;
constexpr int OFF_GP   = OFF_S + 4 * S_Q;
constexpr int U_PL     = 2240;
constexpr int U_CH     = 4416;
constexpr int OFF_U    = 151552;
constexpr int TAB_W    = 3200;
constexpr int T_PL     = 544;
constexpr int T_A      = 2192 - 26 * 8;
constexpr int T_B      = 2568 - 59 * 8;
constexpr int OFF_TAB  = 186880;
constexpr int OFF_XSEL = 212480;
constexpr int XS_ROW   = 2064;
constexpr int OFF_BAND = 228992;
constexpr int OFF_MISC = 229536;
constexpr int M_BARS   = OFF_MISC;
constexpr int M_DSK    = OFF_MISC + 2736;
constexpr int M_SINK   = OFF_MISC + 512;
constexpr int M_TAG    = OFF_MISC + 516;
constexpr int M_BMAP   = OFF_MISC + 528;
constexpr int M_DPIN   = OFF_MISC + 656;
constexpr int M_TOP    = OFF_MISC + 2704;
constexpr int SMEM_BYTES = OFF_MISC + 2768;
__device__ __forceinline__ uint32_t s_addr(uint32_t o, uint32_t half) { return o + (((half ^ (o >> 7)) & 1) << 4); }
__host__ __device__ constexpr uint32_t y_off(uint32_t q) { return OFF_RING + 32768 + (q & 1) * 8192 + (q >> 1) * 65536; }

constexpr int B_W = 0;
constexpr int B_E = 24;
constexpr int B_S = 36;
constexpr int B_Y = 40;
constexpr int B_DP = 44, B_U = 45, B_KG = 46, B_G = 47;
constexpr int B_F = 48;
constexpr int B_H = 60;
constexpr int B_X = 52, B_XE = 56;

struct BandTab { uint32_t w[11][12]; };
constexpr BandTab make_band() {
    BandTab b{};
    for (int cls = 0; cls < 11; cls++)
        for (int wd = 0; wd < 10; wd++) {
            const int tau = cls + 2 - 8 * ((wd < 4 ? wd : wd - 4) >> 1);
            const int lo = (wd < 4) ? ((wd & 1) ? -2 : 3) : ((wd & 1) ? -4 : -11), wid = (wd < 4 ? 3 : 7) + 2 * (wd & 1);
            b.w[cls][wd] = ((tau >= lo && tau < lo + wid) ? 0x3F80u : 0u) | ((tau - 4 >= lo && tau - 4 < lo + wid) ? 0x3F800000u : 0u);
        }
    return b;
}
constexpr int NTOP = 32;
struct Scratch {
    uint4 r[L_ / 4];
    uint4 g[L_ / 4];
    uint4 h[2][8 * F_ / 8];
    uint32_t top[NTOP][32];
    unsigned epoch;
};
__device__ __align__(128) Scratch g_scratch;
__device__ const __align__(16) BandTab g_band = make_band();

struct Params {
    const bf16 *u, *logA, *Aim, *Cre, *Cim, *logdt, *Dskip, *wr, *gatew;
    bf16* out;
    Scratch* sc;
    const uint4* band;
    uint32_t gu_swap;
    uint32_t zero;
};

#define WSTAMP(i) do {} while (0)
#define KSTAMP(i, dep) do {} while (0)
#define WDUMP() do {} while (0)
#define RSTAMP(i) do {} while (0)

__device__ __forceinline__ uint32_t smem_u32(const void* p) { return (uint32_t)__cvta_generic_to_shared(p); }
__device__ __forceinline__ void mbar_init(uint32_t b, uint32_t c) { asm volatile("mbarrier.init.shared::cta.b64 [%0], %1;" :: "r"(b), "r"(c) : "memory"); }
__device__ __forceinline__ void mbar_expect(uint32_t b, uint32_t tx) { asm volatile("mbarrier.arrive.expect_tx.shared::cta.b64 _, [%0], %1;" :: "r"(b), "r"(tx) : "memory"); }
__device__ __forceinline__ void mbar_arrive(uint32_t b) { asm volatile("mbarrier.arrive.shared::cta.b64 _, [%0];" :: "r"(b) : "memory"); }
__device__ __forceinline__ void mbar_wait(uint32_t b, uint32_t parity = 0) {
    asm volatile("{\n\t.reg .pred p;\nW%=:\n\tmbarrier.try_wait.parity.shared::cta.b64 p, [%0], %1, 20000;\n\t@!p bra W%=;\n\t}" :: "r"(b), "r"(parity) : "memory");
}
__device__ __forceinline__ uint32_t mapa(uint32_t addr, uint32_t rank) { uint32_t r; asm("mapa.shared::cluster.u32 %0, %1, %2;" : "=r"(r) : "r"(addr), "r"(rank)); return r; }
__device__ __forceinline__ void tma3d(uint32_t dst, const CUtensorMap* tm, int c0, int c1, uint32_t bar, uint32_t bytes) {
    asm volatile("{\n\t.reg .pred p;\n\telect.sync _|p, 0xffffffff;\n\t"
                 "@p mbarrier.arrive.expect_tx.shared::cta.b64 _, [%2], %5;\n\t"
                 "@p cp.async.bulk.tensor.3d.shared::cluster.global.mbarrier::complete_tx::bytes [%0], [%1, {%3, %4, 0}], [%2];\n\t}"
        :: "r"(dst), "l"(tm), "r"(bar), "r"(c0), "r"(c1), "r"(bytes) : "memory");
}
__device__ __forceinline__ void bulk_load(uint32_t dst, const void* src, uint32_t bytes, uint32_t bar) {
    asm volatile("{\n\t.reg .pred p;\n\telect.sync _|p, 0xffffffff;\n\t"
                 "@p mbarrier.arrive.expect_tx.shared::cta.b64 _, [%2], %3;\n\t"
                 "@p cp.async.bulk.shared::cluster.global.mbarrier::complete_tx::bytes [%0], [%1], %3, [%2];\n\t}"
        :: "r"(dst), "l"(src), "r"(bar), "r"(bytes) : "memory");
}
__device__ __forceinline__ void st_async16(uint32_t dst, const uint4& v, uint32_t bar) {
    asm volatile("st.async.weak.shared::cluster.mbarrier::complete_tx::bytes.v4.b32 [%0], {%1,%2,%3,%4}, [%5];"
                 :: "r"(dst), "r"(v.x), "r"(v.y), "r"(v.z), "r"(v.w), "r"(bar) : "memory");
}
__device__ __forceinline__ void bar_sync(int id, int n) { asm volatile("bar.sync %0, %1;" :: "r"(id), "r"(n) : "memory"); }
__device__ __forceinline__ void cp16(uint32_t dst, const void* src) { asm volatile("cp.async.cg.shared.global [%0], [%1], 16;" :: "r"(dst), "l"(src) : "memory"); }
__device__ __forceinline__ void cp_wait_all() { asm volatile("cp.async.wait_all;" ::: "memory"); }
__device__ __forceinline__ uint4 ld_gpu128(const void* p) { uint4 v; asm volatile("ld.relaxed.gpu.global.v4.u32 {%0,%1,%2,%3}, [%4];" : "=r"(v.x), "=r"(v.y), "=r"(v.z), "=r"(v.w) : "l"(p) : "memory"); return v; }
__device__ __forceinline__ void st_gpu32(void* p, uint32_t v) { asm volatile("st.relaxed.gpu.global.u32 [%0], %1;" :: "l"(p), "r"(v) : "memory"); }

__device__ __forceinline__ void ldsm4(uint32_t a, uint32_t& r0, uint32_t& r1, uint32_t& r2, uint32_t& r3) {
    asm volatile("ldmatrix.sync.aligned.m8n8.x4.shared.b16 {%0,%1,%2,%3}, [%4];" : "=r"(r0), "=r"(r1), "=r"(r2), "=r"(r3) : "r"(a) : "memory");
}
__device__ __forceinline__ void ldsm4t(uint32_t a, uint32_t& r0, uint32_t& r1, uint32_t& r2, uint32_t& r3) {
    asm volatile("ldmatrix.sync.aligned.m8n8.x4.trans.shared.b16 {%0,%1,%2,%3}, [%4];" : "=r"(r0), "=r"(r1), "=r"(r2), "=r"(r3) : "r"(a) : "memory");
}
__device__ __forceinline__ uint32_t lds32(uint32_t a) { uint32_t v; asm volatile("ld.shared.u32 %0, [%1];" : "=r"(v) : "r"(a) : "memory"); return v; }
__device__ __forceinline__ uint2 lds64(uint32_t a) { uint2 v; asm volatile("ld.shared.v2.u32 {%0,%1}, [%2];" : "=r"(v.x), "=r"(v.y) : "r"(a) : "memory"); return v; }
__device__ __forceinline__ uint4 lds128(uint32_t a) { uint4 v; asm volatile("ld.shared.v4.u32 {%0,%1,%2,%3}, [%4];" : "=r"(v.x), "=r"(v.y), "=r"(v.z), "=r"(v.w) : "r"(a) : "memory"); return v; }
__device__ __forceinline__ void sts32(uint32_t a, uint32_t v) { asm volatile("st.shared.u32 [%0], %1;" :: "r"(a), "r"(v) : "memory"); }
__device__ __forceinline__ void sts16(uint32_t a, uint32_t v) { asm volatile("st.shared.u16 [%0], %1;" :: "r"(a), "h"((unsigned short)v) : "memory"); }
__device__ __forceinline__ void sts128(uint32_t a, uint32_t x, uint32_t y, uint32_t z, uint32_t w) { asm volatile("st.shared.v4.u32 [%0], {%1,%2,%3,%4};" :: "r"(a), "r"(x), "r"(y), "r"(z), "r"(w) : "memory"); }
__device__ __forceinline__ float ldsf(uint32_t a) { float v; asm volatile("ld.shared.f32 %0, [%1];" : "=f"(v) : "r"(a) : "memory"); return v; }

__device__ __forceinline__ void mma_bf(float (&d)[4], uint32_t a0, uint32_t a1, uint32_t a2, uint32_t a3, uint32_t b0, uint32_t b1) {
    asm volatile("mma.sync.aligned.m16n8k16.row.col.f32.bf16.bf16.f32 {%0,%1,%2,%3}, {%4,%5,%6,%7}, {%8,%9}, {%0,%1,%2,%3};"
        : "+f"(d[0]), "+f"(d[1]), "+f"(d[2]), "+f"(d[3]) : "r"(a0), "r"(a1), "r"(a2), "r"(a3), "r"(b0), "r"(b1));
}
__device__ __forceinline__ void mma_bf_z(float (&d)[4], uint32_t a0, uint32_t a1, uint32_t a2, uint32_t a3, uint32_t b0, uint32_t b1) {
    asm volatile("mma.sync.aligned.m16n8k16.row.col.f32.bf16.bf16.f32 {%0,%1,%2,%3}, {%4,%5,%6,%7}, {%8,%9}, {%10,%10,%10,%10};"
        : "=f"(d[0]), "=f"(d[1]), "=f"(d[2]), "=f"(d[3]) : "r"(a0), "r"(a1), "r"(a2), "r"(a3), "r"(b0), "r"(b1), "f"(0.f));
}
__device__ __forceinline__ void mma_bf_k8(float (&d)[4], uint32_t a0, uint32_t a1, uint32_t b0) {
    asm volatile("mma.sync.aligned.m16n8k8.row.col.f32.bf16.bf16.f32 {%0,%1,%2,%3}, {%4,%5}, {%6}, {%0,%1,%2,%3};"
        : "+f"(d[0]), "+f"(d[1]), "+f"(d[2]), "+f"(d[3]) : "r"(a0), "r"(a1), "r"(b0));
}
__device__ __forceinline__ void mma_h(float (&d)[4], uint32_t a0, uint32_t a1, uint32_t a2, uint32_t a3, uint32_t b0, uint32_t b1) {
    asm volatile("mma.sync.aligned.m16n8k16.row.col.f32.f16.f16.f32 {%0,%1,%2,%3}, {%4,%5,%6,%7}, {%8,%9}, {%0,%1,%2,%3};"
        : "+f"(d[0]), "+f"(d[1]), "+f"(d[2]), "+f"(d[3]) : "r"(a0), "r"(a1), "r"(a2), "r"(a3), "r"(b0), "r"(b1));
}
__device__ __forceinline__ uint32_t pack_bf(float lo, float hi) { uint32_t r; asm("cvt.rn.bf16x2.f32 %0, %1, %2;" : "=r"(r) : "f"(hi), "f"(lo)); return r; }
__device__ __forceinline__ uint32_t pack_h(float lo, float hi) { uint32_t r; asm("cvt.rn.f16x2.f32 %0, %1, %2;" : "=r"(r) : "f"(hi), "f"(lo)); return r; }
__device__ __forceinline__ float bf_lo(uint32_t v) { return __uint_as_float(v << 16); }
__device__ __forceinline__ float bf_hi(uint32_t v) { return __uint_as_float(v & 0xffff0000u); }
__device__ __forceinline__ float bf_round(float x) { return __uint_as_float(pack_bf(0.f, x)); }
__device__ __forceinline__ uint32_t hmul2_bf(uint32_t a, uint32_t b) { uint32_t r; asm("mul.rn.bf16x2 %0, %1, %2;" : "=r"(r) : "r"(a), "r"(b)); return r; }
__device__ __forceinline__ float ex2f(float x) { float r; asm("ex2.approx.ftz.f32 %0, %1;" : "=f"(r) : "f"(x)); return r; }

__device__ __forceinline__ float exp_acc(float x) {
    const float t = x * 1.4426950216293335f;
    const float r = fmaf(x, 1.4426950216293335f, -t) + x * 1.9259629911266175e-8f;
    return ex2f(t) * fmaf(r, 0.6931471805599453f, 1.f);
}
__device__ __forceinline__ float sigmoid_f(float x) { return __fdividef(1.f, 1.f + ex2f(-x * 1.4426950408889634f)); }
__device__ __forceinline__ void cexp_pow(float l2, float li, float e, float& zr, float& zi) {
    const float mag = ex2f(l2 * e);
    zr = mag * __cosf(li * e);
    zi = mag * __sinf(li * e);
}
__device__ __forceinline__ uint32_t hcmul(uint32_t a, uint32_t k, uint32_t kp) {
    const __half2 A = *reinterpret_cast<const __half2*>(&a);
    const __half2 r = __hfma2(__high2half2(A), *reinterpret_cast<const __half2*>(&kp), __hmul2(__low2half2(A), *reinterpret_cast<const __half2*>(&k)));
    return *reinterpret_cast<const uint32_t*>(&r);
}
#define CMUL(orr, oi, ar, ai, br, bi) do { float _r = (ar) * (br) - (ai) * (bi); float _i = (ar) * (bi) + (ai) * (br); orr = _r; oi = _i; } while (0)
#define CSQ(orr, oi, ar, ai) do { float _r = (ar) * (ar) - (ai) * (ai); float _i = 2.f * (ar) * (ai); orr = _r; oi = _i; } while (0)

__device__ __forceinline__ void mma_bf_k8z(float (&d)[4], uint32_t a0, uint32_t a1, uint32_t b0) {
    asm volatile("mma.sync.aligned.m16n8k8.row.col.f32.bf16.bf16.f32 {%0,%1,%2,%3}, {%4,%5}, {%6}, {%7,%7,%7,%7};"
        : "=f"(d[0]), "=f"(d[1]), "=f"(d[2]), "=f"(d[3]) : "r"(a0), "r"(a1), "r"(b0), "f"(0.f));
}
__device__ __forceinline__ void mma_hh_k8(uint32_t& d0, uint32_t& d1, uint32_t a0, uint32_t a1, uint32_t b0) {
    asm volatile("mma.sync.aligned.m16n8k8.row.col.f16.f16.f16.f16 {%0,%1}, {%2,%3}, {%4}, {%5,%5};"
        : "=r"(d0), "=r"(d1) : "r"(a0), "r"(a1), "r"(b0), "r"(0));
}
__device__ __forceinline__ void sched_fence() { asm volatile("pmevent 0;" ::: "memory"); }
__device__ __forceinline__ uint32_t pin(uint32_t x, int lane) { return __shfl_sync(0xffffffffu, x, lane); }
template <class T> __device__ __forceinline__ T* pin(T* x, int lane) { return (T*)__shfl_sync(0xffffffffu, (unsigned long long)x, lane); }
__device__ __forceinline__ void sts32_if(bool on, uint32_t a, uint32_t v) {
    asm volatile("{\n\t.reg .pred p;\n\tsetp.ne.u32 p, %2, 0;\n\t@p st.shared.u32 [%0], %1;\n\t}" :: "r"(a), "r"(v), "r"((uint32_t)on) : "memory");
}
__device__ __forceinline__ void sts128_if(bool on, uint32_t a, uint32_t x, uint32_t y, uint32_t z, uint32_t w) {
    asm volatile("{\n\t.reg .pred p;\n\tsetp.ne.u32 p, %5, 0;\n\t@p st.shared.v4.u32 [%0], {%1,%2,%3,%4};\n\t}" :: "r"(a), "r"(x), "r"(y), "r"(z), "r"(w), "r"((uint32_t)on) : "memory");
}
__device__ __forceinline__ void lds128_if(bool on, uint32_t a, uint32_t (&v)[4]) {
    asm volatile("{\n\t.reg .pred p;\n\tsetp.ne.u32 p, %5, 0;\n\t@p ld.shared.v4.u32 {%0,%1,%2,%3}, [%4];\n\t}"
        : "+r"(v[0]), "+r"(v[1]), "+r"(v[2]), "+r"(v[3]) : "r"(a), "r"((uint32_t)on) : "memory");
}
__device__ __forceinline__ uint32_t hfma2_bf(uint32_t a, uint32_t b, uint32_t c) { uint32_t r; asm("fma.rn.bf16x2 %0, %1, %2, %3;" : "=r"(r) : "r"(a), "r"(b), "r"(c)); return r; }
__device__ __forceinline__ __nv_bfloat162 bcast(uint32_t a, int hi) { const __nv_bfloat162 v = *reinterpret_cast<const __nv_bfloat162*>(&a); return hi ? __high2bfloat162(v) : __low2bfloat162(v); }
__device__ __forceinline__ uint32_t hmul2_bc(uint32_t a, int hi, uint32_t b) { const __nv_bfloat162 r = __hmul2_rn(bcast(a, hi), *reinterpret_cast<const __nv_bfloat162*>(&b)); return *reinterpret_cast<const uint32_t*>(&r); }
__device__ __forceinline__ uint32_t hfma2_bc(uint32_t a, int hi, uint32_t b, uint32_t c) {
    const __nv_bfloat162 r = __hfma2(bcast(a, hi), *reinterpret_cast<const __nv_bfloat162*>(&b), *reinterpret_cast<const __nv_bfloat162*>(&c));
    return *reinterpret_cast<const uint32_t*>(&r);
}
__device__ __forceinline__ uint32_t row_elem(uint32_t row) { return ((row >> 5) & 4) | ((row >> 2) & 2) | ((row >> 4) & 1); }
__device__ __forceinline__ uint32_t gate_pos(uint32_t row) { return ((row >> 9) << 8) | ((row & 7) << 5) | (row_elem(row) << 2) | ((row >> 5) & 3); }

template <int N>
__device__ __forceinline__ void mix_rows(const Params& p, const CUtensorMap* tm_out, uint32_t sb, uint32_t ob, int Q0, int Q1, int w, int h, int pr, int lane) {
    const int g = lane >> 2, t = lane & 3, mi = lane >> 3, r = lane & 7;
    const int m8 = 16 * (g >> 2) + ((g >> 1) & 1) + 2 * (g & 1);
    uint32_t yi = sb + (4 * (r >> 1) + 2 * (mi & 1) + (r & 1)) * 512 + (((4 * w + (mi >> 1)) ^ r) << 4);
    uint32_t xs = sb + OFF_S + s_addr(w * S_PL + 32 + m8 * 32, t >> 1) + ((t & 1) << 3);
    uint32_t gs = sb + OFF_GP + w * 64 + g * 8, os = ob + m8 * 32 + t * 8;
    if (N > 1) { yi = pin(yi, lane); xs = pin(xs, lane); gs = pin(gs, lane); os = pin(os, lane); }
    mbar_wait(sb + M_BARS + 8 * B_Y);
#pragma unroll 1
    for (int Q = Q0; Q < Q1; Q++) {
        uint2 xq[N][4];
        uint32_t gg[N][2], sw[N];
#pragma unroll
        for (int n = 0; n < N; n++) {
#pragma unroll
            for (int i = 0; i < 4; i++) xq[n][i] = lds64((xs ^ (((i ^ n) & 1) << 4)) + Q * S_Q + n * 4 * S_PL + i * 128);
            const uint2 gq = lds64(gs + Q * 512 + n * 256);
            sw[n] = lds32(sb + M_BMAP + w * 16 + n * 64 + Q * 4);
            gg[n][0] = gq.x; gg[n][1] = gq.y;
#pragma unroll
            for (int i = 0; i < 4; i++) {
                const uint32_t og = hfma2_bf(gg[n][i >> 1], 0xBF80BF80u, 0x3F803F80u);
                xq[n][i].x = hmul2_bc(og, i & 1, xq[n][i].x); xq[n][i].y = hmul2_bc(og, i & 1, xq[n][i].y);
            }
        }
        mbar_wait(sb + M_BARS + 8 * (B_Y + Q));
        __syncwarp();
#pragma unroll
        for (int n = 0; n < N; n++) {
#pragma unroll
            for (int x = 0; x < 2; x++) {
                uint32_t y[4];
                ldsm4t((yi ^ (x << 5)) + y_off(Q) + n * 256, y[0], y[1], y[2], y[3]);
#pragma unroll
                for (int e = 0; e < 2; e++) {
                    uint2& o = xq[n][2 * x + e];
                    o.x = hfma2_bc(gg[n][x], e, y[2 * e], o.x); o.y = hfma2_bc(gg[n][x], e, y[2 * e + 1], o.y);
                }
            }
        }
        if ((sw[0] | sw[N - 1]) == 0) {
#pragma unroll
            for (int n = 0; n < N; n++)
#pragma unroll
                for (int i = 0; i < 4; i++)
                    asm volatile("st.shared.v2.u32 [%0], {%1, %2};" :: "r"(os + Q * 1024 + n * 4 * TAB_W + i * 128), "r"(xq[n][i].x), "r"(xq[n][i].y) : "memory");
            asm volatile("fence.proxy.async.shared::cta;" ::: "memory");
            __syncwarp();
#pragma unroll
            for (int n = 0; n < N; n++)
                asm volatile("{\n\t.reg .pred p;\n\telect.sync _|p, 0xffffffff;\n\t"
                             "@p cp.async.bulk.tensor.3d.global.shared::cta.bulk_group [%1, {%2, %3, %4}], [%0];\n\t}"
                    :: "r"(ob + 4 * n * TAB_W + Q * 1024), "l"(tm_out), "r"(16 * pr), "r"(64 * Q + 32 * h), "r"(w + 4 * n) : "memory");
        } else {
            bf16* op = p.out + (size_t)(512 * Q + 256 * h + 8 * m8 + w) * D_ + 16 * pr + 4 * t;
#pragma unroll
            for (int n = 0; n < N; n++)
#pragma unroll
                for (int i = 0; i < 4; i++)
                    if (!((sw[n] >> (4 * g)) & (1u << i))) *(uint2*)(op + (size_t)(32 * i + 4 * n) * D_) = xq[n][i];
        }
    }
}

__global__ void __cluster_dims__(2, 1, 1) __launch_bounds__(NTHREADS, 1)
fused_kernel(const Params p, const __grid_constant__ CUtensorMap tm_gu, const __grid_constant__ CUtensorMap tm_down,
             const __grid_constant__ CUtensorMap tm_x, const __grid_constant__ CUtensorMap tm_out) {
    extern __shared__ __align__(1024) unsigned char smem[];
    const uint32_t sb = smem_u32(smem);
    int tid;
    asm volatile("mov.u32 %0, %%tid.x;" : "=r"(tid));
    const int pw = tid >> 5, lane = tid & 31;
    const int c = blockIdx.x, h = c & 1, pr = c >> 1;
    const uint32_t bars = sb + M_BARS;

    uint2 v_la, v_ai, v_cr, v_ci;
    uint32_t ldt16;
    {
        const uint32_t po = c * 256 + tid;
        asm volatile("{\n\t.reg .pred p;\n\t.reg .b64 a;\n\tsetp.ne.u32 p, %16, 0;\n\t"
                     "mad.wide.u32 a, %14, 8, %9;\n\t@p ld.global.nc.L1::no_allocate.v2.u32 {%0,%1}, [a];\n\t"
                     "mad.wide.u32 a, %15, 2, %13;\n\t@p ld.global.nc.u16 %8, [a];\n\t"
                     "mad.wide.u32 a, %14, 8, %10;\n\t@p ld.global.nc.L1::no_allocate.v2.u32 {%2,%3}, [a];\n\t"
                     "mad.wide.u32 a, %14, 8, %11;\n\t@p ld.global.nc.L1::no_allocate.v2.u32 {%4,%5}, [a];\n\t"
                     "mad.wide.u32 a, %14, 8, %12;\n\t@p ld.global.nc.L1::no_allocate.v2.u32 {%6,%7}, [a];\n\t}"
            : "=r"(v_la.x), "=r"(v_la.y), "=r"(v_ai.x), "=r"(v_ai.y), "=r"(v_cr.x), "=r"(v_cr.y), "=r"(v_ci.x), "=r"(v_ci.y), "=r"(ldt16)
            : "l"(p.logA), "l"(p.Aim), "l"(p.Cre), "l"(p.Cim), "l"(p.logdt), "r"(po), "r"(po >> 5), "r"((uint32_t)(tid < 256 && c < 128)));
    }

    if (c >= 128) {
        if (c != 128) return;
        RSTAMP(5);
        const unsigned tag = (*(volatile unsigned*)&p.sc->epoch + 1) & 0xffffu;
        const uint32_t list = sb + 128;
        sts128(list + 16 * tid, 0, 0, 0, 0);
        if (tid == 0) sts32(sb + 64, 0);
        uint32_t key[4] = {tag - 1, tag - 1, tag - 1, tag - 1};
#pragma unroll 1
        for (int it = 0; it < (1 << 22); it++) {
            uint32_t a[4];
            asm volatile("{\n\t.reg .b128 o, z;\n\t.reg .b64 l, u;\n\tmov.b64 l, {%5, %5};\n\tmov.b128 z, {l, l};\n\tatom.relaxed.gpu.global.exch.b128 o, [%4], z;\n\t"
                         "mov.b128 {l, u}, o;\n\tmov.b64 {%0, %1}, l;\n\tmov.b64 {%2, %3}, u;\n\t}"
                : "=r"(a[0]), "=r"(a[1]), "=r"(a[2]), "=r"(a[3]) : "l"(&p.sc->r[tid]), "r"(tag - 1) : "memory");
#pragma unroll
            for (int i = 0; i < 4; i++) if (((a[i] ^ tag) & 0xffffu) == 0) key[i] = a[i];
            if ((((key[0] ^ tag) | (key[1] ^ tag) | (key[2] ^ tag) | (key[3] ^ tag)) & 0xffffu) == 0) break;
        }
        WSTAMP(0);
        uint32_t m = 0;
#pragma unroll
        for (int i = 0; i < 4; i++) {
            key[i] = (key[i] & 0xffff0000u) | (uint32_t)(2047 - (4 * tid + i));
            m = max(m, key[i]);
        }
        const uint32_t wm = __reduce_max_sync(0xffffffffu, m);
        if (lane == 0) sts32(sb + pw * 4, wm);
        __syncthreads();
        uint32_t thr = 0xffffffffu;
#pragma unroll
        for (int i = 0; i < 4; i++) { const uint4 q = lds128(sb + 16 * i); thr = min(thr, min(max(q.x, q.y), max(q.z, q.w))); }
        if (thr != 1) WSTAMP(1);
        if (m >= thr) {
            uint32_t pos;
            asm volatile("atom.shared.add.u32 %0, [%1], %2;" : "=r"(pos) : "r"(sb + 64), "r"(4 * ((key[0] >= thr) + (key[1] >= thr) + (key[2] >= thr) + (key[3] >= thr))) : "memory");
#pragma unroll
            for (int i = 0; i < 4; i++) if (key[i] >= thr) { sts32(list + pos, key[i]); pos += 4; }
        }
        __syncthreads();
        const uint32_t nc4 = lds32(sb + 64);
        if (nc4 != 1) WSTAMP(2);
#pragma unroll 1
        for (uint32_t j = 4 * pw; j < nc4; j += 64) {
            const uint32_t mine = lds32(list + j);
            int rank = 0;
#pragma unroll 1
            for (uint32_t i = 0; i < nc4; i += 128) rank += __popc(__ballot_sync(0xffffffffu, lds32(list + i + 4 * lane) > mine));
            if (rank < 8 && lane == 0) sts32(sb + 96 + 4 * rank, mine);
        }
        __syncthreads();
        if (tid < 8 * NTOP) st_gpu32(&p.sc->top[tid >> 3][tid & 7], lds32(sb + 96 + 4 * (tid & 7)) | ((tag & 31) << 11));
        WSTAMP(3);
        WDUMP();
        return;
    }

    WSTAMP(0);
    if (pw < 8) {
        const int d = 8 * c + pw - MAIN_W0;
        if (lane == 0) asm volatile("cp.async.ca.shared.global [%0], [%1], 4;" :: "r"(sb + M_DSK + 4 * (pw - MAIN_W0)), "l"(p.Dskip + (d & ~1)) : "memory");
        asm volatile("barrier.cluster.arrive.relaxed.aligned;" ::: "memory");
        const int warp = pw - MAIN_W0;
        asm volatile("setmaxnreg.inc.sync.aligned.u32 160;");
        const int g = lane >> 2, t = lane & 3;
        const int mi = lane >> 3, r = lane & 7;
        const uint32_t TB = sb + OFF_TAB + warp * TAB_W;
        const uint32_t UB = sb + OFF_U + warp * U_CH;
        if (mi < 2) sts128(UB + mi * U_PL + r * 16, 0, 0, 0, 0);
        if (lane < 4) sts128(TB + lane * T_PL, 0, 0, 0, 0);
        sts128(sb + OFF_SCR + warp * 8192 + lane * 16, 0x3C00u, 0x3C00u, 0x3C00u, 0x3C00u);
        asm volatile("barrier.cluster.wait.acquire.aligned;" ::: "memory");
        __syncwarp();

        uint32_t cfix;
        {
            KSTAMP(4, v_la.x ^ v_ai.x ^ v_cr.x ^ v_ci.x ^ ldt16);
            const float dt = bf_round(exp_acc(__uint_as_float(ldt16 << 16)));
            float l2[4], li[4];
            {
                const uint32_t la[2] = {v_la.x, v_la.y}, ai[2] = {v_ai.x, v_ai.y};
                const float dt2 = -1.4426950408889634f * dt;
#pragma unroll
                for (int i = 0; i < 4; i++) {
                    l2[i] = bf_round(ex2f(((i & 1) ? bf_hi(la[i >> 1]) : bf_lo(la[i >> 1])) * 1.4426950408889634f)) * dt2;
                    li[i] = ((i & 1) ? bf_hi(ai[i >> 1]) : bf_lo(ai[i >> 1])) * dt;
                }
            }
            const uint32_t SX = sb + OFF_SCR + warp * 8192;
            const uint32_t sw = SX + (lane << 4);
#define PUT(buf, row, v) sts128(((sw + (row) * 512) ^ ((row) << 4)) + (buf) * 4096, v[0], v[1], v[2], v[3])
#define EMIT(bufa, rowa, bufb, rowb, xr, xi, k, kp) do { uint32_t pk[4], pd[4]; sched_fence(); \
                _Pragma("unroll") for (int i = 0; i < 4; i++) { pk[i] = pack_h(xr[i], xi[i]); pd[i] = hcmul(pk[i], k[i], kp[i]); } \
                PUT(bufa, rowa, pk); PUT(bufb, rowb, pd); } while (0)
#define CMUL4(orr, oi, ar, ai, br, bi) _Pragma("unroll") for (int i = 0; i < 4; i++) CMUL(orr[i], oi[i], ar[i], ai[i], br[i], bi[i])
#define CSQ4(orr, oi, ar, ai) _Pragma("unroll") for (int i = 0; i < 4; i++) CSQ(orr[i], oi[i], ar[i], ai[i])
            float z1r[4], z1i[4], z2r[4], z2i[4], z8r[4], z8i[4], z256r[4], z256i[4];
            uint32_t k4[4], k4p[4];
            float z4r[4], z4i[4];
#pragma unroll
            for (int i = 0; i < 4; i++) cexp_pow(l2[i], li[i], 1.f, z1r[i], z1i[i]);
            CSQ4(z2r, z2i, z1r, z1i);
            CSQ4(z4r, z4i, z2r, z2i);
            CSQ4(z8r, z8i, z4r, z4i);
            KSTAMP(5, __float_as_uint(z8r[3]));
            uint32_t Ya[16][4];
            float cr[4], ci[4], inv;
            {
                float w1r[4], w1i[4], ar[4], ai[4], br[4], bi[4];
                uint32_t k8[4], k8p[4];
#pragma unroll
                for (int i = 0; i < 4; i++) {
                    k8[i] = pack_h(z8r[i], -z8i[i]); k8p[i] = pack_h(z8i[i], z8r[i]);
                    CSQ(w1r[i], w1i[i], z8r[i], z8i[i]); w1i[i] = -w1i[i];
                }
                PUT(1, 0, k8);
                EMIT(0, 1, 1, 1, w1r, w1i, k8, k8p);
                CSQ4(ar, ai, w1r, w1i);            EMIT(0, 2, 1, 2, ar, ai, k8, k8p);
                CMUL4(br, bi, ar, ai, w1r, w1i);   EMIT(0, 3, 1, 3, br, bi, k8, k8p);
                CSQ4(ar, ai, ar, ai);              EMIT(0, 4, 1, 4, ar, ai, k8, k8p);
                CMUL4(ar, ai, ar, ai, w1r, w1i);   EMIT(0, 5, 1, 5, ar, ai, k8, k8p);
                CSQ4(br, bi, br, bi);              EMIT(0, 6, 1, 6, br, bi, k8, k8p);
                CMUL4(br, bi, br, bi, w1r, w1i);   EMIT(0, 7, 1, 7, br, bi, k8, k8p);
                __syncwarp();
                KSTAMP(6, 0);
                sched_fence();
                const uint32_t ab = SX + (mi & 1) * 4096 + r * 512, ax = ((mi >> 1) ^ r) << 4;
                const uint32_t vr[2] = {v_cr.x, v_cr.y}, vi[2] = {v_ci.x, v_ci.y};
                const uint32_t m2 = __vmaxu2(__vmaxu2(vr[0] & 0x7fff7fffu, vr[1] & 0x7fff7fffu), __vmaxu2(vi[0] & 0x7fff7fffu, vi[1] & 0x7fff7fffu));
                const uint32_t mx = __reduce_max_sync(0xffffffffu, max(m2, m2 << 16));
                const uint32_t e = min(max(mx >> 23, 11u), 254u);
                const float sc = __uint_as_float((264u - e) << 23);
                inv = __uint_as_float((e - 10u) << 23) * (2.f * dt);
#pragma unroll
                for (int i = 0; i < 4; i++) {
#pragma unroll
                    for (int k = 0; k < 4; k++) ldsm4(ab + (ax ^ (i << 5)) + k * 128, Ya[4 * k + i][0], Ya[4 * k + i][1], Ya[4 * k + i][2], Ya[4 * k + i][3]);
                    float tr, ti;
                    cexp_pow(l2[i], li[i], 128.f, tr, ti);
                    sts32(TB + 2176 + 256 * i + 4 * lane, pack_h(tr, ti));
                    sts32(TB + 2176 + 256 * i + 128 + 4 * (lane ^ 16), pack_h(-ti, tr));
                    k4[i] = pack_h(z4r[i], z4i[i]); k4p[i] = pack_h(-z4i[i], z4r[i]);
                    CSQ(z256r[i], z256i[i], tr, ti);
                    cr[i] = ((i & 1) ? bf_hi(vr[i >> 1]) : bf_lo(vr[i >> 1])) * sc;
                    ci[i] = ((i & 1) ? bf_hi(vi[i >> 1]) : bf_lo(vi[i >> 1])) * sc;
                    if (i < 3) sched_fence();
                }
                __syncwarp();
            }
            KSTAMP(7, Ya[15][0]);
            const uint32_t ld0 = SX + r * 512 + ((mi ^ r) << 4), ld1 = ld0 ^ 64;
            float R[6][4], s1024;
            {
                float xr[4], xi[4], yr[4], yi[4];
                EMIT(0, 0, 0, 1, cr, ci, k4, k4p);
                CMUL4(yr, yi, cr, ci, z1r, z1i);        EMIT(0, 2, 0, 3, yr, yi, k4, k4p);
                CMUL4(xr, xi, cr, ci, z256r, z256i);    EMIT(1, 0, 1, 1, xr, xi, k4, k4p);
                CMUL4(yr, yi, yr, yi, z1r, z1i);        EMIT(0, 4, 0, 5, yr, yi, k4, k4p);
                CMUL4(cr, ci, yr, yi, z256r, z256i);    EMIT(1, 2, 1, 3, cr, ci, k4, k4p);
                CMUL4(yr, yi, yr, yi, z1r, z1i);        EMIT(0, 6, 0, 7, yr, yi, k4, k4p);
                CMUL4(xr, xi, xr, xi, z256r, z256i);    EMIT(1, 4, 1, 5, xr, xi, k4, k4p);
                CMUL4(xr, xi, xr, xi, z256r, z256i);    EMIT(1, 6, 1, 7, xr, xi, k4, k4p);
                CMUL4(xr, xi, xr, xi, z256r, z256i);
                s1024 = (xr[0] + xr[1]) + (xr[2] + xr[3]);
#pragma unroll
                for (int m = 0; m < 4; m++) {
                    if (m == 0) { CMUL4(xr, xi, xr, xi, z8r, z8i); } else { CMUL4(xr, xi, xr, xi, z256r, z256i); }
                    sched_fence();
                    sts128(TB + m * T_PL + 16 + 16 * lane, pack_h(xr[0], xi[0]), pack_h(xr[1], xi[1]), pack_h(xr[2], xi[2]), pack_h(xr[3], xi[3]));
                }
            }
            __syncwarp();
            {
                KSTAMP(8, 0);
                uint32_t bd[2][4] = {{0, 0, 0, 0}, {0, 0, 0, 0}};
                const bool on = (g >> 1) == t;
#pragma unroll
                for (int i = 0; i < 6; i++) { R[i][0] = R[i][1] = R[i][2] = R[i][3] = 0.f; }
                uint32_t x[2][4], y[2][4], z[2][4];
                auto fetch = [&](const int k2) {
                    const int b = k2 & 1;
                    lds128_if(on, TB + 2176 + g * 128 + (k2 < 4 ? 64 : -64) * (g & 1) + 16 * k2, bd[b]);
                    ldsm4(((k2 & 1) ? ld1 : ld0) + (k2 >> 1) * 128, x[b][0], x[b][1], x[b][2], x[b][3]);
                    ldsm4(((k2 & 1) ? ld1 : ld0) + (k2 >> 1) * 128 + 4096, y[b][0], y[b][1], y[b][2], y[b][3]);
                    ldsm4(TB + (r & 3) * T_PL + 16 + 16 * mi + 64 * k2, z[b][0], z[b][1], z[b][2], z[b][3]);
                };
                fetch(0);
#pragma unroll
                for (int k2 = 0; k2 < 8; k2++) {
                    const int b = k2 & 1;
                    uint32_t a1[2][4];
                    if (k2 < 7) fetch(k2 + 1);
#pragma unroll
                    for (int u = 0; u < 2; u++) {
                        mma_hh_k8(a1[u][0], a1[u][1], Ya[2 * k2 + u][0], Ya[2 * k2 + u][1], bd[b][2 * u]);
                        mma_hh_k8(a1[u][2], a1[u][3], Ya[2 * k2 + u][2], Ya[2 * k2 + u][3], bd[b][2 * u + 1]);
                    }
#pragma unroll
                    for (int u = 0; u < 2; u++) {
                        const uint32_t(&a0)[4] = Ya[2 * k2 + u];
                        mma_h(R[0], a0[0], a0[1], a0[2], a0[3], x[b][2 * u], x[b][2 * u + 1]);
                        mma_h(R[2], a0[0], a0[1], a0[2], a0[3], y[b][2 * u], y[b][2 * u + 1]);
                        mma_h(R[4], a0[0], a0[1], a0[2], a0[3], z[b][2 * u], z[b][2 * u + 1]);
                        mma_h(R[1], a1[u][0], a1[u][1], a1[u][2], a1[u][3], x[b][2 * u], x[b][2 * u + 1]);
                        mma_h(R[3], a1[u][0], a1[u][1], a1[u][2], a1[u][3], y[b][2 * u], y[b][2 * u + 1]);
                        mma_h(R[5], a1[u][0], a1[u][1], a1[u][2], a1[u][3], z[b][2 * u], z[b][2 * u + 1]);
                    }
                }
            }
            __syncwarp();
            KSTAMP(9, __float_as_uint(R[3][0]));
            if (lane == 0) mbar_arrive(bars + 8 * B_KG + (__float_as_uint(R[0][0]) & __float_as_uint(R[2][0]) & p.zero));
            sts128(TB + 2176 + 16 * lane, 0, 0, 0, 0);
            sts128(TB + 2688 + 16 * lane, 0, 0, 0, 0);
            __syncwarp();
#undef PUT
#undef EMIT
#pragma unroll
            for (int o = 16; o > 0; o >>= 1) s1024 += __shfl_xor_sync(0xffffffffu, s1024, o);
            uint32_t w[4][4], dsk = 0;
            cp_wait_all();
            asm volatile("{\n\t.reg .pred p;\n\tsetp.eq.u32 p, %2, 0;\n\t@p ld.shared.u16 %0, [%1];\n\t}" : "+r"(dsk) : "r"(sb + M_DSK + 4 * warp + 2 * (warp & 1)), "r"(lane) : "memory");
#pragma unroll
            for (int a = 0; a < 4; a++) {
                const float v0 = (a == 0) ? fmaf(R[0][0], inv, __uint_as_float(dsk << 16)) : R[a][0] * inv;
                const float v1 = R[a][1] * inv, v2 = R[a][2] * inv, v3 = R[a][3] * inv;
                w[a][0] = pack_bf(v0, 0.f); w[a][1] = pack_bf(v1, v0); w[a][2] = pack_bf(v2, v1); w[a][3] = pack_bf(v3, v2);
            }
            const uint32_t wb = TB + 16 + 16 * g, w1 = wb + t * T_PL, w2 = wb + 256 + 2 * t * T_PL;
            const uint32_t w3 = (t == 0) ? wb + 256 + 3 * T_PL : TB + T_A + 8 * (16 * t + g);
            const uint32_t w3s = (t == 0) ? 128 : 64, w3o = (t == 0) ? 8 : 12;
            const uint32_t k512 = __shfl_sync(0xffffffffu, w[2][1], 2);
#pragma unroll
            for (int a = 0; a < 2; a++) {
                sts128(w1 + 128 * a, w[a][0], w[a][1], w[a][2], w[a][3]);
                const uint32_t(&q)[4] = w[2 + a];
                if (t < 2) sts128(w2 + 128 * a, q[0], q[1], q[2], q[3]);
                if (t == 0) { sts128(w2 + T_PL + 128 * a, q[0], q[1], q[2], q[3]); sts32(w3 + 128 * a + 4, q[2]); }
                sts32_if(t != 1 && (a == 1 || lane != 2), w3 + w3s * a, q[1]);
                sts32_if(t != 1, w3 + w3s * a + w3o, q[3]);
            }
            sts128_if(lane < 4, w1 + 512, t == 3 ? k512 : k512 >> 16, t < 2 ? k512 : t == 2 ? k512 & 0xffff0000u : k512 << 16, t < 2 ? k512 << 16 : 0u, 0);
            __syncwarp();
#pragma unroll
            for (int a = 0; a < 2; a++) {
                sts16(w1 + 128 * a + 18, w[a][3]);
                const uint32_t(&q)[4] = w[2 + a];
                if (t < 2) sts16(w2 + 128 * a + 18, q[3]);
                if (t == 0) { sts16(w2 + T_PL + 128 * a + 18, q[3]); sts16(w3 + 128 * a + 14, q[3]); }
            }
            if (t == 0) sts16(w3 + 128 - 4, w[3][0]);
            if (lane == 2 || (t == 0 && g > 0)) sts16(lane == 2 ? TB + 16 + 3 * T_PL + 4 * 127 : w3 - 4, w[2][0]);
            {
                float q[4];
#pragma unroll
                for (int i = 0; i < 4; i++) q[i] = (t < 2 ? R[4][i] : R[5][i]) * inv;
                const uint32_t b0 = pack_bf(q[0], q[2]), b1 = pack_bf(q[1], q[3]);
                const uint32_t wq = TB + T_B + 8 * (65 + 32 * (t & 1) + 4 * (t & 2) + g);
                sts32(wq, b0); sts32(wq + 12, b0); sts32(wq + 128, b1); sts32(wq + 140, b1);
            }
            cfix = pack_bf(s1024 * inv, s1024 * inv);
            if (lane == 0) sts32(TB + T_A + 8 * 64, cfix);
            __syncwarp();
        }
        WSTAMP(1);

        mbar_wait(bars + 8 * B_U);
        WSTAMP(2);

        float D[16][4];
        {
            const int x5 = g - t + 5;
            const uint32_t tabD = TB + (x5 & 3) * T_PL + (x5 & 12) + 16;
            {
                const uint32_t a1 = lds32(tabD - 8), a0 = p.zero;
#pragma unroll
                for (int jq = 0; jq < 4; jq++) {
                    uint32_t b[4];
                    ldsm4(UB + (9 + lane) * 16 + jq * 512, b[0], b[1], b[2], b[3]);
#pragma unroll
                    for (int i = 0; i < 4; i++) mma_bf_k8z(D[4 * jq + i], a0, a1, b[i]);
                }
            }
            const uint32_t ua = UB + (mi & 1) * U_PL + (8 + 8 * (mi >> 1) + r) * 16;
#pragma unroll 1
            for (int k0 = 0; k0 < 8; k0++) {
                uint32_t Uf[16][2];
#pragma unroll
                for (int jp = 0; jp < 8; jp++) ldsm4(ua + jp * 256 - k0 * 16, Uf[2 * jp][0], Uf[2 * jp][1], Uf[2 * jp + 1][0], Uf[2 * jp + 1][1]);
#pragma unroll
                for (int k1 = 0; k1 < 4; k1++) {
                    const uint32_t ta = tabD + 16 * (8 * k1 + k0);
                    const uint32_t a0 = lds32(ta), a1 = lds32(ta + 8), a2 = lds32(ta - 8), a3 = a0 ^ p.zero;
#pragma unroll
                    for (int J = k1; J < 16; J++) mma_bf(D[J], a0, a1, a2, a3, Uf[J - k1][0], Uf[J - k1][1]);
                }
                if (k0 == 0) {
                    const uint32_t ta = tabD + 16 * 32;
                    const uint32_t a0 = lds32(ta), a1 = lds32(ta + 8), a2 = lds32(ta - 8), a3 = a0 ^ p.zero;
#pragma unroll
                    for (int J = 4; J < 16; J++) mma_bf(D[J], a0, a1, a2, a3, Uf[J - 4][0], Uf[J - 4][1]);
                    const uint32_t f0 = (cfix ^ 0x80008000u) & (g == t ? 0xffffu : g == t + 4 ? 0xffff0000u : 0u);
                    const uint32_t f1 = p.zero, f2 = p.zero + p.zero, f3 = f0 ^ p.zero;
#pragma unroll
                    for (int J = 8; J < 16; J++) mma_bf(D[J], f0, f1, f2, f3, Uf[J - 8][0], Uf[J - 8][1]);
                }
            }
        }
        WSTAMP(3);
        {
            const int ch = 8 * h + warp;
            const uint32_t yo = sb + ch * 512 + ((lane ^ (((ch >> 2) << 1) | (ch & 1))) << 4);
            const uint32_t yr = mapa(yo, h ^ 1), ybr = mapa(bars + 8 * B_Y, h ^ 1);
            auto ship = [&](const int Q) {
                uint4 y[2];
#pragma unroll
                for (int hh = 0; hh < 2; hh++) {
                    const int J = 4 * Q + 2 * hh;
                    y[hh] = make_uint4(pack_bf(D[J][0], D[J][1]), pack_bf(D[J][2], D[J][3]), pack_bf(D[J + 1][0], D[J + 1][1]), pack_bf(D[J + 1][2], D[J + 1][3]));
                }
                if (!(Q & 1)) mbar_wait(bars + 8 * (B_F + (Q >> 1)));
                asm volatile("{\n\t.reg .pred p;\n\tsetp.eq.u32 p, %11, 0;\n\t"
                             "@p st.async.weak.shared::cluster.mbarrier::complete_tx::bytes.v4.b32 [%9], {%4,%5,%6,%7}, [%10];\n\t"
                             "@!p st.async.weak.shared::cluster.mbarrier::complete_tx::bytes.v4.b32 [%9], {%0,%1,%2,%3}, [%10];\n\t"
                             "@p st.shared.v4.b32 [%8], {%0,%1,%2,%3};\n\t@!p st.shared.v4.b32 [%8], {%4,%5,%6,%7};\n\t}"
                             :: "r"(y[0].x), "r"(y[0].y), "r"(y[0].z), "r"(y[0].w), "r"(y[1].x), "r"(y[1].y), "r"(y[1].z), "r"(y[1].w),
                                "r"(yo + y_off(Q)), "r"(yr + y_off(Q)), "r"(ybr + 8 * Q), "r"(h) : "memory");
                __syncwarp();
                if (lane == 0) mbar_arrive(bars + 8 * (B_Y + Q));
            };
            ship(0);
            const uint4 bA = lds128(sb + OFF_BAND + (g - t + 3) * 48), bB = lds128(sb + OFF_BAND + (g - t + 3) * 48 + 16);
            const uint2 bC = lds64(sb + OFF_BAND + (g - t + 3) * 48 + 32);
            uint2 QA[5][2], QB[8];
            const uint32_t tq = TB + 8 * (1 + g - 2 * t);
#pragma unroll
            for (int dd = 0; dd < 5; dd++) { QA[dd][0] = lds64(tq + T_A + 64 * (dd + 4)); QA[dd][1] = lds64(tq + T_A + 64 * (dd + 4) - 8); }
#pragma unroll
            for (int dd = 0; dd < 8; dd++) QB[dd] = lds64(tq + T_B + 64 * (dd + 8));
            const uint32_t u1 = UB + (mi & 1) * U_PL + (7 + r + (mi >> 1)) * 16;
            const uint32_t u2 = UB + ((mi & 1) ^ 1) * U_PL + (7 + r + (mi & 1) + 8 * (mi >> 1)) * 16;
            uint32_t n[4];
#pragma unroll
            for (int j = 0; j < 12; j++) {
                uint32_t m[4];
                ldsm4(u1 + j * 128, m[0], m[1], m[2], m[3]);
                if (!(j & 1)) ldsm4(u2 + j * 128, n[0], n[1], n[2], n[3]);
                const uint32_t n0 = n[2 * (j & 1)], n1 = n[2 * (j & 1) + 1];
                float wa[4], wb[4], wc[4], g1[4], g2[4];
                mma_bf_z(wa, bA.x, bA.y, bA.z, bA.w, m[0], m[1]);
                mma_bf_z(wb, bA.x, bA.y, bA.z, bA.w, n0, n1);
                mma_bf_z(wc, bA.x, bA.y, bA.z, bA.w, m[2], m[3]);
                if (j < 8) {
                    mma_bf_z(g1, bB.x, bB.y, bB.z, bB.w, m[0], m[1]);
                    mma_bf_z(g2, bB.x, bB.y, bB.z, bB.w, n0, n1);
                    mma_bf_k8(g1, bC.x, bC.y, m[2]);
                    mma_bf_k8(g2, bC.x, bC.y, m[3]);
                }
#pragma unroll
                for (int e = 0; e < 2; e++) {
                    const uint32_t q0 = pack_bf(wa[e], wa[e + 2]), q1 = pack_bf(wb[e], wb[e + 2]), q2 = q1 ^ p.zero, q3 = pack_bf(wc[e], wc[e + 2]);
#pragma unroll
                    for (int dd = 0; dd < 5; dd++)
                        if (j + 4 + dd < 16) mma_bf(D[j + 4 + dd], q0, q1, q2, q3, QA[dd][e].x, QA[dd][e].y);
                }
                if (j < 8) {
                    const uint32_t q0 = pack_bf(g1[0], g1[2]), q1 = pack_bf(g2[0], g2[2]), q2 = pack_bf(g1[1], g1[3]), q3 = pack_bf(g2[1], g2[3]);
#pragma unroll
                    for (int dd = 7 - j; dd >= 0; dd--) mma_bf(D[j + 8 + dd], q0, q1, q2, q3, QB[dd].x, QB[dd].y);
                }
                if ((j & 3) == 3) {
                    WSTAMP(4 + 2 * (j >> 2));
                    ship((j >> 2) + 1);
                }
            }
        }
        const int warpu = __reduce_max_sync(0xffffffffu, warp);
        mix_rows<1>(p, &tm_out, sb, sb + OFF_U + warpu * U_CH + (warpu & 1) * 64, PQ, 4, warpu, h, pr, lane);
        asm volatile("cp.async.bulk.commit_group;\n\tcp.async.bulk.wait_group.read 0;" ::: "memory");
        WSTAMP(10);
        WDUMP();
    } else if ((pw & 12) == AUX_W0) {
        const int v = __reduce_max_sync(0xffffffffu, pw & 3);
        const int at = tid & 127;
        const int g = lane >> 2, t = lane & 3;
        unsigned tag;
        const bool gu = c < NGU_CTA;
        {
            const uint32_t xb = sb + (v < 2 ? OFF_XSEL : OFF_RING + 2 * 8192) + v * 8192;
            const uint32_t gws = sb + M_DPIN;
            const uint32_t row = 16 * c + 4 * v + (g >> 1);
#pragma unroll
            for (int i = 0; i < 8; i++)
                asm volatile("cp.async.ca.shared.global [%0], [%1], 4;" :: "r"((i < 4 ? sb + OFF_GP : gws) + 512 * (i & 3) + (tid & 124) * 4 + (tid & 1) * 8 + (tid & 2) * 2),
                             "l"((i < 4 ? p.wr : p.gatew) + 256 * (i & 3) + (tid & 127) * 2) : "memory");
            if ((tid & 127) < 33) cp16(sb + OFF_BAND + (tid & 127) * 16, p.band + (tid & 127));
            asm volatile("barrier.cluster.arrive.relaxed.aligned;" ::: "memory");
            tag = __reduce_max_sync(0xffffffffu, (*(volatile unsigned*)&p.sc->epoch + 1) & 0xffffu);
            if (gu) st_gpu32((uint32_t*)&p.sc->h[(tag + 1) & 1][32 * c] + at, 0);
            if (v == 2) sts32(sb + M_BMAP + lane * 4, 0);
            if (at == 0) sts32(sb + M_TAG, tag << 16);
            cp_wait_all();
            bar_sync(1, 128);
            uint2 w[16];
#pragma unroll
            for (int kb = 0; kb < 16; kb++) w[kb] = lds64((g < 4 ? sb + OFF_GP : gws) + 128 * kb + 32 * (g & 2) + 16 * t + 8 * (g & 1));
            asm volatile("barrier.cluster.wait.acquire.aligned;" ::: "memory");
            mbar_wait(bars + 8 * (B_X + v));
            WSTAMP(10);
            float dr[4][4];
#pragma unroll
            for (int kb = 0; kb < 16; kb++) {
                const uint4 x = lds128(xb + (g >> 1) * 2048 + 128 * kb + 16 * (lane & 7));
                if (kb < 4) mma_bf_z(dr[kb], x.x, x.y, x.z, x.w, w[kb].x, w[kb].y);
                else mma_bf(dr[kb & 3], x.x, x.y, x.z, x.w, w[kb].x, w[kb].y);
            }
            float rs = ((dr[0][0] + dr[0][3]) + (dr[1][0] + dr[1][3])) + ((dr[2][0] + dr[2][3]) + (dr[3][0] + dr[3][3]));
            if (lane == 0) mbar_arrive(bars + 8 * (B_XE + v) + (__float_as_uint(rs) & p.zero));
            rs += __shfl_xor_sync(0xffffffffu, rs, 5);
            const uint32_t rb = pack_bf(0.f, rs);
            if (!(lane & 7)) st_gpu32((uint32_t*)p.sc->r + row, ((rb ^ (((int)rb >> 31) | 0x80000000u)) & 0xffff0000u) | tag);
            WSTAMP(1);
            {
                const int n = 3 + (lane >> 3) + 4 * (lane & 1);
                const uint32_t so = (n & 7) * S_PL + ((lane & 6) + (n >> 3)) * 32;
                const uint32_t src[2] = {sb + OFF_S + v * S_Q + s_addr(so, h), sb + OFF_S + v * S_Q + s_addr(so + 32, h)};
                const uint32_t dst = sb + OFF_U + g * U_CH + (8 + 32 * v + 16 * h + t) * 16;
                const uint32_t rdst = mapa(dst, h ^ 1), rbar = mapa(bars + 8 * B_U, h ^ 1);
                mbar_wait(bars + 8 * (B_S + v));
                WSTAMP(9);
                uint4 a[8];
#pragma unroll
                for (int b = 0; b < 2; b++) {
#pragma unroll
                    for (int j = 0; j < 8; j++) { const int u = 4 * b + (j >> 1) + 8 * (j & 1); ldsm4t((u < 8 ? src[u & 1] ^ 16 : src[u & 1]) + ((u >> 1) & 3) * 256, a[j].x, a[j].y, a[j].z, a[j].w); }
#pragma unroll
                    for (int j = 0; j < 8; j++) {
                        const int u = 4 * b + (j >> 1) + 8 * (j & 1);
                        if (u < 8) st_async16(rdst + ((u >> 1) & 3) * 64 + (u & 1) * U_PL, a[j], rbar);
                        else sts128(dst + ((u >> 1) & 3) * 64 + (u & 1) * U_PL, a[j].x, a[j].y, a[j].z, a[j].w);
                    }
                }
                if (h && v == 3) {
                    ldsm4t((src[0] ^ 16) + 1024, a[0].x, a[0].y, a[0].z, a[0].w);
                    ldsm4t(src[0] + 1024, a[1].x, a[1].y, a[1].z, a[1].w);
                    if (t == 0) {
                        st_async16(rdst + 256, make_uint4(a[0].x, a[0].y & 0xffffu, a[0].z & 0xffffu, a[0].w & 0xffffu), rbar);
                        sts128(dst + 256, a[1].x, a[1].y & 0xffffu, a[1].z & 0xffffu, a[1].w & 0xffffu);
                    }
                }
                __syncwarp();
                if (lane == 0) mbar_arrive(bars + 8 * B_U);
            }
            if ((lane & 7) == 2) st_gpu32((uint32_t*)p.sc->g + ((row & 256) << 2) + gate_pos(row), pack_bf(sigmoid_f(__uint_as_float(rb)), 0.f) | (tag << 16));
            WSTAMP(2);
        }
        {
            const bool lane0 = pin(lane, lane) == 0;
            const uint32_t own = pin(sb + OFF_XSEL + (at ^ ((at >> 1) & 4)) * 16, lane);
            float acc[8][4];
            const int krow = ((lane >> 1) & 8) + (lane & 7);
            const uint32_t tile0 = pin(sb + OFF_RING + v * 8192 + krow * 64 + ((((lane >> 3) & 1) ^ ((krow >> 1) & 3)) << 4), lane);
            const uint32_t xo = pin(sb + OFF_XSEL + (lane & 7) * XS_ROW + 512 * v + 2 * (lane & 24), lane);
            const uint32_t po = pin(sb + OFF_XSEL + t * XS_ROW + (g & 3) * 128 + (g & 1) * 64 + v * 16 + (lane >> 4) * 8, lane);
            const uint32_t po1 = pin(po + 64 - (g & 1) * 128, lane);
            uint32_t* hdst = pin((uint32_t*)&p.sc->h[tag & 1][32 * c] + at, lane);
            auto signal = [&](const int k, const uint32_t dep) {
                if (lane < 2 && v < 2)
                    asm volatile("st.async.weak.shared::cluster.mbarrier::complete_tx::bytes.b32 [%0], %1, [%2];"
                                 :: "r"(mapa(sb + M_SINK, lane)), "r"(dep), "r"(mapa(bars + 8 * (B_F + k), lane)) : "memory");
            };
            uint32_t a[16][4], b[2][4];
            auto load_a = [&](const uint32_t tile) {
#pragma unroll
                for (int q = 0; q < 16; q++) ldsm4t((tile ^ ((q & 1) << 5)) + ((q >> 1) & 1) * 4096 + (q >> 2) * 1024, a[q][0], a[q][1], a[q][2], a[q][3]);
            };
            auto load_b = [&](const uint32_t x) { ldsm4(x, b[0][0], b[0][1], b[0][2], b[0][3]); ldsm4(x + 64, b[1][0], b[1][1], b[1][2], b[1][3]); };
            auto burst = [&](const bool first) {
#pragma unroll
                for (int q = 0; q < 16; q++) {
                    if (first && q < 8) mma_bf_z(acc[q], a[q][0], a[q][1], a[q][2], a[q][3], b[0][(q >> 1) & 2], b[0][((q >> 1) & 2) + 1]);
                    else mma_bf(acc[q & 7], a[q][0], a[q][1], a[q][2], a[q][3], b[q >> 3][(q >> 1) & 2], b[q >> 3][((q >> 1) & 2) + 1]);
                }
            };
            if (gu) {
                mbar_wait(bars + 8 * (B_W + v));
                load_a(tile0);
                uint32_t dep = p.zero;
#pragma unroll
                for (int q = 0; q < 16; q += 2) dep &= a[q][0] & a[q + 1][0];
                if (lane == 0) mbar_arrive(bars + 8 * (B_E + v) + dep);
            }
            WSTAMP(11);
            uint32_t top;
#pragma unroll 1
            for (int it = 0; it < (1 << 22); it++) {
                asm volatile("ld.relaxed.gpu.global.u32 %0, [%1];" : "=r"(top) : "l"(&p.sc->top[c % NTOP][g]) : "memory");
                if (__all_sync(0xffffffffu, ((top ^ (tag << 11)) & 0xf800u) == 0)) break;
                __nanosleep(40);
            }
            WSTAMP(3);
            if (gu) {
                const uint32_t k = 4 * h + v, row = __reduce_max_sync(0xffffffffu, lane == 4 * k ? ~top & 2047 : 0);
                asm volatile("{\n\t.reg .pred p;\n\telect.sync _|p, 0xffffffff;\n\t"
                             "@p cp.async.bulk.shared::cluster.global.mbarrier::complete_tx::bytes.multicast::cluster [%0], [%1], 2048, [%2], %3;\n\t}"
                    :: "r"(sb + OFF_XSEL + k * XS_ROW), "l"(p.u + (size_t)row * D_), "r"(bars + 8 * B_G), "h"((unsigned short)3) : "memory");
            }
            if (v == 2) {
                const uint32_t row = ~top & 2047;
                if (t == 0 && ((row >> 8) & 1) == h)
                    asm volatile("red.shared.or.b32 [%0], %1;" :: "r"(sb + M_BMAP + (row & 7) * 16 + (row >> 9) * 4), "r"(1u << (gate_pos(row) & 31)) : "memory");
                if (t == 0) sts32(sb + M_TOP + lane, top);
                if (c == 0 && lane == 0) *(volatile unsigned*)&p.sc->epoch = tag;
                __syncwarp();
                if (lane0) mbar_arrive(bars + 8 * B_Y);
            }
            if (gu) {
                mbar_wait(bars + 8 * B_G);
                WSTAMP(4);
                load_b(xo);
                burst(true);
#pragma unroll
                for (int i = 1; i < 4; i++) {
                    mbar_wait(bars + 8 * (B_W + 4 * i + v));
                    load_b(xo + 128 * i);
                    load_a(tile0 + (4 * i + v < 14 ? i : 0) * 32768);
                    if (lane0 && i > 1) mbar_arrive(bars + 8 * (B_E + 4 * i - 4 + v));
                    if (i == 2) signal(0, 0);
                    sched_fence();
                    burst(false);
                    sched_fence();
                }
                WSTAMP(5);
                __syncwarp();
#pragma unroll
                for (int q = 0; q < 4; q++) {
                    const int ct = q >> 1, e = 2 * (q & 1);
                    sts128(own + q * XS_ROW,
                           __float_as_uint(acc[ct][e] + acc[4 + ct][e]), __float_as_uint(acc[2 + ct][e] + acc[6 + ct][e]),
                           __float_as_uint(acc[ct][e + 1] + acc[4 + ct][e + 1]), __float_as_uint(acc[2 + ct][e + 1] + acc[6 + ct][e + 1]));
                }
                bar_sync(1, 128);
                float sl[2], uv[2];
#pragma unroll
                for (int e = 0; e < 2; e++) {
                    uint2 q[4];
#pragma unroll
                    for (int i = 0; i < 4; i++) q[i] = lds64((e ? po1 : po) + 512 * i);
                    const float s0 = (__uint_as_float(q[0].x) + __uint_as_float(q[1].x)) + (__uint_as_float(q[2].x) + __uint_as_float(q[3].x));
                    const float s1 = (__uint_as_float(q[0].y) + __uint_as_float(q[1].y)) + (__uint_as_float(q[2].y) + __uint_as_float(q[3].y));
                    const float gv = bf_round(p.gu_swap ? s1 : s0);
                    uv[e] = p.gu_swap ? s0 : s1;
                    sl[e] = gv * sigmoid_f(gv);
                }
                const uint32_t hw = hmul2_bf(pack_bf(sl[0], sl[1]), pack_bf(uv[0], uv[1]));
                st_gpu32(hdst, hw ? hw : 0x80000000u);
                signal(1, hw);
            }
        }
        WSTAMP(6);
        {
            const uint32_t own = pin(sb + OFF_XSEL + at * 16, lane);
            const uint32_t hb = sb + (v < 2 ? OFF_XSEL + 7168 * v : OFF_RING + 8192 * v), hl = pin(hb + 16 * lane, lane);
            const int krow = ((lane >> 1) & 8) + (lane & 7);
            const uint32_t tile = pin(sb + OFF_RING + v * 8192 + krow * 32 + ((((lane >> 3) ^ (krow >> 2)) & 1) << 4), lane);
            float dd[4][4];
            bar_sync(1, 128);
            mbar_wait(bars + 8 * (B_W + HW));
            WSTAMP(12);
            uint4 hq[7];
            {
                const uint4* hs = &p.sc->h[tag & 1][32 * (56 * h + 14 * v)];
                bulk_load(hb, hs, 3584, bars + 8 * (B_X + v));
                bulk_load(hb + 3584, hs + 224, 3584, bars + 8 * (B_XE + v));
                uint32_t a[14][4];
                mbar_wait(bars + 8 * (B_W + 16 + v));
#pragma unroll
                for (int j = 0; j < 14; j++) ldsm4t(tile + (v & 2) * 16384 + j * 512, a[j][0], a[j][1], a[j][2], a[j][3]);
#pragma unroll
                for (int k = 0; k < 2; k++) {
                    mbar_wait(bars + 8 * ((k ? B_XE : B_X) + v), 1);
                    if (!k) WSTAMP(7);
                    uint32_t mn = 0xffffffffu;
#pragma unroll
                    for (int j = 0; j < 7; j++) { hq[j] = lds128(hl + 3584 * k + 512 * j); mn = min(mn, hq[j].x); }
#pragma unroll 1
                    for (int it = 0; it < (1 << 20) && !__all_sync(0xffffffffu, mn != 0); it++) {
                        mn = 0xffffffffu;
#pragma unroll
                        for (int j = 0; j < 7; j++)
                            asm volatile("{\n\t.reg .pred p;\n\tsetp.eq.u32 p, %0, 0;\n\t@p ld.relaxed.gpu.global.v4.u32 {%0,%1,%2,%3}, [%4];\n\t}"
                                         : "+r"(hq[j].x), "+r"(hq[j].y), "+r"(hq[j].z), "+r"(hq[j].w) : "l"(hs + 224 * k + 32 * j + lane) : "memory");
#pragma unroll
                        for (int j = 0; j < 7; j++) mn = min(mn, hq[j].x);
                    }
                    if (!k) {
#pragma unroll
                        for (int j = 0; j < 14; j++) {
                            const uint4& q = hq[j >> 1];
                            if (j < 4) mma_bf_z(dd[j], a[j][0], a[j][1], a[j][2], a[j][3], (j & 1) ? q.z : q.x, (j & 1) ? q.w : q.y);
                            else mma_bf(dd[j & 3], a[j][0], a[j][1], a[j][2], a[j][3], (j & 1) ? q.z : q.x, (j & 1) ? q.w : q.y);
                        }
                    }
                }
            }
            mbar_wait(bars + 8 * (B_W + 20 + v));
#pragma unroll
            for (int j = 0; j < 14; j++) {
                uint32_t f[4];
                ldsm4t(tile + 65536 + j * 512, f[0], f[1], f[2], f[3]);
                mma_bf(dd[(j + 2) & 3], f[0], f[1], f[2], f[3], (j & 1) ? hq[j >> 1].z : hq[j >> 1].x, (j & 1) ? hq[j >> 1].w : hq[j >> 1].y);
            }
            WSTAMP(8);
            uint4 part;
            part.x = __float_as_uint((dd[0][0] + dd[1][0]) + (dd[2][0] + dd[3][0])); part.y = __float_as_uint((dd[0][1] + dd[1][1]) + (dd[2][1] + dd[3][1]));
            part.z = __float_as_uint((dd[0][2] + dd[1][2]) + (dd[2][2] + dd[3][2])); part.w = __float_as_uint((dd[0][3] + dd[1][3]) + (dd[2][3] + dd[3][3]));
            st_async16(mapa(own + (M_DPIN - OFF_XSEL), h ^ 1), part, mapa(bars + 8 * B_DP, h ^ 1));
            sts128(own + 14336, part.x, part.y, part.z, part.w);
            __syncwarp();
            if (lane == 0) mbar_arrive(bars + 8 * B_DP);
        }
        WDUMP();
    } else {
        asm volatile("setmaxnreg.dec.sync.aligned.u32 64;");
        const int v = __reduce_max_sync(0xffffffffu, pw - PREP_W0);
        const bool gu = c < NGU_CTA;
        const uint32_t t0 = clock();
        const uint32_t bu = bars + 8 * v;
        if (lane == 0) { mbar_init(bu + 8 * B_X, 1); mbar_init(bu + 8 * B_S, 1); }
        __syncwarp();
        while ((uint32_t)clock() - t0 < TX) {}
        bulk_load(sb + (v < 2 ? OFF_XSEL : OFF_RING + 2 * 8192) + v * 8192, p.u + (size_t)(16 * c + 4 * v) * D_, 8192, bu + 8 * B_X);
        tma3d(sb + OFF_S + v * S_Q, &tm_x, 16 * pr, 64 * v + 32 * h - 1, bars + 8 * (B_S + v), S_Q);
        if (lane == 0) {
#pragma unroll
            for (int i = 0; i < 9; i++) mbar_init(bu + 32 * i, 1);
            mbar_init(bu + 8 * B_XE, 1);
            mbar_init(bu + 8 * B_Y, v == 0 ? 11 : 9);
            mbar_init(bu + 8 * B_DP, (0x1855 >> (4 * v)) & 15);
            mbar_init(bu + 8 * B_F, 1);
            mbar_init(bu + 8 * B_H, 1);
            asm volatile("fence.mbarrier_init.release.cluster;" ::: "memory");
            mbar_expect(bu + 8 * B_Y, 4096);
            if (v != 2) mbar_expect(bu + 8 * B_DP, v == 0 ? 2048 : (h || v == 3) ? 16384 : 16384 + 128);
            mbar_expect(bu + 8 * B_F, c < NGU_CTA ? 16 : 0);
        }
        __syncwarp();
        asm volatile("barrier.cluster.arrive.relaxed.aligned;" ::: "memory");
        WSTAMP(9);
        if (v < 3 && lane == 0) asm volatile("prefetch.tensormap [%0];" :: "l"(v == 0 ? &tm_gu : v == 1 ? &tm_down : &tm_out) : "memory");
        asm volatile("barrier.cluster.wait.acquire.aligned;" ::: "memory");
        uint32_t desc;
        {
            const int s = 6 * v + lane, i = s >> 2, w = s & 3, slot = s < 14 ? s : (s | 1) == 17 ? s - 16 : s - 12;
            const int fb = s < 4 ? B_H : (gu && s >= 14) ? B_E + slot : s < 6 ? B_XE + s - 2 : B_KG;
            desc = slot | (fb << 4) | ((i < 4 ? 256 * w + 64 * i : 1792 * h + 448 * w + 224 * (i - 4)) << 10);
            if (lane < 6) mbar_expect(bars + 8 * (B_W + s), i < 4 ? 8192 : 7168);
            if (tid == 32 * PREP_W0) mbar_arrive(bars + 8 * B_H);
        }
        if (v == 3) {
            mbar_wait(bars + 8 * B_U);
            mbar_wait(bars + 8 * (gu ? B_G : B_H + 2));
            const uint32_t tag16 = lds32(sb + M_TAG);
            uint4 q[8];
#pragma unroll 1
            for (int it = 0; it < (1 << 22); it++) {
                uint32_t bad = 0;
#pragma unroll
                for (int i = 0; i < 8; i++) q[i] = ld_gpu128(&p.sc->g[256 * h + 32 * i + lane]);
#pragma unroll
                for (int i = 0; i < 8; i++) bad |= ((q[i].x ^ tag16) | (q[i].y ^ tag16)) | ((q[i].z ^ tag16) | (q[i].w ^ tag16));
                if ((bad >> 16) == 0) break;
                __nanosleep(200);
            }
#pragma unroll
            for (int i = 0; i < 8; i++)
                asm volatile("st.shared.v2.u32 [%0], {%1, %2};" :: "r"(sb + OFF_GP + 256 * i + lane * 8),
                             "r"(__byte_perm(q[i].x, q[i].y, 0x5410)), "r"(__byte_perm(q[i].z, q[i].w, 0x5410)) : "memory");
            __syncwarp();
            if (lane == 0) mbar_arrive(bars + 8 * B_Y);
        }
        mbar_wait(bars + 8 * (B_H + v));
        {
            const int gap = v == 0 ? GAP : v == 1 ? GAP1 : v == 2 ? GAP2 : GAP3;
            uint32_t last = v ? clock() - SLACK : t0 + T0 - GAP + GAP * ((pr * 5) & 15) / 16;
#pragma unroll 1
            for (int k = 0; k < 6; k++) {
                const uint32_t dk = __reduce_max_sync(0xffffffffu, lane == k ? desc : 0);
                const bool dn = 6 * v + k >= 16;
                const uint32_t dst = sb + OFF_RING + (dk & 15) * 8192, bar = bars + 8 * (B_W + 6 * v + k), c0 = dn ? 16 * pr : 32 * c, c1 = dk >> 10;
                const CUtensorMap* tm = dn ? &tm_down : &tm_gu;
                mbar_wait(bars + ((dk >> 1) & 0x1f8));
                int late;
#pragma unroll 1
                while ((late = (int)(clock() - last) - gap) < 0) __nanosleep(max(-late >> 2, 32));
                WSTAMP(3 + k);
                if (gu || dn)
                    asm volatile("{\n\t.reg .pred p;\n\telect.sync _|p, 0xffffffff;\n\t"
                                 "@p cp.async.bulk.tensor.3d.shared::cluster.global.mbarrier::complete_tx::bytes [%0], [%1, {%3, %4, 0}], [%2];\n\t}"
                        :: "r"(dst), "l"(tm), "r"(bar), "r"(c0), "r"(c1) : "memory");
                last += gap + max(late - SLACK, 0);
            }
            if (lane == 0 && v < 3) mbar_arrive(bars + 8 * (B_H + v + 1));
        }
        {
            WSTAMP(1);
            mix_rows<2>(p, &tm_out, sb, sb + OFF_TAB + v * TAB_W, 0, PQ, v, h, pr, lane);
            WSTAMP(2);
            asm volatile("cp.async.bulk.commit_group;" ::: "memory");
            const uint32_t top = lds32(sb + M_TOP + 8 * v + 4 * (lane >> 4));
            const uint32_t row = ~top & 2047, ch = lane & 15, gp = gate_pos(row);
            const bool mine = ((row >> 8) & 1) == h;
            uint32_t gfin, x16, y16 = 0;
            asm volatile("ld.shared.u16 %0, [%1];" : "=r"(gfin) : "r"(sb + OFF_GP + gp * 2) : "memory");
            asm volatile("ld.shared.u16 %0, [%1];" : "=r"(x16) : "r"(sb + OFF_S + (row >> 9) * S_Q + s_addr((row & 7) * S_PL + 32 + (row & 248) * 4, ch >> 3) + 2 * (ch & 7)) : "memory");
            const float rsel = __uint_as_float(pin(__float_as_uint(bf_round(sigmoid_f(__uint_as_float((top ^ (((int)~top >> 31) | 0x80000000u)) & 0xffff0000u)))), lane));
            const uint32_t po = pin(sb + (4 * (ch & 7) + v) * 16 + (ch >> 3) * 8 + (lane >> 4) * 4, lane);
            bf16* op = pin(p.out + (size_t)row * D_ + 16 * pr + ch, lane);
            if (mine) {
                mbar_wait(bars + 8 * (B_Y + (row >> 9)));
                asm volatile("ld.shared.u16 %0, [%1];" : "=r"(y16)
                             : "r"(sb + y_off(row >> 9) + ch * 512 + (((4 * (row & 7) + ((row >> 5) & 3)) ^ (((ch >> 2) << 1) | (ch & 1))) << 4) + 2 * row_elem(row)) : "memory");
            }
            mbar_wait(bars + 8 * B_DP);
            float q[8];
#pragma unroll
            for (int i = 0; i < 4; i++) { q[i] = ldsf(po + M_DPIN + 512 * i); q[4 + i] = ldsf(po + OFF_XSEL + 14336 + 512 * i); }
            const float tot = ((q[0] + q[1]) + (q[2] + q[3])) + ((q[4] + q[5]) + (q[6] + q[7]));
            const float b = bf_round(__uint_as_float(x16 << 16) + bf_round(bf_round(tot) * rsel));
            if (mine) *op = __float2bfloat16_rn(fmaf(bf_lo(gfin), __uint_as_float(y16 << 16), bf_round(bf_round(1.f - bf_lo(gfin)) * b)));
        }
        asm volatile("cp.async.bulk.wait_group.read 0;" ::: "memory");
        WSTAMP(10);
        WDUMP();
    }
}

typedef CUresult (*EncodeFn)(CUtensorMap*, CUtensorMapDataType, cuuint32_t, void*, const cuuint64_t*, const cuuint64_t*,
                             const cuuint32_t*, const cuuint32_t*, CUtensorMapInterleave, CUtensorMapSwizzle,
                             CUtensorMapL2promotion, CUtensorMapFloatOOBfill);

void make_map(EncodeFn f, CUtensorMap* m, const void* ptr, uint64_t cols, uint64_t rows, uint64_t pitch, uint32_t bc, uint32_t br, CUtensorMapSwizzle sw, CUtensorMapL2promotion prom,
              uint32_t planes = 1, uint64_t plane_stride = 0, uint32_t box_planes = 0) {
    cuuint64_t dims[3] = {cols, rows, planes};
    cuuint64_t str[2] = {pitch, planes > 1 ? plane_stride : pitch * rows};
    cuuint32_t box[3] = {bc, br, box_planes ? box_planes : planes};
    cuuint32_t es[3] = {1, 1, 1};
    f(m, CU_TENSOR_MAP_DATA_TYPE_BFLOAT16, 3, (void*)ptr, dims, str, box, es, CU_TENSOR_MAP_INTERLEAVE_NONE, sw,
      prom, CU_TENSOR_MAP_FLOAT_OOB_FILL_NONE);
}

}

extern "C" void kernel_launch(void* const* d_in, const int* in_sizes, int n_in, void* d_out, int out_size) {
    static EncodeFn enc = nullptr;
    static void *sc = nullptr, *band = nullptr;
    if (!enc) {
        void* fn = nullptr;
        cudaDriverEntryPointQueryResult qr;
        cudaGetDriverEntryPoint("cuTensorMapEncodeTiled", &fn, cudaEnableDefault, &qr);
        enc = (EncodeFn)fn;
        cudaGetSymbolAddress(&sc, g_scratch);
        cudaGetSymbolAddress(&band, g_band);
        cudaFuncSetAttribute(fused_kernel, cudaFuncAttributeMaxDynamicSharedMemorySize, SMEM_BYTES);
    }
    CUtensorMap tg, td, tx, to;
    const char *wg = (const char*)d_in[9], *wu = (const char*)d_in[10];
    const bool swap = wu < wg;
    make_map(enc, &tg, swap ? wu : wg, F_, D_, F_ * 2, 32, 64, CU_TENSOR_MAP_SWIZZLE_64B, CU_TENSOR_MAP_L2_PROMOTION_L2_128B, 2, swap ? wg - wu : wu - wg);
    make_map(enc, &td, d_in[11], D_, F_, D_ * 2, 16, 224, CU_TENSOR_MAP_SWIZZLE_32B, CU_TENSOR_MAP_L2_PROMOTION_L2_64B);
    make_map(enc, &tx, d_in[0], D_, L_ / 8, D_ * 16, 16, 33, CU_TENSOR_MAP_SWIZZLE_32B, CU_TENSOR_MAP_L2_PROMOTION_NONE, 8, D_ * 2);
    make_map(enc, &to, d_out, D_, L_ / 8, D_ * 16, 16, 32, CU_TENSOR_MAP_SWIZZLE_NONE, CU_TENSOR_MAP_L2_PROMOTION_NONE, 8, D_ * 2, 1);
    Params p;
    p.u = (const bf16*)d_in[0]; p.logA = (const bf16*)d_in[1]; p.Aim = (const bf16*)d_in[2];
    p.Cre = (const bf16*)d_in[3]; p.Cim = (const bf16*)d_in[4]; p.logdt = (const bf16*)d_in[5];
    p.Dskip = (const bf16*)d_in[6]; p.wr = (const bf16*)d_in[8]; p.gatew = (const bf16*)d_in[12];
    p.out = (bf16*)d_out;
    p.sc = (Scratch*)sc; p.band = (const uint4*)band;
    p.gu_swap = swap;
    p.zero = 0;
    fused_kernel<<<NCTA, NTHREADS, SMEM_BYTES>>>(p, tg, td, tx, to);
}
```

```cpp
#include <cuda_runtime.h>
#include <cuda_bf16.h>
#include <cuda_fp16.h>
#include <cuda.h>
#include <stdint.h>

typedef __nv_bfloat16 bf16;

namespace {

constexpr int L_ = 2048, D_ = 1024, F_ = 3584;
constexpr int NCTA = 130;
constexpr int NTHREADS = 512;
constexpr int MAIN_W0 = 0, PREP_W0 = 8, AUX_W0 = 12;
#define TX 150
#define TR 3300
#define T0 3080
#define GAP 510
#define GAP1 515
#define GAP2 515
#define GAP3 560
#define HW 20
constexpr int SLACK = 300;
constexpr int PQ = 3;
constexpr int NGU_CTA = 112;

constexpr int OFF_RING = 0;
constexpr int OFF_SCR  = 6 * 8192;
constexpr int S_PL     = 1056;
constexpr int S_Q      = 8 * S_PL;
constexpr int OFF_S    = 114688;
constexpr int OFF_GP   = OFF_S + 4 * S_Q;
constexpr int U_PL     = 2240;
constexpr int U_CH     = 4416;
constexpr int OFF_U    = 151552;
constexpr int TAB_W    = 3200;
constexpr int T_PL     = 544;
constexpr int T_A      = 2192 - 26 * 8;
constexpr int T_B      = 2568 - 59 * 8;
constexpr int OFF_TAB  = 186880;
constexpr int OFF_XSEL = 212480;
constexpr int XS_ROW   = 2064;
constexpr int OFF_BAND = 228992;
constexpr int OFF_MISC = 229536;
constexpr int M_BARS   = OFF_MISC;
constexpr int M_DSK    = OFF_MISC + 2736;
constexpr int M_SINK   = OFF_MISC + 512;
constexpr int M_TAG    = OFF_MISC + 516;
constexpr int M_BMAP   = OFF_MISC + 528;
constexpr int M_DPIN   = OFF_MISC + 656;
constexpr int M_TOP    = OFF_MISC + 2704;
constexpr int SMEM_BYTES = OFF_MISC + 2768;
__device__ __forceinline__ uint32_t s_addr(uint32_t o, uint32_t half) { return o + (((half ^ (o >> 7)) & 1) << 4); }
__host__ __device__ constexpr uint32_t y_off(uint32_t q) { return OFF_RING + 32768 + (q & 1) * 8192 + (q >> 1) * 65536; }

constexpr int B_W = 0;
constexpr int B_E = 24;
constexpr int B_S = 36;
constexpr int B_Y = 40;
constexpr int B_DP = 44, B_U = 45, B_KG = 46, B_G = 47;
constexpr int B_F = 48;
constexpr int B_H = 60;
constexpr int B_X = 52, B_XE = 56;

struct BandTab { uint32_t w[11][12]; };
constexpr BandTab make_band() {
    BandTab b{};
    for (int cls = 0; cls < 11; cls++)
        for (int wd = 0; wd < 10; wd++) {
            const int tau = cls + 2 - 8 * ((wd < 4 ? wd : wd - 4) >> 1);
            const int lo = (wd < 4) ? ((wd & 1) ? -2 : 3) : ((wd & 1) ? -4 : -11), wid = (wd < 4 ? 3 : 7) + 2 * (wd & 1);
            b.w[cls][wd] = ((tau >= lo && tau < lo + wid) ? 0x3F80u : 0u) | ((tau - 4 >= lo && tau - 4 < lo + wid) ? 0x3F800000u : 0u);
        }
    return b;
}
constexpr int NTOP = 32;
struct Scratch {
    uint4 r[L_ / 4];
    uint4 g[L_ / 4];
    uint4 h[2][8 * F_ / 8];
    uint32_t top[NTOP][32];
    unsigned epoch;
};
__device__ __align__(128) Scratch g_scratch;
__device__ const __align__(16) BandTab g_band = make_band();

struct Params {
    const bf16 *u, *logA, *Aim, *Cre, *Cim, *logdt, *Dskip, *wr, *gatew;
    bf16* out;
    Scratch* sc;
    const uint4* band;
    uint32_t gu_swap;
    uint32_t zero;
};

#define WSTAMP(i) do {} while (0)
#define KSTAMP(i, dep) do {} while (0)
#define WDUMP() do {} while (0)
#define RSTAMP(i) do {} while (0)

__device__ __forceinline__ uint32_t smem_u32(const void* p) { return (uint32_t)__cvta_generic_to_shared(p); }
__device__ __forceinline__ void mbar_init(uint32_t b, uint32_t c) { asm volatile("mbarrier.init.shared::cta.b64 [%0], %1;" :: "r"(b), "r"(c) : "memory"); }
__device__ __forceinline__ void mbar_expect(uint32_t b, uint32_t tx) { asm volatile("mbarrier.arrive.expect_tx.shared::cta.b64 _, [%0], %1;" :: "r"(b), "r"(tx) : "memory"); }
__device__ __forceinline__ void mbar_arrive(uint32_t b) { asm volatile("mbarrier.arrive.shared::cta.b64 _, [%0];" :: "r"(b) : "memory"); }
__device__ __forceinline__ void mbar_wait(uint32_t b, uint32_t parity = 0) {
    asm volatile("{\n\t.reg .pred p;\nW%=:\n\tmbarrier.try_wait.parity.shared::cta.b64 p, [%0], %1, 20000;\n\t@!p bra W%=;\n\t}" :: "r"(b), "r"(parity) : "memory");
}
__device__ __forceinline__ uint32_t mapa(uint32_t addr, uint32_t rank) { uint32_t r; asm("mapa.shared::cluster.u32 %0, %1, %2;" : "=r"(r) : "r"(addr), "r"(rank)); return r; }
__device__ __forceinline__ void tma3d(uint32_t dst, const CUtensorMap* tm, int c0, int c1, uint32_t bar, uint32_t bytes) {
    asm volatile("{\n\t.reg .pred p;\n\telect.sync _|p, 0xffffffff;\n\t"
                 "@p mbarrier.arrive.expect_tx.shared::cta.b64 _, [%2], %5;\n\t"
                 "@p cp.async.bulk.tensor.3d.shared::cluster.global.mbarrier::complete_tx::bytes [%0], [%1, {%3, %4, 0}], [%2];\n\t}"
        :: "r"(dst), "l"(tm), "r"(bar), "r"(c0), "r"(c1), "r"(bytes) : "memory");
}
__device__ __forceinline__ void bulk_load(uint32_t dst, const void* src, uint32_t bytes, uint32_t bar) {
    asm volatile("{\n\t.reg .pred p;\n\telect.sync _|p, 0xffffffff;\n\t"
                 "@p mbarrier.arrive.expect_tx.shared::cta.b64 _, [%2], %3;\n\t"
                 "@p cp.async.bulk.shared::cluster.global.mbarrier::complete_tx::bytes [%0], [%1], %3, [%2];\n\t}"
        :: "r"(dst), "l"(src), "r"(bar), "r"(bytes) : "memory");
}
__device__ __forceinline__ void st_async16(uint32_t dst, const uint4& v, uint32_t bar) {
    asm volatile("st.async.weak.shared::cluster.mbarrier::complete_tx::bytes.v4.b32 [%0], {%1,%2,%3,%4}, [%5];"
                 :: "r"(dst), "r"(v.x), "r"(v.y), "r"(v.z), "r"(v.w), "r"(bar) : "memory");
}
__device__ __forceinline__ void bar_sync(int id, int n) { asm volatile("bar.sync %0, %1;" :: "r"(id), "r"(n) : "memory"); }
__device__ __forceinline__ void cp16(uint32_t dst, const void* src) { asm volatile("cp.async.cg.shared.global [%0], [%1], 16;" :: "r"(dst), "l"(src) : "memory"); }
__device__ __forceinline__ void cp_wait_all() { asm volatile("cp.async.wait_all;" ::: "memory"); }
__device__ __forceinline__ uint4 ld_gpu128(const void* p) { uint4 v; asm volatile("ld.relaxed.gpu.global.v4.u32 {%0,%1,%2,%3}, [%4];" : "=r"(v.x), "=r"(v.y), "=r"(v.z), "=r"(v.w) : "l"(p) : "memory"); return v; }
__device__ __forceinline__ void st_gpu32(void* p, uint32_t v) { asm volatile("st.relaxed.gpu.global.u32 [%0], %1;" :: "l"(p), "r"(v) : "memory"); }

__device__ __forceinline__ void ldsm4(uint32_t a, uint32_t& r0, uint32_t& r1, uint32_t& r2, uint32_t& r3) {
    asm volatile("ldmatrix.sync.aligned.m8n8.x4.shared.b16 {%0,%1,%2,%3}, [%4];" : "=r"(r0), "=r"(r1), "=r"(r2), "=r"(r3) : "r"(a) : "memory");
}
__device__ __forceinline__ void ldsm4t(uint32_t a, uint32_t& r0, uint32_t& r1, uint32_t& r2, uint32_t& r3) {
    asm volatile("ldmatrix.sync.aligned.m8n8.x4.trans.shared.b16 {%0,%1,%2,%3}, [%4];" : "=r"(r0), "=r"(r1), "=r"(r2), "=r"(r3) : "r"(a) : "memory");
}
__device__ __forceinline__ uint32_t lds32(uint32_t a) { uint32_t v; asm volatile("ld.shared.u32 %0, [%1];" : "=r"(v) : "r"(a) : "memory"); return v; }
__device__ __forceinline__ uint2 lds64(uint32_t a) { uint2 v; asm volatile("ld.shared.v2.u32 {%0,%1}, [%2];" : "=r"(v.x), "=r"(v.y) : "r"(a) : "memory"); return v; }
__device__ __forceinline__ uint4 lds128(uint32_t a) { uint4 v; asm volatile("ld.shared.v4.u32 {%0,%1,%2,%3}, [%4];" : "=r"(v.x), "=r"(v.y), "=r"(v.z), "=r"(v.w) : "r"(a) : "memory"); return v; }
__device__ __forceinline__ void sts32(uint32_t a, uint32_t v) { asm volatile("st.shared.u32 [%0], %1;" :: "r"(a), "r"(v) : "memory"); }
__device__ __forceinline__ void sts16(uint32_t a, uint32_t v) { asm volatile("st.shared.u16 [%0], %1;" :: "r"(a), "h"((unsigned short)v) : "memory"); }
__device__ __forceinline__ void sts128(uint32_t a, uint32_t x, uint32_t y, uint32_t z, uint32_t w) { asm volatile("st.shared.v4.u32 [%0], {%1,%2,%3,%4};" :: "r"(a), "r"(x), "r"(y), "r"(z), "r"(w) : "memory"); }
__device__ __forceinline__ float ldsf(uint32_t a) { float v; asm volatile("ld.shared.f32 %0, [%1];" : "=f"(v) : "r"(a) : "memory"); return v; }

__device__ __forceinline__ void mma_bf(float (&d)[4], uint32_t a0, uint32_t a1, uint32_t a2, uint32_t a3, uint32_t b0, uint32_t b1) {
    asm volatile("mma.sync.aligned.m16n8k16.row.col.f32.bf16.bf16.f32 {%0,%1,%2,%3}, {%4,%5,%6,%7}, {%8,%9}, {%0,%1,%2,%3};"
        : "+f"(d[0]), "+f"(d[1]), "+f"(d[2]), "+f"(d[3]) : "r"(a0), "r"(a1), "r"(a2), "r"(a3), "r"(b0), "r"(b1));
}
__device__ __forceinline__ void mma_bf_z(float (&d)[4], uint32_t a0, uint32_t a1, uint32_t a2, uint32_t a3, uint32_t b0, uint32_t b1) {
    asm volatile("mma.sync.aligned.m16n8k16.row.col.f32.bf16.bf16.f32 {%0,%1,%2,%3}, {%4,%5,%6,%7}, {%8,%9}, {%10,%10,%10,%10};"
        : "=f"(d[0]), "=f"(d[1]), "=f"(d[2]), "=f"(d[3]) : "r"(a0), "r"(a1), "r"(a2), "r"(a3), "r"(b0), "r"(b1), "f"(0.f));
}
__device__ __forceinline__ void mma_bf_k8(float (&d)[4], uint32_t a0, uint32_t a1, uint32_t b0) {
    asm volatile("mma.sync.aligned.m16n8k8.row.col.f32.bf16.bf16.f32 {%0,%1,%2,%3}, {%4,%5}, {%6}, {%0,%1,%2,%3};"
        : "+f"(d[0]), "+f"(d[1]), "+f"(d[2]), "+f"(d[3]) : "r"(a0), "r"(a1), "r"(b0));
}
__device__ __forceinline__ void mma_h(float (&d)[4], uint32_t a0, uint32_t a1, uint32_t a2, uint32_t a3, uint32_t b0, uint32_t b1) {
    asm volatile("mma.sync.aligned.m16n8k16.row.col.f32.f16.f16.f32 {%0,%1,%2,%3}, {%4,%5,%6,%7}, {%8,%9}, {%0,%1,%2,%3};"
        : "+f"(d[0]), "+f"(d[1]), "+f"(d[2]), "+f"(d[3]) : "r"(a0), "r"(a1), "r"(a2), "r"(a3), "r"(b0), "r"(b1));
}
__device__ __forceinline__ uint32_t pack_bf(float lo, float hi) { uint32_t r; asm("cvt.rn.bf16x2.f32 %0, %1, %2;" : "=r"(r) : "f"(hi), "f"(lo)); return r; }
__device__ __forceinline__ uint32_t pack_h(float lo, float hi) { uint32_t r; asm("cvt.rn.f16x2.f32 %0, %1, %2;" : "=r"(r) : "f"(hi), "f"(lo)); return r; }
__device__ __forceinline__ float bf_lo(uint32_t v) { return __uint_as_float(v << 16); }
__device__ __forceinline__ float bf_hi(uint32_t v) { return __uint_as_float(v & 0xffff0000u); }
__device__ __forceinline__ float bf_round(float x) { return __uint_as_float(pack_bf(0.f, x)); }
__device__ __forceinline__ uint32_t hmul2_bf(uint32_t a, uint32_t b) { uint32_t r; asm("mul.rn.bf16x2 %0, %1, %2;" : "=r"(r) : "r"(a), "r"(b)); return r; }
__device__ __forceinline__ float ex2f(float x) { float r; asm("ex2.approx.ftz.f32 %0, %1;" : "=f"(r) : "f"(x)); return r; }

__device__ __forceinline__ float exp_acc(float x) {
    const float t = x * 1.4426950216293335f;
    const float r = fmaf(x, 1.4426950216293335f, -t) + x * 1.9259629911266175e-8f;
    return ex2f(t) * fmaf(r, 0.6931471805599453f, 1.f);
}
__device__ __forceinline__ float sigmoid_f(float x) { return __fdividef(1.f, 1.f + ex2f(-x * 1.4426950408889634f)); }
__device__ __forceinline__ void cexp_pow(float l2, float li, float e, float& zr, float& zi) {
    const float mag = ex2f(l2 * e);
    zr = mag * __cosf(li * e);
    zi = mag * __sinf(li * e);
}
__device__ __forceinline__ uint32_t hcmul(uint32_t a, uint32_t k, uint32_t kp) {
    const __half2 A = *reinterpret_cast<const __half2*>(&a);
    const __half2 r = __hfma2(__high2half2(A), *reinterpret_cast<const __half2*>(&kp), __hmul2(__low2half2(A), *reinterpret_cast<const __half2*>(&k)));
    return *reinterpret_cast<const uint32_t*>(&r);
}
#define CMUL(orr, oi, ar, ai, br, bi) do { float _r = (ar) * (br) - (ai) * (bi); float _i = (ar) * (bi) + (ai) * (br); orr = _r; oi = _i; } while (0)
#define CSQ(orr, oi, ar, ai) do { float _r = (ar) * (ar) - (ai) * (ai); float _i = 2.f * (ar) * (ai); orr = _r; oi = _i; } while (0)

__device__ __forceinline__ void mma_bf_k8z(float (&d)[4], uint32_t a0, uint32_t a1, uint32_t b0) {
    asm volatile("mma.sync.aligned.m16n8k8.row.col.f32.bf16.bf16.f32 {%0,%1,%2,%3}, {%4,%5}, {%6}, {%7,%7,%7,%7};"
        : "=f"(d[0]), "=f"(d[1]), "=f"(d[2]), "=f"(d[3]) : "r"(a0), "r"(a1), "r"(b0), "f"(0.f));
}
__device__ __forceinline__ void mma_hh_k8(uint32_t& d0, uint32_t& d1, uint32_t a0, uint32_t a1, uint32_t b0) {
    asm volatile("mma.sync.aligned.m16n8k8.row.col.f16.f16.f16.f16 {%0,%1}, {%2,%3}, {%4}, {%5,%5};"
        : "=r"(d0), "=r"(d1) : "r"(a0), "r"(a1), "r"(b0), "r"(0));
}
__device__ __forceinline__ void sched_fence() { asm volatile("pmevent 0;" ::: "memory"); }
__device__ __forceinline__ uint32_t pin(uint32_t x, int lane) { return __shfl_sync(0xffffffffu, x, lane); }
template <class T> __device__ __forceinline__ T* pin(T* x, int lane) { return (T*)__shfl_sync(0xffffffffu, (unsigned long long)x, lane); }
__device__ __forceinline__ void sts32_if(bool on, uint32_t a, uint32_t v) {
    asm volatile("{\n\t.reg .pred p;\n\tsetp.ne.u32 p, %2, 0;\n\t@p st.shared.u32 [%0], %1;\n\t}" :: "r"(a), "r"(v), "r"((uint32_t)on) : "memory");
}
__device__ __forceinline__ void sts128_if(bool on, uint32_t a, uint32_t x, uint32_t y, uint32_t z, uint32_t w) {
    asm volatile("{\n\t.reg .pred p;\n\tsetp.ne.u32 p, %5, 0;\n\t@p st.shared.v4.u32 [%0], {%1,%2,%3,%4};\n\t}" :: "r"(a), "r"(x), "r"(y), "r"(z), "r"(w), "r"((uint32_t)on) : "memory");
}
__device__ __forceinline__ void lds128_if(bool on, uint32_t a, uint32_t (&v)[4]) {
    asm volatile("{\n\t.reg .pred p;\n\tsetp.ne.u32 p, %5, 0;\n\t@p ld.shared.v4.u32 {%0,%1,%2,%3}, [%4];\n\t}"
        : "+r"(v[0]), "+r"(v[1]), "+r"(v[2]), "+r"(v[3]) : "r"(a), "r"((uint32_t)on) : "memory");
}
__device__ __forceinline__ uint32_t hfma2_bf(uint32_t a, uint32_t b, uint32_t c) { uint32_t r; asm("fma.rn.bf16x2 %0, %1, %2, %3;" : "=r"(r) : "r"(a), "r"(b), "r"(c)); return r; }
__device__ __forceinline__ __nv_bfloat162 bcast(uint32_t a, int hi) { const __nv_bfloat162 v = *reinterpret_cast<const __nv_bfloat162*>(&a); return hi ? __high2bfloat162(v) : __low2bfloat162(v); }
__device__ __forceinline__ uint32_t hmul2_bc(uint32_t a, int hi, uint32_t b) { const __nv_bfloat162 r = __hmul2_rn(bcast(a, hi), *reinterpret_cast<const __nv_bfloat162*>(&b)); return *reinterpret_cast<const uint32_t*>(&r); }
__device__ __forceinline__ uint32_t hfma2_bc(uint32_t a, int hi, uint32_t b, uint32_t c) {
    const __nv_bfloat162 r = __hfma2(bcast(a, hi), *reinterpret_cast<const __nv_bfloat162*>(&b), *reinterpret_cast<const __nv_bfloat162*>(&c));
    return *reinterpret_cast<const uint32_t*>(&r);
}
__device__ __forceinline__ uint32_t row_elem(uint32_t row) { return ((row >> 5) & 4) | ((row >> 2) & 2) | ((row >> 4) & 1); }
__device__ __forceinline__ uint32_t gate_pos(uint32_t row) { return ((row >> 9) << 8) | ((row & 7) << 5) | (row_elem(row) << 2) | ((row >> 5) & 3); }

template <int N>
__device__ __forceinline__ void mix_rows(const Params& p, const CUtensorMap* tm_out, uint32_t sb, uint32_t ob, int Q0, int Q1, int w, int h, int pr, int lane) {
    const int g = lane >> 2, t = lane & 3, mi = lane >> 3, r = lane & 7;
    const int m8 = 16 * (g >> 2) + ((g >> 1) & 1) + 2 * (g & 1);
    uint32_t yi = sb + (4 * (r >> 1) + 2 * (mi & 1) + (r & 1)) * 512 + (((4 * w + (mi >> 1)) ^ r) << 4);
    uint32_t xs = sb + OFF_S + s_addr(w * S_PL + 32 + m8 * 32, t >> 1) + ((t & 1) << 3);
    uint32_t gs = sb + OFF_GP + w * 64 + g * 8, os = ob + m8 * 32 + t * 8;
    if (N > 1) { yi = pin(yi, lane); xs = pin(xs, lane); gs = pin(gs, lane); os = pin(os, lane); }
    mbar_wait(sb + M_BARS + 8 * B_Y);
#pragma unroll 1
    for (int Q = Q0; Q < Q1; Q++) {
        uint2 xq[N][4];
        uint32_t gg[N][2], sw[N];
#pragma unroll
        for (int n = 0; n < N; n++) {
#pragma unroll
            for (int i = 0; i < 4; i++) xq[n][i] = lds64((xs ^ (((i ^ n) & 1) << 4)) + Q * S_Q + n * 4 * S_PL + i * 128);
            const uint2 gq = lds64(gs + Q * 512 + n * 256);
            sw[n] = lds32(sb + M_BMAP + w * 16 + n * 64 + Q * 4);
            gg[n][0] = gq.x; gg[n][1] = gq.y;
#pragma unroll
            for (int i = 0; i < 4; i++) {
                const uint32_t og = hfma2_bf(gg[n][i >> 1], 0xBF80BF80u, 0x3F803F80u);
                xq[n][i].x = hmul2_bc(og, i & 1, xq[n][i].x); xq[n][i].y = hmul2_bc(og, i & 1, xq[n][i].y);
            }
        }
        mbar_wait(sb + M_BARS + 8 * (B_Y + Q));
        __syncwarp();
#pragma unroll
        for (int n = 0; n < N; n++) {
#pragma unroll
            for (int x = 0; x < 2; x++) {
                uint32_t y[4];
                ldsm4t((yi ^ (x << 5)) + y_off(Q) + n * 256, y[0], y[1], y[2], y[3]);
#pragma unroll
                for (int e = 0; e < 2; e++) {
                    uint2& o = xq[n][2 * x + e];
                    o.x = hfma2_bc(gg[n][x], e, y[2 * e], o.x); o.y = hfma2_bc(gg[n][x], e, y[2 * e + 1], o.y);
                }
            }
        }
        if ((sw[0] | sw[N - 1]) == 0) {
#pragma unroll
            for (int n = 0; n < N; n++)
#pragma unroll
                for (int i = 0; i < 4; i++)
                    asm volatile("st.shared.v2.u32 [%0], {%1, %2};" :: "r"(os + Q * 1024 + n * 4 * TAB_W + i * 128), "r"(xq[n][i].x), "r"(xq[n][i].y) : "memory");
            asm volatile("fence.proxy.async.shared::cta;" ::: "memory");
            __syncwarp();
#pragma unroll
            for (int n = 0; n < N; n++)
                asm volatile("{\n\t.reg .pred p;\n\telect.sync _|p, 0xffffffff;\n\t"
                             "@p cp.async.bulk.tensor.3d.global.shared::cta.bulk_group [%1, {%2, %3, %4}], [%0];\n\t}"
                    :: "r"(ob + 4 * n * TAB_W + Q * 1024), "l"(tm_out), "r"(16 * pr), "r"(64 * Q + 32 * h), "r"(w + 4 * n) : "memory");
        } else {
            bf16* op = p.out + (size_t)(512 * Q + 256 * h + 8 * m8 + w) * D_ + 16 * pr + 4 * t;
#pragma unroll
            for (int n = 0; n < N; n++)
#pragma unroll
                for (int i = 0; i < 4; i++)
                    if (!((sw[n] >> (4 * g)) & (1u << i))) *(uint2*)(op + (size_t)(32 * i + 4 * n) * D_) = xq[n][i];
        }
    }
}

__global__ void __cluster_dims__(2, 1, 1) __launch_bounds__(NTHREADS, 1)
fused_kernel(const Params p, const __grid_constant__ CUtensorMap tm_gu, const __grid_constant__ CUtensorMap tm_down,
             const __grid_constant__ CUtensorMap tm_x, const __grid_constant__ CUtensorMap tm_out) {
    extern __shared__ __align__(1024) unsigned char smem[];
    const uint32_t sb = smem_u32(smem);
    int tid;
    asm volatile("mov.u32 %0, %%tid.x;" : "=r"(tid));
    const int pw = tid >> 5, lane = tid & 31;
    const int c = blockIdx.x, h = c & 1, pr = c >> 1;
    const uint32_t bars = sb + M_BARS;

    uint2 v_la, v_ai, v_cr, v_ci;
    uint32_t ldt16;
    {
        const uint32_t po = c * 256 + tid;
        asm volatile("{\n\t.reg .pred p;\n\t.reg .b64 a;\n\tsetp.ne.u32 p, %16, 0;\n\t"
                     "mad.wide.u32 a, %14, 8, %9;\n\t@p ld.global.nc.L1::no_allocate.v2.u32 {%0,%1}, [a];\n\t"
                     "mad.wide.u32 a, %15, 2, %13;\n\t@p ld.global.nc.u16 %8, [a];\n\t"
                     "mad.wide.u32 a, %14, 8, %10;\n\t@p ld.global.nc.L1::no_allocate.v2.u32 {%2,%3}, [a];\n\t"
                     "mad.wide.u32 a, %14, 8, %11;\n\t@p ld.global.nc.L1::no_allocate.v2.u32 {%4,%5}, [a];\n\t"
                     "mad.wide.u32 a, %14, 8, %12;\n\t@p ld.global.nc.L1::no_allocate.v2.u32 {%6,%7}, [a];\n\t}"
            : "=r"(v_la.x), "=r"(v_la.y), "=r"(v_ai.x), "=r"(v_ai.y), "=r"(v_cr.x), "=r"(v_cr.y), "=r"(v_ci.x), "=r"(v_ci.y), "=r"(ldt16)
            : "l"(p.logA), "l"(p.Aim), "l"(p.Cre), "l"(p.Cim), "l"(p.logdt), "r"(po), "r"(po >> 5), "r"((uint32_t)(tid < 256 && c < 128)));
    }

    if (c >= 128) {
        if (c != 128) return;
        RSTAMP(5);
        const unsigned tag = (*(volatile unsigned*)&p.sc->epoch + 1) & 0xffffu;
        const uint32_t list = sb + 128;
        sts128(list + 16 * tid, 0, 0, 0, 0);
        if (tid == 0) sts32(sb + 64, 0);
        uint32_t key[4] = {tag - 1, tag - 1, tag - 1, tag - 1};
#pragma unroll 1
        for (int it = 0; it < (1 << 22); it++) {
            uint32_t a[4];
            asm volatile("{\n\t.reg .b128 o, z;\n\t.reg .b64 l, u;\n\tmov.b64 l, {%5, %5};\n\tmov.b128 z, {l, l};\n\tatom.relaxed.gpu.global.exch.b128 o, [%4], z;\n\t"
                         "mov.b128 {l, u}, o;\n\tmov.b64 {%0, %1}, l;\n\tmov.b64 {%2, %3}, u;\n\t}"
                : "=r"(a[0]), "=r"(a[1]), "=r"(a[2]), "=r"(a[3]) : "l"(&p.sc->r[tid]), "r"(tag - 1) : "memory");
#pragma unroll
            for (int i = 0; i < 4; i++) if (((a[i] ^ tag) & 0xffffu) == 0) key[i] = a[i];
            if ((((key[0] ^ tag) | (key[1] ^ tag) | (key[2] ^ tag) | (key[3] ^ tag)) & 0xffffu) == 0) break;
        }
        WSTAMP(0);
        uint32_t m = 0;
#pragma unroll
        for (int i = 0; i < 4; i++) {
            key[i] = (key[i] & 0xffff0000u) | (uint32_t)(2047 - (4 * tid + i));
            m = max(m, key[i]);
        }
        const uint32_t wm = __reduce_max_sync(0xffffffffu, m);
        if (lane == 0) sts32(sb + pw * 4, wm);
        __syncthreads();
        uint32_t thr = 0xffffffffu;
#pragma unroll
        for (int i = 0; i < 4; i++) { const uint4 q = lds128(sb + 16 * i); thr = min(thr, min(max(q.x, q.y), max(q.z, q.w))); }
        if (thr != 1) WSTAMP(1);
        if (m >= thr) {
            uint32_t pos;
            asm volatile("atom.shared.add.u32 %0, [%1], %2;" : "=r"(pos) : "r"(sb + 64), "r"(4 * ((key[0] >= thr) + (key[1] >= thr) + (key[2] >= thr) + (key[3] >= thr))) : "memory");
#pragma unroll
            for (int i = 0; i < 4; i++) if (key[i] >= thr) { sts32(list + pos, key[i]); pos += 4; }
        }
        __syncthreads();
        const uint32_t nc4 = lds32(sb + 64);
        if (nc4 != 1) WSTAMP(2);
#pragma unroll 1
        for (uint32_t j = 4 * pw; j < nc4; j += 64) {
            const uint32_t mine = lds32(list + j);
            int rank = 0;
#pragma unroll 1
            for (uint32_t i = 0; i < nc4; i += 128) rank += __popc(__ballot_sync(0xffffffffu, lds32(list + i + 4 * lane) > mine));
            if (rank < 8 && lane == 0) sts32(sb + 96 + 4 * rank, mine);
        }
        __syncthreads();
        if (tid < 8 * NTOP) st_gpu32(&p.sc->top[tid >> 3][tid & 7], lds32(sb + 96 + 4 * (tid & 7)) | ((tag & 31) << 11));
        WSTAMP(3);
        WDUMP();
        return;
    }

    WSTAMP(0);
    if (pw < 8) {
        const int d = 8 * c + pw - MAIN_W0;
        if (lane == 0) asm volatile("cp.async.ca.shared.global [%0], [%1], 4;" :: "r"(sb + M_DSK + 4 * (pw - MAIN_W0)), "l"(p.Dskip + (d & ~1)) : "memory");
        asm volatile("barrier.cluster.arrive.relaxed.aligned;" ::: "memory");
        const int warp = pw - MAIN_W0;
        asm volatile("setmaxnreg.inc.sync.aligned.u32 160;");
        const int g = lane >> 2, t = lane & 3;
        const int mi = lane >> 3, r = lane & 7;
        const uint32_t TB = sb + OFF_TAB + warp * TAB_W;
        const uint32_t UB = sb + OFF_U + warp * U_CH;
        if (mi < 2) sts128(UB + mi * U_PL + r * 16, 0, 0, 0, 0);
        if (lane < 4) sts128(TB + lane * T_PL, 0, 0, 0, 0);
        sts128(sb + OFF_SCR + warp * 8192 + lane * 16, 0x3C00u, 0x3C00u, 0x3C00u, 0x3C00u);
        asm volatile("barrier.cluster.wait.acquire.aligned;" ::: "memory");
        __syncwarp();

        uint32_t cfix;
        {
            KSTAMP(4, v_la.x ^ v_ai.x ^ v_cr.x ^ v_ci.x ^ ldt16);
            const float dt = bf_round(exp_acc(__uint_as_float(ldt16 << 16)));
            float l2[4], li[4];
            {
                const uint32_t la[2] = {v_la.x, v_la.y}, ai[2] = {v_ai.x, v_ai.y};
                const float dt2 = -1.4426950408889634f * dt;
#pragma unroll
                for (int i = 0; i < 4; i++) {
                    l2[i] = bf_round(ex2f(((i & 1) ? bf_hi(la[i >> 1]) : bf_lo(la[i >> 1])) * 1.4426950408889634f)) * dt2;
                    li[i] = ((i & 1) ? bf_hi(ai[i >> 1]) : bf_lo(ai[i >> 1])) * dt;
                }
            }
            const uint32_t SX = sb + OFF_SCR + warp * 8192;
            const uint32_t sw = SX + (lane << 4);
#define PUT(buf, row, v) sts128(((sw + (row) * 512) ^ ((row) << 4)) + (buf) * 4096, v[0], v[1], v[2], v[3])
#define EMIT(bufa, rowa, bufb, rowb, xr, xi, k, kp) do { uint32_t pk[4], pd[4]; sched_fence(); \
                _Pragma("unroll") for (int i = 0; i < 4; i++) { pk[i] = pack_h(xr[i], xi[i]); pd[i] = hcmul(pk[i], k[i], kp[i]); } \
                PUT(bufa, rowa, pk); PUT(bufb, rowb, pd); } while (0)
#define CMUL4(orr, oi, ar, ai, br, bi) _Pragma("unroll") for (int i = 0; i < 4; i++) CMUL(orr[i], oi[i], ar[i], ai[i], br[i], bi[i])
#define CSQ4(orr, oi, ar, ai) _Pragma("unroll") for (int i = 0; i < 4; i++) CSQ(orr[i], oi[i], ar[i], ai[i])
            float z1r[4], z1i[4], z2r[4], z2i[4], z8r[4], z8i[4], z256r[4], z256i[4];
            uint32_t k4[4], k4p[4];
            float z4r[4], z4i[4];
#pragma unroll
            for (int i = 0; i < 4; i++) cexp_pow(l2[i], li[i], 1.f, z1r[i], z1i[i]);
            CSQ4(z2r, z2i, z1r, z1i);
            CSQ4(z4r, z4i, z2r, z2i);
            CSQ4(z8r, z8i, z4r, z4i);
            KSTAMP(5, __float_as_uint(z8r[3]));
            uint32_t Ya[16][4];
            float cr[4], ci[4], inv;
            {
                float w1r[4], w1i[4], ar[4], ai[4], br[4], bi[4];
                uint32_t k8[4], k8p[4];
#pragma unroll
                for (int i = 0; i < 4; i++) {
                    k8[i] = pack_h(z8r[i], -z8i[i]); k8p[i] = pack_h(z8i[i], z8r[i]);
                    CSQ(w1r[i], w1i[i], z8r[i], z8i[i]); w1i[i] = -w1i[i];
                }
                PUT(1, 0, k8);
                EMIT(0, 1, 1, 1, w1r, w1i, k8, k8p);
                CSQ4(ar, ai, w1r, w1i);            EMIT(0, 2, 1, 2, ar, ai, k8, k8p);
                CMUL4(br, bi, ar, ai, w1r, w1i);   EMIT(0, 3, 1, 3, br, bi, k8, k8p);
                CSQ4(ar, ai, ar, ai);              EMIT(0, 4, 1, 4, ar, ai, k8, k8p);
                CMUL4(ar, ai, ar, ai, w1r, w1i);   EMIT(0, 5, 1, 5, ar, ai, k8, k8p);
                CSQ4(br, bi, br, bi);              EMIT(0, 6, 1, 6, br, bi, k8, k8p);
                CMUL4(br, bi, br, bi, w1r, w1i);   EMIT(0, 7, 1, 7, br, bi, k8, k8p);
                __syncwarp();
                KSTAMP(6, 0);
                sched_fence();
                const uint32_t ab = SX + (mi & 1) * 4096 + r * 512, ax = ((mi >> 1) ^ r) << 4;
                const uint32_t vr[2] = {v_cr.x, v_cr.y}, vi[2] = {v_ci.x, v_ci.y};
                const uint32_t m2 = __vmaxu2(__vmaxu2(vr[0] & 0x7fff7fffu, vr[1] & 0x7fff7fffu), __vmaxu2(vi[0] & 0x7fff7fffu, vi[1] & 0x7fff7fffu));
                const uint32_t mx = __reduce_max_sync(0xffffffffu, max(m2, m2 << 16));
                const uint32_t e = min(max(mx >> 23, 11u), 254u);
                const float sc = __uint_as_float((264u - e) << 23);
                inv = __uint_as_float((e - 10u) << 23) * (2.f * dt);
#pragma unroll
                for (int i = 0; i < 4; i++) {
#pragma unroll
                    for (int k = 0; k < 4; k++) ldsm4(ab + (ax ^ (i << 5)) + k * 128, Ya[4 * k + i][0], Ya[4 * k + i][1], Ya[4 * k + i][2], Ya[4 * k + i][3]);
                    float tr, ti;
                    cexp_pow(l2[i], li[i], 128.f, tr, ti);
                    sts32(TB + 2176 + 256 * i + 4 * (lane ^ (8 * i)), pack_h(tr, ti));
                    sts32(TB + 2176 + 256 * i + 128 + 4 * (lane ^ (8 * i + 4)), pack_h(-ti, tr));
                    k4[i] = pack_h(z4r[i], z4i[i]); k4p[i] = pack_h(-z4i[i], z4r[i]);
                    CSQ(z256r[i], z256i[i], tr, ti);
                    cr[i] = ((i & 1) ? bf_hi(vr[i >> 1]) : bf_lo(vr[i >> 1])) * sc;
                    ci[i] = ((i & 1) ? bf_hi(vi[i >> 1]) : bf_lo(vi[i >> 1])) * sc;
                    if (i < 3) sched_fence();
                }
                __syncwarp();
            }
            KSTAMP(7, Ya[15][0]);
            const uint32_t ld0 = SX + r * 512 + ((mi ^ r) << 4), ld1 = ld0 ^ 64;
            float R[6][4], s1024;
            {
                float xr[4], xi[4], yr[4], yi[4];
                EMIT(0, 0, 0, 1, cr, ci, k4, k4p);
                CMUL4(yr, yi, cr, ci, z1r, z1i);        EMIT(0, 2, 0, 3, yr, yi, k4, k4p);
                CMUL4(xr, xi, cr, ci, z256r, z256i);    EMIT(1, 0, 1, 1, xr, xi, k4, k4p);
                CMUL4(yr, yi, yr, yi, z1r, z1i);        EMIT(0, 4, 0, 5, yr, yi, k4, k4p);
                CMUL4(cr, ci, yr, yi, z256r, z256i);    EMIT(1, 2, 1, 3, cr, ci, k4, k4p);
                CMUL4(yr, yi, yr, yi, z1r, z1i);        EMIT(0, 6, 0, 7, yr, yi, k4, k4p);
                CMUL4(xr, xi, xr, xi, z256r, z256i);    EMIT(1, 4, 1, 5, xr, xi, k4, k4p);
                CMUL4(xr, xi, xr, xi, z256r, z256i);    EMIT(1, 6, 1, 7, xr, xi, k4, k4p);
                CMUL4(xr, xi, xr, xi, z256r, z256i);
                s1024 = (xr[0] + xr[1]) + (xr[2] + xr[3]);
#pragma unroll
                for (int m = 0; m < 4; m++) {
                    if (m == 0) { CMUL4(xr, xi, xr, xi, z8r, z8i); } else { CMUL4(xr, xi, xr, xi, z256r, z256i); }
                    sched_fence();
                    sts128(TB + m * T_PL + 16 + 16 * lane, pack_h(xr[0], xi[0]), pack_h(xr[1], xi[1]), pack_h(xr[2], xi[2]), pack_h(xr[3], xi[3]));
                }
            }
            __syncwarp();
            {
                KSTAMP(8, 0);
                uint32_t bd[2][4] = {{0, 0, 0, 0}, {0, 0, 0, 0}};
                const bool on = (g >> 1) == t;
#pragma unroll
                for (int i = 0; i < 6; i++) { R[i][0] = R[i][1] = R[i][2] = R[i][3] = 0.f; }
                uint32_t x[2][4], y[2][4], z[2][4];
                auto fetch = [&](const int k2) {
                    const int b = k2 & 1;
                    lds128_if(on, TB + 2176 + g * 128 + 16 * (k2 ^ g), bd[b]);
                    ldsm4(((k2 & 1) ? ld1 : ld0) + (k2 >> 1) * 128, x[b][0], x[b][1], x[b][2], x[b][3]);
                    ldsm4(((k2 & 1) ? ld1 : ld0) + (k2 >> 1) * 128 + 4096, y[b][0], y[b][1], y[b][2], y[b][3]);
                    ldsm4(TB + (r & 3) * T_PL + 16 + 16 * mi + 64 * k2, z[b][0], z[b][1], z[b][2], z[b][3]);
                };
                fetch(0);
#pragma unroll
                for (int k2 = 0; k2 < 8; k2++) {
                    const int b = k2 & 1;
                    uint32_t a1[2][4];
                    if (k2 < 7) fetch(k2 + 1);
#pragma unroll
                    for (int u = 0; u < 2; u++) {
                        mma_hh_k8(a1[u][0], a1[u][1], Ya[2 * k2 + u][0], Ya[2 * k2 + u][1], bd[b][2 * u]);
                        mma_hh_k8(a1[u][2], a1[u][3], Ya[2 * k2 + u][2], Ya[2 * k2 + u][3], bd[b][2 * u + 1]);
                    }
#pragma unroll
                    for (int u = 0; u < 2; u++) {
                        const uint32_t(&a0)[4] = Ya[2 * k2 + u];
                        mma_h(R[0], a0[0], a0[1], a0[2], a0[3], x[b][2 * u], x[b][2 * u + 1]);
                        mma_h(R[2], a0[0], a0[1], a0[2], a0[3], y[b][2 * u], y[b][2 * u + 1]);
                        mma_h(R[4], a0[0], a0[1], a0[2], a0[3], z[b][2 * u], z[b][2 * u + 1]);
                        mma_h(R[1], a1[u][0], a1[u][1], a1[u][2], a1[u][3], x[b][2 * u], x[b][2 * u + 1]);
                        mma_h(R[3], a1[u][0], a1[u][1], a1[u][2], a1[u][3], y[b][2 * u], y[b][2 * u + 1]);
                        mma_h(R[5], a1[u][0], a1[u][1], a1[u][2], a1[u][3], z[b][2 * u], z[b][2 * u + 1]);
                    }
                }
            }
            __syncwarp();
            KSTAMP(9, __float_as_uint(R[3][0]));
            if (lane == 0) mbar_arrive(bars + 8 * B_KG + (__float_as_uint(R[0][0]) & __float_as_uint(R[2][0]) & p.zero));
            sts128(TB + 2176 + 16 * lane, 0, 0, 0, 0);
            sts128(TB + 2688 + 16 * lane, 0, 0, 0, 0);
            __syncwarp();
#undef PUT
#undef EMIT
#pragma unroll
            for (int o = 16; o > 0; o >>= 1) s1024 += __shfl_xor_sync(0xffffffffu, s1024, o);
            uint32_t w[4][4], dsk = 0;
            cp_wait_all();
            asm volatile("{\n\t.reg .pred p;\n\tsetp.eq.u32 p, %2, 0;\n\t@p ld.shared.u16 %0, [%1];\n\t}" : "+r"(dsk) : "r"(sb + M_DSK + 4 * warp + 2 * (warp & 1)), "r"(lane) : "memory");
#pragma unroll
            for (int a = 0; a < 4; a++) {
                const float v0 = (a == 0) ? fmaf(R[0][0], inv, __uint_as_float(dsk << 16)) : R[a][0] * inv;
                const float v1 = R[a][1] * inv, v2 = R[a][2] * inv, v3 = R[a][3] * inv;
                w[a][0] = pack_bf(v0, 0.f); w[a][1] = pack_bf(v1, v0); w[a][2] = pack_bf(v2, v1); w[a][3] = pack_bf(v3, v2);
            }
            const uint32_t wb = TB + 16 + 16 * g, w1 = wb + t * T_PL, w2 = wb + 256 + 2 * t * T_PL;
            const uint32_t w3 = (t == 0) ? wb + 256 + 3 * T_PL : TB + T_A + 8 * (16 * t + g);
            const uint32_t w3s = (t == 0) ? 128 : 64, w3o = (t == 0) ? 8 : 12;
            const uint32_t k512 = __shfl_sync(0xffffffffu, w[2][1], 2);
#pragma unroll
            for (int a = 0; a < 2; a++) {
                sts128(w1 + 128 * a, w[a][0], w[a][1], w[a][2], w[a][3]);
                const uint32_t(&q)[4] = w[2 + a];
                if (t < 2) sts128(w2 + 128 * a, q[0], q[1], q[2], q[3]);
                if (t == 0) { sts128(w2 + T_PL + 128 * a, q[0], q[1], q[2], q[3]); sts32(w3 + 128 * a + 4, q[2]); }
                sts32_if(t != 1 && (a == 1 || lane != 2), w3 + w3s * a, q[1]);
                sts32_if(t != 1, w3 + w3s * a + w3o, q[3]);
            }
            sts128_if(lane < 4, w1 + 512, t == 3 ? k512 : k512 >> 16, t < 2 ? k512 : t == 2 ? k512 & 0xffff0000u : k512 << 16, t < 2 ? k512 << 16 : 0u, 0);
            __syncwarp();
#pragma unroll
            for (int a = 0; a < 2; a++) {
                sts16(w1 + 128 * a + 18, w[a][3]);
                const uint32_t(&q)[4] = w[2 + a];
                if (t < 2) sts16(w2 + 128 * a + 18, q[3]);
                if (t == 0) { sts16(w2 + T_PL + 128 * a + 18, q[3]); sts16(w3 + 128 * a + 14, q[3]); }
            }
            if (t == 0) sts16(w3 + 128 - 4, w[3][0]);
            if (lane == 2 || (t == 0 && g > 0)) sts16(lane == 2 ? TB + 16 + 3 * T_PL + 4 * 127 : w3 - 4, w[2][0]);
            {
                float q[4];
#pragma unroll
                for (int i = 0; i < 4; i++) q[i] = (t < 2 ? R[4][i] : R[5][i]) * inv;
                const uint32_t b0 = pack_bf(q[0], q[2]), b1 = pack_bf(q[1], q[3]);
                const uint32_t wq = TB + T_B + 8 * (65 + 32 * (t & 1) + 4 * (t & 2) + g);
                sts32(wq, b0); sts32(wq + 12, b0); sts32(wq + 128, b1); sts32(wq + 140, b1);
            }
            cfix = pack_bf(s1024 * inv, s1024 * inv);
            if (lane == 0) sts32(TB + T_A + 8 * 64, cfix);
            __syncwarp();
        }
        WSTAMP(1);

        mbar_wait(bars + 8 * B_U);
        WSTAMP(2);

        float D[16][4];
        {
            const int x5 = g - t + 5;
            const uint32_t tabD = TB + (x5 & 3) * T_PL + (x5 & 12) + 16;
            {
                const uint32_t a1 = lds32(tabD - 8), a0 = p.zero;
#pragma unroll
                for (int jq = 0; jq < 4; jq++) {
                    uint32_t b[4];
                    ldsm4(UB + (9 + lane) * 16 + jq * 512, b[0], b[1], b[2], b[3]);
#pragma unroll
                    for (int i = 0; i < 4; i++) mma_bf_k8z(D[4 * jq + i], a0, a1, b[i]);
                }
            }
            const uint32_t ua = UB + (mi & 1) * U_PL + (8 + 8 * (mi >> 1) + r) * 16;
#pragma unroll 1
            for (int k0 = 0; k0 < 8; k0++) {
                uint32_t Uf[16][2];
#pragma unroll
                for (int jp = 0; jp < 8; jp++) ldsm4(ua + jp * 256 - k0 * 16, Uf[2 * jp][0], Uf[2 * jp][1], Uf[2 * jp + 1][0], Uf[2 * jp + 1][1]);
#pragma unroll
                for (int k1 = 0; k1 < 4; k1++) {
                    const uint32_t ta = tabD + 16 * (8 * k1 + k0);
                    const uint32_t a0 = lds32(ta), a1 = lds32(ta + 8), a2 = lds32(ta - 8), a3 = a0 ^ p.zero;
#pragma unroll
                    for (int J = k1; J < 16; J++) mma_bf(D[J], a0, a1, a2, a3, Uf[J - k1][0], Uf[J - k1][1]);
                }
                if (k0 == 0) {
                    const uint32_t ta = tabD + 16 * 32;
                    const uint32_t a0 = lds32(ta), a1 = lds32(ta + 8), a2 = lds32(ta - 8), a3 = a0 ^ p.zero;
#pragma unroll
                    for (int J = 4; J < 16; J++) mma_bf(D[J], a0, a1, a2, a3, Uf[J - 4][0], Uf[J - 4][1]);
                    const uint32_t f0 = (cfix ^ 0x80008000u) & (g == t ? 0xffffu : g == t + 4 ? 0xffff0000u : 0u);
                    const uint32_t f1 = p.zero, f2 = p.zero + p.zero, f3 = f0 ^ p.zero;
#pragma unroll
                    for (int J = 8; J < 16; J++) mma_bf(D[J], f0, f1, f2, f3, Uf[J - 8][0], Uf[J - 8][1]);
                }
            }
        }
        WSTAMP(3);
        {
            const int ch = 8 * h + warp;
            const uint32_t yo = sb + ch * 512 + ((lane ^ (((ch >> 2) << 1) | (ch & 1))) << 4);
            const uint32_t yr = mapa(yo, h ^ 1), ybr = mapa(bars + 8 * B_Y, h ^ 1);
            auto ship = [&](const int Q) {
                uint4 y[2];
#pragma unroll
                for (int hh = 0; hh < 2; hh++) {
                    const int J = 4 * Q + 2 * hh;
                    y[hh] = make_uint4(pack_bf(D[J][0], D[J][1]), pack_bf(D[J][2], D[J][3]), pack_bf(D[J + 1][0], D[J + 1][1]), pack_bf(D[J + 1][2], D[J + 1][3]));
                }
                if (!(Q & 1)) mbar_wait(bars + 8 * (B_F + (Q >> 1)));
                asm volatile("{\n\t.reg .pred p;\n\tsetp.eq.u32 p, %11, 0;\n\t"
                             "@p st.async.weak.shared::cluster.mbarrier::complete_tx::bytes.v4.b32 [%9], {%4,%5,%6,%7}, [%10];\n\t"
                             "@!p st.async.weak.shared::cluster.mbarrier::complete_tx::bytes.v4.b32 [%9], {%0,%1,%2,%3}, [%10];\n\t"
                             "@p st.shared.v4.b32 [%8], {%0,%1,%2,%3};\n\t@!p st.shared.v4.b32 [%8], {%4,%5,%6,%7};\n\t}"
                             :: "r"(y[0].x), "r"(y[0].y), "r"(y[0].z), "r"(y[0].w), "r"(y[1].x), "r"(y[1].y), "r"(y[1].z), "r"(y[1].w),
                                "r"(yo + y_off(Q)), "r"(yr + y_off(Q)), "r"(ybr + 8 * Q), "r"(h) : "memory");
                __syncwarp();
                if (lane == 0) mbar_arrive(bars + 8 * (B_Y + Q));
            };
            ship(0);
            const uint4 bA = lds128(sb + OFF_BAND + (g - t + 3) * 48), bB = lds128(sb + OFF_BAND + (g - t + 3) * 48 + 16);
            const uint2 bC = lds64(sb + OFF_BAND + (g - t + 3) * 48 + 32);
            uint2 QA[5][2], QB[8];
            const uint32_t tq = TB + 8 * (1 + g - 2 * t);
#pragma unroll
            for (int dd = 0; dd < 5; dd++) { QA[dd][0] = lds64(tq + T_A + 64 * (dd + 4)); QA[dd][1] = lds64(tq + T_A + 64 * (dd + 4) - 8); }
#pragma unroll
            for (int dd = 0; dd < 8; dd++) QB[dd] = lds64(tq + T_B + 64 * (dd + 8));
            const uint32_t u1 = UB + (mi & 1) * U_PL + (7 + r + (mi >> 1)) * 16;
            const uint32_t u2 = UB + ((mi & 1) ^ 1) * U_PL + (7 + r + (mi & 1) + 8 * (mi >> 1)) * 16;
            uint32_t n[4];
#pragma unroll
            for (int j = 0; j < 12; j++) {
                uint32_t m[4];
                ldsm4(u1 + j * 128, m[0], m[1], m[2], m[3]);
                if (!(j & 1)) ldsm4(u2 + j * 128, n[0], n[1], n[2], n[3]);
                const uint32_t n0 = n[2 * (j & 1)], n1 = n[2 * (j & 1) + 1];
                float wa[4], wb[4], wc[4], g1[4], g2[4];
                mma_bf_z(wa, bA.x, bA.y, bA.z, bA.w, m[0], m[1]);
                mma_bf_z(wb, bA.x, bA.y, bA.z, bA.w, n0, n1);
                mma_bf_z(wc, bA.x, bA.y, bA.z, bA.w, m[2], m[3]);
                if (j < 8) {
                    mma_bf_z(g1, bB.x, bB.y, bB.z, bB.w, m[0], m[1]);
                    mma_bf_z(g2, bB.x, bB.y, bB.z, bB.w, n0, n1);
                    mma_bf_k8(g1, bC.x, bC.y, m[2]);
                    mma_bf_k8(g2, bC.x, bC.y, m[3]);
                }
#pragma unroll
                for (int e = 0; e < 2; e++) {
                    const uint32_t q0 = pack_bf(wa[e], wa[e + 2]), q1 = pack_bf(wb[e], wb[e + 2]), q2 = q1 ^ p.zero, q3 = pack_bf(wc[e], wc[e + 2]);
#pragma unroll
                    for (int dd = 0; dd < 5; dd++)
                        if (j + 4 + dd < 16) mma_bf(D[j + 4 + dd], q0, q1, q2, q3, QA[dd][e].x, QA[dd][e].y);
                }
                if (j < 8) {
                    const uint32_t q0 = pack_bf(g1[0], g1[2]), q1 = pack_bf(g2[0], g2[2]), q2 = pack_bf(g1[1], g1[3]), q3 = pack_bf(g2[1], g2[3]);
#pragma unroll
                    for (int dd = 7 - j; dd >= 0; dd--) mma_bf(D[j + 8 + dd], q0, q1, q2, q3, QB[dd].x, QB[dd].y);
                }
                if ((j & 3) == 3) {
                    WSTAMP(4 + 2 * (j >> 2));
                    ship((j >> 2) + 1);
                }
            }
        }
        const int warpu = __reduce_max_sync(0xffffffffu, warp);
        mix_rows<1>(p, &tm_out, sb, sb + OFF_U + warpu * U_CH + (warpu & 1) * 64, PQ, 4, warpu, h, pr, lane);
        asm volatile("cp.async.bulk.commit_group;\n\tcp.async.bulk.wait_group.read 0;" ::: "memory");
        WSTAMP(10);
        WDUMP();
    } else if ((pw & 12) == AUX_W0) {
        const uint32_t t0 = clock();
        const int v = __reduce_max_sync(0xffffffffu, pw & 3);
        const int at = tid & 127;
        const int g = lane >> 2, t = lane & 3;
        unsigned tag;
        const bool gu = c < NGU_CTA;
        {
            const uint32_t xb = sb + (v < 2 ? OFF_XSEL : OFF_RING + 2 * 8192) + v * 8192;
            const uint32_t gws = sb + M_DPIN;
            const uint32_t row = 16 * c + 4 * v + (g >> 1);
#pragma unroll
            for (int i = 0; i < 8; i++)
                asm volatile("cp.async.ca.shared.global [%0], [%1], 4;" :: "r"((i < 4 ? sb + OFF_GP : gws) + 512 * (i & 3) + (tid & 124) * 4 + (tid & 1) * 8 + (tid & 2) * 2),
                             "l"((i < 4 ? p.wr : p.gatew) + 256 * (i & 3) + (tid & 127) * 2) : "memory");
            if ((tid & 127) < 33) cp16(sb + OFF_BAND + (tid & 127) * 16, p.band + (tid & 127));
            asm volatile("barrier.cluster.arrive.relaxed.aligned;" ::: "memory");
            tag = __reduce_max_sync(0xffffffffu, (*(volatile unsigned*)&p.sc->epoch + 1) & 0xffffu);
            if (gu) st_gpu32((uint32_t*)&p.sc->h[(tag + 1) & 1][32 * c] + at, 0);
            if (v == 2) sts32(sb + M_BMAP + lane * 4, 0);
            if (at == 0) sts32(sb + M_TAG, tag << 16);
            cp_wait_all();
            bar_sync(1, 128);
            uint2 w[16];
#pragma unroll
            for (int kb = 0; kb < 16; kb++) w[kb] = lds64((g < 4 ? sb + OFF_GP : gws) + 128 * kb + 32 * (g & 2) + 16 * t + 8 * (g & 1));
            asm volatile("barrier.cluster.wait.acquire.aligned;" ::: "memory");
            int early;
#pragma unroll 1
            while ((early = TR - (int)(clock() - t0)) > 0) __nanosleep(max(early >> 2, 32));
            mbar_wait(bars + 8 * (B_X + v));
            WSTAMP(10);
            float dr[4][4];
#pragma unroll
            for (int kb = 0; kb < 16; kb++) {
                const uint4 x = lds128(xb + (g >> 1) * 2048 + 128 * kb + 16 * (lane & 7));
                if (kb < 4) mma_bf_z(dr[kb], x.x, x.y, x.z, x.w, w[kb].x, w[kb].y);
                else mma_bf(dr[kb & 3], x.x, x.y, x.z, x.w, w[kb].x, w[kb].y);
            }
            float rs = ((dr[0][0] + dr[0][3]) + (dr[1][0] + dr[1][3])) + ((dr[2][0] + dr[2][3]) + (dr[3][0] + dr[3][3]));
            if (lane == 0) mbar_arrive(bars + 8 * (B_XE + v) + (__float_as_uint(rs) & p.zero));
            rs += __shfl_xor_sync(0xffffffffu, rs, 5);
            const uint32_t rb = pack_bf(0.f, rs);
            if (!(lane & 7)) st_gpu32((uint32_t*)p.sc->r + row, ((rb ^ (((int)rb >> 31) | 0x80000000u)) & 0xffff0000u) | tag);
            WSTAMP(1);
            {
                const int n = 3 + (lane >> 3) + 4 * (lane & 1);
                const uint32_t so = (n & 7) * S_PL + ((lane & 6) + (n >> 3)) * 32;
                const uint32_t src[2] = {sb + OFF_S + v * S_Q + s_addr(so, h), sb + OFF_S + v * S_Q + s_addr(so + 32, h)};
                const uint32_t dst = sb + OFF_U + g * U_CH + (8 + 32 * v + 16 * h + t) * 16;
                const uint32_t rdst = mapa(dst, h ^ 1), rbar = mapa(bars + 8 * B_U, h ^ 1);
                mbar_wait(bars + 8 * (B_S + v));
                WSTAMP(9);
                uint4 a[8];
#pragma unroll
                for (int b = 0; b < 2; b++) {
#pragma unroll
                    for (int j = 0; j < 8; j++) { const int u = 4 * b + (j >> 1) + 8 * (j & 1); ldsm4t((u < 8 ? src[u & 1] ^ 16 : src[u & 1]) + ((u >> 1) & 3) * 256, a[j].x, a[j].y, a[j].z, a[j].w); }
#pragma unroll
                    for (int j = 0; j < 8; j++) {
                        const int u = 4 * b + (j >> 1) + 8 * (j & 1);
                        if (u < 8) st_async16(rdst + ((u >> 1) & 3) * 64 + (u & 1) * U_PL, a[j], rbar);
                        else sts128(dst + ((u >> 1) & 3) * 64 + (u & 1) * U_PL, a[j].x, a[j].y, a[j].z, a[j].w);
                    }
                }
                if (h && v == 3) {
                    ldsm4t((src[0] ^ 16) + 1024, a[0].x, a[0].y, a[0].z, a[0].w);
                    ldsm4t(src[0] + 1024, a[1].x, a[1].y, a[1].z, a[1].w);
                    if (t == 0) {
                        st_async16(rdst + 256, make_uint4(a[0].x, a[0].y & 0xffffu, a[0].z & 0xffffu, a[0].w & 0xffffu), rbar);
                        sts128(dst + 256, a[1].x, a[1].y & 0xffffu, a[1].z & 0xffffu, a[1].w & 0xffffu);
                    }
                }
                __syncwarp();
                if (lane == 0) mbar_arrive(bars + 8 * B_U);
            }
            if ((lane & 7) == 2) st_gpu32((uint32_t*)p.sc->g + ((row & 256) << 2) + gate_pos(row), pack_bf(sigmoid_f(__uint_as_float(rb)), 0.f) | (tag << 16));
            WSTAMP(2);
        }
        {
            const bool lane0 = pin(lane, lane) == 0;
            const uint32_t own = pin(sb + OFF_XSEL + (at ^ ((at >> 1) & 4)) * 16, lane);
            float acc[8][4];
            const int krow = ((lane >> 1) & 8) + (lane & 7);
            const uint32_t tile0 = pin(sb + OFF_RING + v * 8192 + krow * 64 + ((((lane >> 3) & 1) ^ ((krow >> 1) & 3)) << 4), lane);
            const uint32_t xo = pin(sb + OFF_XSEL + (lane & 7) * XS_ROW + 512 * v + 2 * (lane & 24), lane);
            const uint32_t po = pin(sb + OFF_XSEL + t * XS_ROW + (g & 3) * 128 + (g & 1) * 64 + v * 16 + (lane >> 4) * 8, lane);
            const uint32_t po1 = pin(po + 64 - (g & 1) * 128, lane);
            uint32_t* hdst = pin((uint32_t*)&p.sc->h[tag & 1][32 * c] + at, lane);
            auto signal = [&](const int k, const uint32_t dep) {
                if (lane < 2 && v < 2)
                    asm volatile("st.async.weak.shared::cluster.mbarrier::complete_tx::bytes.b32 [%0], %1, [%2];"
                                 :: "r"(mapa(sb + M_SINK, lane)), "r"(dep), "r"(mapa(bars + 8 * (B_F + k), lane)) : "memory");
            };
            uint32_t a[16][4], b[2][4];
            auto load_a = [&](const uint32_t tile) {
#pragma unroll
                for (int q = 0; q < 16; q++) ldsm4t((tile ^ ((q & 1) << 5)) + ((q >> 1) & 1) * 4096 + (q >> 2) * 1024, a[q][0], a[q][1], a[q][2], a[q][3]);
            };
            auto load_b = [&](const uint32_t x) { ldsm4(x, b[0][0], b[0][1], b[0][2], b[0][3]); ldsm4(x + 64, b[1][0], b[1][1], b[1][2], b[1][3]); };
            auto burst = [&](const bool first) {
#pragma unroll
                for (int q = 0; q < 16; q++) {
                    if (first && q < 8) mma_bf_z(acc[q], a[q][0], a[q][1], a[q][2], a[q][3], b[0][(q >> 1) & 2], b[0][((q >> 1) & 2) + 1]);
                    else mma_bf(acc[q & 7], a[q][0], a[q][1], a[q][2], a[q][3], b[q >> 3][(q >> 1) & 2], b[q >> 3][((q >> 1) & 2) + 1]);
                }
            };
            if (gu) {
                mbar_wait(bars + 8 * (B_W + v));
                load_a(tile0);
                uint32_t dep = p.zero;
#pragma unroll
                for (int q = 0; q < 16; q += 2) dep &= a[q][0] & a[q + 1][0];
                if (lane == 0) mbar_arrive(bars + 8 * (B_E + v) + dep);
            }
            WSTAMP(11);
            uint32_t top;
#pragma unroll 1
            for (int it = 0; it < (1 << 22); it++) {
                asm volatile("ld.relaxed.gpu.global.u32 %0, [%1];" : "=r"(top) : "l"(&p.sc->top[c % NTOP][g]) : "memory");
                if (__all_sync(0xffffffffu, ((top ^ (tag << 11)) & 0xf800u) == 0)) break;
                __nanosleep(40);
            }
            WSTAMP(3);
            if (gu) {
                const uint32_t k = 4 * h + v, row = __reduce_max_sync(0xffffffffu, lane == 4 * k ? ~top & 2047 : 0);
                asm volatile("{\n\t.reg .pred p;\n\telect.sync _|p, 0xffffffff;\n\t"
                             "@p cp.async.bulk.shared::cluster.global.mbarrier::complete_tx::bytes.multicast::cluster [%0], [%1], 2048, [%2], %3;\n\t}"
                    :: "r"(sb + OFF_XSEL + k * XS_ROW), "l"(p.u + (size_t)row * D_), "r"(bars + 8 * B_G), "h"((unsigned short)3) : "memory");
            }
            if (v == 2) {
                const uint32_t row = ~top & 2047;
                if (t == 0 && ((row >> 8) & 1) == h)
                    asm volatile("red.shared.or.b32 [%0], %1;" :: "r"(sb + M_BMAP + (row & 7) * 16 + (row >> 9) * 4), "r"(1u << (gate_pos(row) & 31)) : "memory");
                if (t == 0) sts32(sb + M_TOP + lane, top);
                if (c == 0 && lane == 0) *(volatile unsigned*)&p.sc->epoch = tag;
                __syncwarp();
                if (lane0) mbar_arrive(bars + 8 * B_Y);
            }
            if (gu) {
                mbar_wait(bars + 8 * B_G);
                WSTAMP(4);
                load_b(xo);
                burst(true);
#pragma unroll
                for (int i = 1; i < 4; i++) {
                    mbar_wait(bars + 8 * (B_W + 4 * i + v));
                    load_b(xo + 128 * i);
                    load_a(tile0 + (4 * i + v < 14 ? i : 0) * 32768);
                    if (lane0 && i > 1) mbar_arrive(bars + 8 * (B_E + 4 * i - 4 + v));
                    if (i == 2) signal(0, 0);
                    sched_fence();
                    burst(false);
                    sched_fence();
                }
                WSTAMP(5);
                __syncwarp();
#pragma unroll
                for (int q = 0; q < 4; q++) {
                    const int ct = q >> 1, e = 2 * (q & 1);
                    sts128(own + q * XS_ROW,
                           __float_as_uint(acc[ct][e] + acc[4 + ct][e]), __float_as_uint(acc[2 + ct][e] + acc[6 + ct][e]),
                           __float_as_uint(acc[ct][e + 1] + acc[4 + ct][e + 1]), __float_as_uint(acc[2 + ct][e + 1] + acc[6 + ct][e + 1]));
                }
                bar_sync(1, 128);
                float sl[2], uv[2];
#pragma unroll
                for (int e = 0; e < 2; e++) {
                    uint2 q[4];
#pragma unroll
                    for (int i = 0; i < 4; i++) q[i] = lds64((e ? po1 : po) + 512 * i);
                    const float s0 = (__uint_as_float(q[0].x) + __uint_as_float(q[1].x)) + (__uint_as_float(q[2].x) + __uint_as_float(q[3].x));
                    const float s1 = (__uint_as_float(q[0].y) + __uint_as_float(q[1].y)) + (__uint_as_float(q[2].y) + __uint_as_float(q[3].y));
                    const float gv = bf_round(p.gu_swap ? s1 : s0);
                    uv[e] = p.gu_swap ? s0 : s1;
                    sl[e] = gv * sigmoid_f(gv);
                }
                const uint32_t hw = hmul2_bf(pack_bf(sl[0], sl[1]), pack_bf(uv[0], uv[1]));
                st_gpu32(hdst, hw ? hw : 0x80000000u);
                signal(1, hw);
            }
        }
        WSTAMP(6);
        {
            const uint32_t own = pin(sb + OFF_XSEL + at * 16, lane);
            const uint32_t hb = sb + (v < 2 ? OFF_XSEL + 7168 * v : OFF_RING + 8192 * v), hl = pin(hb + 16 * lane, lane);
            const int krow = ((lane >> 1) & 8) + (lane & 7);
            const uint32_t tile = pin(sb + OFF_RING + v * 8192 + krow * 32 + ((((lane >> 3) ^ (krow >> 2)) & 1) << 4), lane);
            float dd[4][4];
            bar_sync(1, 128);
            mbar_wait(bars + 8 * (B_W + HW));
            WSTAMP(12);
            uint4 hq[7];
            {
                const uint4* hs = &p.sc->h[tag & 1][32 * (56 * h + 14 * v)];
                bulk_load(hb, hs, 3584, bars + 8 * (B_X + v));
                bulk_load(hb + 3584, hs + 224, 3584, bars + 8 * (B_XE + v));
                uint32_t a[14][4];
                mbar_wait(bars + 8 * (B_W + 16 + v));
#pragma unroll
                for (int j = 0; j < 14; j++) ldsm4t(tile + (v & 2) * 16384 + j * 512, a[j][0], a[j][1], a[j][2], a[j][3]);
#pragma unroll
                for (int k = 0; k < 2; k++) {
                    mbar_wait(bars + 8 * ((k ? B_XE : B_X) + v), 1);
                    if (!k) WSTAMP(7);
                    uint32_t mn = 0xffffffffu;
#pragma unroll
                    for (int j = 0; j < 7; j++) { hq[j] = lds128(hl + 3584 * k + 512 * j); mn = min(mn, hq[j].x); }
#pragma unroll 1
                    for (int it = 0; it < (1 << 20) && !__all_sync(0xffffffffu, mn != 0); it++) {
                        mn = 0xffffffffu;
#pragma unroll
                        for (int j = 0; j < 7; j++)
                            asm volatile("{\n\t.reg .pred p;\n\tsetp.eq.u32 p, %0, 0;\n\t@p ld.relaxed.gpu.global.v4.u32 {%0,%1,%2,%3}, [%4];\n\t}"
                                         : "+r"(hq[j].x), "+r"(hq[j].y), "+r"(hq[j].z), "+r"(hq[j].w) : "l"(hs + 224 * k + 32 * j + lane) : "memory");
#pragma unroll
                        for (int j = 0; j < 7; j++) mn = min(mn, hq[j].x);
                    }
                    if (!k) {
#pragma unroll
                        for (int j = 0; j < 14; j++) {
                            const uint4& q = hq[j >> 1];
                            if (j < 4) mma_bf_z(dd[j], a[j][0], a[j][1], a[j][2], a[j][3], (j & 1) ? q.z : q.x, (j & 1) ? q.w : q.y);
                            else mma_bf(dd[j & 3], a[j][0], a[j][1], a[j][2], a[j][3], (j & 1) ? q.z : q.x, (j & 1) ? q.w : q.y);
                        }
                    }
                }
            }
            mbar_wait(bars + 8 * (B_W + 20 + v));
#pragma unroll
            for (int j = 0; j < 14; j++) {
                uint32_t f[4];
                ldsm4t(tile + 65536 + j * 512, f[0], f[1], f[2], f[3]);
                mma_bf(dd[(j + 2) & 3], f[0], f[1], f[2], f[3], (j & 1) ? hq[j >> 1].z : hq[j >> 1].x, (j & 1) ? hq[j >> 1].w : hq[j >> 1].y);
            }
            WSTAMP(8);
            uint4 part;
            part.x = __float_as_uint((dd[0][0] + dd[1][0]) + (dd[2][0] + dd[3][0])); part.y = __float_as_uint((dd[0][1] + dd[1][1]) + (dd[2][1] + dd[3][1]));
            part.z = __float_as_uint((dd[0][2] + dd[1][2]) + (dd[2][2] + dd[3][2])); part.w = __float_as_uint((dd[0][3] + dd[1][3]) + (dd[2][3] + dd[3][3]));
            st_async16(mapa(own + (M_DPIN - OFF_XSEL), h ^ 1), part, mapa(bars + 8 * B_DP, h ^ 1));
            sts128(own + 14336, part.x, part.y, part.z, part.w);
            __syncwarp();
            if (lane == 0) mbar_arrive(bars + 8 * B_DP);
        }
        WDUMP();
    } else {
        asm volatile("setmaxnreg.dec.sync.aligned.u32 64;");
        const int v = __reduce_max_sync(0xffffffffu, pw - PREP_W0);
        const bool gu = c < NGU_CTA;
        const uint32_t t0 = clock();
        const uint32_t bu = bars + 8 * v;
        if (lane == 0) { mbar_init(bu + 8 * B_X, 1); mbar_init(bu + 8 * B_S, 1); }
        __syncwarp();
        while ((uint32_t)clock() - t0 < TX) {}
        bulk_load(sb + (v < 2 ? OFF_XSEL : OFF_RING + 2 * 8192) + v * 8192, p.u + (size_t)(16 * c + 4 * v) * D_, 8192, bu + 8 * B_X);
        tma3d(sb + OFF_S + v * S_Q, &tm_x, 16 * pr, 64 * v + 32 * h - 1, bars + 8 * (B_S + v), S_Q);
        if (lane == 0) {
#pragma unroll
            for (int i = 0; i < 9; i++) mbar_init(bu + 32 * i, 1);
            mbar_init(bu + 8 * B_XE, 1);
            mbar_init(bu + 8 * B_Y, v == 0 ? 11 : 9);
            mbar_init(bu + 8 * B_DP, (0x1855 >> (4 * v)) & 15);
            mbar_init(bu + 8 * B_F, 1);
            mbar_init(bu + 8 * B_H, 1);
            asm volatile("fence.mbarrier_init.release.cluster;" ::: "memory");
            mbar_expect(bu + 8 * B_Y, 4096);
            if (v != 2) mbar_expect(bu + 8 * B_DP, v == 0 ? 2048 : (h || v == 3) ? 16384 : 16384 + 128);
            mbar_expect(bu + 8 * B_F, c < NGU_CTA ? 16 : 0);
        }
        __syncwarp();
        asm volatile("barrier.cluster.arrive.relaxed.aligned;" ::: "memory");
        WSTAMP(9);
        if (v < 3 && lane == 0) asm volatile("prefetch.tensormap [%0];" :: "l"(v == 0 ? &tm_gu : v == 1 ? &tm_down : &tm_out) : "memory");
        asm volatile("barrier.cluster.wait.acquire.aligned;" ::: "memory");
        uint32_t desc;
        {
            const int s = 6 * v + lane, i = s >> 2, w = s & 3, slot = s < 14 ? s : (s | 1) == 17 ? s - 16 : s - 12;
            const int fb = s < 4 ? B_H : (gu && s >= 14) ? B_E + slot : s < 6 ? B_XE + s - 2 : B_KG;
            desc = slot | (fb << 4) | ((i < 4 ? 256 * w + 64 * i : 1792 * h + 448 * w + 224 * (i - 4)) << 10);
            if (lane < 6) mbar_expect(bars + 8 * (B_W + s), i < 4 ? 8192 : 7168);
            if (tid == 32 * PREP_W0) mbar_arrive(bars + 8 * B_H);
        }
        if (v == 3) {
            mbar_wait(bars + 8 * B_U);
            mbar_wait(bars + 8 * (gu ? B_G : B_H + 2));
            const uint32_t tag16 = lds32(sb + M_TAG);
            uint4 q[8];
#pragma unroll 1
            for (int it = 0; it < (1 << 22); it++) {
                uint32_t bad = 0;
#pragma unroll
                for (int i = 0; i < 8; i++) q[i] = ld_gpu128(&p.sc->g[256 * h + 32 * i + lane]);
#pragma unroll
                for (int i = 0; i < 8; i++) bad |= ((q[i].x ^ tag16) | (q[i].y ^ tag16)) | ((q[i].z ^ tag16) | (q[i].w ^ tag16));
                if ((bad >> 16) == 0) break;
                __nanosleep(200);
            }
#pragma unroll
            for (int i = 0; i < 8; i++)
                asm volatile("st.shared.v2.u32 [%0], {%1, %2};" :: "r"(sb + OFF_GP + 256 * i + lane * 8),
                             "r"(__byte_perm(q[i].x, q[i].y, 0x5410)), "r"(__byte_perm(q[i].z, q[i].w, 0x5410)) : "memory");
            __syncwarp();
            if (lane == 0) mbar_arrive(bars + 8 * B_Y);
        }
        mbar_wait(bars + 8 * (B_H + v));
        {
            const int gap = v == 0 ? GAP : v == 1 ? GAP1 : v == 2 ? GAP2 : GAP3;
            uint32_t last = v ? clock() - SLACK : t0 + T0 - GAP + GAP * ((pr * 5) & 15) / 16;
#pragma unroll 1
            for (int k = 0; k < 6; k++) {
                const uint32_t dk = __reduce_max_sync(0xffffffffu, lane == k ? desc : 0);
                const bool dn = 6 * v + k >= 16;
                const uint32_t dst = sb + OFF_RING + (dk & 15) * 8192, bar = bars + 8 * (B_W + 6 * v + k), c0 = dn ? 16 * pr : 32 * c, c1 = dk >> 10;
                const CUtensorMap* tm = dn ? &tm_down : &tm_gu;
                mbar_wait(bars + ((dk >> 1) & 0x1f8));
                int late;
#pragma unroll 1
                while ((late = (int)(clock() - last) - gap) < 0) __nanosleep(max(-late >> 2, 32));
                WSTAMP(3 + k);
                if (gu || dn)
                    asm volatile("{\n\t.reg .pred p;\n\telect.sync _|p, 0xffffffff;\n\t"
                                 "@p cp.async.bulk.tensor.3d.shared::cluster.global.mbarrier::complete_tx::bytes [%0], [%1, {%3, %4, 0}], [%2];\n\t}"
                        :: "r"(dst), "l"(tm), "r"(bar), "r"(c0), "r"(c1) : "memory");
                last += gap + max(late - SLACK, 0);
            }
            if (lane == 0 && v < 3) mbar_arrive(bars + 8 * (B_H + v + 1));
        }
        {
            WSTAMP(1);
            mix_rows<2>(p, &tm_out, sb, sb + OFF_TAB + v * TAB_W, 0, PQ, v, h, pr, lane);
            WSTAMP(2);
            asm volatile("cp.async.bulk.commit_group;" ::: "memory");
            const uint32_t top = lds32(sb + M_TOP + 8 * v + 4 * (lane >> 4));
            const uint32_t row = ~top & 2047, ch = lane & 15, gp = gate_pos(row);
            const bool mine = ((row >> 8) & 1) == h;
            uint32_t gfin, x16, y16 = 0;
            asm volatile("ld.shared.u16 %0, [%1];" : "=r"(gfin) : "r"(sb + OFF_GP + gp * 2) : "memory");
            asm volatile("ld.shared.u16 %0, [%1];" : "=r"(x16) : "r"(sb + OFF_S + (row >> 9) * S_Q + s_addr((row & 7) * S_PL + 32 + (row & 248) * 4, ch >> 3) + 2 * (ch & 7)) : "memory");
            const float rsel = __uint_as_float(pin(__float_as_uint(bf_round(sigmoid_f(__uint_as_float((top ^ (((int)~top >> 31) | 0x80000000u)) & 0xffff0000u)))), lane));
            const uint32_t po = pin(sb + (4 * (ch & 7) + v) * 16 + (ch >> 3) * 8 + (lane >> 4) * 4, lane);
            bf16* op = pin(p.out + (size_t)row * D_ + 16 * pr + ch, lane);
            if (mine) {
                mbar_wait(bars + 8 * (B_Y + (row >> 9)));
                asm volatile("ld.shared.u16 %0, [%1];" : "=r"(y16)
                             : "r"(sb + y_off(row >> 9) + ch * 512 + (((4 * (row & 7) + ((row >> 5) & 3)) ^ (((ch >> 2) << 1) | (ch & 1))) << 4) + 2 * row_elem(row)) : "memory");
            }
            mbar_wait(bars + 8 * B_DP);
            float q[8];
#pragma unroll
            for (int i = 0; i < 4; i++) { q[i] = ldsf(po + M_DPIN + 512 * i); q[4 + i] = ldsf(po + OFF_XSEL + 14336 + 512 * i); }
            const float tot = ((q[0] + q[1]) + (q[2] + q[3])) + ((q[4] + q[5]) + (q[6] + q[7]));
            const float b = bf_round(__uint_as_float(x16 << 16) + bf_round(bf_round(tot) * rsel));
            if (mine) *op = __float2bfloat16_rn(fmaf(bf_lo(gfin), __uint_as_float(y16 << 16), bf_round(bf_round(1.f - bf_lo(gfin)) * b)));
        }
        asm volatile("cp.async.bulk.wait_group.read 0;" ::: "memory");
        WSTAMP(10);
        WDUMP();
    }
}

typedef CUresult (*EncodeFn)(CUtensorMap*, CUtensorMapDataType, cuuint32_t, void*, const cuuint64_t*, const cuuint64_t*,
                             const cuuint32_t*, const cuuint32_t*, CUtensorMapInterleave, CUtensorMapSwizzle,
                             CUtensorMapL2promotion, CUtensorMapFloatOOBfill);

void make_map(EncodeFn f, CUtensorMap* m, const void* ptr, uint64_t cols, uint64_t rows, uint64_t pitch, uint32_t bc, uint32_t br, CUtensorMapSwizzle sw, CUtensorMapL2promotion prom,
              uint32_t planes = 1, uint64_t plane_stride = 0, uint32_t box_planes = 0) {
    cuuint64_t dims[3] = {cols, rows, planes};
    cuuint64_t str[2] = {pitch, planes > 1 ? plane_stride : pitch * rows};
    cuuint32_t box[3] = {bc, br, box_planes ? box_planes : planes};
    cuuint32_t es[3] = {1, 1, 1};
    f(m, CU_TENSOR_MAP_DATA_TYPE_BFLOAT16, 3, (void*)ptr, dims, str, box, es, CU_TENSOR_MAP_INTERLEAVE_NONE, sw,
      prom, CU_TENSOR_MAP_FLOAT_OOB_FILL_NONE);
}

}

extern "C" void kernel_launch(void* const* d_in, const int* in_sizes, int n_in, void* d_out, int out_size) {
    static EncodeFn enc = nullptr;
    static void *sc = nullptr, *band = nullptr;
    if (!enc) {
        void* fn = nullptr;
        cudaDriverEntryPointQueryResult qr;
        cudaGetDriverEntryPoint("cuTensorMapEncodeTiled", &fn, cudaEnableDefault, &qr);
        enc = (EncodeFn)fn;
        cudaGetSymbolAddress(&sc, g_scratch);
        cudaGetSymbolAddress(&band, g_band);
        cudaFuncSetAttribute(fused_kernel, cudaFuncAttributeMaxDynamicSharedMemorySize, SMEM_BYTES);
    }
    CUtensorMap tg, td, tx, to;
    const char *wg = (const char*)d_in[9], *wu = (const char*)d_in[10];
    const bool swap = wu < wg;
    make_map(enc, &tg, swap ? wu : wg, F_, D_, F_ * 2, 32, 64, CU_TENSOR_MAP_SWIZZLE_64B, CU_TENSOR_MAP_L2_PROMOTION_L2_128B, 2, swap ? wg - wu : wu - wg);
    make_map(enc, &td, d_in[11], D_, F_, D_ * 2, 16, 224, CU_TENSOR_MAP_SWIZZLE_32B, CU_TENSOR_MAP_L2_PROMOTION_L2_64B);
    make_map(enc, &tx, d_in[0], D_, L_ / 8, D_ * 16, 16, 33, CU_TENSOR_MAP_SWIZZLE_32B, CU_TENSOR_MAP_L2_PROMOTION_NONE, 8, D_ * 2);
    make_map(enc, &to, d_out, D_, L_ / 8, D_ * 16, 16, 32, CU_TENSOR_MAP_SWIZZLE_NONE, CU_TENSOR_MAP_L2_PROMOTION_NONE, 8, D_ * 2, 1);
    Params p;
    p.u = (const bf16*)d_in[0]; p.logA = (const bf16*)d_in[1]; p.Aim = (const bf16*)d_in[2];
    p.Cre = (const bf16*)d_in[3]; p.Cim = (const bf16*)d_in[4]; p.logdt = (const bf16*)d_in[5];
    p.Dskip = (const bf16*)d_in[6]; p.wr = (const bf16*)d_in[8]; p.gatew = (const bf16*)d_in[12];
    p.out = (bf16*)d_out;
    p.sc = (Scratch*)sc; p.band = (const uint4*)band;
    p.gu_swap = swap;
    p.zero = 0;
    fused_kernel<<<NCTA, NTHREADS, SMEM_BYTES>>>(p, tg, td, tx, to);
}
```

```cpp
#include <cuda_runtime.h>
#include <cuda_bf16.h>
#include <cuda_fp16.h>
#include <cuda.h>
#include <stdint.h>

typedef __nv_bfloat16 bf16;

namespace {

constexpr int L_ = 2048, D_ = 1024, F_ = 3584;
constexpr int NCTA = 130;
constexpr int NTHREADS = 512;
constexpr int MAIN_W0 = 0, PREP_W0 = 8, AUX_W0 = 12;
#define TX 150
#define TR 3300
#define T0 3080
#define GAP 510
#define GAP1 515
#define GAP2 515
#define GAP3 560
#define HW 20
constexpr int SLACK = 300;
constexpr int PQ = 3;
constexpr int NGU_CTA = 112;

constexpr int OFF_RING = 0;
constexpr int OFF_SCR  = 6 * 8192;
constexpr int S_PL     = 1056;
constexpr int S_Q      = 8 * S_PL;
constexpr int OFF_S    = 114688;
constexpr int OFF_GP   = OFF_S + 4 * S_Q;
constexpr int U_PL     = 2240;
constexpr int U_CH     = 4416;
constexpr int OFF_U    = 151552;
constexpr int TAB_W    = 3200;
constexpr int T_PL     = 544;
constexpr int T_A      = 2192 - 26 * 8;
constexpr int T_B      = 2568 - 59 * 8;
constexpr int OFF_TAB  = 186880;
constexpr int OFF_XSEL = 212480;
constexpr int XS_ROW   = 2064;
constexpr int OFF_BAND = 228992;
constexpr int OFF_MISC = 229536;
constexpr int M_BARS   = OFF_MISC;
constexpr int M_DSK    = OFF_MISC + 2736;
constexpr int M_SINK   = OFF_MISC + 512;
constexpr int M_TAG    = OFF_MISC + 516;
constexpr int M_BMAP   = OFF_MISC + 528;
constexpr int M_DPIN   = OFF_MISC + 656;
constexpr int M_TOP    = OFF_MISC + 2704;
constexpr int SMEM_BYTES = OFF_MISC + 2768;
__device__ __forceinline__ uint32_t s_addr(uint32_t o, uint32_t half) { return o + (((half ^ (o >> 7)) & 1) << 4); }
__host__ __device__ constexpr uint32_t y_off(uint32_t q) { return OFF_RING + 32768 + (q & 1) * 8192 + (q >> 1) * 65536; }

constexpr int B_W = 0;
constexpr int B_E = 24;
constexpr int B_S = 36;
constexpr int B_Y = 40;
constexpr int B_DP = 44, B_U = 45, B_KG = 46, B_G = 47;
constexpr int B_F = 48;
constexpr int B_H = 60;
constexpr int B_X = 52, B_XE = 56;

struct BandTab { uint32_t w[11][12]; };
constexpr BandTab make_band() {
    BandTab b{};
    for (int cls = 0; cls < 11; cls++)
        for (int wd = 0; wd < 10; wd++) {
            const int tau = cls + 2 - 8 * ((wd < 4 ? wd : wd - 4) >> 1);
            const int lo = (wd < 4) ? ((wd & 1) ? -2 : 3) : ((wd & 1) ? -4 : -11), wid = (wd < 4 ? 3 : 7) + 2 * (wd & 1);
            b.w[cls][wd] = ((tau >= lo && tau < lo + wid) ? 0x3F80u : 0u) | ((tau - 4 >= lo && tau - 4 < lo + wid) ? 0x3F800000u : 0u);
        }
    return b;
}
constexpr int NTOP = 32;
struct Scratch {
    uint4 r[L_ / 4];
    uint4 g[L_ / 4];
    uint4 h[2][8 * F_ / 8];
    uint32_t top[NTOP][32];
    unsigned epoch;
};
__device__ __align__(128) Scratch g_scratch;
__device__ const __align__(16) BandTab g_band = make_band();

struct Params {
    const bf16 *u, *logA, *Aim, *Cre, *Cim, *logdt, *Dskip, *wr, *gatew;
    bf16* out;
    Scratch* sc;
    const uint4* band;
    uint32_t gu_swap;
    uint32_t zero;
};

#define WSTAMP(i) do {} while (0)
#define KSTAMP(i, dep) do {} while (0)
#define WDUMP() do {} while (0)
#define RSTAMP(i) do {} while (0)

__device__ __forceinline__ uint32_t smem_u32(const void* p) { return (uint32_t)__cvta_generic_to_shared(p); }
__device__ __forceinline__ void mbar_init(uint32_t b, uint32_t c) { asm volatile("mbarrier.init.shared::cta.b64 [%0], %1;" :: "r"(b), "r"(c) : "memory"); }
__device__ __forceinline__ void mbar_expect(uint32_t b, uint32_t tx) { asm volatile("mbarrier.arrive.expect_tx.shared::cta.b64 _, [%0], %1;" :: "r"(b), "r"(tx) : "memory"); }
__device__ __forceinline__ void mbar_arrive(uint32_t b) { asm volatile("mbarrier.arrive.shared::cta.b64 _, [%0];" :: "r"(b) : "memory"); }
__device__ __forceinline__ void mbar_wait(uint32_t b, uint32_t parity = 0) {
    asm volatile("{\n\t.reg .pred p;\nW%=:\n\tmbarrier.try_wait.parity.shared::cta.b64 p, [%0], %1, 20000;\n\t@!p bra W%=;\n\t}" :: "r"(b), "r"(parity) : "memory");
}
__device__ __forceinline__ uint32_t mapa(uint32_t addr, uint32_t rank) { uint32_t r; asm("mapa.shared::cluster.u32 %0, %1, %2;" : "=r"(r) : "r"(addr), "r"(rank)); return r; }
__device__ __forceinline__ void tma3d(uint32_t dst, const CUtensorMap* tm, int c0, int c1, uint32_t bar, uint32_t bytes) {
    asm volatile("{\n\t.reg .pred p;\n\telect.sync _|p, 0xffffffff;\n\t"
                 "@p mbarrier.arrive.expect_tx.shared::cta.b64 _, [%2], %5;\n\t"
                 "@p cp.async.bulk.tensor.3d.shared::cluster.global.mbarrier::complete_tx::bytes [%0], [%1, {%3, %4, 0}], [%2];\n\t}"
        :: "r"(dst), "l"(tm), "r"(bar), "r"(c0), "r"(c1), "r"(bytes) : "memory");
}
__device__ __forceinline__ void bulk_load(uint32_t dst, const void* src, uint32_t bytes, uint32_t bar) {
    asm volatile("{\n\t.reg .pred p;\n\telect.sync _|p, 0xffffffff;\n\t"
                 "@p mbarrier.arrive.expect_tx.shared::cta.b64 _, [%2], %3;\n\t"
                 "@p cp.async.bulk.shared::cluster.global.mbarrier::complete_tx::bytes [%0], [%1], %3, [%2];\n\t}"
        :: "r"(dst), "l"(src), "r"(bar), "r"(bytes) : "memory");
}
__device__ __forceinline__ void st_async16(uint32_t dst, const uint4& v, uint32_t bar) {
    asm volatile("st.async.weak.shared::cluster.mbarrier::complete_tx::bytes.v4.b32 [%0], {%1,%2,%3,%4}, [%5];"
                 :: "r"(dst), "r"(v.x), "r"(v.y), "r"(v.z), "r"(v.w), "r"(bar) : "memory");
}
__device__ __forceinline__ void bar_sync(int id, int n) { asm volatile("bar.sync %0, %1;" :: "r"(id), "r"(n) : "memory"); }
__device__ __forceinline__ void cp16(uint32_t dst, const void* src) { asm volatile("cp.async.cg.shared.global [%0], [%1], 16;" :: "r"(dst), "l"(src) : "memory"); }
__device__ __forceinline__ void cp_wait_all() { asm volatile("cp.async.wait_all;" ::: "memory"); }
__device__ __forceinline__ uint4 ld_gpu128(const void* p) { uint4 v; asm volatile("ld.relaxed.gpu.global.v4.u32 {%0,%1,%2,%3}, [%4];" : "=r"(v.x), "=r"(v.y), "=r"(v.z), "=r"(v.w) : "l"(p) : "memory"); return v; }
__device__ __forceinline__ void st_gpu32(void* p, uint32_t v) { asm volatile("st.relaxed.gpu.global.u32 [%0], %1;" :: "l"(p), "r"(v) : "memory"); }

__device__ __forceinline__ void ldsm4(uint32_t a, uint32_t& r0, uint32_t& r1, uint32_t& r2, uint32_t& r3) {
    asm volatile("ldmatrix.sync.aligned.m8n8.x4.shared.b16 {%0,%1,%2,%3}, [%4];" : "=r"(r0), "=r"(r1), "=r"(r2), "=r"(r3) : "r"(a) : "memory");
}
__device__ __forceinline__ void ldsm4t(uint32_t a, uint32_t& r0, uint32_t& r1, uint32_t& r2, uint32_t& r3) {
    asm volatile("ldmatrix.sync.aligned.m8n8.x4.trans.shared.b16 {%0,%1,%2,%3}, [%4];" : "=r"(r0), "=r"(r1), "=r"(r2), "=r"(r3) : "r"(a) : "memory");
}
__device__ __forceinline__ uint32_t lds32(uint32_t a) { uint32_t v; asm volatile("ld.shared.u32 %0, [%1];" : "=r"(v) : "r"(a) : "memory"); return v; }
__device__ __forceinline__ uint2 lds64(uint32_t a) { uint2 v; asm volatile("ld.shared.v2.u32 {%0,%1}, [%2];" : "=r"(v.x), "=r"(v.y) : "r"(a) : "memory"); return v; }
__device__ __forceinline__ uint4 lds128(uint32_t a) { uint4 v; asm volatile("ld.shared.v4.u32 {%0,%1,%2,%3}, [%4];" : "=r"(v.x), "=r"(v.y), "=r"(v.z), "=r"(v.w) : "r"(a) : "memory"); return v; }
__device__ __forceinline__ void sts32(uint32_t a, uint32_t v) { asm volatile("st.shared.u32 [%0], %1;" :: "r"(a), "r"(v) : "memory"); }
__device__ __forceinline__ void sts16(uint32_t a, uint32_t v) { asm volatile("st.shared.u16 [%0], %1;" :: "r"(a), "h"((unsigned short)v) : "memory"); }
__device__ __forceinline__ void sts128(uint32_t a, uint32_t x, uint32_t y, uint32_t z, uint32_t w) { asm volatile("st.shared.v4.u32 [%0], {%1,%2,%3,%4};" :: "r"(a), "r"(x), "r"(y), "r"(z), "r"(w) : "memory"); }
__device__ __forceinline__ float ldsf(uint32_t a) { float v; asm volatile("ld.shared.f32 %0, [%1];" : "=f"(v) : "r"(a) : "memory"); return v; }

__device__ __forceinline__ void mma_bf(float (&d)[4], uint32_t a0, uint32_t a1, uint32_t a2, uint32_t a3, uint32_t b0, uint32_t b1) {
    asm volatile("mma.sync.aligned.m16n8k16.row.col.f32.bf16.bf16.f32 {%0,%1,%2,%3}, {%4,%5,%6,%7}, {%8,%9}, {%0,%1,%2,%3};"
        : "+f"(d[0]), "+f"(d[1]), "+f"(d[2]), "+f"(d[3]) : "r"(a0), "r"(a1), "r"(a2), "r"(a3), "r"(b0), "r"(b1));
}
__device__ __forceinline__ void mma_bf_z(float (&d)[4], uint32_t a0, uint32_t a1, uint32_t a2, uint32_t a3, uint32_t b0, uint32_t b1) {
    asm volatile("mma.sync.aligned.m16n8k16.row.col.f32.bf16.bf16.f32 {%0,%1,%2,%3}, {%4,%5,%6,%7}, {%8,%9}, {%10,%10,%10,%10};"
        : "=f"(d[0]), "=f"(d[1]), "=f"(d[2]), "=f"(d[3]) : "r"(a0), "r"(a1), "r"(a2), "r"(a3), "r"(b0), "r"(b1), "f"(0.f));
}
__device__ __forceinline__ void mma_bf_k8(float (&d)[4], uint32_t a0, uint32_t a1, uint32_t b0) {
    asm volatile("mma.sync.aligned.m16n8k8.row.col.f32.bf16.bf16.f32 {%0,%1,%2,%3}, {%4,%5}, {%6}, {%0,%1,%2,%3};"
        : "+f"(d[0]), "+f"(d[1]), "+f"(d[2]), "+f"(d[3]) : "r"(a0), "r"(a1), "r"(b0));
}
__device__ __forceinline__ void mma_h(float (&d)[4], uint32_t a0, uint32_t a1, uint32_t a2, uint32_t a3, uint32_t b0, uint32_t b1) {
    asm volatile("mma.sync.aligned.m16n8k16.row.col.f32.f16.f16.f32 {%0,%1,%2,%3}, {%4,%5,%6,%7}, {%8,%9}, {%0,%1,%2,%3};"
        : "+f"(d[0]), "+f"(d[1]), "+f"(d[2]), "+f"(d[3]) : "r"(a0), "r"(a1), "r"(a2), "r"(a3), "r"(b0), "r"(b1));
}
__device__ __forceinline__ uint32_t pack_bf(float lo, float hi) { uint32_t r; asm("cvt.rn.bf16x2.f32 %0, %1, %2;" : "=r"(r) : "f"(hi), "f"(lo)); return r; }
__device__ __forceinline__ uint32_t pack_h(float lo, float hi) { uint32_t r; asm("cvt.rn.f16x2.f32 %0, %1, %2;" : "=r"(r) : "f"(hi), "f"(lo)); return r; }
__device__ __forceinline__ float bf_lo(uint32_t v) { return __uint_as_float(v << 16); }
__device__ __forceinline__ float bf_hi(uint32_t v) { return __uint_as_float(v & 0xffff0000u); }
__device__ __forceinline__ float bf_round(float x) { return __uint_as_float(pack_bf(0.f, x)); }
__device__ __forceinline__ uint32_t hmul2_bf(uint32_t a, uint32_t b) { uint32_t r; asm("mul.rn.bf16x2 %0, %1, %2;" : "=r"(r) : "r"(a), "r"(b)); return r; }
__device__ __forceinline__ float ex2f(float x) { float r; asm("ex2.approx.ftz.f32 %0, %1;" : "=f"(r) : "f"(x)); return r; }

__device__ __forceinline__ float exp_acc(float x) {
    const float t = x * 1.4426950216293335f;
    const float r = fmaf(x, 1.4426950216293335f, -t) + x * 1.9259629911266175e-8f;
    return ex2f(t) * fmaf(r, 0.6931471805599453f, 1.f);
}
__device__ __forceinline__ float sigmoid_f(float x) { return __fdividef(1.f, 1.f + ex2f(-x * 1.4426950408889634f)); }
__device__ __forceinline__ void cexp_pow(float l2, float li, float e, float& zr, float& zi) {
    const float mag = ex2f(l2 * e);
    zr = mag * __cosf(li * e);
    zi = mag * __sinf(li * e);
}
__device__ __forceinline__ uint32_t hcmul(uint32_t a, uint32_t k, uint32_t kp) {
    const __half2 A = *reinterpret_cast<const __half2*>(&a);
    const __half2 r = __hfma2(__high2half2(A), *reinterpret_cast<const __half2*>(&kp), __hmul2(__low2half2(A), *reinterpret_cast<const __half2*>(&k)));
    return *reinterpret_cast<const uint32_t*>(&r);
}
#define CMUL(orr, oi, ar, ai, br, bi) do { float _r = (ar) * (br) - (ai) * (bi); float _i = (ar) * (bi) + (ai) * (br); orr = _r; oi = _i; } while (0)
#define CSQ(orr, oi, ar, ai) do { float _r = (ar) * (ar) - (ai) * (ai); float _i = 2.f * (ar) * (ai); orr = _r; oi = _i; } while (0)

__device__ __forceinline__ void mma_bf_k8z(float (&d)[4], uint32_t a0, uint32_t a1, uint32_t b0) {
    asm volatile("mma.sync.aligned.m16n8k8.row.col.f32.bf16.bf16.f32 {%0,%1,%2,%3}, {%4,%5}, {%6}, {%7,%7,%7,%7};"
        : "=f"(d[0]), "=f"(d[1]), "=f"(d[2]), "=f"(d[3]) : "r"(a0), "r"(a1), "r"(b0), "f"(0.f));
}
__device__ __forceinline__ void mma_hh_k8(uint32_t& d0, uint32_t& d1, uint32_t a0, uint32_t a1, uint32_t b0) {
    asm volatile("mma.sync.aligned.m16n8k8.row.col.f16.f16.f16.f16 {%0,%1}, {%2,%3}, {%4}, {%5,%5};"
        : "=r"(d0), "=r"(d1) : "r"(a0), "r"(a1), "r"(b0), "r"(0));
}
__device__ __forceinline__ void sched_fence() { asm volatile("pmevent 0;" ::: "memory"); }
__device__ __forceinline__ uint32_t pin(uint32_t x, int lane) { return __shfl_sync(0xffffffffu, x, lane); }
template <class T> __device__ __forceinline__ T* pin(T* x, int lane) { return (T*)__shfl_sync(0xffffffffu, (unsigned long long)x, lane); }
__device__ __forceinline__ void sts32_if(bool on, uint32_t a, uint32_t v) {
    asm volatile("{\n\t.reg .pred p;\n\tsetp.ne.u32 p, %2, 0;\n\t@p st.shared.u32 [%0], %1;\n\t}" :: "r"(a), "r"(v), "r"((uint32_t)on) : "memory");
}
__device__ __forceinline__ void sts128_if(bool on, uint32_t a, uint32_t x, uint32_t y, uint32_t z, uint32_t w) {
    asm volatile("{\n\t.reg .pred p;\n\tsetp.ne.u32 p, %5, 0;\n\t@p st.shared.v4.u32 [%0], {%1,%2,%3,%4};\n\t}" :: "r"(a), "r"(x), "r"(y), "r"(z), "r"(w), "r"((uint32_t)on) : "memory");
}
__device__ __forceinline__ void lds128_if(bool on, uint32_t a, uint32_t (&v)[4]) {
    asm volatile("{\n\t.reg .pred p;\n\tsetp.ne.u32 p, %5, 0;\n\t@p ld.shared.v4.u32 {%0,%1,%2,%3}, [%4];\n\t}"
        : "+r"(v[0]), "+r"(v[1]), "+r"(v[2]), "+r"(v[3]) : "r"(a), "r"((uint32_t)on) : "memory");
}
__device__ __forceinline__ uint32_t hfma2_bf(uint32_t a, uint32_t b, uint32_t c) { uint32_t r; asm("fma.rn.bf16x2 %0, %1, %2, %3;" : "=r"(r) : "r"(a), "r"(b), "r"(c)); return r; }
__device__ __forceinline__ __nv_bfloat162 bcast(uint32_t a, int hi) { const __nv_bfloat162 v = *reinterpret_cast<const __nv_bfloat162*>(&a); return hi ? __high2bfloat162(v) : __low2bfloat162(v); }
__device__ __forceinline__ uint32_t hmul2_bc(uint32_t a, int hi, uint32_t b) { const __nv_bfloat162 r = __hmul2_rn(bcast(a, hi), *reinterpret_cast<const __nv_bfloat162*>(&b)); return *reinterpret_cast<const uint32_t*>(&r); }
__device__ __forceinline__ uint32_t hfma2_bc(uint32_t a, int hi, uint32_t b, uint32_t c) {
    const __nv_bfloat162 r = __hfma2(bcast(a, hi), *reinterpret_cast<const __nv_bfloat162*>(&b), *reinterpret_cast<const __nv_bfloat162*>(&c));
    return *reinterpret_cast<const uint32_t*>(&r);
}
__device__ __forceinline__ uint32_t row_elem(uint32_t row) { return ((row >> 5) & 4) | ((row >> 2) & 2) | ((row >> 4) & 1); }
__device__ __forceinline__ uint32_t gate_pos(uint32_t row) { return ((row >> 9) << 8) | ((row & 7) << 5) | (row_elem(row) << 2) | ((row >> 5) & 3); }

template <int N>
__device__ __forceinline__ void mix_rows(const Params& p, const CUtensorMap* tm_out, uint32_t sb, uint32_t ob, int Q0, int Q1, int w, int h, int pr, int lane) {
    const int g = lane >> 2, t = lane & 3, mi = lane >> 3, r = lane & 7;
    const int m8 = 16 * (g >> 2) + ((g >> 1) & 1) + 2 * (g & 1);
    uint32_t yi = sb + (4 * (r >> 1) + 2 * (mi & 1) + (r & 1)) * 512 + (((4 * w + (mi >> 1)) ^ r) << 4);
    uint32_t xs = sb + OFF_S + s_addr(w * S_PL + 32 + m8 * 32, t >> 1) + ((t & 1) << 3);
    uint32_t gs = sb + OFF_GP + w * 64 + g * 8, os = ob + m8 * 32 + t * 8;
    if (N > 1) { yi = pin(yi, lane); xs = pin(xs, lane); gs = pin(gs, lane); os = pin(os, lane); }
    mbar_wait(sb + M_BARS + 8 * B_Y);
#pragma unroll 1
    for (int Q = Q0; Q < Q1; Q++) {
        uint2 xq[N][4];
        uint32_t gg[N][2], sw[N];
#pragma unroll
        for (int n = 0; n < N; n++) {
#pragma unroll
            for (int i = 0; i < 4; i++) xq[n][i] = lds64((xs ^ (((i ^ n) & 1) << 4)) + Q * S_Q + n * 4 * S_PL + i * 128);
            const uint2 gq = lds64(gs + Q * 512 + n * 256);
            sw[n] = lds32(sb + M_BMAP + w * 16 + n * 64 + Q * 4);
            gg[n][0] = gq.x; gg[n][1] = gq.y;
#pragma unroll
            for (int i = 0; i < 4; i++) {
                const uint32_t og = hfma2_bf(gg[n][i >> 1], 0xBF80BF80u, 0x3F803F80u);
                xq[n][i].x = hmul2_bc(og, i & 1, xq[n][i].x); xq[n][i].y = hmul2_bc(og, i & 1, xq[n][i].y);
            }
        }
        mbar_wait(sb + M_BARS + 8 * (B_Y + Q));
        __syncwarp();
#pragma unroll
        for (int n = 0; n < N; n++) {
#pragma unroll
            for (int x = 0; x < 2; x++) {
                uint32_t y[4];
                ldsm4t((yi ^ (x << 5)) + y_off(Q) + n * 256, y[0], y[1], y[2], y[3]);
#pragma unroll
                for (int e = 0; e < 2; e++) {
                    uint2& o = xq[n][2 * x + e];
                    o.x = hfma2_bc(gg[n][x], e, y[2 * e], o.x); o.y = hfma2_bc(gg[n][x], e, y[2 * e + 1], o.y);
                }
            }
        }
        if ((sw[0] | sw[N - 1]) == 0) {
#pragma unroll
            for (int n = 0; n < N; n++)
#pragma unroll
                for (int i = 0; i < 4; i++)
                    asm volatile("st.shared.v2.u32 [%0], {%1, %2};" :: "r"(os + Q * 1024 + n * 4 * TAB_W + i * 128), "r"(xq[n][i].x), "r"(xq[n][i].y) : "memory");
            asm volatile("fence.proxy.async.shared::cta;" ::: "memory");
            __syncwarp();
#pragma unroll
            for (int n = 0; n < N; n++)
                asm volatile("{\n\t.reg .pred p;\n\telect.sync _|p, 0xffffffff;\n\t"
                             "@p cp.async.bulk.tensor.3d.global.shared::cta.bulk_group [%1, {%2, %3, %4}], [%0];\n\t}"
                    :: "r"(ob + 4 * n * TAB_W + Q * 1024), "l"(tm_out), "r"(16 * pr), "r"(64 * Q + 32 * h), "r"(w + 4 * n) : "memory");
        } else {
            bf16* op = p.out + (size_t)(512 * Q + 256 * h + 8 * m8 + w) * D_ + 16 * pr + 4 * t;
#pragma unroll
            for (int n = 0; n < N; n++)
#pragma unroll
                for (int i = 0; i < 4; i++)
                    if (!((sw[n] >> (4 * g)) & (1u << i))) *(uint2*)(op + (size_t)(32 * i + 4 * n) * D_) = xq[n][i];
        }
    }
}

__global__ void __cluster_dims__(2, 1, 1) __launch_bounds__(NTHREADS, 1)
fused_kernel(const Params p, const __grid_constant__ CUtensorMap tm_gu, const __grid_constant__ CUtensorMap tm_down,
             const __grid_constant__ CUtensorMap tm_x, const __grid_constant__ CUtensorMap tm_out) {
    extern __shared__ __align__(1024) unsigned char smem[];
    const uint32_t sb = smem_u32(smem);
    int tid;
    asm volatile("mov.u32 %0, %%tid.x;" : "=r"(tid));
    const int pw = tid >> 5, lane = tid & 31;
    const int c = blockIdx.x, h = c & 1, pr = c >> 1;
    const uint32_t bars = sb + M_BARS;

    uint2 v_la, v_ai, v_cr, v_ci;
    uint32_t ldt16;
    {
        const uint32_t po = c * 256 + tid;
        asm volatile("{\n\t.reg .pred p;\n\t.reg .b64 a;\n\tsetp.ne.u32 p, %16, 0;\n\t"
                     "mad.wide.u32 a, %14, 8, %9;\n\t@p ld.global.nc.L1::no_allocate.v2.u32 {%0,%1}, [a];\n\t"
                     "mad.wide.u32 a, %15, 2, %13;\n\t@p ld.global.nc.u16 %8, [a];\n\t"
                     "mad.wide.u32 a, %14, 8, %10;\n\t@p ld.global.nc.L1::no_allocate.v2.u32 {%2,%3}, [a];\n\t"
                     "mad.wide.u32 a, %14, 8, %11;\n\t@p ld.global.nc.L1::no_allocate.v2.u32 {%4,%5}, [a];\n\t"
                     "mad.wide.u32 a, %14, 8, %12;\n\t@p ld.global.nc.L1::no_allocate.v2.u32 {%6,%7}, [a];\n\t}"
            : "=r"(v_la.x), "=r"(v_la.y), "=r"(v_ai.x), "=r"(v_ai.y), "=r"(v_cr.x), "=r"(v_cr.y), "=r"(v_ci.x), "=r"(v_ci.y), "=r"(ldt16)
            : "l"(p.logA), "l"(p.Aim), "l"(p.Cre), "l"(p.Cim), "l"(p.logdt), "r"(po), "r"(po >> 5), "r"((uint32_t)(tid < 256 && c < 128)));
    }

    if (c >= 128) {
        if (c != 128) return;
        RSTAMP(5);
        const unsigned tag = (*(volatile unsigned*)&p.sc->epoch + 1) & 0xffffu;
        const uint32_t list = sb + 128;
        sts128(list + 16 * tid, 0, 0, 0, 0);
        if (tid == 0) sts32(sb + 64, 0);
        uint32_t key[4] = {tag - 1, tag - 1, tag - 1, tag - 1};
#pragma unroll 1
        for (int it = 0; it < (1 << 22); it++) {
            uint32_t a[4];
            asm volatile("{\n\t.reg .b128 o, z;\n\t.reg .b64 l, u;\n\tmov.b64 l, {%5, %5};\n\tmov.b128 z, {l, l};\n\tatom.relaxed.gpu.global.exch.b128 o, [%4], z;\n\t"
                         "mov.b128 {l, u}, o;\n\tmov.b64 {%0, %1}, l;\n\tmov.b64 {%2, %3}, u;\n\t}"
                : "=r"(a[0]), "=r"(a[1]), "=r"(a[2]), "=r"(a[3]) : "l"(&p.sc->r[tid]), "r"(tag - 1) : "memory");
#pragma unroll
            for (int i = 0; i < 4; i++) if (((a[i] ^ tag) & 0xffffu) == 0) key[i] = a[i];
            if ((((key[0] ^ tag) | (key[1] ^ tag) | (key[2] ^ tag) | (key[3] ^ tag)) & 0xffffu) == 0) break;
        }
        WSTAMP(0);
        uint32_t m = 0;
#pragma unroll
        for (int i = 0; i < 4; i++) {
            key[i] = (key[i] & 0xffff0000u) | (uint32_t)(2047 - (4 * tid + i));
            m = max(m, key[i]);
        }
        const uint32_t wm = __reduce_max_sync(0xffffffffu, m);
        if (lane == 0) sts32(sb + pw * 4, wm);
        __syncthreads();
        uint32_t thr = 0xffffffffu;
#pragma unroll
        for (int i = 0; i < 4; i++) { const uint4 q = lds128(sb + 16 * i); thr = min(thr, min(max(q.x, q.y), max(q.z, q.w))); }
        if (thr != 1) WSTAMP(1);
        if (m >= thr) {
            uint32_t pos;
            asm volatile("atom.shared.add.u32 %0, [%1], %2;" : "=r"(pos) : "r"(sb + 64), "r"(4 * ((key[0] >= thr) + (key[1] >= thr) + (key[2] >= thr) + (key[3] >= thr))) : "memory");
#pragma unroll
            for (int i = 0; i < 4; i++) if (key[i] >= thr) { sts32(list + pos, key[i]); pos += 4; }
        }
        __syncthreads();
        const uint32_t nc4 = lds32(sb + 64);
        if (nc4 != 1) WSTAMP(2);
#pragma unroll 1
        for (uint32_t j = 4 * pw; j < nc4; j += 64) {
            const uint32_t mine = lds32(list + j);
            int rank = 0;
#pragma unroll 1
            for (uint32_t i = 0; i < nc4; i += 128) rank += __popc(__ballot_sync(0xffffffffu, lds32(list + i + 4 * lane) > mine));
            if (rank < 8 && lane == 0) sts32(sb + 96 + 4 * rank, mine);
        }
        __syncthreads();
        if (tid < 8 * NTOP) st_gpu32(&p.sc->top[tid >> 3][tid & 7], lds32(sb + 96 + 4 * (tid & 7)) | ((tag & 31) << 11));
        WSTAMP(3);
        WDUMP();
        return;
    }

    WSTAMP(0);
    if (pw < 8) {
        const int d = 8 * c + pw - MAIN_W0;
        if (lane == 0) asm volatile("cp.async.ca.shared.global [%0], [%1], 4;" :: "r"(sb + M_DSK + 4 * (pw - MAIN_W0)), "l"(p.Dskip + (d & ~1)) : "memory");
        asm volatile("barrier.cluster.arrive.relaxed.aligned;" ::: "memory");
        const int warp = pw - MAIN_W0;
        asm volatile("setmaxnreg.inc.sync.aligned.u32 160;");
        const int g = lane >> 2, t = lane & 3;
        const int mi = lane >> 3, r = lane & 7;
        const uint32_t TB = sb + OFF_TAB + warp * TAB_W;
        const uint32_t UB = sb + OFF_U + warp * U_CH;
        if (mi < 2) sts128(UB + mi * U_PL + r * 16, 0, 0, 0, 0);
        if (lane < 4) sts128(TB + lane * T_PL, 0, 0, 0, 0);
        sts128(sb + OFF_SCR + warp * 8192 + lane * 16, 0x3C00u, 0x3C00u, 0x3C00u, 0x3C00u);
        asm volatile("barrier.cluster.wait.acquire.aligned;" ::: "memory");
        __syncwarp();

        uint32_t cfix;
        {
            KSTAMP(4, v_la.x ^ v_ai.x ^ v_cr.x ^ v_ci.x ^ ldt16);
            const float dt = bf_round(exp_acc(__uint_as_float(ldt16 << 16)));
            float l2[4], li[4];
            {
                const uint32_t la[2] = {v_la.x, v_la.y}, ai[2] = {v_ai.x, v_ai.y};
                const float dt2 = -1.4426950408889634f * dt;
#pragma unroll
                for (int i = 0; i < 4; i++) {
                    l2[i] = bf_round(ex2f(((i & 1) ? bf_hi(la[i >> 1]) : bf_lo(la[i >> 1])) * 1.4426950408889634f)) * dt2;
                    li[i] = ((i & 1) ? bf_hi(ai[i >> 1]) : bf_lo(ai[i >> 1])) * dt;
                }
            }
            const uint32_t SX = sb + OFF_SCR + warp * 8192;
            const uint32_t sw = SX + (lane << 4);
#define PUT(buf, row, v) sts128((buf) == 2 ? TB + (row) * T_PL + 16 + 16 * lane : ((sw + (row) * 512) ^ ((row) << 4)) + (buf) * 4096, v[0], v[1], v[2], v[3])
#define EMIT(bufa, rowa, bufb, rowb, xr, xi, k, kp) do { uint32_t pk[4], pd[4]; sched_fence(); \
                _Pragma("unroll") for (int i = 0; i < 4; i++) { pk[i] = pack_h(xr[i], xi[i]); pd[i] = hcmul(pk[i], k[i], kp[i]); } \
                PUT(bufa, rowa, pk); PUT(bufb, rowb, pd); } while (0)
#define CMUL4(orr, oi, ar, ai, br, bi) _Pragma("unroll") for (int i = 0; i < 4; i++) CMUL(orr[i], oi[i], ar[i], ai[i], br[i], bi[i])
#define CSQ4(orr, oi, ar, ai) _Pragma("unroll") for (int i = 0; i < 4; i++) CSQ(orr[i], oi[i], ar[i], ai[i])
            float z1r[4], z1i[4], z2r[4], z2i[4], z8r[4], z8i[4], z256r[4], z256i[4];
            uint32_t k4[4], k4p[4];
            float z4r[4], z4i[4];
#pragma unroll
            for (int i = 0; i < 4; i++) cexp_pow(l2[i], li[i], 1.f, z1r[i], z1i[i]);
            CSQ4(z2r, z2i, z1r, z1i);
            CSQ4(z4r, z4i, z2r, z2i);
            CSQ4(z8r, z8i, z4r, z4i);
            KSTAMP(5, __float_as_uint(z8r[3]));
            uint32_t Ya[16][4];
            float cr[4], ci[4], inv;
            {
                float w1r[4], w1i[4], ar[4], ai[4], br[4], bi[4];
                uint32_t k8[4], k8p[4];
#pragma unroll
                for (int i = 0; i < 4; i++) {
                    k8[i] = pack_h(z8r[i], -z8i[i]); k8p[i] = pack_h(z8i[i], z8r[i]);
                    CSQ(w1r[i], w1i[i], z8r[i], z8i[i]); w1i[i] = -w1i[i];
                }
                PUT(1, 0, k8);
                EMIT(0, 1, 1, 1, w1r, w1i, k8, k8p);
                CSQ4(ar, ai, w1r, w1i);            EMIT(0, 2, 1, 2, ar, ai, k8, k8p);
                CMUL4(br, bi, ar, ai, w1r, w1i);   EMIT(0, 3, 1, 3, br, bi, k8, k8p);
                CSQ4(ar, ai, ar, ai);              EMIT(0, 4, 1, 4, ar, ai, k8, k8p);
                CMUL4(ar, ai, ar, ai, w1r, w1i);   EMIT(0, 5, 1, 5, ar, ai, k8, k8p);
                CSQ4(br, bi, br, bi);              EMIT(0, 6, 1, 6, br, bi, k8, k8p);
                CMUL4(br, bi, br, bi, w1r, w1i);   EMIT(0, 7, 1, 7, br, bi, k8, k8p);
                __syncwarp();
                KSTAMP(6, 0);
                sched_fence();
                const uint32_t ab = SX + (mi & 1) * 4096 + r * 512, ax = ((mi >> 1) ^ r) << 4;
                const uint32_t vr[2] = {v_cr.x, v_cr.y}, vi[2] = {v_ci.x, v_ci.y};
                const uint32_t m2 = __vmaxu2(__vmaxu2(vr[0] & 0x7fff7fffu, vr[1] & 0x7fff7fffu), __vmaxu2(vi[0] & 0x7fff7fffu, vi[1] & 0x7fff7fffu));
                const uint32_t mx = __reduce_max_sync(0xffffffffu, max(m2, m2 << 16));
                const uint32_t e = min(max(mx >> 23, 11u), 254u);
                const float sc = __uint_as_float((264u - e) << 23);
                inv = __uint_as_float((e - 10u) << 23) * (2.f * dt);
#pragma unroll
                for (int i = 0; i < 4; i++) {
#pragma unroll
                    for (int k = 0; k < 4; k++) ldsm4(ab + (ax ^ (i << 5)) + k * 128, Ya[4 * k + i][0], Ya[4 * k + i][1], Ya[4 * k + i][2], Ya[4 * k + i][3]);
                    float tr, ti;
                    cexp_pow(l2[i], li[i], 128.f, tr, ti);
                    sts32(TB + 2176 + 256 * i + 4 * (lane ^ (8 * i)), pack_h(tr, ti));
                    sts32(TB + 2176 + 256 * i + 128 + 4 * (lane ^ (8 * i + 4)), pack_h(-ti, tr));
                    k4[i] = pack_h(z4r[i], z4i[i]); k4p[i] = pack_h(-z4i[i], z4r[i]);
                    CSQ(z256r[i], z256i[i], tr, ti);
                    cr[i] = ((i & 1) ? bf_hi(vr[i >> 1]) : bf_lo(vr[i >> 1])) * sc;
                    ci[i] = ((i & 1) ? bf_hi(vi[i >> 1]) : bf_lo(vi[i >> 1])) * sc;
                    if (i < 3) sched_fence();
                }
                __syncwarp();
            }
            KSTAMP(7, Ya[15][0]);
            const uint32_t ld0 = SX + r * 512 + ((mi ^ r) << 4), ld1 = ld0 ^ 64;
            float R[6][4], s1024;
            {
                float xr[4], xi[4], yr[4], yi[4];
                EMIT(0, 0, 0, 1, cr, ci, k4, k4p);
                CMUL4(yr, yi, cr, ci, z1r, z1i);        EMIT(0, 2, 0, 3, yr, yi, k4, k4p);
                CMUL4(xr, xi, cr, ci, z256r, z256i);    EMIT(2, 0, 2, 1, xr, xi, k4, k4p);
                CMUL4(yr, yi, yr, yi, z1r, z1i);        EMIT(0, 4, 0, 5, yr, yi, k4, k4p);
                CMUL4(cr, ci, yr, yi, z256r, z256i);    EMIT(2, 2, 2, 3, cr, ci, k4, k4p);
                CMUL4(yr, yi, yr, yi, z1r, z1i);        EMIT(0, 6, 0, 7, yr, yi, k4, k4p);
                CMUL4(xr, xi, xr, xi, z256r, z256i);    EMIT(1, 0, 1, 1, xr, xi, k4, k4p);
                CMUL4(xr, xi, xr, xi, z256r, z256i);    EMIT(1, 2, 1, 3, xr, xi, k4, k4p);
                CMUL4(xr, xi, xr, xi, z256r, z256i);
                s1024 = (xr[0] + xr[1]) + (xr[2] + xr[3]);
#pragma unroll
                for (int m = 4; m < 8; m++) {
                    if (m == 4) { CMUL4(xr, xi, xr, xi, z8r, z8i); } else { CMUL4(xr, xi, xr, xi, z256r, z256i); }
                    sched_fence();
                    const uint32_t pk[4] = {pack_h(xr[0], xi[0]), pack_h(xr[1], xi[1]), pack_h(xr[2], xi[2]), pack_h(xr[3], xi[3])};
                    PUT(1, m, pk);
                }
            }
            __syncwarp();
            {
                KSTAMP(8, 0);
                uint32_t bd[2][4] = {{0, 0, 0, 0}, {0, 0, 0, 0}};
                const bool on = (g >> 1) == t;
#pragma unroll
                for (int i = 0; i < 6; i++) { R[i][0] = R[i][1] = R[i][2] = R[i][3] = 0.f; }
                uint32_t x[2][4], y[2][4], z[2][4];
                auto fetch = [&](const int k2) {
                    const int b = k2 & 1;
                    lds128_if(on, TB + 2176 + g * 128 + 16 * (k2 ^ g), bd[b]);
                    ldsm4(((k2 & 1) ? ld1 : ld0) + (k2 >> 1) * 128, x[b][0], x[b][1], x[b][2], x[b][3]);
                    ldsm4(TB + ((r & 1) + ((r >> 1) == 2 ? 2 : 0)) * T_PL + 16 + 16 * mi + 64 * k2, y[b][0], y[b][1], y[b][2], y[b][3]);
                    ldsm4(((k2 & 1) ? ld1 : ld0) + (k2 >> 1) * 128 + 4096, z[b][0], z[b][1], z[b][2], z[b][3]);
                };
                fetch(0);
#pragma unroll
                for (int k2 = 0; k2 < 8; k2++) {
                    const int b = k2 & 1;
                    uint32_t a1[2][4];
                    if (k2 < 7) fetch(k2 + 1);
#pragma unroll
                    for (int u = 0; u < 2; u++) {
                        mma_hh_k8(a1[u][0], a1[u][1], Ya[2 * k2 + u][0], Ya[2 * k2 + u][1], bd[b][2 * u]);
                        mma_hh_k8(a1[u][2], a1[u][3], Ya[2 * k2 + u][2], Ya[2 * k2 + u][3], bd[b][2 * u + 1]);
                    }
#pragma unroll
                    for (int u = 0; u < 2; u++) {
                        const uint32_t(&a0)[4] = Ya[2 * k2 + u];
                        mma_h(R[0], a0[0], a0[1], a0[2], a0[3], x[b][2 * u], x[b][2 * u + 1]);
                        mma_h(R[2], a0[0], a0[1], a0[2], a0[3], y[b][2 * u], y[b][2 * u + 1]);
                        mma_h(R[4], a0[0], a0[1], a0[2], a0[3], z[b][2 * u], z[b][2 * u + 1]);
                        mma_h(R[1], a1[u][0], a1[u][1], a1[u][2], a1[u][3], x[b][2 * u], x[b][2 * u + 1]);
                        mma_h(R[3], a1[u][0], a1[u][1], a1[u][2], a1[u][3], y[b][2 * u], y[b][2 * u + 1]);
                        mma_h(R[5], a1[u][0], a1[u][1], a1[u][2], a1[u][3], z[b][2 * u], z[b][2 * u + 1]);
                    }
                }
            }
            __syncwarp();
            KSTAMP(9, __float_as_uint(R[3][0]));
            if (lane == 0) mbar_arrive(bars + 8 * B_KG + (__float_as_uint(R[0][0]) & __float_as_uint(R[4][0]) & p.zero));
            if (lane < 24) asm volatile("st.shared.v2.u32 [%0], {%1, %1};" :: "r"(TB + (lane < 9 ? 2176 : 2432) + 8 * lane), "r"(0) : "memory");
            __syncwarp();
#undef PUT
#undef EMIT
#pragma unroll
            for (int o = 16; o > 0; o >>= 1) s1024 += __shfl_xor_sync(0xffffffffu, s1024, o);
            uint32_t dsk = 0;
            cp_wait_all();
            asm volatile("{\n\t.reg .pred p;\n\tsetp.eq.u32 p, %2, 0;\n\t@p ld.shared.u16 %0, [%1];\n\t}" : "+r"(dsk) : "r"(sb + M_DSK + 4 * warp + 2 * (warp & 1)), "r"(lane) : "memory");
#pragma unroll
            for (int a = 0; a < 6; a++)
#pragma unroll
                for (int i = 0; i < 4; i++) R[a][i] = (a + i == 0) ? fmaf(R[0][0], inv, __uint_as_float(dsk << 16)) : R[a][i] * inv;
            const float k512 = __shfl_sync(0xffffffffu, R[4][0], 0), k516 = __shfl_sync(0xffffffffu, R[4][1], 0);
            const uint32_t w1 = TB + 16 + 16 * g + t * T_PL;
            float last;
#pragma unroll
            for (int a = 0; a < 4; a++) {
                const bool ahead = a >= 2 && t == 3;
                const float back = g == 7 ? (a ? R[a ? a - 1 : 0][3] : 0.f) : R[a][3], fwd = g == 0 ? (a == 2 ? R[3][0] : k512) : R[a][0];
                const float nb = __shfl_sync(0xffffffffu, ahead ? fwd : back, lane + (ahead ? 4 : 28));
                const float q0 = ahead ? R[a][0] : nb, q1 = ahead ? R[a][1] : R[a][0], q2 = ahead ? R[a][2] : R[a][1], q3 = ahead ? R[a][3] : R[a][2];
                last = ahead ? nb : R[a][3];
                sts128(w1 + 128 * a, pack_bf(q1, q0), pack_bf(q2, q1), pack_bf(q3, q2), pack_bf(last, q3));
            }
            {
                const float s0 = t == 3 ? k516 : k512, s1 = t < 2 ? k516 : 0.f;
                sts128_if(g == 7, w1 + 400, pack_bf(s0, last), pack_bf(s1, s0), pack_bf(0.f, s1), 0);
            }
            const uint32_t wq = TB + 8 * g + (t < 2 ? T_A + 8 * (32 + 16 * t) : T_B + 8 * (1 + 32 * t)), wq1 = wq + (t < 2 ? 12 : 128);
#pragma unroll
            for (int a = 0; a < 2; a++) {
                const uint32_t lo = pack_bf(R[4 + a][0], R[4 + a][1]), hi = pack_bf(R[4 + a][2], R[4 + a][3]);
                const uint32_t b0 = __byte_perm(lo, hi, t < 2 ? 0x1032 : 0x5410), b1 = __byte_perm(lo, hi, t < 2 ? 0x5476 : 0x7632);
                sts32_if(a == 1 || lane != 0, wq + 64 * a, b0);
                sts32(wq1 + 64 * a, b1);
                sts32_if(t >= 2, wq + 64 * a + 12, b0);
                sts32_if(t >= 2, wq + 64 * a + 140, b1);
            }
            __syncwarp();
            if (lane == 31) sts16(w1 + 146, pack_bf(R[1][3], 0.f));
            cfix = pack_bf(s1024 * inv, s1024 * inv);
            if (lane == 0) sts32(TB + T_A + 8 * 64, cfix);
            __syncwarp();
        }
        WSTAMP(1);

        mbar_wait(bars + 8 * B_U);
        WSTAMP(2);

        float D[16][4];
        {
            const int x5 = g - t + 5;
            const uint32_t tabD = TB + (x5 & 3) * T_PL + (x5 & 12) + 16;
            {
                const uint32_t a1 = lds32(tabD - 8), a0 = p.zero;
#pragma unroll
                for (int jq = 0; jq < 4; jq++) {
                    uint32_t b[4];
                    ldsm4(UB + (9 + lane) * 16 + jq * 512, b[0], b[1], b[2], b[3]);
#pragma unroll
                    for (int i = 0; i < 4; i++) mma_bf_k8z(D[4 * jq + i], a0, a1, b[i]);
                }
            }
            const uint32_t ua = UB + (mi & 1) * U_PL + (8 + 8 * (mi >> 1) + r) * 16;
#pragma unroll 1
            for (int k0 = 0; k0 < 8; k0++) {
                uint32_t Uf[16][2];
#pragma unroll
                for (int jp = 0; jp < 8; jp++) ldsm4(ua + jp * 256 - k0 * 16, Uf[2 * jp][0], Uf[2 * jp][1], Uf[2 * jp + 1][0], Uf[2 * jp + 1][1]);
#pragma unroll
                for (int k1 = 0; k1 < 4; k1++) {
                    const uint32_t ta = tabD + 16 * (8 * k1 + k0);
                    const uint32_t a0 = lds32(ta), a1 = lds32(ta + 8), a2 = lds32(ta - 8), a3 = a0 ^ p.zero;
#pragma unroll
                    for (int J = k1; J < 16; J++) mma_bf(D[J], a0, a1, a2, a3, Uf[J - k1][0], Uf[J - k1][1]);
                }
                if (k0 == 0) {
                    const uint32_t ta = tabD + 16 * 32;
                    const uint32_t a0 = lds32(ta), a1 = lds32(ta + 8), a2 = lds32(ta - 8), a3 = a0 ^ p.zero;
#pragma unroll
                    for (int J = 4; J < 16; J++) mma_bf(D[J], a0, a1, a2, a3, Uf[J - 4][0], Uf[J - 4][1]);
                    const uint32_t f0 = (cfix ^ 0x80008000u) & (g == t ? 0xffffu : g == t + 4 ? 0xffff0000u : 0u);
                    const uint32_t f1 = p.zero, f2 = p.zero + p.zero, f3 = f0 ^ p.zero;
#pragma unroll
                    for (int J = 8; J < 16; J++) mma_bf(D[J], f0, f1, f2, f3, Uf[J - 8][0], Uf[J - 8][1]);
                }
            }
        }
        WSTAMP(3);
        {
            const int ch = 8 * h + warp;
            const uint32_t yo = sb + ch * 512 + ((lane ^ (((ch >> 2) << 1) | (ch & 1))) << 4);
            const uint32_t yr = mapa(yo, h ^ 1), ybr = mapa(bars + 8 * B_Y, h ^ 1);
            auto ship = [&](const int Q) {
                uint4 y[2];
#pragma unroll
                for (int hh = 0; hh < 2; hh++) {
                    const int J = 4 * Q + 2 * hh;
                    y[hh] = make_uint4(pack_bf(D[J][0], D[J][1]), pack_bf(D[J][2], D[J][3]), pack_bf(D[J + 1][0], D[J + 1][1]), pack_bf(D[J + 1][2], D[J + 1][3]));
                }
                if (!(Q & 1)) mbar_wait(bars + 8 * (B_F + (Q >> 1)));
                asm volatile("{\n\t.reg .pred p;\n\tsetp.eq.u32 p, %11, 0;\n\t"
                             "@p st.async.weak.shared::cluster.mbarrier::complete_tx::bytes.v4.b32 [%9], {%4,%5,%6,%7}, [%10];\n\t"
                             "@!p st.async.weak.shared::cluster.mbarrier::complete_tx::bytes.v4.b32 [%9], {%0,%1,%2,%3}, [%10];\n\t"
                             "@p st.shared.v4.b32 [%8], {%0,%1,%2,%3};\n\t@!p st.shared.v4.b32 [%8], {%4,%5,%6,%7};\n\t}"
                             :: "r"(y[0].x), "r"(y[0].y), "r"(y[0].z), "r"(y[0].w), "r"(y[1].x), "r"(y[1].y), "r"(y[1].z), "r"(y[1].w),
                                "r"(yo + y_off(Q)), "r"(yr + y_off(Q)), "r"(ybr + 8 * Q), "r"(h) : "memory");
                __syncwarp();
                if (lane == 0) mbar_arrive(bars + 8 * (B_Y + Q));
            };
            ship(0);
            const uint4 bA = lds128(sb + OFF_BAND + (g - t + 3) * 48), bB = lds128(sb + OFF_BAND + (g - t + 3) * 48 + 16);
            const uint2 bC = lds64(sb + OFF_BAND + (g - t + 3) * 48 + 32);
            uint2 QA[5][2], QB[8];
            const uint32_t tq = TB + 8 * (1 + g - 2 * t);
#pragma unroll
            for (int dd = 0; dd < 5; dd++) { QA[dd][0] = lds64(tq + T_A + 64 * (dd + 4)); QA[dd][1] = lds64(tq + T_A + 64 * (dd + 4) - 8); }
#pragma unroll
            for (int dd = 0; dd < 8; dd++) QB[dd] = lds64(tq + T_B + 64 * (dd + 8));
            const uint32_t u1 = UB + (mi & 1) * U_PL + (7 + r + (mi >> 1)) * 16;
            const uint32_t u2 = UB + ((mi & 1) ^ 1) * U_PL + (7 + r + (mi & 1) + 8 * (mi >> 1)) * 16;
            uint32_t n[4];
#pragma unroll
            for (int j = 0; j < 12; j++) {
                uint32_t m[4];
                ldsm4(u1 + j * 128, m[0], m[1], m[2], m[3]);
                if (!(j & 1)) ldsm4(u2 + j * 128, n[0], n[1], n[2], n[3]);
                const uint32_t n0 = n[2 * (j & 1)], n1 = n[2 * (j & 1) + 1];
                float wa[4], wb[4], wc[4], g1[4], g2[4];
                mma_bf_z(wa, bA.x, bA.y, bA.z, bA.w, m[0], m[1]);
                mma_bf_z(wb, bA.x, bA.y, bA.z, bA.w, n0, n1);
                mma_bf_z(wc, bA.x, bA.y, bA.z, bA.w, m[2], m[3]);
                if (j < 8) {
                    mma_bf_z(g1, bB.x, bB.y, bB.z, bB.w, m[0], m[1]);
                    mma_bf_z(g2, bB.x, bB.y, bB.z, bB.w, n0, n1);
                    mma_bf_k8(g1, bC.x, bC.y, m[2]);
                    mma_bf_k8(g2, bC.x, bC.y, m[3]);
                }
#pragma unroll
                for (int e = 0; e < 2; e++) {
                    const uint32_t q0 = pack_bf(wa[e], wa[e + 2]), q1 = pack_bf(wb[e], wb[e + 2]), q2 = q1 ^ p.zero, q3 = pack_bf(wc[e], wc[e + 2]);
#pragma unroll
                    for (int dd = 0; dd < 5; dd++)
                        if (j + 4 + dd < 16) mma_bf(D[j + 4 + dd], q0, q1, q2, q3, QA[dd][e].x, QA[dd][e].y);
                }
                if (j < 8) {
                    const uint32_t q0 = pack_bf(g1[0], g1[2]), q1 = pack_bf(g2[0], g2[2]), q2 = pack_bf(g1[1], g1[3]), q3 = pack_bf(g2[1], g2[3]);
#pragma unroll
                    for (int dd = 7 - j; dd >= 0; dd--) mma_bf(D[j + 8 + dd], q0, q1, q2, q3, QB[dd].x, QB[dd].y);
                }
                if ((j & 3) == 3) {
                    WSTAMP(4 + 2 * (j >> 2));
                    ship((j >> 2) + 1);
                }
            }
        }
        const int warpu = __reduce_max_sync(0xffffffffu, warp);
        mix_rows<1>(p, &tm_out, sb, sb + OFF_U + warpu * U_CH + (warpu & 1) * 64, PQ, 4, warpu, h, pr, lane);
        asm volatile("cp.async.bulk.commit_group;\n\tcp.async.bulk.wait_group.read 0;" ::: "memory");
        WSTAMP(10);
        WDUMP();
    } else if ((pw & 12) == AUX_W0) {
        const uint32_t t0 = clock();
        const int v = __reduce_max_sync(0xffffffffu, pw & 3);
        const int at = tid & 127;
        const int g = lane >> 2, t = lane & 3;
        unsigned tag;
        const bool gu = c < NGU_CTA;
        {
            const uint32_t xb = sb + (v < 2 ? OFF_XSEL : OFF_RING + 2 * 8192) + v * 8192;
            const uint32_t gws = sb + M_DPIN;
            const uint32_t row = 16 * c + 4 * v + (g >> 1);
#pragma unroll
            for (int i = 0; i < 8; i++)
                asm volatile("cp.async.ca.shared.global [%0], [%1], 4;" :: "r"((i < 4 ? sb + OFF_GP : gws) + 512 * (i & 3) + (tid & 124) * 4 + (tid & 1) * 8 + (tid & 2) * 2),
                             "l"((i < 4 ? p.wr : p.gatew) + 256 * (i & 3) + (tid & 127) * 2) : "memory");
            if ((tid & 127) < 33) cp16(sb + OFF_BAND + (tid & 127) * 16, p.band + (tid & 127));
            asm volatile("barrier.cluster.arrive.relaxed.aligned;" ::: "memory");
            tag = __reduce_max_sync(0xffffffffu, (*(volatile unsigned*)&p.sc->epoch + 1) & 0xffffu);
            if (gu) st_gpu32((uint32_t*)&p.sc->h[(tag + 1) & 1][32 * c] + at, 0);
            if (v == 2) sts32(sb + M_BMAP + lane * 4, 0);
            if (at == 0) sts32(sb + M_TAG, tag << 16);
            cp_wait_all();
            bar_sync(1, 128);
            uint2 w[16];
#pragma unroll
            for (int kb = 0; kb < 16; kb++) w[kb] = lds64((g < 4 ? sb + OFF_GP : gws) + 128 * kb + 32 * (g & 2) + 16 * t + 8 * (g & 1));
            asm volatile("barrier.cluster.wait.acquire.aligned;" ::: "memory");
            int early;
#pragma unroll 1
            while ((early = TR - (int)(clock() - t0)) > 0) __nanosleep(max(early >> 2, 32));
            mbar_wait(bars + 8 * (B_X + v));
            WSTAMP(10);
            float dr[4][4];
#pragma unroll
            for (int kb = 0; kb < 16; kb++) {
                const uint4 x = lds128(xb + (g >> 1) * 2048 + 128 * kb + 16 * (lane & 7));
                if (kb < 4) mma_bf_z(dr[kb], x.x, x.y, x.z, x.w, w[kb].x, w[kb].y);
                else mma_bf(dr[kb & 3], x.x, x.y, x.z, x.w, w[kb].x, w[kb].y);
            }
            float rs = ((dr[0][0] + dr[0][3]) + (dr[1][0] + dr[1][3])) + ((dr[2][0] + dr[2][3]) + (dr[3][0] + dr[3][3]));
            if (lane == 0) mbar_arrive(bars + 8 * (B_XE + v) + (__float_as_uint(rs) & p.zero));
            rs += __shfl_xor_sync(0xffffffffu, rs, 5);
            const uint32_t rb = pack_bf(0.f, rs);
            if (!(lane & 7)) st_gpu32((uint32_t*)p.sc->r + row, ((rb ^ (((int)rb >> 31) | 0x80000000u)) & 0xffff0000u) | tag);
            WSTAMP(1);
            {
                const int n = 3 + (lane >> 3) + 4 * (lane & 1);
                const uint32_t so = (n & 7) * S_PL + ((lane & 6) + (n >> 3)) * 32;
                const uint32_t src[2] = {sb + OFF_S + v * S_Q + s_addr(so, h), sb + OFF_S + v * S_Q + s_addr(so + 32, h)};
                const uint32_t dst = sb + OFF_U + g * U_CH + (8 + 32 * v + 16 * h + t) * 16;
                const uint32_t rdst = mapa(dst, h ^ 1), rbar = mapa(bars + 8 * B_U, h ^ 1);
                mbar_wait(bars + 8 * (B_S + v));
                WSTAMP(9);
                uint4 a[8];
#pragma unroll
                for (int b = 0; b < 2; b++) {
#pragma unroll
                    for (int j = 0; j < 8; j++) { const int u = 4 * b + (j >> 1) + 8 * (j & 1); ldsm4t((u < 8 ? src[u & 1] ^ 16 : src[u & 1]) + ((u >> 1) & 3) * 256, a[j].x, a[j].y, a[j].z, a[j].w); }
#pragma unroll
                    for (int j = 0; j < 8; j++) {
                        const int u = 4 * b + (j >> 1) + 8 * (j & 1);
                        if (u < 8) st_async16(rdst + ((u >> 1) & 3) * 64 + (u & 1) * U_PL, a[j], rbar);
                        else sts128(dst + ((u >> 1) & 3) * 64 + (u & 1) * U_PL, a[j].x, a[j].y, a[j].z, a[j].w);
                    }
                }
                if (h && v == 3) {
                    ldsm4t((src[0] ^ 16) + 1024, a[0].x, a[0].y, a[0].z, a[0].w);
                    ldsm4t(src[0] + 1024, a[1].x, a[1].y, a[1].z, a[1].w);
                    if (t == 0) {
                        st_async16(rdst + 256, make_uint4(a[0].x, a[0].y & 0xffffu, a[0].z & 0xffffu, a[0].w & 0xffffu), rbar);
                        sts128(dst + 256, a[1].x, a[1].y & 0xffffu, a[1].z & 0xffffu, a[1].w & 0xffffu);
                    }
                }
                __syncwarp();
                if (lane == 0) mbar_arrive(bars + 8 * B_U);
            }
            if ((lane & 7) == 2) st_gpu32((uint32_t*)p.sc->g + ((row & 256) << 2) + gate_pos(row), pack_bf(sigmoid_f(__uint_as_float(rb)), 0.f) | (tag << 16));
            WSTAMP(2);
        }
        {
            const bool lane0 = pin(lane, lane) == 0;
            const uint32_t own = pin(sb + OFF_XSEL + (at ^ ((at >> 1) & 4)) * 16, lane);
            float acc[8][4];
            const int krow = ((lane >> 1) & 8) + (lane & 7);
            const uint32_t tile0 = pin(sb + OFF_RING + v * 8192 + krow * 64 + ((((lane >> 3) & 1) ^ ((krow >> 1) & 3)) << 4), lane);
            const uint32_t xo = pin(sb + OFF_XSEL + (lane & 7) * XS_ROW + 512 * v + 2 * (lane & 24), lane);
            const uint32_t po = pin(sb + OFF_XSEL + t * XS_ROW + (g & 3) * 128 + (g & 1) * 64 + v * 16 + (lane >> 4) * 8, lane);
            const uint32_t po1 = pin(po + 64 - (g & 1) * 128, lane);
            uint32_t* hdst = pin((uint32_t*)&p.sc->h[tag & 1][32 * c] + at, lane);
            auto signal = [&](const int k, const uint32_t dep) {
                if (lane < 2 && v < 2)
                    asm volatile("st.async.weak.shared::cluster.mbarrier::complete_tx::bytes.b32 [%0], %1, [%2];"
                                 :: "r"(mapa(sb + M_SINK, lane)), "r"(dep), "r"(mapa(bars + 8 * (B_F + k), lane)) : "memory");
            };
            uint32_t a[16][4], b[2][4];
            auto load_a = [&](const uint32_t tile) {
#pragma unroll
                for (int q = 0; q < 16; q++) ldsm4t((tile ^ ((q & 1) << 5)) + ((q >> 1) & 1) * 4096 + (q >> 2) * 1024, a[q][0], a[q][1], a[q][2], a[q][3]);
            };
            auto load_b = [&](const uint32_t x) { ldsm4(x, b[0][0], b[0][1], b[0][2], b[0][3]); ldsm4(x + 64, b[1][0], b[1][1], b[1][2], b[1][3]); };
            auto burst = [&](const bool first) {
#pragma unroll
                for (int q = 0; q < 16; q++) {
                    if (first && q < 8) mma_bf_z(acc[q], a[q][0], a[q][1], a[q][2], a[q][3], b[0][(q >> 1) & 2], b[0][((q >> 1) & 2) + 1]);
                    else mma_bf(acc[q & 7], a[q][0], a[q][1], a[q][2], a[q][3], b[q >> 3][(q >> 1) & 2], b[q >> 3][((q >> 1) & 2) + 1]);
                }
            };
            if (gu) {
                mbar_wait(bars + 8 * (B_W + v));
                load_a(tile0);
                uint32_t dep = p.zero;
#pragma unroll
                for (int q = 0; q < 16; q += 2) dep &= a[q][0] & a[q + 1][0];
                if (lane == 0) mbar_arrive(bars + 8 * (B_E + v) + dep);
            }
            WSTAMP(11);
            uint32_t top;
#pragma unroll 1
            for (int it = 0; it < (1 << 22); it++) {
                asm volatile("ld.relaxed.gpu.global.u32 %0, [%1];" : "=r"(top) : "l"(&p.sc->top[c % NTOP][g]) : "memory");
                if (__all_sync(0xffffffffu, ((top ^ (tag << 11)) & 0xf800u) == 0)) break;
                __nanosleep(40);
            }
            WSTAMP(3);
            if (gu) {
                const uint32_t k = 4 * h + v, row = __reduce_max_sync(0xffffffffu, lane == 4 * k ? ~top & 2047 : 0);
                asm volatile("{\n\t.reg .pred p;\n\telect.sync _|p, 0xffffffff;\n\t"
                             "@p cp.async.bulk.shared::cluster.global.mbarrier::complete_tx::bytes.multicast::cluster [%0], [%1], 2048, [%2], %3;\n\t}"
                    :: "r"(sb + OFF_XSEL + k * XS_ROW), "l"(p.u + (size_t)row * D_), "r"(bars + 8 * B_G), "h"((unsigned short)3) : "memory");
            }
            if (v == 2) {
                const uint32_t row = ~top & 2047;
                if (t == 0 && ((row >> 8) & 1) == h)
                    asm volatile("red.shared.or.b32 [%0], %1;" :: "r"(sb + M_BMAP + (row & 7) * 16 + (row >> 9) * 4), "r"(1u << (gate_pos(row) & 31)) : "memory");
                if (t == 0) sts32(sb + M_TOP + lane, top);
                if (c == 0 && lane == 0) *(volatile unsigned*)&p.sc->epoch = tag;
                __syncwarp();
                if (lane0) mbar_arrive(bars + 8 * B_Y);
            }
            if (gu) {
                mbar_wait(bars + 8 * B_G);
                WSTAMP(4);
                load_b(xo);
                burst(true);
#pragma unroll
                for (int i = 1; i < 4; i++) {
                    mbar_wait(bars + 8 * (B_W + 4 * i + v));
                    load_b(xo + 128 * i);
                    load_a(tile0 + (4 * i + v < 14 ? i : 0) * 32768);
                    if (lane0 && i > 1) mbar_arrive(bars + 8 * (B_E + 4 * i - 4 + v));
                    if (i == 2) signal(0, 0);
                    sched_fence();
                    burst(false);
                    sched_fence();
                }
                WSTAMP(5);
                __syncwarp();
#pragma unroll
                for (int q = 0; q < 4; q++) {
                    const int ct = q >> 1, e = 2 * (q & 1);
                    sts128(own + q * XS_ROW,
                           __float_as_uint(acc[ct][e] + acc[4 + ct][e]), __float_as_uint(acc[2 + ct][e] + acc[6 + ct][e]),
                           __float_as_uint(acc[ct][e + 1] + acc[4 + ct][e + 1]), __float_as_uint(acc[2 + ct][e + 1] + acc[6 + ct][e + 1]));
                }
                bar_sync(1, 128);
                float sl[2], uv[2];
#pragma unroll
                for (int e = 0; e < 2; e++) {
                    uint2 q[4];
#pragma unroll
                    for (int i = 0; i < 4; i++) q[i] = lds64((e ? po1 : po) + 512 * i);
                    const float s0 = (__uint_as_float(q[0].x) + __uint_as_float(q[1].x)) + (__uint_as_float(q[2].x) + __uint_as_float(q[3].x));
                    const float s1 = (__uint_as_float(q[0].y) + __uint_as_float(q[1].y)) + (__uint_as_float(q[2].y) + __uint_as_float(q[3].y));
                    const float gv = bf_round(p.gu_swap ? s1 : s0);
                    uv[e] = p.gu_swap ? s0 : s1;
                    sl[e] = gv * sigmoid_f(gv);
                }
                const uint32_t hw = hmul2_bf(pack_bf(sl[0], sl[1]), pack_bf(uv[0], uv[1]));
                st_gpu32(hdst, hw ? hw : 0x80000000u);
                signal(1, hw);
            }
        }
        WSTAMP(6);
        {
            const uint32_t own = pin(sb + OFF_XSEL + at * 16, lane);
            const uint32_t hb = sb + (v < 2 ? OFF_XSEL + 7168 * v : OFF_RING + 8192 * v), hl = pin(hb + 16 * lane, lane);
            const int krow = ((lane >> 1) & 8) + (lane & 7);
            const uint32_t tile = pin(sb + OFF_RING + v * 8192 + krow * 32 + ((((lane >> 3) ^ (krow >> 2)) & 1) << 4), lane);
            float dd[4][4];
            bar_sync(1, 128);
            mbar_wait(bars + 8 * (B_W + HW));
            WSTAMP(12);
            uint4 hq[7];
            {
                const uint4* hs = &p.sc->h[tag & 1][32 * (56 * h + 14 * v)];
                bulk_load(hb, hs, 3584, bars + 8 * (B_X + v));
                bulk_load(hb + 3584, hs + 224, 3584, bars + 8 * (B_XE + v));
                uint32_t a[14][4];
                mbar_wait(bars + 8 * (B_W + 16 + v));
#pragma unroll
                for (int j = 0; j < 14; j++) ldsm4t(tile + (v & 2) * 16384 + j * 512, a[j][0], a[j][1], a[j][2], a[j][3]);
#pragma unroll
                for (int k = 0; k < 2; k++) {
                    mbar_wait(bars + 8 * ((k ? B_XE : B_X) + v), 1);
                    if (!k) WSTAMP(7);
                    uint32_t mn = 0xffffffffu;
#pragma unroll
                    for (int j = 0; j < 7; j++) { hq[j] = lds128(hl + 3584 * k + 512 * j); mn = min(mn, hq[j].x); }
#pragma unroll 1
                    for (int it = 0; it < (1 << 20) && !__all_sync(0xffffffffu, mn != 0); it++) {
                        mn = 0xffffffffu;
#pragma unroll
                        for (int j = 0; j < 7; j++)
                            asm volatile("{\n\t.reg .pred p;\n\tsetp.eq.u32 p, %0, 0;\n\t@p ld.relaxed.gpu.global.v4.u32 {%0,%1,%2,%3}, [%4];\n\t}"
                                         : "+r"(hq[j].x), "+r"(hq[j].y), "+r"(hq[j].z), "+r"(hq[j].w) : "l"(hs + 224 * k + 32 * j + lane) : "memory");
#pragma unroll
                        for (int j = 0; j < 7; j++) mn = min(mn, hq[j].x);
                    }
                    if (!k) {
#pragma unroll
                        for (int j = 0; j < 14; j++) {
                            const uint4& q = hq[j >> 1];
                            if (j < 4) mma_bf_z(dd[j], a[j][0], a[j][1], a[j][2], a[j][3], (j & 1) ? q.z : q.x, (j & 1) ? q.w : q.y);
                            else mma_bf(dd[j & 3], a[j][0], a[j][1], a[j][2], a[j][3], (j & 1) ? q.z : q.x, (j & 1) ? q.w : q.y);
                        }
                    }
                }
            }
            mbar_wait(bars + 8 * (B_W + 20 + v));
#pragma unroll
            for (int j = 0; j < 14; j++) {
                uint32_t f[4];
                ldsm4t(tile + 65536 + j * 512, f[0], f[1], f[2], f[3]);
                mma_bf(dd[(j + 2) & 3], f[0], f[1], f[2], f[3], (j & 1) ? hq[j >> 1].z : hq[j >> 1].x, (j & 1) ? hq[j >> 1].w : hq[j >> 1].y);
            }
            WSTAMP(8);
            uint4 part;
            part.x = __float_as_uint((dd[0][0] + dd[1][0]) + (dd[2][0] + dd[3][0])); part.y = __float_as_uint((dd[0][1] + dd[1][1]) + (dd[2][1] + dd[3][1]));
            part.z = __float_as_uint((dd[0][2] + dd[1][2]) + (dd[2][2] + dd[3][2])); part.w = __float_as_uint((dd[0][3] + dd[1][3]) + (dd[2][3] + dd[3][3]));
            st_async16(mapa(own + (M_DPIN - OFF_XSEL), h ^ 1), part, mapa(bars + 8 * B_DP, h ^ 1));
            sts128(own + 14336, part.x, part.y, part.z, part.w);
            __syncwarp();
            if (lane == 0) mbar_arrive(bars + 8 * B_DP);
        }
        WDUMP();
    } else {
        asm volatile("setmaxnreg.dec.sync.aligned.u32 64;");
        const int v = __reduce_max_sync(0xffffffffu, pw - PREP_W0);
        const bool gu = c < NGU_CTA;
        const uint32_t t0 = clock();
        const uint32_t bu = bars + 8 * v;
        if (lane == 0) { mbar_init(bu + 8 * B_X, 1); mbar_init(bu + 8 * B_S, 1); }
        __syncwarp();
        while ((uint32_t)clock() - t0 < TX) {}
        bulk_load(sb + (v < 2 ? OFF_XSEL : OFF_RING + 2 * 8192) + v * 8192, p.u + (size_t)(16 * c + 4 * v) * D_, 8192, bu + 8 * B_X);
        tma3d(sb + OFF_S + v * S_Q, &tm_x, 16 * pr, 64 * v + 32 * h - 1, bars + 8 * (B_S + v), S_Q);
        if (lane == 0) {
#pragma unroll
            for (int i = 0; i < 9; i++) mbar_init(bu + 32 * i, 1);
            mbar_init(bu + 8 * B_XE, 1);
            mbar_init(bu + 8 * B_Y, v == 0 ? 11 : 9);
            mbar_init(bu + 8 * B_DP, (0x1855 >> (4 * v)) & 15);
            mbar_init(bu + 8 * B_F, 1);
            mbar_init(bu + 8 * B_H, 1);
            asm volatile("fence.mbarrier_init.release.cluster;" ::: "memory");
            mbar_expect(bu + 8 * B_Y, 4096);
            if (v != 2) mbar_expect(bu + 8 * B_DP, v == 0 ? 2048 : (h || v == 3) ? 16384 : 16384 + 128);
            mbar_expect(bu + 8 * B_F, c < NGU_CTA ? 16 : 0);
        }
        __syncwarp();
        asm volatile("barrier.cluster.arrive.relaxed.aligned;" ::: "memory");
        WSTAMP(9);
        if (v < 3 && lane == 0) asm volatile("prefetch.tensormap [%0];" :: "l"(v == 0 ? &tm_gu : v == 1 ? &tm_down : &tm_out) : "memory");
        asm volatile("barrier.cluster.wait.acquire.aligned;" ::: "memory");
        uint32_t desc;
        {
            const int s = 6 * v + lane, i = s >> 2, w = s & 3, slot = s < 14 ? s : (s | 1) == 17 ? s - 16 : s - 12;
            const int fb = s < 4 ? B_H : (gu && s >= 14) ? B_E + slot : s < 6 ? B_XE + s - 2 : B_KG;
            desc = slot | (fb << 4) | ((i < 4 ? 256 * w + 64 * i : 1792 * h + 448 * w + 224 * (i - 4)) << 10);
            if (lane < 6) mbar_expect(bars + 8 * (B_W + s), i < 4 ? 8192 : 7168);
            if (tid == 32 * PREP_W0) mbar_arrive(bars + 8 * B_H);
        }
        if (v == 3) {
            mbar_wait(bars + 8 * B_U);
            mbar_wait(bars + 8 * (gu ? B_G : B_H + 2));
            const uint32_t tag16 = lds32(sb + M_TAG);
            uint4 q[8];
#pragma unroll 1
            for (int it = 0; it < (1 << 22); it++) {
                uint32_t bad = 0;
#pragma unroll
                for (int i = 0; i < 8; i++) q[i] = ld_gpu128(&p.sc->g[256 * h + 32 * i + lane]);
#pragma unroll
                for (int i = 0; i < 8; i++) bad |= ((q[i].x ^ tag16) | (q[i].y ^ tag16)) | ((q[i].z ^ tag16) | (q[i].w ^ tag16));
                if ((bad >> 16) == 0) break;
                __nanosleep(200);
            }
#pragma unroll
            for (int i = 0; i < 8; i++)
                asm volatile("st.shared.v2.u32 [%0], {%1, %2};" :: "r"(sb + OFF_GP + 256 * i + lane * 8),
                             "r"(__byte_perm(q[i].x, q[i].y, 0x5410)), "r"(__byte_perm(q[i].z, q[i].w, 0x5410)) : "memory");
            __syncwarp();
            if (lane == 0) mbar_arrive(bars + 8 * B_Y);
        }
        mbar_wait(bars + 8 * (B_H + v));
        {
            const int gap = v == 0 ? GAP : v == 1 ? GAP1 : v == 2 ? GAP2 : GAP3;
            uint32_t last = v ? clock() - SLACK : t0 + T0 - GAP + GAP * ((pr * 5) & 15) / 16;
#pragma unroll 1
            for (int k = 0; k < 6; k++) {
                const uint32_t dk = __reduce_max_sync(0xffffffffu, lane == k ? desc : 0);
                const bool dn = 6 * v + k >= 16;
                const uint32_t dst = sb + OFF_RING + (dk & 15) * 8192, bar = bars + 8 * (B_W + 6 * v + k), c0 = dn ? 16 * pr : 32 * c, c1 = dk >> 10;
                const CUtensorMap* tm = dn ? &tm_down : &tm_gu;
                mbar_wait(bars + ((dk >> 1) & 0x1f8));
                int late;
#pragma unroll 1
                while ((late = (int)(clock() - last) - gap) < 0) __nanosleep(max(-late >> 2, 32));
                WSTAMP(3 + k);
                if (gu || dn)
                    asm volatile("{\n\t.reg .pred p;\n\telect.sync _|p, 0xffffffff;\n\t"
                                 "@p cp.async.bulk.tensor.3d.shared::cluster.global.mbarrier::complete_tx::bytes [%0], [%1, {%3, %4, 0}], [%2];\n\t}"
                        :: "r"(dst), "l"(tm), "r"(bar), "r"(c0), "r"(c1) : "memory");
                last += gap + max(late - SLACK, 0);
            }
            if (lane == 0 && v < 3) mbar_arrive(bars + 8 * (B_H + v + 1));
        }
        {
            WSTAMP(1);
            mix_rows<2>(p, &tm_out, sb, sb + OFF_TAB + v * TAB_W, 0, PQ, v, h, pr, lane);
            WSTAMP(2);
            asm volatile("cp.async.bulk.commit_group;" ::: "memory");
            const uint32_t top = lds32(sb + M_TOP + 8 * v + 4 * (lane >> 4));
            const uint32_t row = ~top & 2047, ch = lane & 15, gp = gate_pos(row);
            const bool mine = ((row >> 8) & 1) == h;
            uint32_t gfin, x16, y16 = 0;
            asm volatile("ld.shared.u16 %0, [%1];" : "=r"(gfin) : "r"(sb + OFF_GP + gp * 2) : "memory");
            asm volatile("ld.shared.u16 %0, [%1];" : "=r"(x16) : "r"(sb + OFF_S + (row >> 9) * S_Q + s_addr((row & 7) * S_PL + 32 + (row & 248) * 4, ch >> 3) + 2 * (ch & 7)) : "memory");
            const float rsel = __uint_as_float(pin(__float_as_uint(bf_round(sigmoid_f(__uint_as_float((top ^ (((int)~top >> 31) | 0x80000000u)) & 0xffff0000u)))), lane));
            const uint32_t po = pin(sb + (4 * (ch & 7) + v) * 16 + (ch >> 3) * 8 + (lane >> 4) * 4, lane);
            bf16* op = pin(p.out + (size_t)row * D_ + 16 * pr + ch, lane);
            if (mine) {
                mbar_wait(bars + 8 * (B_Y + (row >> 9)));
                asm volatile("ld.shared.u16 %0, [%1];" : "=r"(y16)
                             : "r"(sb + y_off(row >> 9) + ch * 512 + (((4 * (row & 7) + ((row >> 5) & 3)) ^ (((ch >> 2) << 1) | (ch & 1))) << 4) + 2 * row_elem(row)) : "memory");
            }
            mbar_wait(bars + 8 * B_DP);
            float q[8];
#pragma unroll
            for (int i = 0; i < 4; i++) { q[i] = ldsf(po + M_DPIN + 512 * i); q[4 + i] = ldsf(po + OFF_XSEL + 14336 + 512 * i); }
            const float tot = ((q[0] + q[1]) + (q[2] + q[3])) + ((q[4] + q[5]) + (q[6] + q[7]));
            const float b = bf_round(__uint_as_float(x16 << 16) + bf_round(bf_round(tot) * rsel));
            if (mine) *op = __float2bfloat16_rn(fmaf(bf_lo(gfin), __uint_as_float(y16 << 16), bf_round(bf_round(1.f - bf_lo(gfin)) * b)));
        }
        asm volatile("cp.async.bulk.wait_group.read 0;" ::: "memory");
        WSTAMP(10);
        WDUMP();
    }
}

typedef CUresult (*EncodeFn)(CUtensorMap*, CUtensorMapDataType, cuuint32_t, void*, const cuuint64_t*, const cuuint64_t*,
                             const cuuint32_t*, const cuuint32_t*, CUtensorMapInterleave, CUtensorMapSwizzle,
                             CUtensorMapL2promotion, CUtensorMapFloatOOBfill);

void make_map(EncodeFn f, CUtensorMap* m, const void* ptr, uint64_t cols, uint64_t rows, uint64_t pitch, uint32_t bc, uint32_t br, CUtensorMapSwizzle sw, CUtensorMapL2promotion prom,
              uint32_t planes = 1, uint64_t plane_stride = 0, uint32_t box_planes = 0) {
    cuuint64_t dims[3] = {cols, rows, planes};
    cuuint64_t str[2] = {pitch, planes > 1 ? plane_stride : pitch * rows};
    cuuint32_t box[3] = {bc, br, box_planes ? box_planes : planes};
    cuuint32_t es[3] = {1, 1, 1};
    f(m, CU_TENSOR_MAP_DATA_TYPE_BFLOAT16, 3, (void*)ptr, dims, str, box, es, CU_TENSOR_MAP_INTERLEAVE_NONE, sw,
      prom, CU_TENSOR_MAP_FLOAT_OOB_FILL_NONE);
}

}

extern "C" void kernel_launch(void* const* d_in, const int* in_sizes, int n_in, void* d_out, int out_size) {
    static EncodeFn enc = nullptr;
    static void *sc = nullptr, *band = nullptr;
    if (!enc) {
        void* fn = nullptr;
        cudaDriverEntryPointQueryResult qr;
        cudaGetDriverEntryPoint("cuTensorMapEncodeTiled", &fn, cudaEnableDefault, &qr);
        enc = (EncodeFn)fn;
        cudaGetSymbolAddress(&sc, g_scratch);
        cudaGetSymbolAddress(&band, g_band);
        cudaFuncSetAttribute(fused_kernel, cudaFuncAttributeMaxDynamicSharedMemorySize, SMEM_BYTES);
    }
    CUtensorMap tg, td, tx, to;
    const char *wg = (const char*)d_in[9], *wu = (const char*)d_in[10];
    const bool swap = wu < wg;
    make_map(enc, &tg, swap ? wu : wg, F_, D_, F_ * 2, 32, 64, CU_TENSOR_MAP_SWIZZLE_64B, CU_TENSOR_MAP_L2_PROMOTION_L2_128B, 2, swap ? wg - wu : wu - wg);
    make_map(enc, &td, d_in[11], D_, F_, D_ * 2, 16, 224, CU_TENSOR_MAP_SWIZZLE_32B, CU_TENSOR_MAP_L2_PROMOTION_L2_64B);
    make_map(enc, &tx, d_in[0], D_, L_ / 8, D_ * 16, 16, 33, CU_TENSOR_MAP_SWIZZLE_32B, CU_TENSOR_MAP_L2_PROMOTION_NONE, 8, D_ * 2);
    make_map(enc, &to, d_out, D_, L_ / 8, D_ * 16, 16, 32, CU_TENSOR_MAP_SWIZZLE_NONE, CU_TENSOR_MAP_L2_PROMOTION_NONE, 8, D_ * 2, 1);
    Params p;
    p.u = (const bf16*)d_in[0]; p.logA = (const bf16*)d_in[1]; p.Aim = (const bf16*)d_in[2];
    p.Cre = (const bf16*)d_in[3]; p.Cim = (const bf16*)d_in[4]; p.logdt = (const bf16*)d_in[5];
    p.Dskip = (const bf16*)d_in[6]; p.wr = (const bf16*)d_in[8]; p.gatew = (const bf16*)d_in[12];
    p.out = (bf16*)d_out;
    p.sc = (Scratch*)sc; p.band = (const uint4*)band;
    p.gu_swap = swap;
    p.zero = 0;
    fused_kernel<<<NCTA, NTHREADS, SMEM_BYTES>>>(p, tg, td, tx, to);
}
```

```cpp
#include <cuda_runtime.h>
#include <cuda_bf16.h>
#include <cuda_fp16.h>
#include <cuda.h>
#include <stdint.h>

typedef __nv_bfloat16 bf16;

namespace {

constexpr int L_ = 2048, D_ = 1024, F_ = 3584;
constexpr int NCTA = 130;
constexpr int NTHREADS = 512;
constexpr int MAIN_W0 = 0, PREP_W0 = 8, AUX_W0 = 12;
#define TX 150
#define TR 3300
#define T0 3080
#define GAP 510
#define GAP1 515
#define GAP2 515
#define GAP3 560
#define HW 20
constexpr int SLACK = 300;
constexpr int PQ = 3;
constexpr int NGU_CTA = 112;

constexpr int OFF_RING = 0;
constexpr int OFF_SCR  = 6 * 8192;
constexpr int S_PL     = 1056;
constexpr int S_Q      = 8 * S_PL;
constexpr int OFF_S    = 114688;
constexpr int OFF_GP   = OFF_S + 4 * S_Q;
constexpr int U_PL     = 2240;
constexpr int U_CH     = 4416;
constexpr int OFF_U    = 151552;
constexpr int TAB_W    = 3200;
constexpr int T_PL     = 544;
constexpr int T_A      = 2192 - 26 * 8;
constexpr int T_B      = 2568 - 59 * 8;
constexpr int OFF_TAB  = 186880;
constexpr int OFF_XSEL = 212480;
constexpr int XS_ROW   = 2064;
constexpr int OFF_BAND = 228992;
constexpr int OFF_MISC = 229536;
constexpr int M_BARS   = OFF_MISC;
constexpr int M_DSK    = OFF_MISC + 2736;
constexpr int M_SINK   = OFF_MISC + 512;
constexpr int M_TAG    = OFF_MISC + 516;
constexpr int M_BMAP   = OFF_MISC + 528;
constexpr int M_DPIN   = OFF_MISC + 656;
constexpr int M_TOP    = OFF_MISC + 2704;
constexpr int SMEM_BYTES = OFF_MISC + 2768;
__device__ __forceinline__ uint32_t s_addr(uint32_t o, uint32_t half) { return o + (((half ^ (o >> 7)) & 1) << 4); }
__host__ __device__ constexpr uint32_t y_off(uint32_t q) { return OFF_RING + 32768 + (q & 1) * 8192 + (q >> 1) * 65536; }

constexpr int B_W = 0;
constexpr int B_E = 24;
constexpr int B_S = 36;
constexpr int B_Y = 40;
constexpr int B_DP = 44, B_U = 45, B_KG = 46, B_G = 47;
constexpr int B_F = 48;
constexpr int B_H = 60;
constexpr int B_X = 52, B_XE = 56;

struct BandTab { uint32_t w[11][12]; };
constexpr BandTab make_band() {
    BandTab b{};
    for (int cls = 0; cls < 11; cls++)
        for (int wd = 0; wd < 10; wd++) {
            const int tau = cls + 2 - 8 * ((wd < 4 ? wd : wd - 4) >> 1);
            const int lo = (wd < 4) ? ((wd & 1) ? -2 : 3) : ((wd & 1) ? -4 : -11), wid = (wd < 4 ? 3 : 7) + 2 * (wd & 1);
            b.w[cls][wd] = ((tau >= lo && tau < lo + wid) ? 0x3F80u : 0u) | ((tau - 4 >= lo && tau - 4 < lo + wid) ? 0x3F800000u : 0u);
        }
    return b;
}
constexpr int NTOP = 32;
struct Scratch {
    uint4 r[L_ / 4];
    uint4 g[L_ / 4];
    uint4 h[2][8 * F_ / 8];
    uint32_t top[NTOP][32];
    unsigned epoch;
};
__device__ __align__(128) Scratch g_scratch;
__device__ const __align__(16) BandTab g_band = make_band();

struct Params {
    const bf16 *u, *logA, *Aim, *Cre, *Cim, *logdt, *Dskip, *wr, *gatew;
    bf16* out;
    Scratch* sc;
    const uint4* band;
    uint32_t gu_swap;
    uint32_t zero;
};

#define WSTAMP(i) do {} while (0)
#define KSTAMP(i, dep) do {} while (0)
#define WDUMP() do {} while (0)
#define RSTAMP(i) do {} while (0)

__device__ __forceinline__ uint32_t smem_u32(const void* p) { return (uint32_t)__cvta_generic_to_shared(p); }
__device__ __forceinline__ void mbar_init(uint32_t b, uint32_t c) { asm volatile("mbarrier.init.shared::cta.b64 [%0], %1;" :: "r"(b), "r"(c) : "memory"); }
__device__ __forceinline__ void mbar_expect(uint32_t b, uint32_t tx) { asm volatile("mbarrier.arrive.expect_tx.shared::cta.b64 _, [%0], %1;" :: "r"(b), "r"(tx) : "memory"); }
__device__ __forceinline__ void mbar_arrive(uint32_t b) { asm volatile("mbarrier.arrive.shared::cta.b64 _, [%0];" :: "r"(b) : "memory"); }
__device__ __forceinline__ void mbar_wait(uint32_t b, uint32_t parity = 0) {
    asm volatile("{\n\t.reg .pred p;\nW%=:\n\tmbarrier.try_wait.parity.shared::cta.b64 p, [%0], %1, 20000;\n\t@!p bra W%=;\n\t}" :: "r"(b), "r"(parity) : "memory");
}
__device__ __forceinline__ uint32_t mapa(uint32_t addr, uint32_t rank) { uint32_t r; asm("mapa.shared::cluster.u32 %0, %1, %2;" : "=r"(r) : "r"(addr), "r"(rank)); return r; }
__device__ __forceinline__ void tma3d(uint32_t dst, const CUtensorMap* tm, int c0, int c1, uint32_t bar, uint32_t bytes) {
    asm volatile("{\n\t.reg .pred p;\n\telect.sync _|p, 0xffffffff;\n\t"
                 "@p mbarrier.arrive.expect_tx.shared::cta.b64 _, [%2], %5;\n\t"
                 "@p cp.async.bulk.tensor.3d.shared::cluster.global.mbarrier::complete_tx::bytes [%0], [%1, {%3, %4, 0}], [%2];\n\t}"
        :: "r"(dst), "l"(tm), "r"(bar), "r"(c0), "r"(c1), "r"(bytes) : "memory");
}
__device__ __forceinline__ void bulk_load(uint32_t dst, const void* src, uint32_t bytes, uint32_t bar) {
    asm volatile("{\n\t.reg .pred p;\n\telect.sync _|p, 0xffffffff;\n\t"
                 "@p mbarrier.arrive.expect_tx.shared::cta.b64 _, [%2], %3;\n\t"
                 "@p cp.async.bulk.shared::cluster.global.mbarrier::complete_tx::bytes [%0], [%1], %3, [%2];\n\t}"
        :: "r"(dst), "l"(src), "r"(bar), "r"(bytes) : "memory");
}
__device__ __forceinline__ void st_async16(uint32_t dst, const uint4& v, uint32_t bar) {
    asm volatile("st.async.weak.shared::cluster.mbarrier::complete_tx::bytes.v4.b32 [%0], {%1,%2,%3,%4}, [%5];"
                 :: "r"(dst), "r"(v.x), "r"(v.y), "r"(v.z), "r"(v.w), "r"(bar) : "memory");
}
__device__ __forceinline__ void bar_sync(int id, int n) { asm volatile("bar.sync %0, %1;" :: "r"(id), "r"(n) : "memory"); }
__device__ __forceinline__ void cp16(uint32_t dst, const void* src) { asm volatile("cp.async.cg.shared.global [%0], [%1], 16;" :: "r"(dst), "l"(src) : "memory"); }
__device__ __forceinline__ void cp_wait_all() { asm volatile("cp.async.wait_all;" ::: "memory"); }
__device__ __forceinline__ uint4 ld_gpu128(const void* p) { uint4 v; asm volatile("ld.relaxed.gpu.global.v4.u32 {%0,%1,%2,%3}, [%4];" : "=r"(v.x), "=r"(v.y), "=r"(v.z), "=r"(v.w) : "l"(p) : "memory"); return v; }
__device__ __forceinline__ void st_gpu32(void* p, uint32_t v) { asm volatile("st.relaxed.gpu.global.u32 [%0], %1;" :: "l"(p), "r"(v) : "memory"); }

__device__ __forceinline__ void ldsm4(uint32_t a, uint32_t& r0, uint32_t& r1, uint32_t& r2, uint32_t& r3) {
    asm volatile("ldmatrix.sync.aligned.m8n8.x4.shared.b16 {%0,%1,%2,%3}, [%4];" : "=r"(r0), "=r"(r1), "=r"(r2), "=r"(r3) : "r"(a) : "memory");
}
__device__ __forceinline__ void ldsm4t(uint32_t a, uint32_t& r0, uint32_t& r1, uint32_t& r2, uint32_t& r3) {
    asm volatile("ldmatrix.sync.aligned.m8n8.x4.trans.shared.b16 {%0,%1,%2,%3}, [%4];" : "=r"(r0), "=r"(r1), "=r"(r2), "=r"(r3) : "r"(a) : "memory");
}
__device__ __forceinline__ uint32_t lds32(uint32_t a) { uint32_t v; asm volatile("ld.shared.u32 %0, [%1];" : "=r"(v) : "r"(a) : "memory"); return v; }
__device__ __forceinline__ uint2 lds64(uint32_t a) { uint2 v; asm volatile("ld.shared.v2.u32 {%0,%1}, [%2];" : "=r"(v.x), "=r"(v.y) : "r"(a) : "memory"); return v; }
__device__ __forceinline__ uint4 lds128(uint32_t a) { uint4 v; asm volatile("ld.shared.v4.u32 {%0,%1,%2,%3}, [%4];" : "=r"(v.x), "=r"(v.y), "=r"(v.z), "=r"(v.w) : "r"(a) : "memory"); return v; }
__device__ __forceinline__ void sts32(uint32_t a, uint32_t v) { asm volatile("st.shared.u32 [%0], %1;" :: "r"(a), "r"(v) : "memory"); }
__device__ __forceinline__ void sts16(uint32_t a, uint32_t v) { asm volatile("st.shared.u16 [%0], %1;" :: "r"(a), "h"((unsigned short)v) : "memory"); }
__device__ __forceinline__ void sts128(uint32_t a, uint32_t x, uint32_t y, uint32_t z, uint32_t w) { asm volatile("st.shared.v4.u32 [%0], {%1,%2,%3,%4};" :: "r"(a), "r"(x), "r"(y), "r"(z), "r"(w) : "memory"); }
__device__ __forceinline__ float ldsf(uint32_t a) { float v; asm volatile("ld.shared.f32 %0, [%1];" : "=f"(v) : "r"(a) : "memory"); return v; }

__device__ __forceinline__ void mma_bf(float (&d)[4], uint32_t a0, uint32_t a1, uint32_t a2, uint32_t a3, uint32_t b0, uint32_t b1) {
    asm volatile("mma.sync.aligned.m16n8k16.row.col.f32.bf16.bf16.f32 {%0,%1,%2,%3}, {%4,%5,%6,%7}, {%8,%9}, {%0,%1,%2,%3};"
        : "+f"(d[0]), "+f"(d[1]), "+f"(d[2]), "+f"(d[3]) : "r"(a0), "r"(a1), "r"(a2), "r"(a3), "r"(b0), "r"(b1));
}
__device__ __forceinline__ void mma_bf_z(float (&d)[4], uint32_t a0, uint32_t a1, uint32_t a2, uint32_t a3, uint32_t b0, uint32_t b1) {
    asm volatile("mma.sync.aligned.m16n8k16.row.col.f32.bf16.bf16.f32 {%0,%1,%2,%3}, {%4,%5,%6,%7}, {%8,%9}, {%10,%10,%10,%10};"
        : "=f"(d[0]), "=f"(d[1]), "=f"(d[2]), "=f"(d[3]) : "r"(a0), "r"(a1), "r"(a2), "r"(a3), "r"(b0), "r"(b1), "f"(0.f));
}
__device__ __forceinline__ void mma_bf_k8(float (&d)[4], uint32_t a0, uint32_t a1, uint32_t b0) {
    asm volatile("mma.sync.aligned.m16n8k8.row.col.f32.bf16.bf16.f32 {%0,%1,%2,%3}, {%4,%5}, {%6}, {%0,%1,%2,%3};"
        : "+f"(d[0]), "+f"(d[1]), "+f"(d[2]), "+f"(d[3]) : "r"(a0), "r"(a1), "r"(b0));
}
__device__ __forceinline__ void mma_h(float (&d)[4], uint32_t a0, uint32_t a1, uint32_t a2, uint32_t a3, uint32_t b0, uint32_t b1) {
    asm volatile("mma.sync.aligned.m16n8k16.row.col.f32.f16.f16.f32 {%0,%1,%2,%3}, {%4,%5,%6,%7}, {%8,%9}, {%0,%1,%2,%3};"
        : "+f"(d[0]), "+f"(d[1]), "+f"(d[2]), "+f"(d[3]) : "r"(a0), "r"(a1), "r"(a2), "r"(a3), "r"(b0), "r"(b1));
}
__device__ __forceinline__ uint32_t pack_bf(float lo, float hi) { uint32_t r; asm("cvt.rn.bf16x2.f32 %0, %1, %2;" : "=r"(r) : "f"(hi), "f"(lo)); return r; }
__device__ __forceinline__ uint32_t pack_h(float lo, float hi) { uint32_t r; asm("cvt.rn.f16x2.f32 %0, %1, %2;" : "=r"(r) : "f"(hi), "f"(lo)); return r; }
__device__ __forceinline__ float bf_lo(uint32_t v) { return __uint_as_float(v << 16); }
__device__ __forceinline__ float bf_hi(uint32_t v) { return __uint_as_float(v & 0xffff0000u); }
__device__ __forceinline__ float bf_round(float x) { return __uint_as_float(pack_bf(0.f, x)); }
__device__ __forceinline__ uint32_t hmul2_bf(uint32_t a, uint32_t b) { uint32_t r; asm("mul.rn.bf16x2 %0, %1, %2;" : "=r"(r) : "r"(a), "r"(b)); return r; }
__device__ __forceinline__ float ex2f(float x) { float r; asm("ex2.approx.ftz.f32 %0, %1;" : "=f"(r) : "f"(x)); return r; }

__device__ __forceinline__ float exp_acc(float x) {
    const float t = x * 1.4426950216293335f;
    const float r = fmaf(x, 1.4426950216293335f, -t) + x * 1.9259629911266175e-8f;
    return ex2f(t) * fmaf(r, 0.6931471805599453f, 1.f);
}
__device__ __forceinline__ float sigmoid_f(float x) { return __fdividef(1.f, 1.f + ex2f(-x * 1.4426950408889634f)); }
__device__ __forceinline__ void cexp_pow(float l2, float li, float e, float& zr, float& zi) {
    const float mag = ex2f(l2 * e);
    zr = mag * __cosf(li * e);
    zi = mag * __sinf(li * e);
}
__device__ __forceinline__ uint32_t hcmul(uint32_t a, uint32_t k, uint32_t kp) {
    const __half2 A = *reinterpret_cast<const __half2*>(&a);
    const __half2 r = __hfma2(__high2half2(A), *reinterpret_cast<const __half2*>(&kp), __hmul2(__low2half2(A), *reinterpret_cast<const __half2*>(&k)));
    return *reinterpret_cast<const uint32_t*>(&r);
}
#define CMUL(orr, oi, ar, ai, br, bi) do { float _r = (ar) * (br) - (ai) * (bi); float _i = (ar) * (bi) + (ai) * (br); orr = _r; oi = _i; } while (0)
#define CSQ(orr, oi, ar, ai) do { float _r = (ar) * (ar) - (ai) * (ai); float _i = 2.f * (ar) * (ai); orr = _r; oi = _i; } while (0)

__device__ __forceinline__ void mma_bf_k8z(float (&d)[4], uint32_t a0, uint32_t a1, uint32_t b0) {
    asm volatile("mma.sync.aligned.m16n8k8.row.col.f32.bf16.bf16.f32 {%0,%1,%2,%3}, {%4,%5}, {%6}, {%7,%7,%7,%7};"
        : "=f"(d[0]), "=f"(d[1]), "=f"(d[2]), "=f"(d[3]) : "r"(a0), "r"(a1), "r"(b0), "f"(0.f));
}
__device__ __forceinline__ void mma_hh_k8(uint32_t& d0, uint32_t& d1, uint32_t a0, uint32_t a1, uint32_t b0) {
    asm volatile("mma.sync.aligned.m16n8k8.row.col.f16.f16.f16.f16 {%0,%1}, {%2,%3}, {%4}, {%5,%5};"
        : "=r"(d0), "=r"(d1) : "r"(a0), "r"(a1), "r"(b0), "r"(0));
}
__device__ __forceinline__ void sched_fence() { asm volatile("pmevent 0;" ::: "memory"); }
__device__ __forceinline__ uint32_t pin(uint32_t x, int lane) { return __shfl_sync(0xffffffffu, x, lane); }
template <class T> __device__ __forceinline__ T* pin(T* x, int lane) { return (T*)__shfl_sync(0xffffffffu, (unsigned long long)x, lane); }
__device__ __forceinline__ void sts32_if(bool on, uint32_t a, uint32_t v) {
    asm volatile("{\n\t.reg .pred p;\n\tsetp.ne.u32 p, %2, 0;\n\t@p st.shared.u32 [%0], %1;\n\t}" :: "r"(a), "r"(v), "r"((uint32_t)on) : "memory");
}
__device__ __forceinline__ void sts128_if(bool on, uint32_t a, uint32_t x, uint32_t y, uint32_t z, uint32_t w) {
    asm volatile("{\n\t.reg .pred p;\n\tsetp.ne.u32 p, %5, 0;\n\t@p st.shared.v4.u32 [%0], {%1,%2,%3,%4};\n\t}" :: "r"(a), "r"(x), "r"(y), "r"(z), "r"(w), "r"((uint32_t)on) : "memory");
}
__device__ __forceinline__ void lds128_if(bool on, uint32_t a, uint32_t (&v)[4]) {
    asm volatile("{\n\t.reg .pred p;\n\tsetp.ne.u32 p, %5, 0;\n\t@p ld.shared.v4.u32 {%0,%1,%2,%3}, [%4];\n\t}"
        : "+r"(v[0]), "+r"(v[1]), "+r"(v[2]), "+r"(v[3]) : "r"(a), "r"((uint32_t)on) : "memory");
}
__device__ __forceinline__ uint32_t hfma2_bf(uint32_t a, uint32_t b, uint32_t c) { uint32_t r; asm("fma.rn.bf16x2 %0, %1, %2, %3;" : "=r"(r) : "r"(a), "r"(b), "r"(c)); return r; }
__device__ __forceinline__ __nv_bfloat162 bcast(uint32_t a, int hi) { const __nv_bfloat162 v = *reinterpret_cast<const __nv_bfloat162*>(&a); return hi ? __high2bfloat162(v) : __low2bfloat162(v); }
__device__ __forceinline__ uint32_t hmul2_bc(uint32_t a, int hi, uint32_t b) { const __nv_bfloat162 r = __hmul2_rn(bcast(a, hi), *reinterpret_cast<const __nv_bfloat162*>(&b)); return *reinterpret_cast<const uint32_t*>(&r); }
__device__ __forceinline__ uint32_t hfma2_bc(uint32_t a, int hi, uint32_t b, uint32_t c) {
    const __nv_bfloat162 r = __hfma2(bcast(a, hi), *reinterpret_cast<const __nv_bfloat162*>(&b), *reinterpret_cast<const __nv_bfloat162*>(&c));
    return *reinterpret_cast<const uint32_t*>(&r);
}
__device__ __forceinline__ uint32_t row_elem(uint32_t row) { return ((row >> 5) & 4) | ((row >> 2) & 2) | ((row >> 4) & 1); }
__device__ __forceinline__ uint32_t gate_pos(uint32_t row) { return ((row >> 9) << 8) | ((row & 7) << 5) | (row_elem(row) << 2) | ((row >> 5) & 3); }

template <int N>
__device__ __forceinline__ void mix_rows(const Params& p, const CUtensorMap* tm_out, uint32_t sb, uint32_t ob, int Q0, int Q1, int w, int h, int pr, int lane) {
    const int g = lane >> 2, t = lane & 3, mi = lane >> 3, r = lane & 7;
    const int m8 = 16 * (g >> 2) + ((g >> 1) & 1) + 2 * (g & 1);
    uint32_t yi = sb + (4 * (r >> 1) + 2 * (mi & 1) + (r & 1)) * 512 + (((4 * w + (mi >> 1)) ^ r) << 4);
    uint32_t xs = sb + OFF_S + s_addr(w * S_PL + 32 + m8 * 32, t >> 1) + ((t & 1) << 3);
    uint32_t gs = sb + OFF_GP + w * 64 + g * 8, os = ob + m8 * 32 + t * 8;
    if (N > 1) { yi = pin(yi, lane); xs = pin(xs, lane); gs = pin(gs, lane); os = pin(os, lane); }
    mbar_wait(sb + M_BARS + 8 * B_Y);
#pragma unroll 1
    for (int Q = Q0; Q < Q1; Q++) {
        uint2 xq[N][4];
        uint32_t gg[N][2], sw[N];
#pragma unroll
        for (int n = 0; n < N; n++) {
#pragma unroll
            for (int i = 0; i < 4; i++) xq[n][i] = lds64((xs ^ (((i ^ n) & 1) << 4)) + Q * S_Q + n * 4 * S_PL + i * 128);
            const uint2 gq = lds64(gs + Q * 512 + n * 256);
            sw[n] = lds32(sb + M_BMAP + w * 16 + n * 64 + Q * 4);
            gg[n][0] = gq.x; gg[n][1] = gq.y;
#pragma unroll
            for (int i = 0; i < 4; i++) {
                const uint32_t og = hfma2_bf(gg[n][i >> 1], 0xBF80BF80u, 0x3F803F80u);
                xq[n][i].x = hmul2_bc(og, i & 1, xq[n][i].x); xq[n][i].y = hmul2_bc(og, i & 1, xq[n][i].y);
            }
        }
        mbar_wait(sb + M_BARS + 8 * (B_Y + Q));
        __syncwarp();
#pragma unroll
        for (int n = 0; n < N; n++) {
#pragma unroll
            for (int x = 0; x < 2; x++) {
                uint32_t y[4];
                ldsm4t((yi ^ (x << 5)) + y_off(Q) + n * 256, y[0], y[1], y[2], y[3]);
#pragma unroll
                for (int e = 0; e < 2; e++) {
                    uint2& o = xq[n][2 * x + e];
                    o.x = hfma2_bc(gg[n][x], e, y[2 * e], o.x); o.y = hfma2_bc(gg[n][x], e, y[2 * e + 1], o.y);
                }
            }
        }
        if ((sw[0] | sw[N - 1]) == 0) {
#pragma unroll
            for (int n = 0; n < N; n++)
#pragma unroll
                for (int i = 0; i < 4; i++)
                    asm volatile("st.shared.v2.u32 [%0], {%1, %2};" :: "r"(os + Q * 1024 + n * 4 * TAB_W + i * 128), "r"(xq[n][i].x), "r"(xq[n][i].y) : "memory");
            asm volatile("fence.proxy.async.shared::cta;" ::: "memory");
            __syncwarp();
#pragma unroll
            for (int n = 0; n < N; n++)
                asm volatile("{\n\t.reg .pred p;\n\telect.sync _|p, 0xffffffff;\n\t"
                             "@p cp.async.bulk.tensor.3d.global.shared::cta.bulk_group [%1, {%2, %3, %4}], [%0];\n\t}"
                    :: "r"(ob + 4 * n * TAB_W + Q * 1024), "l"(tm_out), "r"(16 * pr), "r"(64 * Q + 32 * h), "r"(w + 4 * n) : "memory");
        } else {
            bf16* op = p.out + (size_t)(512 * Q + 256 * h + 8 * m8 + w) * D_ + 16 * pr + 4 * t;
#pragma unroll
            for (int n = 0; n < N; n++)
#pragma unroll
                for (int i = 0; i < 4; i++)
                    if (!((sw[n] >> (4 * g)) & (1u << i))) *(uint2*)(op + (size_t)(32 * i + 4 * n) * D_) = xq[n][i];
        }
    }
}

__global__ void __cluster_dims__(2, 1, 1) __launch_bounds__(NTHREADS, 1)
fused_kernel(const Params p, const __grid_constant__ CUtensorMap tm_gu, const __grid_constant__ CUtensorMap tm_down,
             const __grid_constant__ CUtensorMap tm_x, const __grid_constant__ CUtensorMap tm_out) {
    extern __shared__ __align__(1024) unsigned char smem[];
    const uint32_t sb = smem_u32(smem);
    int tid;
    asm volatile("mov.u32 %0, %%tid.x;" : "=r"(tid));
    const int pw = tid >> 5, lane = tid & 31;
    const int c = blockIdx.x, h = c & 1, pr = c >> 1;
    const uint32_t bars = sb + M_BARS;

    uint2 v_la, v_ai, v_cr, v_ci;
    uint32_t ldt16;
    {
        const uint32_t po = c * 256 + tid;
        asm volatile("{\n\t.reg .pred p;\n\t.reg .b64 a;\n\tsetp.ne.u32 p, %16, 0;\n\t"
                     "mad.wide.u32 a, %14, 8, %9;\n\t@p ld.global.nc.L1::no_allocate.v2.u32 {%0,%1}, [a];\n\t"
                     "mad.wide.u32 a, %15, 2, %13;\n\t@p ld.global.nc.u16 %8, [a];\n\t"
                     "mad.wide.u32 a, %14, 8, %10;\n\t@p ld.global.nc.L1::no_allocate.v2.u32 {%2,%3}, [a];\n\t"
                     "mad.wide.u32 a, %14, 8, %11;\n\t@p ld.global.nc.L1::no_allocate.v2.u32 {%4,%5}, [a];\n\t"
                     "mad.wide.u32 a, %14, 8, %12;\n\t@p ld.global.nc.L1::no_allocate.v2.u32 {%6,%7}, [a];\n\t}"
            : "=r"(v_la.x), "=r"(v_la.y), "=r"(v_ai.x), "=r"(v_ai.y), "=r"(v_cr.x), "=r"(v_cr.y), "=r"(v_ci.x), "=r"(v_ci.y), "=r"(ldt16)
            : "l"(p.logA), "l"(p.Aim), "l"(p.Cre), "l"(p.Cim), "l"(p.logdt), "r"(po), "r"(po >> 5), "r"((uint32_t)(tid < 256 && c < 128)));
    }

    if (c >= 128) {
        if (c != 128) return;
        RSTAMP(5);
        const unsigned tag = (*(volatile unsigned*)&p.sc->epoch + 1) & 0xffffu;
        const uint32_t list = sb + 128;
        sts128(list + 16 * tid, 0, 0, 0, 0);
        if (tid == 0) sts32(sb + 64, 0);
        uint32_t key[4] = {tag - 1, tag - 1, tag - 1, tag - 1};
#pragma unroll 1
        for (int it = 0; it < (1 << 22); it++) {
            uint32_t a[4];
            asm volatile("{\n\t.reg .b128 o, z;\n\t.reg .b64 l, u;\n\tmov.b64 l, {%5, %5};\n\tmov.b128 z, {l, l};\n\tatom.relaxed.gpu.global.exch.b128 o, [%4], z;\n\t"
                         "mov.b128 {l, u}, o;\n\tmov.b64 {%0, %1}, l;\n\tmov.b64 {%2, %3}, u;\n\t}"
                : "=r"(a[0]), "=r"(a[1]), "=r"(a[2]), "=r"(a[3]) : "l"(&p.sc->r[tid]), "r"(tag - 1) : "memory");
#pragma unroll
            for (int i = 0; i < 4; i++) if (((a[i] ^ tag) & 0xffffu) == 0) key[i] = a[i];
            if ((((key[0] ^ tag) | (key[1] ^ tag) | (key[2] ^ tag) | (key[3] ^ tag)) & 0xffffu) == 0) break;
        }
        WSTAMP(0);
        uint32_t m = 0;
#pragma unroll
        for (int i = 0; i < 4; i++) {
            key[i] = (key[i] & 0xffff0000u) | (uint32_t)(2047 - (4 * tid + i));
            m = max(m, key[i]);
        }
        const uint32_t wm = __reduce_max_sync(0xffffffffu, m);
        if (lane == 0) sts32(sb + pw * 4, wm);
        __syncthreads();
        uint32_t thr = 0xffffffffu;
#pragma unroll
        for (int i = 0; i < 4; i++) { const uint4 q = lds128(sb + 16 * i); thr = min(thr, min(max(q.x, q.y), max(q.z, q.w))); }
        if (thr != 1) WSTAMP(1);
        if (m >= thr) {
            uint32_t pos;
            asm volatile("atom.shared.add.u32 %0, [%1], %2;" : "=r"(pos) : "r"(sb + 64), "r"(4 * ((key[0] >= thr) + (key[1] >= thr) + (key[2] >= thr) + (key[3] >= thr))) : "memory");
#pragma unroll
            for (int i = 0; i < 4; i++) if (key[i] >= thr) { sts32(list + pos, key[i]); pos += 4; }
        }
        __syncthreads();
        const uint32_t nc4 = lds32(sb + 64);
        if (nc4 != 1) WSTAMP(2);
#pragma unroll 1
        for (uint32_t j = 4 * pw; j < nc4; j += 64) {
            const uint32_t mine = lds32(list + j);
            int rank = 0;
#pragma unroll 1
            for (uint32_t i = 0; i < nc4; i += 128) rank += __popc(__ballot_sync(0xffffffffu, lds32(list + i + 4 * lane) > mine));
            if (rank < 8 && lane == 0) sts32(sb + 96 + 4 * rank, mine);
        }
        __syncthreads();
        if (tid < 8 * NTOP) st_gpu32(&p.sc->top[tid >> 3][tid & 7], lds32(sb + 96 + 4 * (tid & 7)) | ((tag & 31) << 11));
        WSTAMP(3);
        WDUMP();
        return;
    }

    WSTAMP(0);
    if (pw < 8) {
        const int d = 8 * c + pw - MAIN_W0;
        if (lane == 0) asm volatile("cp.async.ca.shared.global [%0], [%1], 4;" :: "r"(sb + M_DSK + 4 * (pw - MAIN_W0)), "l"(p.Dskip + (d & ~1)) : "memory");
        asm volatile("barrier.cluster.arrive.relaxed.aligned;" ::: "memory");
        const int warp = pw - MAIN_W0;
        asm volatile("setmaxnreg.inc.sync.aligned.u32 160;");
        const int g = lane >> 2, t = lane & 3;
        const int mi = lane >> 3, r = lane & 7;
        const uint32_t TB = sb + OFF_TAB + warp * TAB_W;
        const uint32_t UB = sb + OFF_U + warp * U_CH;
        if (mi < 2) sts128(UB + mi * U_PL + r * 16, 0, 0, 0, 0);
        if (lane < 4) sts128(TB + lane * T_PL, 0, 0, 0, 0);
        sts128(sb + OFF_SCR + warp * 8192 + lane * 16, 0x3C00u, 0x3C00u, 0x3C00u, 0x3C00u);
        asm volatile("barrier.cluster.wait.acquire.aligned;" ::: "memory");
        __syncwarp();

        uint32_t cfix;
        {
            KSTAMP(4, v_la.x ^ v_ai.x ^ v_cr.x ^ v_ci.x ^ ldt16);
            const float dt = bf_round(exp_acc(__uint_as_float(ldt16 << 16)));
            float l2[4], li[4];
            {
                const uint32_t la[2] = {v_la.x, v_la.y}, ai[2] = {v_ai.x, v_ai.y};
                const float dt2 = -1.4426950408889634f * dt;
#pragma unroll
                for (int i = 0; i < 4; i++) {
                    l2[i] = bf_round(ex2f(((i & 1) ? bf_hi(la[i >> 1]) : bf_lo(la[i >> 1])) * 1.4426950408889634f)) * dt2;
                    li[i] = ((i & 1) ? bf_hi(ai[i >> 1]) : bf_lo(ai[i >> 1])) * dt;
                }
            }
            const uint32_t SX = sb + OFF_SCR + warp * 8192;
            const uint32_t sw = SX + (lane << 4);
#define PUT(buf, row, v) sts128((buf) == 2 ? TB + (row) * T_PL + 16 + 16 * lane : ((sw + (row) * 512) ^ ((row) << 4)) + (buf) * 4096, v[0], v[1], v[2], v[3])
#define EMIT(bufa, rowa, bufb, rowb, xr, xi, k, kp) do { uint32_t pk[4], pd[4]; sched_fence(); \
                _Pragma("unroll") for (int i = 0; i < 4; i++) { pk[i] = pack_h(xr[i], xi[i]); pd[i] = hcmul(pk[i], k[i], kp[i]); } \
                PUT(bufa, rowa, pk); PUT(bufb, rowb, pd); } while (0)
#define CMUL4(orr, oi, ar, ai, br, bi) _Pragma("unroll") for (int i = 0; i < 4; i++) CMUL(orr[i], oi[i], ar[i], ai[i], br[i], bi[i])
#define CSQ4(orr, oi, ar, ai) _Pragma("unroll") for (int i = 0; i < 4; i++) CSQ(orr[i], oi[i], ar[i], ai[i])
            float z1r[4], z1i[4], z2r[4], z2i[4], z8r[4], z8i[4], z256r[4], z256i[4];
            uint32_t k4[4], k4p[4];
            float z4r[4], z4i[4];
#pragma unroll
            for (int i = 0; i < 4; i++) cexp_pow(l2[i], li[i], 1.f, z1r[i], z1i[i]);
            CSQ4(z2r, z2i, z1r, z1i);
            CSQ4(z4r, z4i, z2r, z2i);
            CSQ4(z8r, z8i, z4r, z4i);
            KSTAMP(5, __float_as_uint(z8r[3]));
            uint32_t Ya[16][4];
            float cr[4], ci[4], inv;
            {
                float w1r[4], w1i[4], ar[4], ai[4], br[4], bi[4];
                uint32_t k8[4], k8p[4];
#pragma unroll
                for (int i = 0; i < 4; i++) {
                    k8[i] = pack_h(z8r[i], -z8i[i]); k8p[i] = pack_h(z8i[i], z8r[i]);
                    CSQ(w1r[i], w1i[i], z8r[i], z8i[i]); w1i[i] = -w1i[i];
                }
                PUT(1, 0, k8);
                EMIT(0, 1, 1, 1, w1r, w1i, k8, k8p);
                CSQ4(ar, ai, w1r, w1i);            EMIT(0, 2, 1, 2, ar, ai, k8, k8p);
                CMUL4(br, bi, ar, ai, w1r, w1i);   EMIT(0, 3, 1, 3, br, bi, k8, k8p);
                CSQ4(ar, ai, ar, ai);              EMIT(0, 4, 1, 4, ar, ai, k8, k8p);
                CMUL4(ar, ai, ar, ai, w1r, w1i);   EMIT(0, 5, 1, 5, ar, ai, k8, k8p);
                CSQ4(br, bi, br, bi);              EMIT(0, 6, 1, 6, br, bi, k8, k8p);
                CMUL4(br, bi, br, bi, w1r, w1i);   EMIT(0, 7, 1, 7, br, bi, k8, k8p);
                __syncwarp();
                KSTAMP(6, 0);
                sched_fence();
                const uint32_t ab = SX + (mi & 1) * 4096 + r * 512, ax = ((mi >> 1) ^ r) << 4;
                const uint32_t vr[2] = {v_cr.x, v_cr.y}, vi[2] = {v_ci.x, v_ci.y};
                const uint32_t m2 = __vmaxu2(__vmaxu2(vr[0] & 0x7fff7fffu, vr[1] & 0x7fff7fffu), __vmaxu2(vi[0] & 0x7fff7fffu, vi[1] & 0x7fff7fffu));
                const uint32_t mx = __reduce_max_sync(0xffffffffu, max(m2, m2 << 16));
                const uint32_t e = min(max(mx >> 23, 11u), 254u);
                const float sc = __uint_as_float((264u - e) << 23);
                inv = __uint_as_float((e - 10u) << 23) * (2.f * dt);
#pragma unroll
                for (int i = 0; i < 4; i++) {
#pragma unroll
                    for (int k = 0; k < 4; k++) ldsm4(ab + (ax ^ (i << 5)) + k * 128, Ya[4 * k + i][0], Ya[4 * k + i][1], Ya[4 * k + i][2], Ya[4 * k + i][3]);
                    float tr, ti;
                    cexp_pow(l2[i], li[i], 128.f, tr, ti);
                    sts32(TB + 2176 + 256 * i + 4 * (lane ^ (8 * i)), pack_h(tr, ti));
                    sts32(TB + 2176 + 256 * i + 128 + 4 * (lane ^ (8 * i + 4)), pack_h(-ti, tr));
                    k4[i] = pack_h(z4r[i], z4i[i]); k4p[i] = pack_h(-z4i[i], z4r[i]);
                    CSQ(z256r[i], z256i[i], tr, ti);
                    cr[i] = ((i & 1) ? bf_hi(vr[i >> 1]) : bf_lo(vr[i >> 1])) * sc;
                    ci[i] = ((i & 1) ? bf_hi(vi[i >> 1]) : bf_lo(vi[i >> 1])) * sc;
                    if (i < 3) sched_fence();
                }
                __syncwarp();
            }
            KSTAMP(7, Ya[15][0]);
            const uint32_t ld0 = SX + r * 512 + ((mi ^ r) << 4), ld1 = ld0 ^ 64;
            float R[6][4], s1024;
            {
                float xr[4], xi[4], yr[4], yi[4];
                EMIT(0, 0, 0, 1, cr, ci, k4, k4p);
                CMUL4(yr, yi, cr, ci, z1r, z1i);        EMIT(0, 2, 0, 3, yr, yi, k4, k4p);
                CMUL4(xr, xi, cr, ci, z256r, z256i);    EMIT(2, 0, 2, 1, xr, xi, k4, k4p);
                CMUL4(yr, yi, yr, yi, z1r, z1i);        EMIT(0, 4, 0, 5, yr, yi, k4, k4p);
                CMUL4(cr, ci, yr, yi, z256r, z256i);    EMIT(2, 2, 2, 3, cr, ci, k4, k4p);
                CMUL4(yr, yi, yr, yi, z1r, z1i);        EMIT(0, 6, 0, 7, yr, yi, k4, k4p);
                CMUL4(xr, xi, xr, xi, z256r, z256i);    EMIT(1, 0, 1, 1, xr, xi, k4, k4p);
                CMUL4(xr, xi, xr, xi, z256r, z256i);    EMIT(1, 2, 1, 3, xr, xi, k4, k4p);
                CMUL4(xr, xi, xr, xi, z256r, z256i);
                s1024 = (xr[0] + xr[1]) + (xr[2] + xr[3]);
#pragma unroll
                for (int m = 4; m < 8; m++) {
                    if (m == 4) { CMUL4(xr, xi, xr, xi, z8r, z8i); } else { CMUL4(xr, xi, xr, xi, z256r, z256i); }
                    sched_fence();
                    const uint32_t pk[4] = {pack_h(xr[0], xi[0]), pack_h(xr[1], xi[1]), pack_h(xr[2], xi[2]), pack_h(xr[3], xi[3])};
                    PUT(1, m, pk);
                }
            }
            __syncwarp();
            {
                KSTAMP(8, 0);
                uint32_t bd[2][4] = {{0, 0, 0, 0}, {0, 0, 0, 0}};
                const bool on = (g >> 1) == t;
#pragma unroll
                for (int i = 0; i < 6; i++) { R[i][0] = R[i][1] = R[i][2] = R[i][3] = 0.f; }
                uint32_t x[2][4], y[2][4], z[2][4];
                auto fetch = [&](const int k2) {
                    const int b = k2 & 1;
                    lds128_if(on, TB + 2176 + g * 128 + 16 * (k2 ^ g), bd[b]);
                    ldsm4(((k2 & 1) ? ld1 : ld0) + (k2 >> 1) * 128, x[b][0], x[b][1], x[b][2], x[b][3]);
                    ldsm4(TB + ((r & 1) + ((r >> 1) == 2 ? 2 : 0)) * T_PL + 16 + 16 * mi + 64 * k2, y[b][0], y[b][1], y[b][2], y[b][3]);
                    ldsm4(((k2 & 1) ? ld1 : ld0) + (k2 >> 1) * 128 + 4096, z[b][0], z[b][1], z[b][2], z[b][3]);
                };
                fetch(0);
#pragma unroll
                for (int k2 = 0; k2 < 8; k2++) {
                    const int b = k2 & 1;
                    uint32_t a1[2][4];
                    if (k2 < 7) fetch(k2 + 1);
#pragma unroll
                    for (int u = 0; u < 2; u++) {
                        mma_hh_k8(a1[u][0], a1[u][1], Ya[2 * k2 + u][0], Ya[2 * k2 + u][1], bd[b][2 * u]);
                        mma_hh_k8(a1[u][2], a1[u][3], Ya[2 * k2 + u][2], Ya[2 * k2 + u][3], bd[b][2 * u + 1]);
                    }
#pragma unroll
                    for (int u = 0; u < 2; u++) {
                        const uint32_t(&a0)[4] = Ya[2 * k2 + u];
                        mma_h(R[0], a0[0], a0[1], a0[2], a0[3], x[b][2 * u], x[b][2 * u + 1]);
                        mma_h(R[2], a0[0], a0[1], a0[2], a0[3], y[b][2 * u], y[b][2 * u + 1]);
                        mma_h(R[4], a0[0], a0[1], a0[2], a0[3], z[b][2 * u], z[b][2 * u + 1]);
                        mma_h(R[1], a1[u][0], a1[u][1], a1[u][2], a1[u][3], x[b][2 * u], x[b][2 * u + 1]);
                        mma_h(R[3], a1[u][0], a1[u][1], a1[u][2], a1[u][3], y[b][2 * u], y[b][2 * u + 1]);
                        mma_h(R[5], a1[u][0], a1[u][1], a1[u][2], a1[u][3], z[b][2 * u], z[b][2 * u + 1]);
                    }
                }
            }
            __syncwarp();
            KSTAMP(9, __float_as_uint(R[3][0]));
            if (lane == 0) mbar_arrive(bars + 8 * B_KG + (__float_as_uint(R[0][0]) & __float_as_uint(R[4][0]) & p.zero));
            if (lane < 24) asm volatile("st.shared.v2.u32 [%0], {%1, %1};" :: "r"(TB + (lane < 9 ? 2176 : 2432) + 8 * lane), "r"(0) : "memory");
            __syncwarp();
#undef PUT
#undef EMIT
#pragma unroll
            for (int o = 16; o > 0; o >>= 1) s1024 += __shfl_xor_sync(0xffffffffu, s1024, o);
            uint32_t dsk = 0;
            cp_wait_all();
            asm volatile("{\n\t.reg .pred p;\n\tsetp.eq.u32 p, %2, 0;\n\t@p ld.shared.u16 %0, [%1];\n\t}" : "+r"(dsk) : "r"(sb + M_DSK + 4 * warp + 2 * (warp & 1)), "r"(lane) : "memory");
#pragma unroll
            for (int a = 0; a < 6; a++)
#pragma unroll
                for (int i = 0; i < 4; i++) R[a][i] = (a + i == 0) ? fmaf(R[0][0], inv, __uint_as_float(dsk << 16)) : R[a][i] * inv;
            const float k512 = __shfl_sync(0xffffffffu, R[4][0], 0), k516 = __shfl_sync(0xffffffffu, R[4][1], 0);
            const uint32_t w1 = TB + 16 + 16 * g + t * T_PL;
            float last;
#pragma unroll
            for (int a = 0; a < 4; a++) {
                const bool ahead = a >= 2 && t == 3;
                const float back = g == 7 ? (a ? R[a ? a - 1 : 0][3] : 0.f) : R[a][3], fwd = g == 0 ? (a == 2 ? R[3][0] : k512) : R[a][0];
                const float nb = __shfl_sync(0xffffffffu, ahead ? fwd : back, lane + (ahead ? 4 : 28));
                const float q0 = ahead ? R[a][0] : nb, q1 = ahead ? R[a][1] : R[a][0], q2 = ahead ? R[a][2] : R[a][1], q3 = ahead ? R[a][3] : R[a][2];
                last = ahead ? nb : R[a][3];
                sts128(w1 + 128 * a, pack_bf(q1, q0), pack_bf(q2, q1), pack_bf(q3, q2), pack_bf(last, q3));
            }
            {
                const float s0 = t == 3 ? k516 : k512, s1 = t < 2 ? k516 : 0.f;
                sts128_if(g == 7, w1 + 400, pack_bf(s0, last), pack_bf(s1, s0), pack_bf(0.f, s1), 0);
            }
            const uint32_t wq = TB + 8 * g + (t < 2 ? T_A + 8 * (32 + 16 * t) : T_B + 8 * (1 + 32 * t) + 12) + 64 * (t & 1), dq = 64 - 128 * (t & 1);
            uint32_t bw[2][2];
#pragma unroll
            for (int a = 0; a < 2; a++) {
                const uint32_t lo = pack_bf(R[4 + a][0], R[4 + a][1]), hi = pack_bf(R[4 + a][2], R[4 + a][3]);
                bw[a][0] = __byte_perm(lo, hi, t < 2 ? 0x1032 : 0x5410); bw[a][1] = __byte_perm(lo, hi, t < 2 ? 0x5476 : 0x7632);
            }
#pragma unroll
            for (int a = 0; a < 2; a++) {
                const uint32_t b0 = (t & 1) ? bw[a ^ 1][0] : bw[a][0], b1 = (t & 1) ? bw[a ^ 1][1] : bw[a][1], w = wq + a * dq;
                sts32_if(a == 1 || lane != 0, w, b0);
                sts32(w + (t < 2 ? 12 : 116), b1);
                sts32_if(t >= 2, w - 12, b0);
                sts32_if(t >= 2, w + 128, b1);
            }
            __syncwarp();
            if (lane == 31) sts16(w1 + 146, pack_bf(R[1][3], 0.f));
            cfix = pack_bf(s1024 * inv, s1024 * inv);
            if (lane == 0) sts32(TB + T_A + 8 * 64, cfix);
            __syncwarp();
        }
        WSTAMP(1);

        mbar_wait(bars + 8 * B_U);
        WSTAMP(2);

        float D[16][4];
        {
            const int x5 = g - t + 5;
            const uint32_t tabD = TB + (x5 & 3) * T_PL + (x5 & 12) + 16;
            {
                const uint32_t a1 = lds32(tabD - 8), a0 = p.zero;
#pragma unroll
                for (int jq = 0; jq < 4; jq++) {
                    uint32_t b[4];
                    ldsm4(UB + (9 + lane) * 16 + jq * 512, b[0], b[1], b[2], b[3]);
#pragma unroll
                    for (int i = 0; i < 4; i++) mma_bf_k8z(D[4 * jq + i], a0, a1, b[i]);
                }
            }
            const uint32_t ua = UB + (mi & 1) * U_PL + (8 + 8 * (mi >> 1) + r) * 16;
#pragma unroll 1
            for (int k0 = 0; k0 < 8; k0++) {
                uint32_t Uf[16][2];
#pragma unroll
                for (int jp = 0; jp < 8; jp++) ldsm4(ua + jp * 256 - k0 * 16, Uf[2 * jp][0], Uf[2 * jp][1], Uf[2 * jp + 1][0], Uf[2 * jp + 1][1]);
#pragma unroll
                for (int k1 = 0; k1 < 4; k1++) {
                    const uint32_t ta = tabD + 16 * (8 * k1 + k0);
                    const uint32_t a0 = lds32(ta), a1 = lds32(ta + 8), a2 = lds32(ta - 8), a3 = a0 ^ p.zero;
#pragma unroll
                    for (int J = k1; J < 16; J++) mma_bf(D[J], a0, a1, a2, a3, Uf[J - k1][0], Uf[J - k1][1]);
                }
                if (k0 == 0) {
                    const uint32_t ta = tabD + 16 * 32;
                    const uint32_t a0 = lds32(ta), a1 = lds32(ta + 8), a2 = lds32(ta - 8), a3 = a0 ^ p.zero;
#pragma unroll
                    for (int J = 4; J < 16; J++) mma_bf(D[J], a0, a1, a2, a3, Uf[J - 4][0], Uf[J - 4][1]);
                    const uint32_t f0 = (cfix ^ 0x80008000u) & (g == t ? 0xffffu : g == t + 4 ? 0xffff0000u : 0u);
                    const uint32_t f1 = p.zero, f2 = p.zero + p.zero, f3 = f0 ^ p.zero;
#pragma unroll
                    for (int J = 8; J < 16; J++) mma_bf(D[J], f0, f1, f2, f3, Uf[J - 8][0], Uf[J - 8][1]);
                }
            }
        }
        WSTAMP(3);
        {
            const int ch = 8 * h + warp;
            const uint32_t yo = sb + ch * 512 + ((lane ^ (((ch >> 2) << 1) | (ch & 1))) << 4);
            const uint32_t yr = mapa(yo, h ^ 1), ybr = mapa(bars + 8 * B_Y, h ^ 1);
            auto ship = [&](const int Q) {
                uint4 y[2];
#pragma unroll
                for (int hh = 0; hh < 2; hh++) {
                    const int J = 4 * Q + 2 * hh;
                    y[hh] = make_uint4(pack_bf(D[J][0], D[J][1]), pack_bf(D[J][2], D[J][3]), pack_bf(D[J + 1][0], D[J + 1][1]), pack_bf(D[J + 1][2], D[J + 1][3]));
                }
                if (!(Q & 1)) mbar_wait(bars + 8 * (B_F + (Q >> 1)));
                asm volatile("{\n\t.reg .pred p;\n\tsetp.eq.u32 p, %11, 0;\n\t"
                             "@p st.async.weak.shared::cluster.mbarrier::complete_tx::bytes.v4.b32 [%9], {%4,%5,%6,%7}, [%10];\n\t"
                             "@!p st.async.weak.shared::cluster.mbarrier::complete_tx::bytes.v4.b32 [%9], {%0,%1,%2,%3}, [%10];\n\t"
                             "@p st.shared.v4.b32 [%8], {%0,%1,%2,%3};\n\t@!p st.shared.v4.b32 [%8], {%4,%5,%6,%7};\n\t}"
                             :: "r"(y[0].x), "r"(y[0].y), "r"(y[0].z), "r"(y[0].w), "r"(y[1].x), "r"(y[1].y), "r"(y[1].z), "r"(y[1].w),
                                "r"(yo + y_off(Q)), "r"(yr + y_off(Q)), "r"(ybr + 8 * Q), "r"(h) : "memory");
                __syncwarp();
                if (lane == 0) mbar_arrive(bars + 8 * (B_Y + Q));
            };
            ship(0);
            const uint4 bA = lds128(sb + OFF_BAND + (g - t + 3) * 48), bB = lds128(sb + OFF_BAND + (g - t + 3) * 48 + 16);
            const uint2 bC = lds64(sb + OFF_BAND + (g - t + 3) * 48 + 32);
            uint2 QA[5][2], QB[8];
            const uint32_t tq = TB + 8 * (1 + g - 2 * t);
#pragma unroll
            for (int dd = 0; dd < 5; dd++) { QA[dd][0] = lds64(tq + T_A + 64 * (dd + 4)); QA[dd][1] = lds64(tq + T_A + 64 * (dd + 4) - 8); }
#pragma unroll
            for (int dd = 0; dd < 8; dd++) QB[dd] = lds64(tq + T_B + 64 * (dd + 8));
            const uint32_t u1 = UB + (mi & 1) * U_PL + (7 + r + (mi >> 1)) * 16;
            const uint32_t u2 = UB + ((mi & 1) ^ 1) * U_PL + (7 + r + (mi & 1) + 8 * (mi >> 1)) * 16;
            uint32_t n[4];
#pragma unroll
            for (int j = 0; j < 12; j++) {
                uint32_t m[4];
                ldsm4(u1 + j * 128, m[0], m[1], m[2], m[3]);
                if (!(j & 1)) ldsm4(u2 + j * 128, n[0], n[1], n[2], n[3]);
                const uint32_t n0 = n[2 * (j & 1)], n1 = n[2 * (j & 1) + 1];
                float wa[4], wb[4], wc[4], g1[4], g2[4];
                mma_bf_z(wa, bA.x, bA.y, bA.z, bA.w, m[0], m[1]);
                mma_bf_z(wb, bA.x, bA.y, bA.z, bA.w, n0, n1);
                mma_bf_z(wc, bA.x, bA.y, bA.z, bA.w, m[2], m[3]);
                if (j < 8) {
                    mma_bf_z(g1, bB.x, bB.y, bB.z, bB.w, m[0], m[1]);
                    mma_bf_z(g2, bB.x, bB.y, bB.z, bB.w, n0, n1);
                    mma_bf_k8(g1, bC.x, bC.y, m[2]);
                    mma_bf_k8(g2, bC.x, bC.y, m[3]);
                }
#pragma unroll
                for (int e = 0; e < 2; e++) {
                    const uint32_t q0 = pack_bf(wa[e], wa[e + 2]), q1 = pack_bf(wb[e], wb[e + 2]), q2 = q1 ^ p.zero, q3 = pack_bf(wc[e], wc[e + 2]);
#pragma unroll
                    for (int dd = 0; dd < 5; dd++)
                        if (j + 4 + dd < 16) mma_bf(D[j + 4 + dd], q0, q1, q2, q3, QA[dd][e].x, QA[dd][e].y);
                }
                if (j < 8) {
                    const uint32_t q0 = pack_bf(g1[0], g1[2]), q1 = pack_bf(g2[0], g2[2]), q2 = pack_bf(g1[1], g1[3]), q3 = pack_bf(g2[1], g2[3]);
#pragma unroll
                    for (int dd = 7 - j; dd >= 0; dd--) mma_bf(D[j + 8 + dd], q0, q1, q2, q3, QB[dd].x, QB[dd].y);
                }
                if ((j & 3) == 3) {
                    WSTAMP(4 + 2 * (j >> 2));
                    ship((j >> 2) + 1);
                }
            }
        }
        const int warpu = __reduce_max_sync(0xffffffffu, warp);
        mix_rows<1>(p, &tm_out, sb, sb + OFF_U + warpu * U_CH + (warpu & 1) * 64, PQ, 4, warpu, h, pr, lane);
        asm volatile("cp.async.bulk.commit_group;\n\tcp.async.bulk.wait_group.read 0;" ::: "memory");
        WSTAMP(10);
        WDUMP();
    } else if ((pw & 12) == AUX_W0) {
        const uint32_t t0 = clock();
        const int v = __reduce_max_sync(0xffffffffu, pw & 3);
        const int at = tid & 127;
        const int g = lane >> 2, t = lane & 3;
        unsigned tag;
        const bool gu = c < NGU_CTA;
        {
            const uint32_t xb = sb + (v < 2 ? OFF_XSEL : OFF_RING + 2 * 8192) + v * 8192;
            const uint32_t gws = sb + M_DPIN;
            const uint32_t row = 16 * c + 4 * v + (g >> 1);
#pragma unroll
            for (int i = 0; i < 8; i++)
                asm volatile("cp.async.ca.shared.global [%0], [%1], 4;" :: "r"((i < 4 ? sb + OFF_GP : gws) + 512 * (i & 3) + (tid & 124) * 4 + (tid & 1) * 8 + (tid & 2) * 2),
                             "l"((i < 4 ? p.wr : p.gatew) + 256 * (i & 3) + (tid & 127) * 2) : "memory");
            if ((tid & 127) < 33) cp16(sb + OFF_BAND + (tid & 127) * 16, p.band + (tid & 127));
            asm volatile("barrier.cluster.arrive.relaxed.aligned;" ::: "memory");
            tag = __reduce_max_sync(0xffffffffu, (*(volatile unsigned*)&p.sc->epoch + 1) & 0xffffu);
            if (gu) st_gpu32((uint32_t*)&p.sc->h[(tag + 1) & 1][32 * c] + at, 0);
            if (v == 2) sts32(sb + M_BMAP + lane * 4, 0);
            if (at == 0) sts32(sb + M_TAG, tag << 16);
            cp_wait_all();
            bar_sync(1, 128);
            uint2 w[16];
#pragma unroll
            for (int kb = 0; kb < 16; kb++) w[kb] = lds64((g < 4 ? sb + OFF_GP : gws) + 128 * kb + 32 * (g & 2) + 16 * t + 8 * (g & 1));
            asm volatile("barrier.cluster.wait.acquire.aligned;" ::: "memory");
            int early;
#pragma unroll 1
            while ((early = TR - (int)(clock() - t0)) > 0) __nanosleep(max(early >> 2, 32));
            mbar_wait(bars + 8 * (B_X + v));
            WSTAMP(10);
            float dr[4][4];
#pragma unroll
            for (int kb = 0; kb < 16; kb++) {
                const uint4 x = lds128(xb + (g >> 1) * 2048 + 128 * kb + 16 * (lane & 7));
                if (kb < 4) mma_bf_z(dr[kb], x.x, x.y, x.z, x.w, w[kb].x, w[kb].y);
                else mma_bf(dr[kb & 3], x.x, x.y, x.z, x.w, w[kb].x, w[kb].y);
            }
            float rs = ((dr[0][0] + dr[0][3]) + (dr[1][0] + dr[1][3])) + ((dr[2][0] + dr[2][3]) + (dr[3][0] + dr[3][3]));
            if (lane == 0) mbar_arrive(bars + 8 * (B_XE + v) + (__float_as_uint(rs) & p.zero));
            rs += __shfl_xor_sync(0xffffffffu, rs, 5);
            const uint32_t rb = pack_bf(0.f, rs);
            if (!(lane & 7)) st_gpu32((uint32_t*)p.sc->r + row, ((rb ^ (((int)rb >> 31) | 0x80000000u)) & 0xffff0000u) | tag);
            WSTAMP(1);
            {
                const int n = 3 + (lane >> 3) + 4 * (lane & 1);
                const uint32_t so = (n & 7) * S_PL + ((lane & 6) + (n >> 3)) * 32;
                const uint32_t src[2] = {sb + OFF_S + v * S_Q + s_addr(so, h), sb + OFF_S + v * S_Q + s_addr(so + 32, h)};
                const uint32_t dst = sb + OFF_U + g * U_CH + (8 + 32 * v + 16 * h + t) * 16;
                const uint32_t rdst = mapa(dst, h ^ 1), rbar = mapa(bars + 8 * B_U, h ^ 1);
                mbar_wait(bars + 8 * (B_S + v));
                WSTAMP(9);
                uint4 a[8];
#pragma unroll
                for (int b = 0; b < 2; b++) {
#pragma unroll
                    for (int j = 0; j < 8; j++) { const int u = 4 * b + (j >> 1) + 8 * (j & 1); ldsm4t((u < 8 ? src[u & 1] ^ 16 : src[u & 1]) + ((u >> 1) & 3) * 256, a[j].x, a[j].y, a[j].z, a[j].w); }
#pragma unroll
                    for (int j = 0; j < 8; j++) {
                        const int u = 4 * b + (j >> 1) + 8 * (j & 1);
                        if (u < 8) st_async16(rdst + ((u >> 1) & 3) * 64 + (u & 1) * U_PL, a[j], rbar);
                        else sts128(dst + ((u >> 1) & 3) * 64 + (u & 1) * U_PL, a[j].x, a[j].y, a[j].z, a[j].w);
                    }
                }
                if (h && v == 3) {
                    ldsm4t((src[0] ^ 16) + 1024, a[0].x, a[0].y, a[0].z, a[0].w);
                    ldsm4t(src[0] + 1024, a[1].x, a[1].y, a[1].z, a[1].w);
                    if (t == 0) {
                        st_async16(rdst + 256, make_uint4(a[0].x, a[0].y & 0xffffu, a[0].z & 0xffffu, a[0].w & 0xffffu), rbar);
                        sts128(dst + 256, a[1].x, a[1].y & 0xffffu, a[1].z & 0xffffu, a[1].w & 0xffffu);
                    }
                }
                __syncwarp();
                if (lane == 0) mbar_arrive(bars + 8 * B_U);
            }
            if ((lane & 7) == 2) st_gpu32((uint32_t*)p.sc->g + ((row & 256) << 2) + gate_pos(row), pack_bf(sigmoid_f(__uint_as_float(rb)), 0.f) | (tag << 16));
            WSTAMP(2);
        }
        {
            const bool lane0 = pin(lane, lane) == 0;
            const uint32_t own = pin(sb + OFF_XSEL + (at ^ ((at >> 1) & 4)) * 16, lane);
            float acc[8][4];
            const int krow = ((lane >> 1) & 8) + (lane & 7);
            const uint32_t tile0 = pin(sb + OFF_RING + v * 8192 + krow * 64 + ((((lane >> 3) & 1) ^ ((krow >> 1) & 3)) << 4), lane);
            const uint32_t xo = pin(sb + OFF_XSEL + (lane & 7) * XS_ROW + 512 * v + 2 * (lane & 24), lane);
            const uint32_t po = pin(sb + OFF_XSEL + t * XS_ROW + (g & 3) * 128 + (g & 1) * 64 + v * 16 + (lane >> 4) * 8, lane);
            const uint32_t po1 = pin(po + 64 - (g & 1) * 128, lane);
            uint32_t* hdst = pin((uint32_t*)&p.sc->h[tag & 1][32 * c] + at, lane);
            auto signal = [&](const int k, const uint32_t dep) {
                if (lane < 2 && v < 2)
                    asm volatile("st.async.weak.shared::cluster.mbarrier::complete_tx::bytes.b32 [%0], %1, [%2];"
                                 :: "r"(mapa(sb + M_SINK, lane)), "r"(dep), "r"(mapa(bars + 8 * (B_F + k), lane)) : "memory");
            };
            uint32_t a[16][4], b[2][4];
            auto load_a = [&](const uint32_t tile) {
#pragma unroll
                for (int q = 0; q < 16; q++) ldsm4t((tile ^ ((q & 1) << 5)) + ((q >> 1) & 1) * 4096 + (q >> 2) * 1024, a[q][0], a[q][1], a[q][2], a[q][3]);
            };
            auto load_b = [&](const uint32_t x) { ldsm4(x, b[0][0], b[0][1], b[0][2], b[0][3]); ldsm4(x + 64, b[1][0], b[1][1], b[1][2], b[1][3]); };
            auto burst = [&](const bool first) {
#pragma unroll
                for (int q = 0; q < 16; q++) {
                    if (first && q < 8) mma_bf_z(acc[q], a[q][0], a[q][1], a[q][2], a[q][3], b[0][(q >> 1) & 2], b[0][((q >> 1) & 2) + 1]);
                    else mma_bf(acc[q & 7], a[q][0], a[q][1], a[q][2], a[q][3], b[q >> 3][(q >> 1) & 2], b[q >> 3][((q >> 1) & 2) + 1]);
                }
            };
            if (gu) {
                mbar_wait(bars + 8 * (B_W + v));
                load_a(tile0);
                uint32_t dep = p.zero;
#pragma unroll
                for (int q = 0; q < 16; q += 2) dep &= a[q][0] & a[q + 1][0];
                if (lane == 0) mbar_arrive(bars + 8 * (B_E + v) + dep);
            }
            WSTAMP(11);
            uint32_t top;
#pragma unroll 1
            for (int it = 0; it < (1 << 22); it++) {
                asm volatile("ld.relaxed.gpu.global.u32 %0, [%1];" : "=r"(top) : "l"(&p.sc->top[c % NTOP][g]) : "memory");
                if (__all_sync(0xffffffffu, ((top ^ (tag << 11)) & 0xf800u) == 0)) break;
                __nanosleep(40);
            }
            WSTAMP(3);
            if (gu) {
                const uint32_t k = 4 * h + v, row = __reduce_max_sync(0xffffffffu, lane == 4 * k ? ~top & 2047 : 0);
                asm volatile("{\n\t.reg .pred p;\n\telect.sync _|p, 0xffffffff;\n\t"
                             "@p cp.async.bulk.shared::cluster.global.mbarrier::complete_tx::bytes.multicast::cluster [%0], [%1], 2048, [%2], %3;\n\t}"
                    :: "r"(sb + OFF_XSEL + k * XS_ROW), "l"(p.u + (size_t)row * D_), "r"(bars + 8 * B_G), "h"((unsigned short)3) : "memory");
            }
            if (v == 2) {
                const uint32_t row = ~top & 2047;
                if (t == 0 && ((row >> 8) & 1) == h)
                    asm volatile("red.shared.or.b32 [%0], %1;" :: "r"(sb + M_BMAP + (row & 7) * 16 + (row >> 9) * 4), "r"(1u << (gate_pos(row) & 31)) : "memory");
                if (t == 0) sts32(sb + M_TOP + lane, top);
                if (c == 0 && lane == 0) *(volatile unsigned*)&p.sc->epoch = tag;
                __syncwarp();
                if (lane0) mbar_arrive(bars + 8 * B_Y);
            }
            if (gu) {
                mbar_wait(bars + 8 * B_G);
                WSTAMP(4);
                load_b(xo);
                burst(true);
#pragma unroll
                for (int i = 1; i < 4; i++) {
                    mbar_wait(bars + 8 * (B_W + 4 * i + v));
                    load_b(xo + 128 * i);
                    load_a(tile0 + (4 * i + v < 14 ? i : 0) * 32768);
                    if (lane0 && i > 1) mbar_arrive(bars + 8 * (B_E + 4 * i - 4 + v));
                    if (i == 2) signal(0, 0);
                    sched_fence();
                    burst(false);
                    sched_fence();
                }
                WSTAMP(5);
                __syncwarp();
#pragma unroll
                for (int q = 0; q < 4; q++) {
                    const int ct = q >> 1, e = 2 * (q & 1);
                    sts128(own + q * XS_ROW,
                           __float_as_uint(acc[ct][e] + acc[4 + ct][e]), __float_as_uint(acc[2 + ct][e] + acc[6 + ct][e]),
                           __float_as_uint(acc[ct][e + 1] + acc[4 + ct][e + 1]), __float_as_uint(acc[2 + ct][e + 1] + acc[6 + ct][e + 1]));
                }
                bar_sync(1, 128);
                float sl[2], uv[2];
#pragma unroll
                for (int e = 0; e < 2; e++) {
                    uint2 q[4];
#pragma unroll
                    for (int i = 0; i < 4; i++) q[i] = lds64((e ? po1 : po) + 512 * i);
                    const float s0 = (__uint_as_float(q[0].x) + __uint_as_float(q[1].x)) + (__uint_as_float(q[2].x) + __uint_as_float(q[3].x));
                    const float s1 = (__uint_as_float(q[0].y) + __uint_as_float(q[1].y)) + (__uint_as_float(q[2].y) + __uint_as_float(q[3].y));
                    const float gv = bf_round(p.gu_swap ? s1 : s0);
                    uv[e] = p.gu_swap ? s0 : s1;
                    sl[e] = gv * sigmoid_f(gv);
                }
                const uint32_t hw = hmul2_bf(pack_bf(sl[0], sl[1]), pack_bf(uv[0], uv[1]));
                st_gpu32(hdst, hw ? hw : 0x80000000u);
                signal(1, hw);
            }
        }
        WSTAMP(6);
        {
            const uint32_t own = pin(sb + OFF_XSEL + at * 16, lane);
            const uint32_t hb = sb + (v < 2 ? OFF_XSEL + 7168 * v : OFF_RING + 8192 * v), hl = pin(hb + 16 * lane, lane);
            const int krow = ((lane >> 1) & 8) + (lane & 7);
            const uint32_t tile = pin(sb + OFF_RING + v * 8192 + krow * 32 + ((((lane >> 3) ^ (krow >> 2)) & 1) << 4), lane);
            float dd[4][4];
            bar_sync(1, 128);
            mbar_wait(bars + 8 * (B_W + HW));
            WSTAMP(12);
            uint4 hq[7];
            {
                const uint4* hs = &p.sc->h[tag & 1][32 * (56 * h + 14 * v)];
                bulk_load(hb, hs, 3584, bars + 8 * (B_X + v));
                bulk_load(hb + 3584, hs + 224, 3584, bars + 8 * (B_XE + v));
                uint32_t a[14][4];
                mbar_wait(bars + 8 * (B_W + 16 + v));
#pragma unroll
                for (int j = 0; j < 14; j++) ldsm4t(tile + (v & 2) * 16384 + j * 512, a[j][0], a[j][1], a[j][2], a[j][3]);
#pragma unroll
                for (int k = 0; k < 2; k++) {
                    mbar_wait(bars + 8 * ((k ? B_XE : B_X) + v), 1);
                    if (!k) WSTAMP(7);
                    uint32_t mn = 0xffffffffu;
#pragma unroll
                    for (int j = 0; j < 7; j++) { hq[j] = lds128(hl + 3584 * k + 512 * j); mn = min(mn, hq[j].x); }
#pragma unroll 1
                    for (int it = 0; it < (1 << 20) && !__all_sync(0xffffffffu, mn != 0); it++) {
                        mn = 0xffffffffu;
#pragma unroll
                        for (int j = 0; j < 7; j++)
                            asm volatile("{\n\t.reg .pred p;\n\tsetp.eq.u32 p, %0, 0;\n\t@p ld.relaxed.gpu.global.v4.u32 {%0,%1,%2,%3}, [%4];\n\t}"
                                         : "+r"(hq[j].x), "+r"(hq[j].y), "+r"(hq[j].z), "+r"(hq[j].w) : "l"(hs + 224 * k + 32 * j + lane) : "memory");
#pragma unroll
                        for (int j = 0; j < 7; j++) mn = min(mn, hq[j].x);
                    }
                    if (!k) {
#pragma unroll
                        for (int j = 0; j < 14; j++) {
                            const uint4& q = hq[j >> 1];
                            if (j < 4) mma_bf_z(dd[j], a[j][0], a[j][1], a[j][2], a[j][3], (j & 1) ? q.z : q.x, (j & 1) ? q.w : q.y);
                            else mma_bf(dd[j & 3], a[j][0], a[j][1], a[j][2], a[j][3], (j & 1) ? q.z : q.x, (j & 1) ? q.w : q.y);
                        }
                    }
                }
            }
            mbar_wait(bars + 8 * (B_W + 20 + v));
#pragma unroll
            for (int j = 0; j < 14; j++) {
                uint32_t f[4];
                ldsm4t(tile + 65536 + j * 512, f[0], f[1], f[2], f[3]);
                mma_bf(dd[(j + 2) & 3], f[0], f[1], f[2], f[3], (j & 1) ? hq[j >> 1].z : hq[j >> 1].x, (j & 1) ? hq[j >> 1].w : hq[j >> 1].y);
            }
            WSTAMP(8);
            uint4 part;
            part.x = __float_as_uint((dd[0][0] + dd[1][0]) + (dd[2][0] + dd[3][0])); part.y = __float_as_uint((dd[0][1] + dd[1][1]) + (dd[2][1] + dd[3][1]));
            part.z = __float_as_uint((dd[0][2] + dd[1][2]) + (dd[2][2] + dd[3][2])); part.w = __float_as_uint((dd[0][3] + dd[1][3]) + (dd[2][3] + dd[3][3]));
            st_async16(mapa(own + (M_DPIN - OFF_XSEL), h ^ 1), part, mapa(bars + 8 * B_DP, h ^ 1));
            sts128(own + 14336, part.x, part.y, part.z, part.w);
            __syncwarp();
            if (lane == 0) mbar_arrive(bars + 8 * B_DP);
        }
        WDUMP();
    } else {
        asm volatile("setmaxnreg.dec.sync.aligned.u32 64;");
        const int v = __reduce_max_sync(0xffffffffu, pw - PREP_W0);
        const bool gu = c < NGU_CTA;
        const uint32_t t0 = clock();
        const uint32_t bu = bars + 8 * v;
        if (lane == 0) { mbar_init(bu + 8 * B_X, 1); mbar_init(bu + 8 * B_S, 1); }
        __syncwarp();
        while ((uint32_t)clock() - t0 < TX) {}
        bulk_load(sb + (v < 2 ? OFF_XSEL : OFF_RING + 2 * 8192) + v * 8192, p.u + (size_t)(16 * c + 4 * v) * D_, 8192, bu + 8 * B_X);
        tma3d(sb + OFF_S + v * S_Q, &tm_x, 16 * pr, 64 * v + 32 * h - 1, bars + 8 * (B_S + v), S_Q);
        if (lane == 0) {
#pragma unroll
            for (int i = 0; i < 9; i++) mbar_init(bu + 32 * i, 1);
            mbar_init(bu + 8 * B_XE, 1);
            mbar_init(bu + 8 * B_Y, v == 0 ? 11 : 9);
            mbar_init(bu + 8 * B_DP, (0x1855 >> (4 * v)) & 15);
            mbar_init(bu + 8 * B_F, 1);
            mbar_init(bu + 8 * B_H, 1);
            asm volatile("fence.mbarrier_init.release.cluster;" ::: "memory");
            mbar_expect(bu + 8 * B_Y, 4096);
            if (v != 2) mbar_expect(bu + 8 * B_DP, v == 0 ? 2048 : (h || v == 3) ? 16384 : 16384 + 128);
            mbar_expect(bu + 8 * B_F, c < NGU_CTA ? 16 : 0);
        }
        __syncwarp();
        asm volatile("barrier.cluster.arrive.relaxed.aligned;" ::: "memory");
        WSTAMP(9);
        if (v < 3 && lane == 0) asm volatile("prefetch.tensormap [%0];" :: "l"(v == 0 ? &tm_gu : v == 1 ? &tm_down : &tm_out) : "memory");
        asm volatile("barrier.cluster.wait.acquire.aligned;" ::: "memory");
        uint32_t desc;
        {
            const int s = 6 * v + lane, i = s >> 2, w = s & 3, slot = s < 14 ? s : (s | 1) == 17 ? s - 16 : s - 12;
            const int fb = s < 4 ? B_H : (gu && s >= 14) ? B_E + slot : s < 6 ? B_XE + s - 2 : B_KG;
            desc = slot | (fb << 4) | ((i < 4 ? 256 * w + 64 * i : 1792 * h + 448 * w + 224 * (i - 4)) << 10);
            if (lane < 6) mbar_expect(bars + 8 * (B_W + s), i < 4 ? 8192 : 7168);
            if (tid == 32 * PREP_W0) mbar_arrive(bars + 8 * B_H);
        }
        if (v == 3) {
            mbar_wait(bars + 8 * B_U);
            mbar_wait(bars + 8 * (gu ? B_G : B_H + 2));
            const uint32_t tag16 = lds32(sb + M_TAG);
            uint4 q[8];
#pragma unroll 1
            for (int it = 0; it < (1 << 22); it++) {
                uint32_t bad = 0;
#pragma unroll
                for (int i = 0; i < 8; i++) q[i] = ld_gpu128(&p.sc->g[256 * h + 32 * i + lane]);
#pragma unroll
                for (int i = 0; i < 8; i++) bad |= ((q[i].x ^ tag16) | (q[i].y ^ tag16)) | ((q[i].z ^ tag16) | (q[i].w ^ tag16));
                if ((bad >> 16) == 0) break;
                __nanosleep(200);
            }
#pragma unroll
            for (int i = 0; i < 8; i++)
                asm volatile("st.shared.v2.u32 [%0], {%1, %2};" :: "r"(sb + OFF_GP + 256 * i + lane * 8),
                             "r"(__byte_perm(q[i].x, q[i].y, 0x5410)), "r"(__byte_perm(q[i].z, q[i].w, 0x5410)) : "memory");
            __syncwarp();
            if (lane == 0) mbar_arrive(bars + 8 * B_Y);
        }
        mbar_wait(bars + 8 * (B_H + v));
        {
            const int gap = v == 0 ? GAP : v == 1 ? GAP1 : v == 2 ? GAP2 : GAP3;
            uint32_t last = v ? clock() - SLACK : t0 + T0 - GAP + GAP * ((pr * 5) & 15) / 16;
#pragma unroll 1
            for (int k = 0; k < 6; k++) {
                const uint32_t dk = __reduce_max_sync(0xffffffffu, lane == k ? desc : 0);
                const bool dn = 6 * v + k >= 16;
                const uint32_t dst = sb + OFF_RING + (dk & 15) * 8192, bar = bars + 8 * (B_W + 6 * v + k), c0 = dn ? 16 * pr : 32 * c, c1 = dk >> 10;
                const CUtensorMap* tm = dn ? &tm_down : &tm_gu;
                mbar_wait(bars + ((dk >> 1) & 0x1f8));
                int late;
#pragma unroll 1
                while ((late = (int)(clock() - last) - gap) < 0) __nanosleep(max(-late >> 2, 32));
                WSTAMP(3 + k);
                if (gu || dn)
                    asm volatile("{\n\t.reg .pred p;\n\telect.sync _|p, 0xffffffff;\n\t"
                                 "@p cp.async.bulk.tensor.3d.shared::cluster.global.mbarrier::complete_tx::bytes [%0], [%1, {%3, %4, 0}], [%2];\n\t}"
                        :: "r"(dst), "l"(tm), "r"(bar), "r"(c0), "r"(c1) : "memory");
                last += gap + max(late - SLACK, 0);
            }
            if (lane == 0 && v < 3) mbar_arrive(bars + 8 * (B_H + v + 1));
        }
        {
            WSTAMP(1);
            mix_rows<2>(p, &tm_out, sb, sb + OFF_TAB + v * TAB_W, 0, PQ, v, h, pr, lane);
            WSTAMP(2);
            asm volatile("cp.async.bulk.commit_group;" ::: "memory");
            const uint32_t top = lds32(sb + M_TOP + 8 * v + 4 * (lane >> 4));
            const uint32_t row = ~top & 2047, ch = lane & 15, gp = gate_pos(row);
            const bool mine = ((row >> 8) & 1) == h;
            uint32_t gfin, x16, y16 = 0;
            asm volatile("ld.shared.u16 %0, [%1];" : "=r"(gfin) : "r"(sb + OFF_GP + gp * 2) : "memory");
            asm volatile("ld.shared.u16 %0, [%1];" : "=r"(x16) : "r"(sb + OFF_S + (row >> 9) * S_Q + s_addr((row & 7) * S_PL + 32 + (row & 248) * 4, ch >> 3) + 2 * (ch & 7)) : "memory");
            const float rsel = __uint_as_float(pin(__float_as_uint(bf_round(sigmoid_f(__uint_as_float((top ^ (((int)~top >> 31) | 0x80000000u)) & 0xffff0000u)))), lane));
            const uint32_t po = pin(sb + (4 * (ch & 7) + v) * 16 + (ch >> 3) * 8 + (lane >> 4) * 4, lane);
            bf16* op = pin(p.out + (size_t)row * D_ + 16 * pr + ch, lane);
            if (mine) {
                mbar_wait(bars + 8 * (B_Y + (row >> 9)));
                asm volatile("ld.shared.u16 %0, [%1];" : "=r"(y16)
                             : "r"(sb + y_off(row >> 9) + ch * 512 + (((4 * (row & 7) + ((row >> 5) & 3)) ^ (((ch >> 2) << 1) | (ch & 1))) << 4) + 2 * row_elem(row)) : "memory");
            }
            mbar_wait(bars + 8 * B_DP);
            float q[8];
#pragma unroll
            for (int i = 0; i < 4; i++) { q[i] = ldsf(po + M_DPIN + 512 * i); q[4 + i] = ldsf(po + OFF_XSEL + 14336 + 512 * i); }
            const float tot = ((q[0] + q[1]) + (q[2] + q[3])) + ((q[4] + q[5]) + (q[6] + q[7]));
            const float b = bf_round(__uint_as_float(x16 << 16) + bf_round(bf_round(tot) * rsel));
            if (mine) *op = __float2bfloat16_rn(fmaf(bf_lo(gfin), __uint_as_float(y16 << 16), bf_round(bf_round(1.f - bf_lo(gfin)) * b)));
        }
        asm volatile("cp.async.bulk.wait_group.read 0;" ::: "memory");
        WSTAMP(10);
        WDUMP();
    }
}

typedef CUresult (*EncodeFn)(CUtensorMap*, CUtensorMapDataType, cuuint32_t, void*, const cuuint64_t*, const cuuint64_t*,
                             const cuuint32_t*, const cuuint32_t*, CUtensorMapInterleave, CUtensorMapSwizzle,
                             CUtensorMapL2promotion, CUtensorMapFloatOOBfill);

void make_map(EncodeFn f, CUtensorMap* m, const void* ptr, uint64_t cols, uint64_t rows, uint64_t pitch, uint32_t bc, uint32_t br, CUtensorMapSwizzle sw, CUtensorMapL2promotion prom,
              uint32_t planes = 1, uint64_t plane_stride = 0, uint32_t box_planes = 0) {
    cuuint64_t dims[3] = {cols, rows, planes};
    cuuint64_t str[2] = {pitch, planes > 1 ? plane_stride : pitch * rows};
    cuuint32_t box[3] = {bc, br, box_planes ? box_planes : planes};
    cuuint32_t es[3] = {1, 1, 1};
    f(m, CU_TENSOR_MAP_DATA_TYPE_BFLOAT16, 3, (void*)ptr, dims, str, box, es, CU_TENSOR_MAP_INTERLEAVE_NONE, sw,
      prom, CU_TENSOR_MAP_FLOAT_OOB_FILL_NONE);
}

}

extern "C" void kernel_launch(void* const* d_in, const int* in_sizes, int n_in, void* d_out, int out_size) {
    static EncodeFn enc = nullptr;
    static void *sc = nullptr, *band = nullptr;
    if (!enc) {
        void* fn = nullptr;
        cudaDriverEntryPointQueryResult qr;
        cudaGetDriverEntryPoint("cuTensorMapEncodeTiled", &fn, cudaEnableDefault, &qr);
        enc = (EncodeFn)fn;
        cudaGetSymbolAddress(&sc, g_scratch);
        cudaGetSymbolAddress(&band, g_band);
        cudaFuncSetAttribute(fused_kernel, cudaFuncAttributeMaxDynamicSharedMemorySize, SMEM_BYTES);
    }
    CUtensorMap tg, td, tx, to;
    const char *wg = (const char*)d_in[9], *wu = (const char*)d_in[10];
    const bool swap = wu < wg;
    make_map(enc, &tg, swap ? wu : wg, F_, D_, F_ * 2, 32, 64, CU_TENSOR_MAP_SWIZZLE_64B, CU_TENSOR_MAP_L2_PROMOTION_L2_128B, 2, swap ? wg - wu : wu - wg);
    make_map(enc, &td, d_in[11], D_, F_, D_ * 2, 16, 224, CU_TENSOR_MAP_SWIZZLE_32B, CU_TENSOR_MAP_L2_PROMOTION_L2_64B);
    make_map(enc, &tx, d_in[0], D_, L_ / 8, D_ * 16, 16, 33, CU_TENSOR_MAP_SWIZZLE_32B, CU_TENSOR_MAP_L2_PROMOTION_NONE, 8, D_ * 2);
    make_map(enc, &to, d_out, D_, L_ / 8, D_ * 16, 16, 32, CU_TENSOR_MAP_SWIZZLE_NONE, CU_TENSOR_MAP_L2_PROMOTION_NONE, 8, D_ * 2, 1);
    Params p;
    p.u = (const bf16*)d_in[0]; p.logA = (const bf16*)d_in[1]; p.Aim = (const bf16*)d_in[2];
    p.Cre = (const bf16*)d_in[3]; p.Cim = (const bf16*)d_in[4]; p.logdt = (const bf16*)d_in[5];
    p.Dskip = (const bf16*)d_in[6]; p.wr = (const bf16*)d_in[8]; p.gatew = (const bf16*)d_in[12];
    p.out = (bf16*)d_out;
    p.sc = (Scratch*)sc; p.band = (const uint4*)band;
    p.gu_swap = swap;
    p.zero = 0;
    fused_kernel<<<NCTA, NTHREADS, SMEM_BYTES>>>(p, tg, td, tx, to);
}
```

```cpp
#include <cuda_runtime.h>
#include <cuda_bf16.h>
#include <cuda_fp16.h>
#include <cuda.h>
#include <stdint.h>

typedef __nv_bfloat16 bf16;

namespace {

constexpr int L_ = 2048, D_ = 1024, F_ = 3584;
constexpr int NCTA = 130;
constexpr int NTHREADS = 512;
constexpr int MAIN_W0 = 0, PREP_W0 = 8, AUX_W0 = 12;
#define TX 150
#define TR 3300
#define T0 3000
#define GAP 510
#define GAP1 515
#define GAP2 515
#define GAP3 560
#define HW 20
constexpr int SLACK = 300;
constexpr int PQ = 3;
constexpr int NGU_CTA = 112;

constexpr int OFF_RING = 0;
constexpr int OFF_SCR  = 6 * 8192;
constexpr int S_PL     = 1056;
constexpr int S_Q      = 8 * S_PL;
constexpr int OFF_S    = 114688;
constexpr int OFF_GP   = OFF_S + 4 * S_Q;
constexpr int U_PL     = 2240;
constexpr int U_CH     = 4416;
constexpr int OFF_U    = 151552;
constexpr int TAB_W    = 3200;
constexpr int T_PL     = 544;
constexpr int T_A      = 2192 - 26 * 8;
constexpr int T_B      = 2568 - 59 * 8;
constexpr int OFF_TAB  = 186880;
constexpr int OFF_XSEL = 212480;
constexpr int XS_ROW   = 2064;
constexpr int OFF_BAND = 228992;
constexpr int OFF_MISC = 229536;
constexpr int M_BARS   = OFF_MISC;
constexpr int M_DSK    = OFF_MISC + 2736;
constexpr int M_SINK   = OFF_MISC + 512;
constexpr int M_TAG    = OFF_MISC + 516;
constexpr int M_BMAP   = OFF_MISC + 528;
constexpr int M_DPIN   = OFF_MISC + 656;
constexpr int M_TOP    = OFF_MISC + 2704;
constexpr int SMEM_BYTES = OFF_MISC + 2768;
__device__ __forceinline__ uint32_t s_addr(uint32_t o, uint32_t half) { return o + (((half ^ (o >> 7)) & 1) << 4); }
__host__ __device__ constexpr uint32_t y_off(uint32_t q) { return OFF_RING + 32768 + (q & 1) * 8192 + (q >> 1) * 65536; }

constexpr int B_W = 0;
constexpr int B_E = 24;
constexpr int B_S = 36;
constexpr int B_Y = 40;
constexpr int B_DP = 44, B_U = 45, B_KG = 46, B_G = 47;
constexpr int B_F = 48;
constexpr int B_H = 60;
constexpr int B_X = 52, B_XE = 56;

struct BandTab { uint32_t w[11][12]; };
constexpr BandTab make_band() {
    BandTab b{};
    for (int cls = 0; cls < 11; cls++)
        for (int wd = 0; wd < 10; wd++) {
            const int tau = cls + 2 - 8 * ((wd < 4 ? wd : wd - 4) >> 1);
            const int lo = (wd < 4) ? ((wd & 1) ? -2 : 3) : ((wd & 1) ? -4 : -11), wid = (wd < 4 ? 3 : 7) + 2 * (wd & 1);
            b.w[cls][wd] = ((tau >= lo && tau < lo + wid) ? 0x3F80u : 0u) | ((tau - 4 >= lo && tau - 4 < lo + wid) ? 0x3F800000u : 0u);
        }
    return b;
}
constexpr int NTOP = 32;
struct Scratch {
    uint4 r[L_ / 4];
    uint4 g[L_ / 4];
    uint4 h[2][8 * F_ / 8];
    uint32_t top[NTOP][32];
    unsigned epoch;
};
__device__ __align__(128) Scratch g_scratch;
__device__ const __align__(16) BandTab g_band = make_band();

struct Params {
    const bf16 *u, *logA, *Aim, *Cre, *Cim, *logdt, *Dskip, *wr, *gatew;
    bf16* out;
    Scratch* sc;
    const uint4* band;
    uint32_t gu_swap;
    uint32_t zero;
};

#define WSTAMP(i) do {} while (0)
#define KSTAMP(i, dep) do {} while (0)
#define WDUMP() do {} while (0)
#define RSTAMP(i) do {} while (0)

__device__ __forceinline__ uint32_t smem_u32(const void* p) { return (uint32_t)__cvta_generic_to_shared(p); }
__device__ __forceinline__ void mbar_init(uint32_t b, uint32_t c) { asm volatile("mbarrier.init.shared::cta.b64 [%0], %1;" :: "r"(b), "r"(c) : "memory"); }
__device__ __forceinline__ void mbar_expect(uint32_t b, uint32_t tx) { asm volatile("mbarrier.arrive.expect_tx.shared::cta.b64 _, [%0], %1;" :: "r"(b), "r"(tx) : "memory"); }
__device__ __forceinline__ void mbar_arrive(uint32_t b) { asm volatile("mbarrier.arrive.shared::cta.b64 _, [%0];" :: "r"(b) : "memory"); }
__device__ __forceinline__ void mbar_wait(uint32_t b, uint32_t parity = 0) {
    asm volatile("{\n\t.reg .pred p;\nW%=:\n\tmbarrier.try_wait.parity.shared::cta.b64 p, [%0], %1, 20000;\n\t@!p bra W%=;\n\t}" :: "r"(b), "r"(parity) : "memory");
}
__device__ __forceinline__ uint32_t mapa(uint32_t addr, uint32_t rank) { uint32_t r; asm("mapa.shared::cluster.u32 %0, %1, %2;" : "=r"(r) : "r"(addr), "r"(rank)); return r; }
__device__ __forceinline__ void tma3d(uint32_t dst, const CUtensorMap* tm, int c0, int c1, uint32_t bar, uint32_t bytes) {
    asm volatile("{\n\t.reg .pred p;\n\telect.sync _|p, 0xffffffff;\n\t"
                 "@p mbarrier.arrive.expect_tx.shared::cta.b64 _, [%2], %5;\n\t"
                 "@p cp.async.bulk.tensor.3d.shared::cluster.global.mbarrier::complete_tx::bytes [%0], [%1, {%3, %4, 0}], [%2];\n\t}"
        :: "r"(dst), "l"(tm), "r"(bar), "r"(c0), "r"(c1), "r"(bytes) : "memory");
}
__device__ __forceinline__ void bulk_load(uint32_t dst, const void* src, uint32_t bytes, uint32_t bar) {
    asm volatile("{\n\t.reg .pred p;\n\telect.sync _|p, 0xffffffff;\n\t"
                 "@p mbarrier.arrive.expect_tx.shared::cta.b64 _, [%2], %3;\n\t"
                 "@p cp.async.bulk.shared::cluster.global.mbarrier::complete_tx::bytes [%0], [%1], %3, [%2];\n\t}"
        :: "r"(dst), "l"(src), "r"(bar), "r"(bytes) : "memory");
}
__device__ __forceinline__ void st_async16(uint32_t dst, const uint4& v, uint32_t bar) {
    asm volatile("st.async.weak.shared::cluster.mbarrier::complete_tx::bytes.v4.b32 [%0], {%1,%2,%3,%4}, [%5];"
                 :: "r"(dst), "r"(v.x), "r"(v.y), "r"(v.z), "r"(v.w), "r"(bar) : "memory");
}
__device__ __forceinline__ void bar_sync(int id, int n) { asm volatile("bar.sync %0, %1;" :: "r"(id), "r"(n) : "memory"); }
__device__ __forceinline__ void cp16(uint32_t dst, const void* src) { asm volatile("cp.async.cg.shared.global [%0], [%1], 16;" :: "r"(dst), "l"(src) : "memory"); }
__device__ __forceinline__ void cp_wait_all() { asm volatile("cp.async.wait_all;" ::: "memory"); }
__device__ __forceinline__ uint4 ld_gpu128(const void* p) { uint4 v; asm volatile("ld.relaxed.gpu.global.v4.u32 {%0,%1,%2,%3}, [%4];" : "=r"(v.x), "=r"(v.y), "=r"(v.z), "=r"(v.w) : "l"(p) : "memory"); return v; }
__device__ __forceinline__ void st_gpu32(void* p, uint32_t v) { asm volatile("st.relaxed.gpu.global.u32 [%0], %1;" :: "l"(p), "r"(v) : "memory"); }

__device__ __forceinline__ void ldsm4(uint32_t a, uint32_t& r0, uint32_t& r1, uint32_t& r2, uint32_t& r3) {
    asm volatile("ldmatrix.sync.aligned.m8n8.x4.shared.b16 {%0,%1,%2,%3}, [%4];" : "=r"(r0), "=r"(r1), "=r"(r2), "=r"(r3) : "r"(a) : "memory");
}
__device__ __forceinline__ void ldsm4t(uint32_t a, uint32_t& r0, uint32_t& r1, uint32_t& r2, uint32_t& r3) {
    asm volatile("ldmatrix.sync.aligned.m8n8.x4.trans.shared.b16 {%0,%1,%2,%3}, [%4];" : "=r"(r0), "=r"(r1), "=r"(r2), "=r"(r3) : "r"(a) : "memory");
}
__device__ __forceinline__ uint32_t lds32(uint32_t a) { uint32_t v; asm volatile("ld.shared.u32 %0, [%1];" : "=r"(v) : "r"(a) : "memory"); return v; }
__device__ __forceinline__ uint2 lds64(uint32_t a) { uint2 v; asm volatile("ld.shared.v2.u32 {%0,%1}, [%2];" : "=r"(v.x), "=r"(v.y) : "r"(a) : "memory"); return v; }
__device__ __forceinline__ uint4 lds128(uint32_t a) { uint4 v; asm volatile("ld.shared.v4.u32 {%0,%1,%2,%3}, [%4];" : "=r"(v.x), "=r"(v.y), "=r"(v.z), "=r"(v.w) : "r"(a) : "memory"); return v; }
__device__ __forceinline__ void sts32(uint32_t a, uint32_t v) { asm volatile("st.shared.u32 [%0], %1;" :: "r"(a), "r"(v) : "memory"); }
__device__ __forceinline__ void sts16(uint32_t a, uint32_t v) { asm volatile("st.shared.u16 [%0], %1;" :: "r"(a), "h"((unsigned short)v) : "memory"); }
__device__ __forceinline__ void sts128(uint32_t a, uint32_t x, uint32_t y, uint32_t z, uint32_t w) { asm volatile("st.shared.v4.u32 [%0], {%1,%2,%3,%4};" :: "r"(a), "r"(x), "r"(y), "r"(z), "r"(w) : "memory"); }
__device__ __forceinline__ float ldsf(uint32_t a) { float v; asm volatile("ld.shared.f32 %0, [%1];" : "=f"(v) : "r"(a) : "memory"); return v; }

__device__ __forceinline__ void mma_bf(float (&d)[4], uint32_t a0, uint32_t a1, uint32_t a2, uint32_t a3, uint32_t b0, uint32_t b1) {
    asm volatile("mma.sync.aligned.m16n8k16.row.col.f32.bf16.bf16.f32 {%0,%1,%2,%3}, {%4,%5,%6,%7}, {%8,%9}, {%0,%1,%2,%3};"
        : "+f"(d[0]), "+f"(d[1]), "+f"(d[2]), "+f"(d[3]) : "r"(a0), "r"(a1), "r"(a2), "r"(a3), "r"(b0), "r"(b1));
}
__device__ __forceinline__ void mma_bf_z(float (&d)[4], uint32_t a0, uint32_t a1, uint32_t a2, uint32_t a3, uint32_t b0, uint32_t b1) {
    asm volatile("mma.sync.aligned.m16n8k16.row.col.f32.bf16.bf16.f32 {%0,%1,%2,%3}, {%4,%5,%6,%7}, {%8,%9}, {%10,%10,%10,%10};"
        : "=f"(d[0]), "=f"(d[1]), "=f"(d[2]), "=f"(d[3]) : "r"(a0), "r"(a1), "r"(a2), "r"(a3), "r"(b0), "r"(b1), "f"(0.f));
}
__device__ __forceinline__ void mma_bf_k8(float (&d)[4], uint32_t a0, uint32_t a1, uint32_t b0) {
    asm volatile("mma.sync.aligned.m16n8k8.row.col.f32.bf16.bf16.f32 {%0,%1,%2,%3}, {%4,%5}, {%6}, {%0,%1,%2,%3};"
        : "+f"(d[0]), "+f"(d[1]), "+f"(d[2]), "+f"(d[3]) : "r"(a0), "r"(a1), "r"(b0));
}
__device__ __forceinline__ void mma_h(float (&d)[4], uint32_t a0, uint32_t a1, uint32_t a2, uint32_t a3, uint32_t b0, uint32_t b1) {
    asm volatile("mma.sync.aligned.m16n8k16.row.col.f32.f16.f16.f32 {%0,%1,%2,%3}, {%4,%5,%6,%7}, {%8,%9}, {%0,%1,%2,%3};"
        : "+f"(d[0]), "+f"(d[1]), "+f"(d[2]), "+f"(d[3]) : "r"(a0), "r"(a1), "r"(a2), "r"(a3), "r"(b0), "r"(b1));
}
__device__ __forceinline__ uint32_t pack_bf(float lo, float hi) { uint32_t r; asm("cvt.rn.bf16x2.f32 %0, %1, %2;" : "=r"(r) : "f"(hi), "f"(lo)); return r; }
__device__ __forceinline__ uint32_t pack_h(float lo, float hi) { uint32_t r; asm("cvt.rn.f16x2.f32 %0, %1, %2;" : "=r"(r) : "f"(hi), "f"(lo)); return r; }
__device__ __forceinline__ float bf_lo(uint32_t v) { return __uint_as_float(v << 16); }
__device__ __forceinline__ float bf_hi(uint32_t v) { return __uint_as_float(v & 0xffff0000u); }
__device__ __forceinline__ float bf_round(float x) { return __uint_as_float(pack_bf(0.f, x)); }
__device__ __forceinline__ uint32_t hmul2_bf(uint32_t a, uint32_t b) { uint32_t r; asm("mul.rn.bf16x2 %0, %1, %2;" : "=r"(r) : "r"(a), "r"(b)); return r; }
__device__ __forceinline__ float ex2f(float x) { float r; asm("ex2.approx.ftz.f32 %0, %1;" : "=f"(r) : "f"(x)); return r; }

__device__ __forceinline__ float exp_acc(float x) {
    const float t = x * 1.4426950216293335f;
    const float r = fmaf(x, 1.4426950216293335f, -t) + x * 1.9259629911266175e-8f;
    return ex2f(t) * fmaf(r, 0.6931471805599453f, 1.f);
}
__device__ __forceinline__ float sigmoid_f(float x) { return __fdividef(1.f, 1.f + ex2f(-x * 1.4426950408889634f)); }
__device__ __forceinline__ void cexp_pow(float l2, float li, float e, float& zr, float& zi) {
    const float mag = ex2f(l2 * e);
    zr = mag * __cosf(li * e);
    zi = mag * __sinf(li * e);
}
__device__ __forceinline__ uint32_t hcmul(uint32_t a, uint32_t k, uint32_t kp) {
    const __half2 A = *reinterpret_cast<const __half2*>(&a);
    const __half2 r = __hfma2(__high2half2(A), *reinterpret_cast<const __half2*>(&kp), __hmul2(__low2half2(A), *reinterpret_cast<const __half2*>(&k)));
    return *reinterpret_cast<const uint32_t*>(&r);
}
#define CMUL(orr, oi, ar, ai, br, bi) do { float _r = (ar) * (br) - (ai) * (bi); float _i = (ar) * (bi) + (ai) * (br); orr = _r; oi = _i; } while (0)
#define CSQ(orr, oi, ar, ai) do { float _r = (ar) * (ar) - (ai) * (ai); float _i = 2.f * (ar) * (ai); orr = _r; oi = _i; } while (0)

__device__ __forceinline__ void mma_bf_k8z(float (&d)[4], uint32_t a0, uint32_t a1, uint32_t b0) {
    asm volatile("mma.sync.aligned.m16n8k8.row.col.f32.bf16.bf16.f32 {%0,%1,%2,%3}, {%4,%5}, {%6}, {%7,%7,%7,%7};"
        : "=f"(d[0]), "=f"(d[1]), "=f"(d[2]), "=f"(d[3]) : "r"(a0), "r"(a1), "r"(b0), "f"(0.f));
}
__device__ __forceinline__ void mma_hh_k8(uint32_t& d0, uint32_t& d1, uint32_t a0, uint32_t a1, uint32_t b0) {
    asm volatile("mma.sync.aligned.m16n8k8.row.col.f16.f16.f16.f16 {%0,%1}, {%2,%3}, {%4}, {%5,%5};"
        : "=r"(d0), "=r"(d1) : "r"(a0), "r"(a1), "r"(b0), "r"(0));
}
__device__ __forceinline__ void sched_fence() { asm volatile("pmevent 0;" ::: "memory"); }
__device__ __forceinline__ uint32_t pin(uint32_t x, int lane) { return __shfl_sync(0xffffffffu, x, lane); }
template <class T> __device__ __forceinline__ T* pin(T* x, int lane) { return (T*)__shfl_sync(0xffffffffu, (unsigned long long)x, lane); }
__device__ __forceinline__ void sts32_if(bool on, uint32_t a, uint32_t v) {
    asm volatile("{\n\t.reg .pred p;\n\tsetp.ne.u32 p, %2, 0;\n\t@p st.shared.u32 [%0], %1;\n\t}" :: "r"(a), "r"(v), "r"((uint32_t)on) : "memory");
}
__device__ __forceinline__ void sts128_if(bool on, uint32_t a, uint32_t x, uint32_t y, uint32_t z, uint32_t w) {
    asm volatile("{\n\t.reg .pred p;\n\tsetp.ne.u32 p, %5, 0;\n\t@p st.shared.v4.u32 [%0], {%1,%2,%3,%4};\n\t}" :: "r"(a), "r"(x), "r"(y), "r"(z), "r"(w), "r"((uint32_t)on) : "memory");
}
__device__ __forceinline__ void lds128_if(bool on, uint32_t a, uint32_t (&v)[4]) {
    asm volatile("{\n\t.reg .pred p;\n\tsetp.ne.u32 p, %5, 0;\n\t@p ld.shared.v4.u32 {%0,%1,%2,%3}, [%4];\n\t}"
        : "+r"(v[0]), "+r"(v[1]), "+r"(v[2]), "+r"(v[3]) : "r"(a), "r"((uint32_t)on) : "memory");
}
__device__ __forceinline__ uint32_t hfma2_bf(uint32_t a, uint32_t b, uint32_t c) { uint32_t r; asm("fma.rn.bf16x2 %0, %1, %2, %3;" : "=r"(r) : "r"(a), "r"(b), "r"(c)); return r; }
__device__ __forceinline__ __nv_bfloat162 bcast(uint32_t a, int hi) { const __nv_bfloat162 v = *reinterpret_cast<const __nv_bfloat162*>(&a); return hi ? __high2bfloat162(v) : __low2bfloat162(v); }
__device__ __forceinline__ uint32_t hmul2_bc(uint32_t a, int hi, uint32_t b) { const __nv_bfloat162 r = __hmul2_rn(bcast(a, hi), *reinterpret_cast<const __nv_bfloat162*>(&b)); return *reinterpret_cast<const uint32_t*>(&r); }
__device__ __forceinline__ uint32_t hfma2_bc(uint32_t a, int hi, uint32_t b, uint32_t c) {
    const __nv_bfloat162 r = __hfma2(bcast(a, hi), *reinterpret_cast<const __nv_bfloat162*>(&b), *reinterpret_cast<const __nv_bfloat162*>(&c));
    return *reinterpret_cast<const uint32_t*>(&r);
}
__device__ __forceinline__ uint32_t row_elem(uint32_t row) { return ((row >> 5) & 4) | ((row >> 2) & 2) | ((row >> 4) & 1); }
__device__ __forceinline__ uint32_t gate_pos(uint32_t row) { return ((row >> 9) << 8) | ((row & 7) << 5) | (row_elem(row) << 2) | ((row >> 5) & 3); }

template <int N>
__device__ __forceinline__ void mix_rows(const Params& p, const CUtensorMap* tm_out, uint32_t sb, uint32_t ob, int Q0, int Q1, int w, int h, int pr, int lane) {
    const int g = lane >> 2, t = lane & 3, mi = lane >> 3, r = lane & 7;
    const int m8 = 16 * (g >> 2) + ((g >> 1) & 1) + 2 * (g & 1);
    uint32_t yi = sb + (4 * (r >> 1) + 2 * (mi & 1) + (r & 1)) * 512 + (((4 * w + (mi >> 1)) ^ r) << 4);
    uint32_t xs = sb + OFF_S + s_addr(w * S_PL + 32 + m8 * 32, t >> 1) + ((t & 1) << 3);
    uint32_t gs = sb + OFF_GP + w * 64 + g * 8, os = ob + m8 * 32 + t * 8;
    if (N > 1) { yi = pin(yi, lane); xs = pin(xs, lane); gs = pin(gs, lane); os = pin(os, lane); }
    mbar_wait(sb + M_BARS + 8 * B_Y);
#pragma unroll 1
    for (int Q = Q0; Q < Q1; Q++) {
        uint2 xq[N][4];
        uint32_t gg[N][2], sw[N];
#pragma unroll
        for (int n = 0; n < N; n++) {
#pragma unroll
            for (int i = 0; i < 4; i++) xq[n][i] = lds64((xs ^ (((i ^ n) & 1) << 4)) + Q * S_Q + n * 4 * S_PL + i * 128);
            const uint2 gq = lds64(gs + Q * 512 + n * 256);
            sw[n] = lds32(sb + M_BMAP + w * 16 + n * 64 + Q * 4);
            gg[n][0] = gq.x; gg[n][1] = gq.y;
#pragma unroll
            for (int i = 0; i < 4; i++) {
                const uint32_t og = hfma2_bf(gg[n][i >> 1], 0xBF80BF80u, 0x3F803F80u);
                xq[n][i].x = hmul2_bc(og, i & 1, xq[n][i].x); xq[n][i].y = hmul2_bc(og, i & 1, xq[n][i].y);
            }
        }
        mbar_wait(sb + M_BARS + 8 * (B_Y + Q));
        __syncwarp();
#pragma unroll
        for (int n = 0; n < N; n++) {
#pragma unroll
            for (int x = 0; x < 2; x++) {
                uint32_t y[4];
                ldsm4t((yi ^ (x << 5)) + y_off(Q) + n * 256, y[0], y[1], y[2], y[3]);
#pragma unroll
                for (int e = 0; e < 2; e++) {
                    uint2& o = xq[n][2 * x + e];
                    o.x = hfma2_bc(gg[n][x], e, y[2 * e], o.x); o.y = hfma2_bc(gg[n][x], e, y[2 * e + 1], o.y);
                }
            }
        }
        if ((sw[0] | sw[N - 1]) == 0) {
#pragma unroll
            for (int n = 0; n < N; n++)
#pragma unroll
                for (int i = 0; i < 4; i++)
                    asm volatile("st.shared.v2.u32 [%0], {%1, %2};" :: "r"(os + Q * 1024 + n * 4 * TAB_W + i * 128), "r"(xq[n][i].x), "r"(xq[n][i].y) : "memory");
            asm volatile("fence.proxy.async.shared::cta;" ::: "memory");
            __syncwarp();
#pragma unroll
            for (int n = 0; n < N; n++)
                asm volatile("{\n\t.reg .pred p;\n\telect.sync _|p, 0xffffffff;\n\t"
                             "@p cp.async.bulk.tensor.3d.global.shared::cta.bulk_group [%1, {%2, %3, %4}], [%0];\n\t}"
                    :: "r"(ob + 4 * n * TAB_W + Q * 1024), "l"(tm_out), "r"(16 * pr), "r"(64 * Q + 32 * h), "r"(w + 4 * n) : "memory");
        } else {
            bf16* op = p.out + (size_t)(512 * Q + 256 * h + 8 * m8 + w) * D_ + 16 * pr + 4 * t;
#pragma unroll
            for (int n = 0; n < N; n++)
#pragma unroll
                for (int i = 0; i < 4; i++)
                    if (!((sw[n] >> (4 * g)) & (1u << i))) *(uint2*)(op + (size_t)(32 * i + 4 * n) * D_) = xq[n][i];
        }
    }
}

__global__ void __cluster_dims__(2, 1, 1) __launch_bounds__(NTHREADS, 1)
fused_kernel(const Params p, const __grid_constant__ CUtensorMap tm_gu, const __grid_constant__ CUtensorMap tm_down,
             const __grid_constant__ CUtensorMap tm_x, const __grid_constant__ CUtensorMap tm_out) {
    extern __shared__ __align__(1024) unsigned char smem[];
    const uint32_t sb = smem_u32(smem);
    int tid;
    asm volatile("mov.u32 %0, %%tid.x;" : "=r"(tid));
    const int pw = tid >> 5, lane = tid & 31;
    const int c = blockIdx.x, h = c & 1, pr = c >> 1;
    const uint32_t bars = sb + M_BARS;

    uint2 v_la, v_ai, v_cr, v_ci;
    uint32_t ldt16;
    {
        const uint32_t po = c * 256 + tid;
        asm volatile("{\n\t.reg .pred p;\n\t.reg .b64 a;\n\tsetp.ne.u32 p, %16, 0;\n\t"
                     "mad.wide.u32 a, %14, 8, %9;\n\t@p ld.global.nc.L1::no_allocate.v2.u32 {%0,%1}, [a];\n\t"
                     "mad.wide.u32 a, %15, 2, %13;\n\t@p ld.global.nc.u16 %8, [a];\n\t"
                     "mad.wide.u32 a, %14, 8, %10;\n\t@p ld.global.nc.L1::no_allocate.v2.u32 {%2,%3}, [a];\n\t"
                     "mad.wide.u32 a, %14, 8, %11;\n\t@p ld.global.nc.L1::no_allocate.v2.u32 {%4,%5}, [a];\n\t"
                     "mad.wide.u32 a, %14, 8, %12;\n\t@p ld.global.nc.L1::no_allocate.v2.u32 {%6,%7}, [a];\n\t}"
            : "=r"(v_la.x), "=r"(v_la.y), "=r"(v_ai.x), "=r"(v_ai.y), "=r"(v_cr.x), "=r"(v_cr.y), "=r"(v_ci.x), "=r"(v_ci.y), "=r"(ldt16)
            : "l"(p.logA), "l"(p.Aim), "l"(p.Cre), "l"(p.Cim), "l"(p.logdt), "r"(po), "r"(po >> 5), "r"((uint32_t)(tid < 256 && c < 128)));
    }

    if (c >= 128) {
        if (c != 128) return;
        RSTAMP(5);
        const unsigned tag = (*(volatile unsigned*)&p.sc->epoch + 1) & 0xffffu;
        const uint32_t list = sb + 128;
        sts128(list + 16 * tid, 0, 0, 0, 0);
        if (tid == 0) sts32(sb + 64, 0);
        uint32_t key[4] = {tag - 1, tag - 1, tag - 1, tag - 1};
#pragma unroll 1
        for (int it = 0; it < (1 << 22); it++) {
            uint32_t a[4];
            asm volatile("{\n\t.reg .b128 o, z;\n\t.reg .b64 l, u;\n\tmov.b64 l, {%5, %5};\n\tmov.b128 z, {l, l};\n\tatom.relaxed.gpu.global.exch.b128 o, [%4], z;\n\t"
                         "mov.b128 {l, u}, o;\n\tmov.b64 {%0, %1}, l;\n\tmov.b64 {%2, %3}, u;\n\t}"
                : "=r"(a[0]), "=r"(a[1]), "=r"(a[2]), "=r"(a[3]) : "l"(&p.sc->r[tid]), "r"(tag - 1) : "memory");
#pragma unroll
            for (int i = 0; i < 4; i++) if (((a[i] ^ tag) & 0xffffu) == 0) key[i] = a[i];
            if ((((key[0] ^ tag) | (key[1] ^ tag) | (key[2] ^ tag) | (key[3] ^ tag)) & 0xffffu) == 0) break;
        }
        WSTAMP(0);
        uint32_t m = 0;
#pragma unroll
        for (int i = 0; i < 4; i++) {
            key[i] = (key[i] & 0xffff0000u) | (uint32_t)(2047 - (4 * tid + i));
            m = max(m, key[i]);
        }
        const uint32_t wm = __reduce_max_sync(0xffffffffu, m);
        if (lane == 0) sts32(sb + pw * 4, wm);
        __syncthreads();
        uint32_t thr = 0xffffffffu;
#pragma unroll
        for (int i = 0; i < 4; i++) { const uint4 q = lds128(sb + 16 * i); thr = min(thr, min(max(q.x, q.y), max(q.z, q.w))); }
        if (thr != 1) WSTAMP(1);
        if (m >= thr) {
            uint32_t pos;
            asm volatile("atom.shared.add.u32 %0, [%1], %2;" : "=r"(pos) : "r"(sb + 64), "r"(4 * ((key[0] >= thr) + (key[1] >= thr) + (key[2] >= thr) + (key[3] >= thr))) : "memory");
#pragma unroll
            for (int i = 0; i < 4; i++) if (key[i] >= thr) { sts32(list + pos, key[i]); pos += 4; }
        }
        __syncthreads();
        const uint32_t nc4 = lds32(sb + 64);
        if (nc4 != 1) WSTAMP(2);
#pragma unroll 1
        for (uint32_t j = 4 * pw; j < nc4; j += 64) {
            const uint32_t mine = lds32(list + j);
            int rank = 0;
#pragma unroll 1
            for (uint32_t i = 0; i < nc4; i += 128) rank += __popc(__ballot_sync(0xffffffffu, lds32(list + i + 4 * lane) > mine));
            if (rank < 8 && lane == 0) sts32(sb + 96 + 4 * rank, mine);
        }
        __syncthreads();
        if (tid < 8 * NTOP) st_gpu32(&p.sc->top[tid >> 3][tid & 7], lds32(sb + 96 + 4 * (tid & 7)) | ((tag & 31) << 11));
        WSTAMP(3);
        WDUMP();
        return;
    }

    WSTAMP(0);
    if (pw < 8) {
        const int d = 8 * c + pw - MAIN_W0;
        if (lane == 0) asm volatile("cp.async.ca.shared.global [%0], [%1], 4;" :: "r"(sb + M_DSK + 4 * (pw - MAIN_W0)), "l"(p.Dskip + (d & ~1)) : "memory");
        asm volatile("barrier.cluster.arrive.relaxed.aligned;" ::: "memory");
        const int warp = pw - MAIN_W0;
        asm volatile("setmaxnreg.inc.sync.aligned.u32 160;");
        const int g = lane >> 2, t = lane & 3;
        const int mi = lane >> 3, r = lane & 7;
        const uint32_t TB = sb + OFF_TAB + warp * TAB_W;
        const uint32_t UB = sb + OFF_U + warp * U_CH;
        if (mi < 2) sts128(UB + mi * U_PL + r * 16, 0, 0, 0, 0);
        if (lane < 4) sts128(TB + lane * T_PL, 0, 0, 0, 0);
        sts128(sb + OFF_SCR + warp * 8192 + lane * 16, 0x3C00u, 0x3C00u, 0x3C00u, 0x3C00u);
        asm volatile("barrier.cluster.wait.acquire.aligned;" ::: "memory");
        __syncwarp();

        uint32_t cfix;
        {
            KSTAMP(4, v_la.x ^ v_ai.x ^ v_cr.x ^ v_ci.x ^ ldt16);
            const float dt = bf_round(exp_acc(__uint_as_float(ldt16 << 16)));
            float l2[4], li[4];
            {
                const uint32_t la[2] = {v_la.x, v_la.y}, ai[2] = {v_ai.x, v_ai.y};
                const float dt2 = -1.4426950408889634f * dt;
#pragma unroll
                for (int i = 0; i < 4; i++) {
                    l2[i] = bf_round(ex2f(((i & 1) ? bf_hi(la[i >> 1]) : bf_lo(la[i >> 1])) * 1.4426950408889634f)) * dt2;
                    li[i] = ((i & 1) ? bf_hi(ai[i >> 1]) : bf_lo(ai[i >> 1])) * dt;
                }
            }
            const uint32_t SX = sb + OFF_SCR + warp * 8192;
            const uint32_t sw = SX + (lane << 4);
#define PUT(buf, row, v) sts128((buf) == 2 ? TB + (row) * T_PL + 16 + 16 * lane : ((sw + (row) * 512) ^ ((row) << 4)) + (buf) * 4096, v[0], v[1], v[2], v[3])
#define EMIT(bufa, rowa, bufb, rowb, xr, xi, k, kp) do { uint32_t pk[4], pd[4]; sched_fence(); \
                _Pragma("unroll") for (int i = 0; i < 4; i++) { pk[i] = pack_h(xr[i], xi[i]); pd[i] = hcmul(pk[i], k[i], kp[i]); } \
                PUT(bufa, rowa, pk); PUT(bufb, rowb, pd); } while (0)
#define CMUL4(orr, oi, ar, ai, br, bi) _Pragma("unroll") for (int i = 0; i < 4; i++) CMUL(orr[i], oi[i], ar[i], ai[i], br[i], bi[i])
#define CSQ4(orr, oi, ar, ai) _Pragma("unroll") for (int i = 0; i < 4; i++) CSQ(orr[i], oi[i], ar[i], ai[i])
            float z1r[4], z1i[4], z2r[4], z2i[4], z8r[4], z8i[4], z256r[4], z256i[4];
            uint32_t k4[4], k4p[4];
            float z4r[4], z4i[4];
#pragma unroll
            for (int i = 0; i < 4; i++) cexp_pow(l2[i], li[i], 1.f, z1r[i], z1i[i]);
            CSQ4(z2r, z2i, z1r, z1i);
            CSQ4(z4r, z4i, z2r, z2i);
            CSQ4(z8r, z8i, z4r, z4i);
            KSTAMP(5, __float_as_uint(z8r[3]));
            uint32_t Ya[16][4];
            float cr[4], ci[4], inv;
            {
                float w1r[4], w1i[4], ar[4], ai[4], br[4], bi[4];
                uint32_t k8[4], k8p[4];
#pragma unroll
                for (int i = 0; i < 4; i++) {
                    k8[i] = pack_h(z8r[i], -z8i[i]); k8p[i] = pack_h(z8i[i], z8r[i]);
                    CSQ(w1r[i], w1i[i], z8r[i], z8i[i]); w1i[i] = -w1i[i];
                }
                PUT(1, 0, k8);
                EMIT(0, 1, 1, 1, w1r, w1i, k8, k8p);
                CSQ4(ar, ai, w1r, w1i);            EMIT(0, 2, 1, 2, ar, ai, k8, k8p);
                CMUL4(br, bi, ar, ai, w1r, w1i);   EMIT(0, 3, 1, 3, br, bi, k8, k8p);
                CSQ4(ar, ai, ar, ai);              EMIT(0, 4, 1, 4, ar, ai, k8, k8p);
                CMUL4(ar, ai, ar, ai, w1r, w1i);   EMIT(0, 5, 1, 5, ar, ai, k8, k8p);
                CSQ4(br, bi, br, bi);              EMIT(0, 6, 1, 6, br, bi, k8, k8p);
                CMUL4(br, bi, br, bi, w1r, w1i);   EMIT(0, 7, 1, 7, br, bi, k8, k8p);
                __syncwarp();
                KSTAMP(6, 0);
                sched_fence();
                const uint32_t ab = SX + (mi & 1) * 4096 + r * 512, ax = ((mi >> 1) ^ r) << 4;
                const uint32_t vr[2] = {v_cr.x, v_cr.y}, vi[2] = {v_ci.x, v_ci.y};
                const uint32_t m2 = __vmaxu2(__vmaxu2(vr[0] & 0x7fff7fffu, vr[1] & 0x7fff7fffu), __vmaxu2(vi[0] & 0x7fff7fffu, vi[1] & 0x7fff7fffu));
                const uint32_t mx = __reduce_max_sync(0xffffffffu, max(m2, m2 << 16));
                const uint32_t e = min(max(mx >> 23, 11u), 254u);
                const float sc = __uint_as_float((264u - e) << 23);
                inv = __uint_as_float((e - 10u) << 23) * (2.f * dt);
#pragma unroll
                for (int i = 0; i < 4; i++) {
#pragma unroll
                    for (int k = 0; k < 4; k++) ldsm4(ab + (ax ^ (i << 5)) + k * 128, Ya[4 * k + i][0], Ya[4 * k + i][1], Ya[4 * k + i][2], Ya[4 * k + i][3]);
                    float tr, ti;
                    cexp_pow(l2[i], li[i], 128.f, tr, ti);
                    sts32(TB + 2176 + 256 * i + 4 * (lane ^ (8 * i)), pack_h(tr, ti));
                    sts32(TB + 2176 + 256 * i + 128 + 4 * (lane ^ (8 * i + 4)), pack_h(-ti, tr));
                    k4[i] = pack_h(z4r[i], z4i[i]); k4p[i] = pack_h(-z4i[i], z4r[i]);
                    CSQ(z256r[i], z256i[i], tr, ti);
                    cr[i] = ((i & 1) ? bf_hi(vr[i >> 1]) : bf_lo(vr[i >> 1])) * sc;
                    ci[i] = ((i & 1) ? bf_hi(vi[i >> 1]) : bf_lo(vi[i >> 1])) * sc;
                    if (i < 3) sched_fence();
                }
                __syncwarp();
            }
            KSTAMP(7, Ya[15][0]);
            const uint32_t ld0 = SX + r * 512 + ((mi ^ r) << 4), ld1 = ld0 ^ 64;
            float R[6][4], s1024;
            {
                float xr[4], xi[4], yr[4], yi[4];
                EMIT(0, 0, 0, 1, cr, ci, k4, k4p);
                CMUL4(yr, yi, cr, ci, z1r, z1i);        EMIT(0, 2, 0, 3, yr, yi, k4, k4p);
                CMUL4(xr, xi, cr, ci, z256r, z256i);    EMIT(2, 0, 2, 1, xr, xi, k4, k4p);
                CMUL4(yr, yi, yr, yi, z1r, z1i);        EMIT(0, 4, 0, 5, yr, yi, k4, k4p);
                CMUL4(cr, ci, yr, yi, z256r, z256i);    EMIT(2, 2, 2, 3, cr, ci, k4, k4p);
                CMUL4(yr, yi, yr, yi, z1r, z1i);        EMIT(0, 6, 0, 7, yr, yi, k4, k4p);
                CMUL4(xr, xi, xr, xi, z256r, z256i);    EMIT(1, 0, 1, 1, xr, xi, k4, k4p);
                CMUL4(xr, xi, xr, xi, z256r, z256i);    EMIT(1, 2, 1, 3, xr, xi, k4, k4p);
                CMUL4(xr, xi, xr, xi, z256r, z256i);
                s1024 = (xr[0] + xr[1]) + (xr[2] + xr[3]);
#pragma unroll
                for (int m = 4; m < 8; m++) {
                    if (m == 4) { CMUL4(xr, xi, xr, xi, z8r, z8i); } else { CMUL4(xr, xi, xr, xi, z256r, z256i); }
                    sched_fence();
                    const uint32_t pk[4] = {pack_h(xr[0], xi[0]), pack_h(xr[1], xi[1]), pack_h(xr[2], xi[2]), pack_h(xr[3], xi[3])};
                    PUT(1, m, pk);
                }
            }
            __syncwarp();
            {
                KSTAMP(8, 0);
                uint32_t bd[2][4] = {{0, 0, 0, 0}, {0, 0, 0, 0}};
                const bool on = (g >> 1) == t;
#pragma unroll
                for (int i = 0; i < 6; i++) { R[i][0] = R[i][1] = R[i][2] = R[i][3] = 0.f; }
                uint32_t x[2][4], y[2][4], z[2][4];
                auto fetch = [&](const int k2) {
                    const int b = k2 & 1;
                    lds128_if(on, TB + 2176 + g * 128 + 16 * (k2 ^ g), bd[b]);
                    ldsm4(((k2 & 1) ? ld1 : ld0) + (k2 >> 1) * 128, x[b][0], x[b][1], x[b][2], x[b][3]);
                    ldsm4(TB + ((r & 1) + ((r >> 1) == 2 ? 2 : 0)) * T_PL + 16 + 16 * mi + 64 * k2, y[b][0], y[b][1], y[b][2], y[b][3]);
                    ldsm4(((k2 & 1) ? ld1 : ld0) + (k2 >> 1) * 128 + 4096, z[b][0], z[b][1], z[b][2], z[b][3]);
                };
                fetch(0);
#pragma unroll
                for (int k2 = 0; k2 < 8; k2++) {
                    const int b = k2 & 1;
                    uint32_t a1[2][4];
                    if (k2 < 7) fetch(k2 + 1);
#pragma unroll
                    for (int u = 0; u < 2; u++) {
                        mma_hh_k8(a1[u][0], a1[u][1], Ya[2 * k2 + u][0], Ya[2 * k2 + u][1], bd[b][2 * u]);
                        mma_hh_k8(a1[u][2], a1[u][3], Ya[2 * k2 + u][2], Ya[2 * k2 + u][3], bd[b][2 * u + 1]);
                    }
#pragma unroll
                    for (int u = 0; u < 2; u++) {
                        const uint32_t(&a0)[4] = Ya[2 * k2 + u];
                        mma_h(R[0], a0[0], a0[1], a0[2], a0[3], x[b][2 * u], x[b][2 * u + 1]);
                        mma_h(R[2], a0[0], a0[1], a0[2], a0[3], y[b][2 * u], y[b][2 * u + 1]);
                        mma_h(R[4], a0[0], a0[1], a0[2], a0[3], z[b][2 * u], z[b][2 * u + 1]);
                        mma_h(R[1], a1[u][0], a1[u][1], a1[u][2], a1[u][3], x[b][2 * u], x[b][2 * u + 1]);
                        mma_h(R[3], a1[u][0], a1[u][1], a1[u][2], a1[u][3], y[b][2 * u], y[b][2 * u + 1]);
                        mma_h(R[5], a1[u][0], a1[u][1], a1[u][2], a1[u][3], z[b][2 * u], z[b][2 * u + 1]);
                    }
                }
            }
            __syncwarp();
            KSTAMP(9, __float_as_uint(R[3][0]));
            if (lane == 0) mbar_arrive(bars + 8 * B_KG + (__float_as_uint(R[0][0]) & __float_as_uint(R[4][0]) & p.zero));
            if (lane < 24) asm volatile("st.shared.v2.u32 [%0], {%1, %1};" :: "r"(TB + (lane < 9 ? 2176 : 2432) + 8 * lane), "r"(0) : "memory");
            __syncwarp();
#undef PUT
#undef EMIT
#pragma unroll
            for (int o = 16; o > 0; o >>= 1) s1024 += __shfl_xor_sync(0xffffffffu, s1024, o);
            uint32_t dsk = 0;
            cp_wait_all();
            asm volatile("{\n\t.reg .pred p;\n\tsetp.eq.u32 p, %2, 0;\n\t@p ld.shared.u16 %0, [%1];\n\t}" : "+r"(dsk) : "r"(sb + M_DSK + 4 * warp + 2 * (warp & 1)), "r"(lane) : "memory");
#pragma unroll
            for (int a = 0; a < 6; a++)
#pragma unroll
                for (int i = 0; i < 4; i++) R[a][i] = (a + i == 0) ? fmaf(R[0][0], inv, __uint_as_float(dsk << 16)) : R[a][i] * inv;
            const float k512 = __shfl_sync(0xffffffffu, R[4][0], 0), k516 = __shfl_sync(0xffffffffu, R[4][1], 0);
            const uint32_t w1 = TB + 16 + 16 * g + t * T_PL;
            float last;
#pragma unroll
            for (int a = 0; a < 4; a++) {
                const bool ahead = a >= 2 && t == 3;
                const float back = g == 7 ? (a ? R[a ? a - 1 : 0][3] : 0.f) : R[a][3], fwd = g == 0 ? (a == 2 ? R[3][0] : k512) : R[a][0];
                const float nb = __shfl_sync(0xffffffffu, ahead ? fwd : back, lane + (ahead ? 4 : 28));
                const float q0 = ahead ? R[a][0] : nb, q1 = ahead ? R[a][1] : R[a][0], q2 = ahead ? R[a][2] : R[a][1], q3 = ahead ? R[a][3] : R[a][2];
                last = ahead ? nb : R[a][3];
                sts128(w1 + 128 * a, pack_bf(q1, q0), pack_bf(q2, q1), pack_bf(q3, q2), pack_bf(last, q3));
            }
            {
                const float s0 = t == 3 ? k516 : k512, s1 = t < 2 ? k516 : 0.f;
                sts128_if(g == 7, w1 + 400, pack_bf(s0, last), pack_bf(s1, s0), pack_bf(0.f, s1), 0);
            }
            const uint32_t wq = TB + 8 * g + (t < 2 ? T_A + 8 * (32 + 16 * t) : T_B + 8 * (1 + 32 * t) + 12) + 64 * (t & 1), dq = 64 - 128 * (t & 1);
            uint32_t bw[2][2];
#pragma unroll
            for (int a = 0; a < 2; a++) {
                const uint32_t lo = pack_bf(R[4 + a][0], R[4 + a][1]), hi = pack_bf(R[4 + a][2], R[4 + a][3]);
                bw[a][0] = __byte_perm(lo, hi, t < 2 ? 0x1032 : 0x5410); bw[a][1] = __byte_perm(lo, hi, t < 2 ? 0x5476 : 0x7632);
            }
#pragma unroll
            for (int a = 0; a < 2; a++) {
                const uint32_t b0 = (t & 1) ? bw[a ^ 1][0] : bw[a][0], b1 = (t & 1) ? bw[a ^ 1][1] : bw[a][1], w = wq + a * dq;
                sts32_if(a == 1 || lane != 0, w, b0);
                sts32(w + (t < 2 ? 12 : 116), b1);
                sts32_if(t >= 2, w - 12, b0);
                sts32_if(t >= 2, w + 128, b1);
            }
            __syncwarp();
            if (lane == 31) sts16(w1 + 146, pack_bf(R[1][3], 0.f));
            cfix = pack_bf(s1024 * inv, s1024 * inv);
            if (lane == 0) sts32(TB + T_A + 8 * 64, cfix);
            __syncwarp();
        }
        WSTAMP(1);

        mbar_wait(bars + 8 * B_U);
        WSTAMP(2);

        float D[16][4];
        {
            const int x5 = g - t + 5;
            const uint32_t tabD = TB + (x5 & 3) * T_PL + (x5 & 12) + 16;
            {
                const uint32_t a1 = lds32(tabD - 8), a0 = p.zero;
#pragma unroll
                for (int jq = 0; jq < 4; jq++) {
                    uint32_t b[4];
                    ldsm4(UB + (9 + lane) * 16 + jq * 512, b[0], b[1], b[2], b[3]);
#pragma unroll
                    for (int i = 0; i < 4; i++) mma_bf_k8z(D[4 * jq + i], a0, a1, b[i]);
                }
            }
            const uint32_t ua = UB + (mi & 1) * U_PL + (8 + 8 * (mi >> 1) + r) * 16;
#pragma unroll 1
            for (int k0 = 0; k0 < 8; k0++) {
                uint32_t Uf[16][2];
#pragma unroll
                for (int jp = 0; jp < 8; jp++) ldsm4(ua + jp * 256 - k0 * 16, Uf[2 * jp][0], Uf[2 * jp][1], Uf[2 * jp + 1][0], Uf[2 * jp + 1][1]);
#pragma unroll
                for (int k1 = 0; k1 < 4; k1++) {
                    const uint32_t ta = tabD + 16 * (8 * k1 + k0);
                    const uint32_t a0 = lds32(ta), a1 = lds32(ta + 8), a2 = lds32(ta - 8), a3 = a0 ^ p.zero;
#pragma unroll
                    for (int J = k1; J < 16; J++) mma_bf(D[J], a0, a1, a2, a3, Uf[J - k1][0], Uf[J - k1][1]);
                }
                if (k0 == 0) {
                    const uint32_t ta = tabD + 16 * 32;
                    const uint32_t a0 = lds32(ta), a1 = lds32(ta + 8), a2 = lds32(ta - 8), a3 = a0 ^ p.zero;
#pragma unroll
                    for (int J = 4; J < 16; J++) mma_bf(D[J], a0, a1, a2, a3, Uf[J - 4][0], Uf[J - 4][1]);
                    const uint32_t f0 = (cfix ^ 0x80008000u) & (g == t ? 0xffffu : g == t + 4 ? 0xffff0000u : 0u);
                    const uint32_t f1 = p.zero, f2 = p.zero + p.zero, f3 = f0 ^ p.zero;
#pragma unroll
                    for (int J = 8; J < 16; J++) mma_bf(D[J], f0, f1, f2, f3, Uf[J - 8][0], Uf[J - 8][1]);
                }
            }
        }
        WSTAMP(3);
        {
            const int ch = 8 * h + warp;
            const uint32_t yo = sb + ch * 512 + ((lane ^ (((ch >> 2) << 1) | (ch & 1))) << 4);
            const uint32_t yr = mapa(yo, h ^ 1), ybr = mapa(bars + 8 * B_Y, h ^ 1);
            auto ship = [&](const int Q) {
                uint4 y[2];
#pragma unroll
                for (int hh = 0; hh < 2; hh++) {
                    const int J = 4 * Q + 2 * hh;
                    y[hh] = make_uint4(pack_bf(D[J][0], D[J][1]), pack_bf(D[J][2], D[J][3]), pack_bf(D[J + 1][0], D[J + 1][1]), pack_bf(D[J + 1][2], D[J + 1][3]));
                }
                if (!(Q & 1)) mbar_wait(bars + 8 * (B_F + (Q >> 1)));
                asm volatile("{\n\t.reg .pred p;\n\tsetp.eq.u32 p, %11, 0;\n\t"
                             "@p st.async.weak.shared::cluster.mbarrier::complete_tx::bytes.v4.b32 [%9], {%4,%5,%6,%7}, [%10];\n\t"
                             "@!p st.async.weak.shared::cluster.mbarrier::complete_tx::bytes.v4.b32 [%9], {%0,%1,%2,%3}, [%10];\n\t"
                             "@p st.shared.v4.b32 [%8], {%0,%1,%2,%3};\n\t@!p st.shared.v4.b32 [%8], {%4,%5,%6,%7};\n\t}"
                             :: "r"(y[0].x), "r"(y[0].y), "r"(y[0].z), "r"(y[0].w), "r"(y[1].x), "r"(y[1].y), "r"(y[1].z), "r"(y[1].w),
                                "r"(yo + y_off(Q)), "r"(yr + y_off(Q)), "r"(ybr + 8 * Q), "r"(h) : "memory");
                __syncwarp();
                if (lane == 0) mbar_arrive(bars + 8 * (B_Y + Q));
            };
            ship(0);
            const uint4 bA = lds128(sb + OFF_BAND + (g - t + 3) * 48), bB = lds128(sb + OFF_BAND + (g - t + 3) * 48 + 16);
            const uint2 bC = lds64(sb + OFF_BAND + (g - t + 3) * 48 + 32);
            uint2 QA[5][2], QB[8];
            const uint32_t tq = TB + 8 * (1 + g - 2 * t);
#pragma unroll
            for (int dd = 0; dd < 5; dd++) { QA[dd][0] = lds64(tq + T_A + 64 * (dd + 4)); QA[dd][1] = lds64(tq + T_A + 64 * (dd + 4) - 8); }
#pragma unroll
            for (int dd = 0; dd < 8; dd++) QB[dd] = lds64(tq + T_B + 64 * (dd + 8));
            const uint32_t u1 = UB + (mi & 1) * U_PL + (7 + r + (mi >> 1)) * 16;
            const uint32_t u2 = UB + ((mi & 1) ^ 1) * U_PL + (7 + r + (mi & 1) + 8 * (mi >> 1)) * 16;
            uint32_t n[4];
#pragma unroll
            for (int j = 0; j < 12; j++) {
                uint32_t m[4];
                ldsm4(u1 + j * 128, m[0], m[1], m[2], m[3]);
                if (!(j & 1)) ldsm4(u2 + j * 128, n[0], n[1], n[2], n[3]);
                const uint32_t n0 = n[2 * (j & 1)], n1 = n[2 * (j & 1) + 1];
                float wa[4], wb[4], wc[4], g1[4], g2[4];
                mma_bf_z(wa, bA.x, bA.y, bA.z, bA.w, m[0], m[1]);
                mma_bf_z(wb, bA.x, bA.y, bA.z, bA.w, n0, n1);
                mma_bf_z(wc, bA.x, bA.y, bA.z, bA.w, m[2], m[3]);
                if (j < 8) {
                    mma_bf_z(g1, bB.x, bB.y, bB.z, bB.w, m[0], m[1]);
                    mma_bf_z(g2, bB.x, bB.y, bB.z, bB.w, n0, n1);
                    mma_bf_k8(g1, bC.x, bC.y, m[2]);
                    mma_bf_k8(g2, bC.x, bC.y, m[3]);
                }
#pragma unroll
                for (int e = 0; e < 2; e++) {
                    const uint32_t q0 = pack_bf(wa[e], wa[e + 2]), q1 = pack_bf(wb[e], wb[e + 2]), q2 = q1 ^ p.zero, q3 = pack_bf(wc[e], wc[e + 2]);
#pragma unroll
                    for (int dd = 0; dd < 5; dd++)
                        if (j + 4 + dd < 16) mma_bf(D[j + 4 + dd], q0, q1, q2, q3, QA[dd][e].x, QA[dd][e].y);
                }
                if (j < 8) {
                    const uint32_t q0 = pack_bf(g1[0], g1[2]), q1 = pack_bf(g2[0], g2[2]), q2 = pack_bf(g1[1], g1[3]), q3 = pack_bf(g2[1], g2[3]);
#pragma unroll
                    for (int dd = 7 - j; dd >= 0; dd--) mma_bf(D[j + 8 + dd], q0, q1, q2, q3, QB[dd].x, QB[dd].y);
                }
                if ((j & 3) == 3) {
                    WSTAMP(4 + 2 * (j >> 2));
                    ship((j >> 2) + 1);
                }
            }
        }
        const int warpu = __reduce_max_sync(0xffffffffu, warp);
        mix_rows<1>(p, &tm_out, sb, sb + OFF_U + warpu * U_CH + (warpu & 1) * 64, PQ, 4, warpu, h, pr, lane);
        asm volatile("cp.async.bulk.commit_group;\n\tcp.async.bulk.wait_group.read 0;" ::: "memory");
        WSTAMP(10);
        WDUMP();
    } else if ((pw & 12) == AUX_W0) {
        const uint32_t t0 = clock();
        const int v = __reduce_max_sync(0xffffffffu, pw & 3);
        const int at = tid & 127;
        const int g = lane >> 2, t = lane & 3;
        unsigned tag;
        const bool gu = c < NGU_CTA;
        {
            const uint32_t xb = sb + (v < 2 ? OFF_XSEL : OFF_RING + 2 * 8192) + v * 8192;
            const uint32_t gws = sb + M_DPIN;
            const uint32_t row = 16 * c + 4 * v + (g >> 1);
#pragma unroll
            for (int i = 0; i < 8; i++)
                asm volatile("cp.async.ca.shared.global [%0], [%1], 4;" :: "r"((i < 4 ? sb + OFF_GP : gws) + 512 * (i & 3) + (tid & 124) * 4 + (tid & 1) * 8 + (tid & 2) * 2),
                             "l"((i < 4 ? p.wr : p.gatew) + 256 * (i & 3) + (tid & 127) * 2) : "memory");
            if ((tid & 127) < 33) cp16(sb + OFF_BAND + (tid & 127) * 16, p.band + (tid & 127));
            asm volatile("barrier.cluster.arrive.relaxed.aligned;" ::: "memory");
            tag = __reduce_max_sync(0xffffffffu, (*(volatile unsigned*)&p.sc->epoch + 1) & 0xffffu);
            if (gu) st_gpu32((uint32_t*)&p.sc->h[(tag + 1) & 1][32 * c] + at, 0);
            if (v == 2) sts32(sb + M_BMAP + lane * 4, 0);
            if (at == 0) sts32(sb + M_TAG, tag << 16);
            cp_wait_all();
            bar_sync(1, 128);
            uint2 w[16];
#pragma unroll
            for (int kb = 0; kb < 16; kb++) w[kb] = lds64((g < 4 ? sb + OFF_GP : gws) + 128 * kb + 32 * (g & 2) + 16 * t + 8 * (g & 1));
            asm volatile("barrier.cluster.wait.acquire.aligned;" ::: "memory");
            int early;
#pragma unroll 1
            while ((early = TR - (int)(clock() - t0)) > 0) __nanosleep(max(early >> 2, 32));
            mbar_wait(bars + 8 * (B_X + v));
            WSTAMP(10);
            float dr[4][4];
#pragma unroll
            for (int kb = 0; kb < 16; kb++) {
                const uint4 x = lds128(xb + (g >> 1) * 2048 + 128 * kb + 16 * (lane & 7));
                if (kb < 4) mma_bf_z(dr[kb], x.x, x.y, x.z, x.w, w[kb].x, w[kb].y);
                else mma_bf(dr[kb & 3], x.x, x.y, x.z, x.w, w[kb].x, w[kb].y);
            }
            float rs = ((dr[0][0] + dr[0][3]) + (dr[1][0] + dr[1][3])) + ((dr[2][0] + dr[2][3]) + (dr[3][0] + dr[3][3]));
            if (lane == 0) mbar_arrive(bars + 8 * (B_XE + v) + (__float_as_uint(rs) & p.zero));
            rs += __shfl_xor_sync(0xffffffffu, rs, 5);
            const uint32_t rb = pack_bf(0.f, rs);
            if (!(lane & 7)) st_gpu32((uint32_t*)p.sc->r + row, ((rb ^ (((int)rb >> 31) | 0x80000000u)) & 0xffff0000u) | tag);
            WSTAMP(1);
            {
                const int n = 3 + (lane >> 3) + 4 * (lane & 1);
                const uint32_t so = (n & 7) * S_PL + ((lane & 6) + (n >> 3)) * 32;
                const uint32_t src[2] = {sb + OFF_S + v * S_Q + s_addr(so, h), sb + OFF_S + v * S_Q + s_addr(so + 32, h)};
                const uint32_t dst = sb + OFF_U + g * U_CH + (8 + 32 * v + 16 * h + t) * 16;
                const uint32_t rdst = mapa(dst, h ^ 1), rbar = mapa(bars + 8 * B_U, h ^ 1);
                mbar_wait(bars + 8 * (B_S + v));
                WSTAMP(9);
                uint4 a[8];
#pragma unroll
                for (int b = 0; b < 2; b++) {
#pragma unroll
                    for (int j = 0; j < 8; j++) { const int u = 4 * b + (j >> 1) + 8 * (j & 1); ldsm4t((u < 8 ? src[u & 1] ^ 16 : src[u & 1]) + ((u >> 1) & 3) * 256, a[j].x, a[j].y, a[j].z, a[j].w); }
#pragma unroll
                    for (int j = 0; j < 8; j++) {
                        const int u = 4 * b + (j >> 1) + 8 * (j & 1);
                        if (u < 8) st_async16(rdst + ((u >> 1) & 3) * 64 + (u & 1) * U_PL, a[j], rbar);
                        else sts128(dst + ((u >> 1) & 3) * 64 + (u & 1) * U_PL, a[j].x, a[j].y, a[j].z, a[j].w);
                    }
                }
                if (h && v == 3) {
                    ldsm4t((src[0] ^ 16) + 1024, a[0].x, a[0].y, a[0].z, a[0].w);
                    ldsm4t(src[0] + 1024, a[1].x, a[1].y, a[1].z, a[1].w);
                    if (t == 0) {
                        st_async16(rdst + 256, make_uint4(a[0].x, a[0].y & 0xffffu, a[0].z & 0xffffu, a[0].w & 0xffffu), rbar);
                        sts128(dst + 256, a[1].x, a[1].y & 0xffffu, a[1].z & 0xffffu, a[1].w & 0xffffu);
                    }
                }
                __syncwarp();
                if (lane == 0) mbar_arrive(bars + 8 * B_U);
            }
            if ((lane & 7) == 2) st_gpu32((uint32_t*)p.sc->g + ((row & 256) << 2) + gate_pos(row), pack_bf(sigmoid_f(__uint_as_float(rb)), 0.f) | (tag << 16));
            WSTAMP(2);
        }
        {
            const bool lane0 = pin(lane, lane) == 0;
            const uint32_t own = pin(sb + OFF_XSEL + (at ^ ((at >> 1) & 4)) * 16, lane);
            float acc[8][4];
            const int krow = ((lane >> 1) & 8) + (lane & 7);
            const uint32_t tile0 = pin(sb + OFF_RING + v * 8192 + krow * 64 + ((((lane >> 3) & 1) ^ ((krow >> 1) & 3)) << 4), lane);
            const uint32_t xo = pin(sb + OFF_XSEL + (lane & 7) * XS_ROW + 512 * v + 2 * (lane & 24), lane);
            const uint32_t po = pin(sb + OFF_XSEL + t * XS_ROW + (g & 3) * 128 + (g & 1) * 64 + v * 16 + (lane >> 4) * 8, lane);
            const uint32_t po1 = pin(po + 64 - (g & 1) * 128, lane);
            uint32_t* hdst = pin((uint32_t*)&p.sc->h[tag & 1][32 * c] + at, lane);
            auto signal = [&](const int k, const uint32_t dep) {
                if (lane < 2 && v < 2)
                    asm volatile("st.async.weak.shared::cluster.mbarrier::complete_tx::bytes.b32 [%0], %1, [%2];"
                                 :: "r"(mapa(sb + M_SINK, lane)), "r"(dep), "r"(mapa(bars + 8 * (B_F + k), lane)) : "memory");
            };
            uint32_t a[16][4], b[2][4];
            auto load_a = [&](const uint32_t tile) {
#pragma unroll
                for (int q = 0; q < 16; q++) ldsm4t((tile ^ ((q & 1) << 5)) + ((q >> 1) & 1) * 4096 + (q >> 2) * 1024, a[q][0], a[q][1], a[q][2], a[q][3]);
            };
            auto load_b = [&](const uint32_t x) { ldsm4(x, b[0][0], b[0][1], b[0][2], b[0][3]); ldsm4(x + 64, b[1][0], b[1][1], b[1][2], b[1][3]); };
            auto burst = [&](const bool first) {
#pragma unroll
                for (int q = 0; q < 16; q++) {
                    if (first && q < 8) mma_bf_z(acc[q], a[q][0], a[q][1], a[q][2], a[q][3], b[0][(q >> 1) & 2], b[0][((q >> 1) & 2) + 1]);
                    else mma_bf(acc[q & 7], a[q][0], a[q][1], a[q][2], a[q][3], b[q >> 3][(q >> 1) & 2], b[q >> 3][((q >> 1) & 2) + 1]);
                }
            };
            if (gu) {
                mbar_wait(bars + 8 * (B_W + v));
                load_a(tile0);
                uint32_t dep = p.zero;
#pragma unroll
                for (int q = 0; q < 16; q += 2) dep &= a[q][0] & a[q + 1][0];
                if (lane == 0) mbar_arrive(bars + 8 * (B_E + v) + dep);
            }
            uint32_t top;
#pragma unroll 1
            for (int it = 0; it < (1 << 22); it++) {
                asm volatile("ld.relaxed.gpu.global.u32 %0, [%1];" : "=r"(top) : "l"(&p.sc->top[c % NTOP][g]) : "memory");
                if (__all_sync(0xffffffffu, ((top ^ (tag << 11)) & 0xf800u) == 0)) break;
                __nanosleep(40);
            }
            WSTAMP(3);
            if (gu) {
                const uint32_t k = 4 * h + v, row = __reduce_max_sync(0xffffffffu, lane == 4 * k ? ~top & 2047 : 0);
                asm volatile("{\n\t.reg .pred p;\n\telect.sync _|p, 0xffffffff;\n\t"
                             "@p cp.async.bulk.shared::cluster.global.mbarrier::complete_tx::bytes.multicast::cluster [%0], [%1], 2048, [%2], %3;\n\t}"
                    :: "r"(sb + OFF_XSEL + k * XS_ROW), "l"(p.u + (size_t)row * D_), "r"(bars + 8 * B_G), "h"((unsigned short)3) : "memory");
            }
            if (v == 2) {
                const uint32_t row = ~top & 2047;
                if (t == 0 && ((row >> 8) & 1) == h)
                    asm volatile("red.shared.or.b32 [%0], %1;" :: "r"(sb + M_BMAP + (row & 7) * 16 + (row >> 9) * 4), "r"(1u << (gate_pos(row) & 31)) : "memory");
                if (t == 0) sts32(sb + M_TOP + lane, top);
                if (c == 0 && lane == 0) *(volatile unsigned*)&p.sc->epoch = tag;
                __syncwarp();
                if (lane0) mbar_arrive(bars + 8 * B_Y);
            }
            if (gu) {
                mbar_wait(bars + 8 * B_G);
                WSTAMP(4);
                load_b(xo);
                burst(true);
#pragma unroll
                for (int i = 1; i < 4; i++) {
                    mbar_wait(bars + 8 * (B_W + 4 * i + v));
                    load_b(xo + 128 * i);
                    load_a(tile0 + (4 * i + v < 14 ? i : 0) * 32768);
                    if (lane0 && i > 1) mbar_arrive(bars + 8 * (B_E + 4 * i - 4 + v));
                    if (i == 2) signal(0, 0);
                    sched_fence();
                    burst(false);
                    sched_fence();
                }
                WSTAMP(5);
                __syncwarp();
#pragma unroll
                for (int q = 0; q < 4; q++) {
                    const int ct = q >> 1, e = 2 * (q & 1);
                    sts128(own + q * XS_ROW,
                           __float_as_uint(acc[ct][e] + acc[4 + ct][e]), __float_as_uint(acc[2 + ct][e] + acc[6 + ct][e]),
                           __float_as_uint(acc[ct][e + 1] + acc[4 + ct][e + 1]), __float_as_uint(acc[2 + ct][e + 1] + acc[6 + ct][e + 1]));
                }
                bar_sync(1, 128);
                float sl[2], uv[2];
#pragma unroll
                for (int e = 0; e < 2; e++) {
                    uint2 q[4];
#pragma unroll
                    for (int i = 0; i < 4; i++) q[i] = lds64((e ? po1 : po) + 512 * i);
                    const float s0 = (__uint_as_float(q[0].x) + __uint_as_float(q[1].x)) + (__uint_as_float(q[2].x) + __uint_as_float(q[3].x));
                    const float s1 = (__uint_as_float(q[0].y) + __uint_as_float(q[1].y)) + (__uint_as_float(q[2].y) + __uint_as_float(q[3].y));
                    const float gv = bf_round(p.gu_swap ? s1 : s0);
                    uv[e] = p.gu_swap ? s0 : s1;
                    sl[e] = gv * sigmoid_f(gv);
                }
                const uint32_t hw = hmul2_bf(pack_bf(sl[0], sl[1]), pack_bf(uv[0], uv[1]));
                st_gpu32(hdst, hw ? hw : 0x80000000u);
            }
            mbar_wait(bars + 8 * B_KG);
            signal(1, 0);
        }
        WSTAMP(6);
        {
            const uint32_t own = pin(sb + OFF_XSEL + at * 16, lane);
            const uint32_t hb = sb + (v < 2 ? OFF_XSEL + 7168 * v : OFF_RING + 8192 * v), hl = pin(hb + 16 * lane, lane);
            const int krow = ((lane >> 1) & 8) + (lane & 7);
            const uint32_t tile = pin(sb + OFF_RING + v * 8192 + krow * 32 + ((((lane >> 3) ^ (krow >> 2)) & 1) << 4), lane);
            float dd[4][4];
            bar_sync(1, 128);
            mbar_wait(bars + 8 * (B_W + HW));
            WSTAMP(12);
            const uint4* hs = &p.sc->h[tag & 1][32 * (56 * h + 14 * v)];
            bulk_load(hb, hs, 3584, bars + 8 * (B_X + v));
            bulk_load(hb + 3584, hs + 224, 3584, bars + 8 * (B_XE + v));
            mbar_wait(bars + 8 * B_Y);
            const uint32_t top = lds32(sb + M_TOP + 8 * v + 4 * (lane >> 4));
            const uint32_t row = ~top & 2047, ch = lane & 15;
            uint32_t gx, x16;
            asm volatile("ld.shared.u16 %0, [%1];" : "=r"(gx) : "r"(sb + OFF_GP + gate_pos(row) * 2) : "memory");
            asm volatile("ld.shared.u16 %0, [%1];" : "=r"(x16) : "r"(sb + OFF_S + (row >> 9) * S_Q + s_addr((row & 7) * S_PL + 32 + (row & 248) * 4, ch >> 3) + 2 * (ch & 7)) : "memory");
            gx = pin(gx | (x16 << 16), lane);
            const uint32_t rq = pin(pack_bf(0.f, sigmoid_f(__uint_as_float((top ^ (((int)~top >> 31) | 0x80000000u)) & 0xffff0000u))) | (row >> 8), lane);
            const uint32_t po = pin(sb + (4 * (ch & 7) + v) * 16 + (ch >> 3) * 8 + (lane >> 4) * 4, lane);
            const uint32_t ya = pin(sb + y_off(row >> 9) + ch * 512 + (((4 * (row & 7) + ((row >> 5) & 3)) ^ (((ch >> 2) << 1) | (ch & 1))) << 4) + 2 * row_elem(row), lane);
            const uint32_t oo = pin(row * D_ + 16 * pr + ch, lane);
            uint4 hq[7];
            {
                uint32_t a[14][4];
                mbar_wait(bars + 8 * (B_W + 16 + v));
#pragma unroll
                for (int j = 0; j < 14; j++) ldsm4t(tile + (v & 2) * 16384 + j * 512, a[j][0], a[j][1], a[j][2], a[j][3]);
#pragma unroll
                for (int k = 0; k < 2; k++) {
                    mbar_wait(bars + 8 * ((k ? B_XE : B_X) + v), 1);
                    if (!k) WSTAMP(7);
                    uint32_t mn = 0xffffffffu;
#pragma unroll
                    for (int j = 0; j < 7; j++) { hq[j] = lds128(hl + 3584 * k + 512 * j); mn = min(mn, hq[j].x); }
#pragma unroll 1
                    for (int it = 0; it < (1 << 20) && !__all_sync(0xffffffffu, mn != 0); it++) {
                        mn = 0xffffffffu;
#pragma unroll
                        for (int j = 0; j < 7; j++)
                            asm volatile("{\n\t.reg .pred p;\n\tsetp.eq.u32 p, %0, 0;\n\t@p ld.relaxed.gpu.global.v4.u32 {%0,%1,%2,%3}, [%4];\n\t}"
                                         : "+r"(hq[j].x), "+r"(hq[j].y), "+r"(hq[j].z), "+r"(hq[j].w) : "l"(hs + 224 * k + 32 * j + lane) : "memory");
#pragma unroll
                        for (int j = 0; j < 7; j++) mn = min(mn, hq[j].x);
                    }
                    if (!k) {
#pragma unroll
                        for (int j = 0; j < 14; j++) {
                            const uint4& q = hq[j >> 1];
                            if (j < 4) mma_bf_z(dd[j], a[j][0], a[j][1], a[j][2], a[j][3], (j & 1) ? q.z : q.x, (j & 1) ? q.w : q.y);
                            else mma_bf(dd[j & 3], a[j][0], a[j][1], a[j][2], a[j][3], (j & 1) ? q.z : q.x, (j & 1) ? q.w : q.y);
                        }
                    }
                }
            }
            mbar_wait(bars + 8 * (B_W + 20 + v));
#pragma unroll
            for (int j = 0; j < 14; j++) {
                uint32_t f[4];
                ldsm4t(tile + 65536 + j * 512, f[0], f[1], f[2], f[3]);
                mma_bf(dd[(j + 2) & 3], f[0], f[1], f[2], f[3], (j & 1) ? hq[j >> 1].z : hq[j >> 1].x, (j & 1) ? hq[j >> 1].w : hq[j >> 1].y);
            }
            WSTAMP(8);
            uint4 part;
            part.x = __float_as_uint((dd[0][0] + dd[1][0]) + (dd[2][0] + dd[3][0])); part.y = __float_as_uint((dd[0][1] + dd[1][1]) + (dd[2][1] + dd[3][1]));
            part.z = __float_as_uint((dd[0][2] + dd[1][2]) + (dd[2][2] + dd[3][2])); part.w = __float_as_uint((dd[0][3] + dd[1][3]) + (dd[2][3] + dd[3][3]));
            st_async16(mapa(own + (M_DPIN - OFF_XSEL), h ^ 1), part, mapa(bars + 8 * B_DP, h ^ 1));
            sts128(own + 14336, part.x, part.y, part.z, part.w);
            __syncwarp();
            if (lane == 0) mbar_arrive(bars + 8 * B_DP);
            const bool mine = (rq & 1) == h;
            uint32_t y16 = 0;
            if (mine) {
                mbar_wait(bars + 8 * B_Y + 4 * (rq & 6));
                asm volatile("ld.shared.u16 %0, [%1];" : "=r"(y16) : "r"(ya) : "memory");
            }
            mbar_wait(bars + 8 * B_DP);
            float q[8];
#pragma unroll
            for (int i = 0; i < 4; i++) { q[i] = ldsf(po + M_DPIN + 512 * i); q[4 + i] = ldsf(po + OFF_XSEL + 14336 + 512 * i); }
            const float tot = ((q[0] + q[1]) + (q[2] + q[3])) + ((q[4] + q[5]) + (q[6] + q[7]));
            const float b = bf_round(bf_hi(gx) + bf_round(bf_round(tot) * bf_hi(rq)));
            if (mine) p.out[oo] = __float2bfloat16_rn(fmaf(bf_lo(gx), __uint_as_float(y16 << 16), bf_round(bf_round(1.f - bf_lo(gx)) * b)));
            WSTAMP(11);
        }
        WDUMP();
    } else {
        asm volatile("setmaxnreg.dec.sync.aligned.u32 64;");
        const int v = __reduce_max_sync(0xffffffffu, pw - PREP_W0);
        const bool gu = c < NGU_CTA;
        const uint32_t t0 = clock();
        const uint32_t bu = bars + 8 * v;
        if (lane == 0) { mbar_init(bu + 8 * B_X, 1); mbar_init(bu + 8 * B_S, 1); }
        __syncwarp();
        while ((uint32_t)clock() - t0 < TX) {}
        bulk_load(sb + (v < 2 ? OFF_XSEL : OFF_RING + 2 * 8192) + v * 8192, p.u + (size_t)(16 * c + 4 * v) * D_, 8192, bu + 8 * B_X);
        tma3d(sb + OFF_S + v * S_Q, &tm_x, 16 * pr, 64 * v + 32 * h - 1, bars + 8 * (B_S + v), S_Q);
        if (lane == 0) {
#pragma unroll
            for (int i = 0; i < 9; i++) mbar_init(bu + 32 * i, 1);
            mbar_init(bu + 8 * B_XE, 1);
            mbar_init(bu + 8 * B_Y, v == 0 ? 11 : 9);
            mbar_init(bu + 8 * B_DP, (0x1855 >> (4 * v)) & 15);
            mbar_init(bu + 8 * B_F, 1);
            mbar_init(bu + 8 * B_H, 1);
            asm volatile("fence.mbarrier_init.release.cluster;" ::: "memory");
            mbar_expect(bu + 8 * B_Y, 4096);
            if (v != 2) mbar_expect(bu + 8 * B_DP, v == 0 ? 2048 : (h || v == 3) ? 16384 : 16384 + 128);
            mbar_expect(bu + 8 * B_F, (gu || v) ? 16 : 0);
        }
        __syncwarp();
        asm volatile("barrier.cluster.arrive.relaxed.aligned;" ::: "memory");
        WSTAMP(9);
        if (v < 3 && lane == 0) asm volatile("prefetch.tensormap [%0];" :: "l"(v == 0 ? &tm_gu : v == 1 ? &tm_down : &tm_out) : "memory");
        asm volatile("barrier.cluster.wait.acquire.aligned;" ::: "memory");
        uint32_t desc;
        {
            const int s = 6 * v + lane, i = s >> 2, w = s & 3, slot = s < 14 ? s : (s | 1) == 17 ? s - 16 : s - 12;
            const int fb = s < 4 ? B_H : (gu && s >= 14) ? B_E + slot : s < 6 ? B_XE + s - 2 : B_KG;
            desc = slot | (fb << 4) | ((i < 4 ? 256 * w + 64 * i : 1792 * h + 448 * w + 224 * (i - 4)) << 10);
            if (lane < 6) mbar_expect(bars + 8 * (B_W + s), i < 4 ? 8192 : 7168);
            if (tid == 32 * PREP_W0) mbar_arrive(bars + 8 * B_H);
        }
        if (v == 3) {
            mbar_wait(bars + 8 * B_U);
            mbar_wait(bars + 8 * (gu ? B_G : B_H + 2));
            const uint32_t tag16 = lds32(sb + M_TAG);
            uint4 q[8];
#pragma unroll 1
            for (int it = 0; it < (1 << 22); it++) {
                uint32_t bad = 0;
#pragma unroll
                for (int i = 0; i < 8; i++) q[i] = ld_gpu128(&p.sc->g[256 * h + 32 * i + lane]);
#pragma unroll
                for (int i = 0; i < 8; i++) bad |= ((q[i].x ^ tag16) | (q[i].y ^ tag16)) | ((q[i].z ^ tag16) | (q[i].w ^ tag16));
                if ((bad >> 16) == 0) break;
                __nanosleep(200);
            }
#pragma unroll
            for (int i = 0; i < 8; i++)
                asm volatile("st.shared.v2.u32 [%0], {%1, %2};" :: "r"(sb + OFF_GP + 256 * i + lane * 8),
                             "r"(__byte_perm(q[i].x, q[i].y, 0x5410)), "r"(__byte_perm(q[i].z, q[i].w, 0x5410)) : "memory");
            __syncwarp();
            if (lane == 0) mbar_arrive(bars + 8 * B_Y);
        }
        mbar_wait(bars + 8 * (B_H + v));
        {
            const int gap = v == 0 ? GAP : v == 1 ? GAP1 : v == 2 ? GAP2 : GAP3;
            uint32_t last = v ? clock() - SLACK : t0 + T0 - GAP + GAP * ((pr * 5) & 15) / 16;
#pragma unroll 1
            for (int k = 0; k < 6; k++) {
                const uint32_t dk = __reduce_max_sync(0xffffffffu, lane == k ? desc : 0);
                const bool dn = 6 * v + k >= 16;
                const uint32_t dst = sb + OFF_RING + (dk & 15) * 8192, bar = bars + 8 * (B_W + 6 * v + k), c0 = dn ? 16 * pr : 32 * c, c1 = dk >> 10;
                const CUtensorMap* tm = dn ? &tm_down : &tm_gu;
                mbar_wait(bars + ((dk >> 1) & 0x1f8));
                int late;
#pragma unroll 1
                while ((late = (int)(clock() - last) - gap) < 0) __nanosleep(max(-late >> 2, 32));
                WSTAMP(3 + k);
                if (gu || dn)
                    asm volatile("{\n\t.reg .pred p;\n\telect.sync _|p, 0xffffffff;\n\t"
                                 "@p cp.async.bulk.tensor.3d.shared::cluster.global.mbarrier::complete_tx::bytes [%0], [%1, {%3, %4, 0}], [%2];\n\t}"
                        :: "r"(dst), "l"(tm), "r"(bar), "r"(c0), "r"(c1) : "memory");
                last += gap + max(late - SLACK, 0);
            }
            if (lane == 0 && v < 3) mbar_arrive(bars + 8 * (B_H + v + 1));
        }
        {
            WSTAMP(1);
            mix_rows<2>(p, &tm_out, sb, sb + OFF_TAB + v * TAB_W, 0, PQ, v, h, pr, lane);
            WSTAMP(2);
            asm volatile("cp.async.bulk.commit_group;" ::: "memory");
        }
        asm volatile("cp.async.bulk.wait_group.read 0;" ::: "memory");
        WSTAMP(10);
        WDUMP();
    }
}

typedef CUresult (*EncodeFn)(CUtensorMap*, CUtensorMapDataType, cuuint32_t, void*, const cuuint64_t*, const cuuint64_t*,
                             const cuuint32_t*, const cuuint32_t*, CUtensorMapInterleave, CUtensorMapSwizzle,
                             CUtensorMapL2promotion, CUtensorMapFloatOOBfill);

void make_map(EncodeFn f, CUtensorMap* m, const void* ptr, uint64_t cols, uint64_t rows, uint64_t pitch, uint32_t bc, uint32_t br, CUtensorMapSwizzle sw, CUtensorMapL2promotion prom,
              uint32_t planes = 1, uint64_t plane_stride = 0, uint32_t box_planes = 0) {
    cuuint64_t dims[3] = {cols, rows, planes};
    cuuint64_t str[2] = {pitch, planes > 1 ? plane_stride : pitch * rows};
    cuuint32_t box[3] = {bc, br, box_planes ? box_planes : planes};
    cuuint32_t es[3] = {1, 1, 1};
    f(m, CU_TENSOR_MAP_DATA_TYPE_BFLOAT16, 3, (void*)ptr, dims, str, box, es, CU_TENSOR_MAP_INTERLEAVE_NONE, sw,
      prom, CU_TENSOR_MAP_FLOAT_OOB_FILL_NONE);
}

}

extern "C" void kernel_launch(void* const* d_in, const int* in_sizes, int n_in, void* d_out, int out_size) {
    static EncodeFn enc = nullptr;
    static void *sc = nullptr, *band = nullptr;
    if (!enc) {
        void* fn = nullptr;
        cudaDriverEntryPointQueryResult qr;
        cudaGetDriverEntryPoint("cuTensorMapEncodeTiled", &fn, cudaEnableDefault, &qr);
        enc = (EncodeFn)fn;
        cudaGetSymbolAddress(&sc, g_scratch);
        cudaGetSymbolAddress(&band, g_band);
        cudaFuncSetAttribute(fused_kernel, cudaFuncAttributeMaxDynamicSharedMemorySize, SMEM_BYTES);
    }
    CUtensorMap tg, td, tx, to;
    const char *wg = (const char*)d_in[9], *wu = (const char*)d_in[10];
    const bool swap = wu < wg;
    make_map(enc, &tg, swap ? wu : wg, F_, D_, F_ * 2, 32, 64, CU_TENSOR_MAP_SWIZZLE_64B, CU_TENSOR_MAP_L2_PROMOTION_L2_128B, 2, swap ? wg - wu : wu - wg);
    make_map(enc, &td, d_in[11], D_, F_, D_ * 2, 16, 224, CU_TENSOR_MAP_SWIZZLE_32B, CU_TENSOR_MAP_L2_PROMOTION_L2_64B);
    make_map(enc, &tx, d_in[0], D_, L_ / 8, D_ * 16, 16, 33, CU_TENSOR_MAP_SWIZZLE_32B, CU_TENSOR_MAP_L2_PROMOTION_NONE, 8, D_ * 2);
    make_map(enc, &to, d_out, D_, L_ / 8, D_ * 16, 16, 32, CU_TENSOR_MAP_SWIZZLE_NONE, CU_TENSOR_MAP_L2_PROMOTION_NONE, 8, D_ * 2, 1);
    Params p;
    p.u = (const bf16*)d_in[0]; p.logA = (const bf16*)d_in[1]; p.Aim = (const bf16*)d_in[2];
    p.Cre = (const bf16*)d_in[3]; p.Cim = (const bf16*)d_in[4]; p.logdt = (const bf16*)d_in[5];
    p.Dskip = (const bf16*)d_in[6]; p.wr = (const bf16*)d_in[8]; p.gatew = (const bf16*)d_in[12];
    p.out = (bf16*)d_out;
    p.sc = (Scratch*)sc; p.band = (const uint4*)band;
    p.gu_swap = swap;
    p.zero = 0;
    fused_kernel<<<NCTA, NTHREADS, SMEM_BYTES>>>(p, tg, td, tx, to);
}
```

```cpp
#include <cuda_runtime.h>
#include <cuda_bf16.h>
#include <cuda_fp16.h>
#include <cuda.h>
#include <stdint.h>

typedef __nv_bfloat16 bf16;

namespace {

constexpr int L_ = 2048, D_ = 1024, F_ = 3584;
constexpr int NCTA = 130;
constexpr int NTHREADS = 512;
constexpr int MAIN_W0 = 0, PREP_W0 = 8, AUX_W0 = 12;
#define TX 150
#define TR 3300
#define T0 3000
#define GAP 510
#define GAP1 500
#define GAP2 500
#define GAP3 530
#define HW 20
constexpr int SLACK = 300;
constexpr int PQ = 3;
constexpr int NGU_CTA = 112;

constexpr int OFF_RING = 0;
constexpr int OFF_SCR  = 6 * 8192;
constexpr int S_PL     = 1056;
constexpr int S_Q      = 8 * S_PL;
constexpr int OFF_S    = 114688;
constexpr int OFF_GP   = OFF_S + 4 * S_Q;
constexpr int U_PL     = 2240;
constexpr int U_CH     = 4416;
constexpr int OFF_U    = 151552;
constexpr int TAB_W    = 3200;
constexpr int T_PL     = 544;
constexpr int T_A      = 2192 - 26 * 8;
constexpr int T_B      = 2568 - 59 * 8;
constexpr int OFF_TAB  = 186880;
constexpr int OFF_XSEL = 212480;
constexpr int XS_ROW   = 2064;
constexpr int OFF_BAND = 228992;
constexpr int OFF_MISC = 229536;
constexpr int M_BARS   = OFF_MISC;
constexpr int M_DSK    = OFF_MISC + 2736;
constexpr int M_SINK   = OFF_MISC + 512;
constexpr int M_TAG    = OFF_MISC + 516;
constexpr int M_BMAP   = OFF_MISC + 528;
constexpr int M_DPIN   = OFF_MISC + 656;
constexpr int M_TOP    = OFF_MISC + 2704;
constexpr int SMEM_BYTES = OFF_MISC + 2768;
__device__ __forceinline__ uint32_t s_addr(uint32_t o, uint32_t half) { return o + (((half ^ (o >> 7)) & 1) << 4); }
__host__ __device__ constexpr uint32_t y_off(uint32_t q) { return OFF_RING + 32768 + (q & 1) * 8192 + (q >> 1) * 65536; }

constexpr int B_W = 0;
constexpr int B_E = 24;
constexpr int B_S = 36;
constexpr int B_Y = 40;
constexpr int B_DP = 44, B_U = 45, B_KG = 46, B_G = 47;
constexpr int B_F = 48;
constexpr int B_H = 60;
constexpr int B_X = 52, B_XE = 56;

struct BandTab { uint32_t w[11][12]; };
constexpr BandTab make_band() {
    BandTab b{};
    for (int cls = 0; cls < 11; cls++)
        for (int wd = 0; wd < 10; wd++) {
            const int tau = cls + 2 - 8 * ((wd < 4 ? wd : wd - 4) >> 1);
            const int lo = (wd < 4) ? ((wd & 1) ? -2 : 3) : ((wd & 1) ? -4 : -11), wid = (wd < 4 ? 3 : 7) + 2 * (wd & 1);
            b.w[cls][wd] = ((tau >= lo && tau < lo + wid) ? 0x3F80u : 0u) | ((tau - 4 >= lo && tau - 4 < lo + wid) ? 0x3F800000u : 0u);
        }
    return b;
}
constexpr int NTOP = 32;
struct Scratch {
    uint4 r[L_ / 4];
    uint4 g[L_ / 4];
    uint4 h[2][8 * F_ / 8];
    uint32_t top[NTOP][32];
    unsigned epoch;
};
__device__ __align__(128) Scratch g_scratch;
__device__ const __align__(16) BandTab g_band = make_band();

struct Params {
    const bf16 *u, *logA, *Aim, *Cre, *Cim, *logdt, *Dskip, *wr, *gatew;
    bf16* out;
    Scratch* sc;
    const uint4* band;
    uint32_t gu_swap;
    uint32_t zero;
};

#define WSTAMP(i) do {} while (0)
#define KSTAMP(i, dep) do {} while (0)
#define WDUMP() do {} while (0)
#define RSTAMP(i) do {} while (0)

__device__ __forceinline__ uint32_t smem_u32(const void* p) { return (uint32_t)__cvta_generic_to_shared(p); }
__device__ __forceinline__ void mbar_init(uint32_t b, uint32_t c) { asm volatile("mbarrier.init.shared::cta.b64 [%0], %1;" :: "r"(b), "r"(c) : "memory"); }
__device__ __forceinline__ void mbar_expect(uint32_t b, uint32_t tx) { asm volatile("mbarrier.arrive.expect_tx.shared::cta.b64 _, [%0], %1;" :: "r"(b), "r"(tx) : "memory"); }
__device__ __forceinline__ void mbar_arrive(uint32_t b) { asm volatile("mbarrier.arrive.shared::cta.b64 _, [%0];" :: "r"(b) : "memory"); }
__device__ __forceinline__ void mbar_wait(uint32_t b, uint32_t parity = 0) {
    asm volatile("{\n\t.reg .pred p;\nW%=:\n\tmbarrier.try_wait.parity.shared::cta.b64 p, [%0], %1, 20000;\n\t@!p bra W%=;\n\t}" :: "r"(b), "r"(parity) : "memory");
}
__device__ __forceinline__ uint32_t mapa(uint32_t addr, uint32_t rank) { uint32_t r; asm("mapa.shared::cluster.u32 %0, %1, %2;" : "=r"(r) : "r"(addr), "r"(rank)); return r; }
__device__ __forceinline__ void tma3d(uint32_t dst, const CUtensorMap* tm, int c0, int c1, uint32_t bar, uint32_t bytes) {
    asm volatile("{\n\t.reg .pred p;\n\telect.sync _|p, 0xffffffff;\n\t"
                 "@p mbarrier.arrive.expect_tx.shared::cta.b64 _, [%2], %5;\n\t"
                 "@p cp.async.bulk.tensor.3d.shared::cluster.global.mbarrier::complete_tx::bytes [%0], [%1, {%3, %4, 0}], [%2];\n\t}"
        :: "r"(dst), "l"(tm), "r"(bar), "r"(c0), "r"(c1), "r"(bytes) : "memory");
}
__device__ __forceinline__ void bulk_load(uint32_t dst, const void* src, uint32_t bytes, uint32_t bar) {
    asm volatile("{\n\t.reg .pred p;\n\telect.sync _|p, 0xffffffff;\n\t"
                 "@p mbarrier.arrive.expect_tx.shared::cta.b64 _, [%2], %3;\n\t"
                 "@p cp.async.bulk.shared::cluster.global.mbarrier::complete_tx::bytes [%0], [%1], %3, [%2];\n\t}"
        :: "r"(dst), "l"(src), "r"(bar), "r"(bytes) : "memory");
}
__device__ __forceinline__ void st_async16(uint32_t dst, const uint4& v, uint32_t bar) {
    asm volatile("st.async.weak.shared::cluster.mbarrier::complete_tx::bytes.v4.b32 [%0], {%1,%2,%3,%4}, [%5];"
                 :: "r"(dst), "r"(v.x), "r"(v.y), "r"(v.z), "r"(v.w), "r"(bar) : "memory");
}
__device__ __forceinline__ void bar_sync(int id, int n) { asm volatile("bar.sync %0, %1;" :: "r"(id), "r"(n) : "memory"); }
__device__ __forceinline__ void cp16(uint32_t dst, const void* src) { asm volatile("cp.async.cg.shared.global [%0], [%1], 16;" :: "r"(dst), "l"(src) : "memory"); }
__device__ __forceinline__ void cp_wait_all() { asm volatile("cp.async.wait_all;" ::: "memory"); }
__device__ __forceinline__ uint4 ld_gpu128(const void* p) { uint4 v; asm volatile("ld.relaxed.gpu.global.v4.u32 {%0,%1,%2,%3}, [%4];" : "=r"(v.x), "=r"(v.y), "=r"(v.z), "=r"(v.w) : "l"(p) : "memory"); return v; }
__device__ __forceinline__ void st_gpu32(void* p, uint32_t v) { asm volatile("st.relaxed.gpu.global.u32 [%0], %1;" :: "l"(p), "r"(v) : "memory"); }

__device__ __forceinline__ void ldsm4(uint32_t a, uint32_t& r0, uint32_t& r1, uint32_t& r2, uint32_t& r3) {
    asm volatile("ldmatrix.sync.aligned.m8n8.x4.shared.b16 {%0,%1,%2,%3}, [%4];" : "=r"(r0), "=r"(r1), "=r"(r2), "=r"(r3) : "r"(a) : "memory");
}
__device__ __forceinline__ void ldsm4t(uint32_t a, uint32_t& r0, uint32_t& r1, uint32_t& r2, uint32_t& r3) {
    asm volatile("ldmatrix.sync.aligned.m8n8.x4.trans.shared.b16 {%0,%1,%2,%3}, [%4];" : "=r"(r0), "=r"(r1), "=r"(r2), "=r"(r3) : "r"(a) : "memory");
}
__device__ __forceinline__ uint32_t lds32(uint32_t a) { uint32_t v; asm volatile("ld.shared.u32 %0, [%1];" : "=r"(v) : "r"(a) : "memory"); return v; }
__device__ __forceinline__ uint2 lds64(uint32_t a) { uint2 v; asm volatile("ld.shared.v2.u32 {%0,%1}, [%2];" : "=r"(v.x), "=r"(v.y) : "r"(a) : "memory"); return v; }
__device__ __forceinline__ uint4 lds128(uint32_t a) { uint4 v; asm volatile("ld.shared.v4.u32 {%0,%1,%2,%3}, [%4];" : "=r"(v.x), "=r"(v.y), "=r"(v.z), "=r"(v.w) : "r"(a) : "memory"); return v; }
__device__ __forceinline__ void sts32(uint32_t a, uint32_t v) { asm volatile("st.shared.u32 [%0], %1;" :: "r"(a), "r"(v) : "memory"); }
__device__ __forceinline__ void sts16(uint32_t a, uint32_t v) { asm volatile("st.shared.u16 [%0], %1;" :: "r"(a), "h"((unsigned short)v) : "memory"); }
__device__ __forceinline__ void sts128(uint32_t a, uint32_t x, uint32_t y, uint32_t z, uint32_t w) { asm volatile("st.shared.v4.u32 [%0], {%1,%2,%3,%4};" :: "r"(a), "r"(x), "r"(y), "r"(z), "r"(w) : "memory"); }
__device__ __forceinline__ float ldsf(uint32_t a) { float v; asm volatile("ld.shared.f32 %0, [%1];" : "=f"(v) : "r"(a) : "memory"); return v; }

__device__ __forceinline__ void mma_bf(float (&d)[4], uint32_t a0, uint32_t a1, uint32_t a2, uint32_t a3, uint32_t b0, uint32_t b1) {
    asm volatile("mma.sync.aligned.m16n8k16.row.col.f32.bf16.bf16.f32 {%0,%1,%2,%3}, {%4,%5,%6,%7}, {%8,%9}, {%0,%1,%2,%3};"
        : "+f"(d[0]), "+f"(d[1]), "+f"(d[2]), "+f"(d[3]) : "r"(a0), "r"(a1), "r"(a2), "r"(a3), "r"(b0), "r"(b1));
}
__device__ __forceinline__ void mma_bf_z(float (&d)[4], uint32_t a0, uint32_t a1, uint32_t a2, uint32_t a3, uint32_t b0, uint32_t b1) {
    asm volatile("mma.sync.aligned.m16n8k16.row.col.f32.bf16.bf16.f32 {%0,%1,%2,%3}, {%4,%5,%6,%7}, {%8,%9}, {%10,%10,%10,%10};"
        : "=f"(d[0]), "=f"(d[1]), "=f"(d[2]), "=f"(d[3]) : "r"(a0), "r"(a1), "r"(a2), "r"(a3), "r"(b0), "r"(b1), "f"(0.f));
}
__device__ __forceinline__ void mma_bf_k8(float (&d)[4], uint32_t a0, uint32_t a1, uint32_t b0) {
    asm volatile("mma.sync.aligned.m16n8k8.row.col.f32.bf16.bf16.f32 {%0,%1,%2,%3}, {%4,%5}, {%6}, {%0,%1,%2,%3};"
        : "+f"(d[0]), "+f"(d[1]), "+f"(d[2]), "+f"(d[3]) : "r"(a0), "r"(a1), "r"(b0));
}
__device__ __forceinline__ void mma_h(float (&d)[4], uint32_t a0, uint32_t a1, uint32_t a2, uint32_t a3, uint32_t b0, uint32_t b1) {
    asm volatile("mma.sync.aligned.m16n8k16.row.col.f32.f16.f16.f32 {%0,%1,%2,%3}, {%4,%5,%6,%7}, {%8,%9}, {%0,%1,%2,%3};"
        : "+f"(d[0]), "+f"(d[1]), "+f"(d[2]), "+f"(d[3]) : "r"(a0), "r"(a1), "r"(a2), "r"(a3), "r"(b0), "r"(b1));
}
__device__ __forceinline__ uint32_t pack_bf(float lo, float hi) { uint32_t r; asm("cvt.rn.bf16x2.f32 %0, %1, %2;" : "=r"(r) : "f"(hi), "f"(lo)); return r; }
__device__ __forceinline__ uint32_t pack_h(float lo, float hi) { uint32_t r; asm("cvt.rn.f16x2.f32 %0, %1, %2;" : "=r"(r) : "f"(hi), "f"(lo)); return r; }
__device__ __forceinline__ float bf_lo(uint32_t v) { return __uint_as_float(v << 16); }
__device__ __forceinline__ float bf_hi(uint32_t v) { return __uint_as_float(v & 0xffff0000u); }
__device__ __forceinline__ float bf_round(float x) { return __uint_as_float(pack_bf(0.f, x)); }
__device__ __forceinline__ uint32_t hmul2_bf(uint32_t a, uint32_t b) { uint32_t r; asm("mul.rn.bf16x2 %0, %1, %2;" : "=r"(r) : "r"(a), "r"(b)); return r; }
__device__ __forceinline__ float ex2f(float x) { float r; asm("ex2.approx.ftz.f32 %0, %1;" : "=f"(r) : "f"(x)); return r; }

__device__ __forceinline__ float exp_acc(float x) {
    const float t = x * 1.4426950216293335f;
    const float r = fmaf(x, 1.4426950216293335f, -t) + x * 1.9259629911266175e-8f;
    return ex2f(t) * fmaf(r, 0.6931471805599453f, 1.f);
}
__device__ __forceinline__ float sigmoid_f(float x) { return __fdividef(1.f, 1.f + ex2f(-x * 1.4426950408889634f)); }
__device__ __forceinline__ void cexp_pow(float l2, float li, float e, float& zr, float& zi) {
    const float mag = ex2f(l2 * e);
    zr = mag * __cosf(li * e);
    zi = mag * __sinf(li * e);
}
__device__ __forceinline__ uint32_t hcmul(uint32_t a, uint32_t k, uint32_t kp) {
    const __half2 A = *reinterpret_cast<const __half2*>(&a);
    const __half2 r = __hfma2(__high2half2(A), *reinterpret_cast<const __half2*>(&kp), __hmul2(__low2half2(A), *reinterpret_cast<const __half2*>(&k)));
    return *reinterpret_cast<const uint32_t*>(&r);
}
#define CMUL(orr, oi, ar, ai, br, bi) do { float _r = (ar) * (br) - (ai) * (bi); float _i = (ar) * (bi) + (ai) * (br); orr = _r; oi = _i; } while (0)
#define CSQ(orr, oi, ar, ai) do { float _r = (ar) * (ar) - (ai) * (ai); float _i = 2.f * (ar) * (ai); orr = _r; oi = _i; } while (0)

__device__ __forceinline__ void mma_bf_k8z(float (&d)[4], uint32_t a0, uint32_t a1, uint32_t b0) {
    asm volatile("mma.sync.aligned.m16n8k8.row.col.f32.bf16.bf16.f32 {%0,%1,%2,%3}, {%4,%5}, {%6}, {%7,%7,%7,%7};"
        : "=f"(d[0]), "=f"(d[1]), "=f"(d[2]), "=f"(d[3]) : "r"(a0), "r"(a1), "r"(b0), "f"(0.f));
}
__device__ __forceinline__ void mma_hh_k8(uint32_t& d0, uint32_t& d1, uint32_t a0, uint32_t a1, uint32_t b0) {
    asm volatile("mma.sync.aligned.m16n8k8.row.col.f16.f16.f16.f16 {%0,%1}, {%2,%3}, {%4}, {%5,%5};"
        : "=r"(d0), "=r"(d1) : "r"(a0), "r"(a1), "r"(b0), "r"(0));
}
__device__ __forceinline__ void sched_fence() { asm volatile("pmevent 0;" ::: "memory"); }
__device__ __forceinline__ uint32_t pin(uint32_t x, int lane) { return __shfl_sync(0xffffffffu, x, lane); }
template <class T> __device__ __forceinline__ T* pin(T* x, int lane) { return (T*)__shfl_sync(0xffffffffu, (unsigned long long)x, lane); }
__device__ __forceinline__ void sts32_if(bool on, uint32_t a, uint32_t v) {
    asm volatile("{\n\t.reg .pred p;\n\tsetp.ne.u32 p, %2, 0;\n\t@p st.shared.u32 [%0], %1;\n\t}" :: "r"(a), "r"(v), "r"((uint32_t)on) : "memory");
}
__device__ __forceinline__ void sts128_if(bool on, uint32_t a, uint32_t x, uint32_t y, uint32_t z, uint32_t w) {
    asm volatile("{\n\t.reg .pred p;\n\tsetp.ne.u32 p, %5, 0;\n\t@p st.shared.v4.u32 [%0], {%1,%2,%3,%4};\n\t}" :: "r"(a), "r"(x), "r"(y), "r"(z), "r"(w), "r"((uint32_t)on) : "memory");
}
__device__ __forceinline__ void lds128_if(bool on, uint32_t a, uint32_t (&v)[4]) {
    asm volatile("{\n\t.reg .pred p;\n\tsetp.ne.u32 p, %5, 0;\n\t@p ld.shared.v4.u32 {%0,%1,%2,%3}, [%4];\n\t}"
        : "+r"(v[0]), "+r"(v[1]), "+r"(v[2]), "+r"(v[3]) : "r"(a), "r"((uint32_t)on) : "memory");
}
__device__ __forceinline__ uint32_t hfma2_bf(uint32_t a, uint32_t b, uint32_t c) { uint32_t r; asm("fma.rn.bf16x2 %0, %1, %2, %3;" : "=r"(r) : "r"(a), "r"(b), "r"(c)); return r; }
__device__ __forceinline__ __nv_bfloat162 bcast(uint32_t a, int hi) { const __nv_bfloat162 v = *reinterpret_cast<const __nv_bfloat162*>(&a); return hi ? __high2bfloat162(v) : __low2bfloat162(v); }
__device__ __forceinline__ uint32_t hmul2_bc(uint32_t a, int hi, uint32_t b) { const __nv_bfloat162 r = __hmul2_rn(bcast(a, hi), *reinterpret_cast<const __nv_bfloat162*>(&b)); return *reinterpret_cast<const uint32_t*>(&r); }
__device__ __forceinline__ uint32_t hfma2_bc(uint32_t a, int hi, uint32_t b, uint32_t c) {
    const __nv_bfloat162 r = __hfma2(bcast(a, hi), *reinterpret_cast<const __nv_bfloat162*>(&b), *reinterpret_cast<const __nv_bfloat162*>(&c));
    return *reinterpret_cast<const uint32_t*>(&r);
}
__device__ __forceinline__ uint32_t row_elem(uint32_t row) { return ((row >> 5) & 4) | ((row >> 2) & 2) | ((row >> 4) & 1); }
__device__ __forceinline__ uint32_t gate_pos(uint32_t row) { return ((row >> 9) << 8) | ((row & 7) << 5) | (row_elem(row) << 2) | ((row >> 5) & 3); }

template <int N>
__device__ __forceinline__ void mix_rows(const Params& p, const CUtensorMap* tm_out, uint32_t sb, int Q0, int Q1, int w, int h, int pr, int lane) {
    const int g = lane >> 2, t = lane & 3, mi = lane >> 3, r = lane & 7;
    const int m8 = 16 * (g >> 2) + ((g >> 1) & 1) + 2 * (g & 1);
    uint32_t yi = sb + (4 * (r >> 1) + 2 * (mi & 1) + (r & 1)) * 512 + (((4 * w + (mi >> 1)) ^ r) << 4);
    uint32_t xs = sb + OFF_S + s_addr(w * S_PL + 32 + m8 * 32, t >> 1) + ((t & 1) << 3);
    const uint32_t ob = sb + OFF_TAB + w * TAB_W;
    uint32_t gs = sb + OFF_GP + w * 64 + g * 8, os = ob + m8 * 32 + t * 8;
    if (N > 1) { yi = pin(yi, lane); xs = pin(xs, lane); gs = pin(gs, lane); os = pin(os, lane); }
    mbar_wait(sb + M_BARS + 8 * B_Y);
#pragma unroll 1
    for (int Q = Q0; Q < Q1; Q++) {
        uint2 xq[N][4];
        uint32_t gg[N][2], sw[N];
#pragma unroll
        for (int n = 0; n < N; n++) {
#pragma unroll
            for (int i = 0; i < 4; i++) xq[n][i] = lds64((xs ^ (((i ^ n) & 1) << 4)) + Q * S_Q + n * 4 * S_PL + i * 128);
            const uint2 gq = lds64(gs + Q * 512 + n * 256);
            sw[n] = lds32(sb + M_BMAP + w * 16 + n * 64 + Q * 4);
            gg[n][0] = gq.x; gg[n][1] = gq.y;
#pragma unroll
            for (int i = 0; i < 4; i++) {
                const uint32_t og = hfma2_bf(gg[n][i >> 1], 0xBF80BF80u, 0x3F803F80u);
                xq[n][i].x = hmul2_bc(og, i & 1, xq[n][i].x); xq[n][i].y = hmul2_bc(og, i & 1, xq[n][i].y);
            }
        }
        mbar_wait(sb + M_BARS + 8 * (B_Y + Q));
        __syncwarp();
#pragma unroll
        for (int n = 0; n < N; n++) {
#pragma unroll
            for (int x = 0; x < 2; x++) {
                uint32_t y[4];
                ldsm4t((yi ^ (x << 5)) + y_off(Q) + n * 256, y[0], y[1], y[2], y[3]);
#pragma unroll
                for (int e = 0; e < 2; e++) {
                    uint2& o = xq[n][2 * x + e];
                    o.x = hfma2_bc(gg[n][x], e, y[2 * e], o.x); o.y = hfma2_bc(gg[n][x], e, y[2 * e + 1], o.y);
                }
            }
        }
        if (N > 1 && (sw[0] | sw[N - 1]) == 0) {
#pragma unroll
            for (int n = 0; n < N; n++)
#pragma unroll
                for (int i = 0; i < 4; i++)
                    asm volatile("st.shared.v2.u32 [%0], {%1, %2};" :: "r"(os + Q * 1024 + n * 4 * TAB_W + i * 128), "r"(xq[n][i].x), "r"(xq[n][i].y) : "memory");
            asm volatile("fence.proxy.async.shared::cta;" ::: "memory");
            __syncwarp();
#pragma unroll
            for (int n = 0; n < N; n++)
                asm volatile("{\n\t.reg .pred p;\n\telect.sync _|p, 0xffffffff;\n\t"
                             "@p cp.async.bulk.tensor.3d.global.shared::cta.bulk_group [%1, {%2, %3, %4}], [%0];\n\t}"
                    :: "r"(ob + 4 * n * TAB_W + Q * 1024), "l"(tm_out), "r"(16 * pr), "r"(64 * Q + 32 * h), "r"(w + 4 * n) : "memory");
        } else {
            bf16* op = p.out + (size_t)(512 * Q + 256 * h + 8 * m8 + w) * D_ + 16 * pr + 4 * t;
#pragma unroll
            for (int n = 0; n < N; n++)
#pragma unroll
                for (int i = 0; i < 4; i++)
                    if (!((sw[n] >> (4 * g)) & (1u << i))) *(uint2*)(op + (size_t)(32 * i + 4 * n) * D_) = xq[n][i];
        }
    }
}

__device__ __forceinline__ uint32_t pair_of_cluster(uint32_t cl) {
    uint32_t r;
    asm("{\n\t.reg .u32 x, a, b, f;\n\t.reg .pred p, q;\n\tadd.u32 x, %1, 60;\n\tand.b32 x, x, 63;\n\tshl.b32 f, x, 2;\n\t"
        "shr.u32 a, x, 3;\n\tmad.lo.u32 a, a, -31, f;\n\tmad.lo.u32 b, x, 37, -160;\n\tshr.u32 b, b, 8;\n\tmad.lo.u32 b, b, -27, f;\n\tadd.u32 b, b, 12;\n\t"
        "setp.lt.u32 p, x, 32;\n\tsetp.lt.u32 q, x, 60;\n\tselp.u32 b, b, x, q;\n\tselp.u32 %0, a, b, p;\n\t}" : "=r"(r) : "r"(cl));
    return r;
}

__global__ void __cluster_dims__(2, 1, 1) __launch_bounds__(NTHREADS, 1)
fused_kernel(const Params p, const __grid_constant__ CUtensorMap tm_gu, const __grid_constant__ CUtensorMap tm_down,
             const __grid_constant__ CUtensorMap tm_x, const __grid_constant__ CUtensorMap tm_out) {
    extern __shared__ __align__(1024) unsigned char smem[];
    const uint32_t sb = smem_u32(smem);
    int tid;
    asm volatile("mov.u32 %0, %%tid.x;" : "=r"(tid));
    const int pw = tid >> 5, lane = tid & 31;
    const int h = blockIdx.x & 1;
    const uint32_t bars = sb + M_BARS;

    uint2 v_la, v_ai, v_cr, v_ci;
    uint32_t ldt16;
    const uint32_t gt = blockIdx.x * 512 + tid, prv = pair_of_cluster(gt >> 10);
    {
        const uint32_t po = prv * 512 + h * 256 + tid;
        asm volatile("{\n\t.reg .pred p;\n\t.reg .b64 a;\n\tsetp.ne.u32 p, %16, 0;\n\t"
                     "mad.wide.u32 a, %14, 8, %9;\n\t@p ld.global.nc.L1::no_allocate.v2.u32 {%0,%1}, [a];\n\t"
                     "mad.wide.u32 a, %15, 2, %13;\n\t@p ld.global.nc.u16 %8, [a];\n\t"
                     "mad.wide.u32 a, %14, 8, %10;\n\t@p ld.global.nc.L1::no_allocate.v2.u32 {%2,%3}, [a];\n\t"
                     "mad.wide.u32 a, %14, 8, %11;\n\t@p ld.global.nc.L1::no_allocate.v2.u32 {%4,%5}, [a];\n\t"
                     "mad.wide.u32 a, %14, 8, %12;\n\t@p ld.global.nc.L1::no_allocate.v2.u32 {%6,%7}, [a];\n\t}"
            : "=r"(v_la.x), "=r"(v_la.y), "=r"(v_ai.x), "=r"(v_ai.y), "=r"(v_cr.x), "=r"(v_cr.y), "=r"(v_ci.x), "=r"(v_ci.y), "=r"(ldt16)
            : "l"(p.logA), "l"(p.Aim), "l"(p.Cre), "l"(p.Cim), "l"(p.logdt), "r"(po), "r"(po >> 5), "r"((uint32_t)((gt & 0x10100) == 0)));
    }
    const int pr = __reduce_max_sync(0xffffffffu, prv), c = 2 * pr + h;

    if (blockIdx.x >= 128) {
        if (h) return;
        RSTAMP(5);
        const unsigned tag = (*(volatile unsigned*)&p.sc->epoch + 1) & 0xffffu;
        const uint32_t list = sb + 128;
        sts128(list + 16 * tid, 0, 0, 0, 0);
        if (tid == 0) sts32(sb + 64, 0);
        uint32_t key[4] = {tag - 1, tag - 1, tag - 1, tag - 1};
#pragma unroll 1
        for (int it = 0; it < (1 << 22); it++) {
            uint32_t a[4];
            asm volatile("{\n\t.reg .b128 o, z;\n\t.reg .b64 l, u;\n\tmov.b64 l, {%5, %5};\n\tmov.b128 z, {l, l};\n\tatom.relaxed.gpu.global.exch.b128 o, [%4], z;\n\t"
                         "mov.b128 {l, u}, o;\n\tmov.b64 {%0, %1}, l;\n\tmov.b64 {%2, %3}, u;\n\t}"
                : "=r"(a[0]), "=r"(a[1]), "=r"(a[2]), "=r"(a[3]) : "l"(&p.sc->r[tid]), "r"(tag - 1) : "memory");
#pragma unroll
            for (int i = 0; i < 4; i++) if (((a[i] ^ tag) & 0xffffu) == 0) key[i] = a[i];
            if ((((key[0] ^ tag) | (key[1] ^ tag) | (key[2] ^ tag) | (key[3] ^ tag)) & 0xffffu) == 0) break;
        }
        WSTAMP(0);
        uint32_t m = 0;
#pragma unroll
        for (int i = 0; i < 4; i++) {
            key[i] = (key[i] & 0xffff0000u) | (uint32_t)(2047 - (4 * tid + i));
            m = max(m, key[i]);
        }
        const uint32_t wm = __reduce_max_sync(0xffffffffu, m);
        if (lane == 0) sts32(sb + pw * 4, wm);
        __syncthreads();
        uint32_t thr = 0xffffffffu;
#pragma unroll
        for (int i = 0; i < 4; i++) { const uint4 q = lds128(sb + 16 * i); thr = min(thr, min(max(q.x, q.y), max(q.z, q.w))); }
        if (thr != 1) WSTAMP(1);
        if (m >= thr) {
            uint32_t pos;
            asm volatile("atom.shared.add.u32 %0, [%1], %2;" : "=r"(pos) : "r"(sb + 64), "r"(4 * ((key[0] >= thr) + (key[1] >= thr) + (key[2] >= thr) + (key[3] >= thr))) : "memory");
#pragma unroll
            for (int i = 0; i < 4; i++) if (key[i] >= thr) { sts32(list + pos, key[i]); pos += 4; }
        }
        __syncthreads();
        const uint32_t nc4 = lds32(sb + 64);
        if (nc4 != 1) WSTAMP(2);
#pragma unroll 1
        for (uint32_t j = 4 * pw; j < nc4; j += 64) {
            const uint32_t mine = lds32(list + j);
            int rank = 0;
#pragma unroll 1
            for (uint32_t i = 0; i < nc4; i += 128) rank += __popc(__ballot_sync(0xffffffffu, lds32(list + i + 4 * lane) > mine));
            if (rank < 8 && lane == 0) sts32(sb + 96 + 4 * rank, mine);
        }
        __syncthreads();
        if (tid < 8 * NTOP) st_gpu32(&p.sc->top[tid >> 3][tid & 7], lds32(sb + 96 + 4 * (tid & 7)) | ((tag & 31) << 11));
        WSTAMP(3);
        WDUMP();
        return;
    }

    WSTAMP(0);
    if (pw < 8) {
        const int d = 8 * c + pw - MAIN_W0;
        if (lane == 0) asm volatile("cp.async.ca.shared.global [%0], [%1], 4;" :: "r"(sb + M_DSK + 4 * (pw - MAIN_W0)), "l"(p.Dskip + (d & ~1)) : "memory");
        asm volatile("barrier.cluster.arrive.relaxed.aligned;" ::: "memory");
        const int warp = pw - MAIN_W0;
        asm volatile("setmaxnreg.inc.sync.aligned.u32 160;");
        const int g = lane >> 2, t = lane & 3;
        const int mi = lane >> 3, r = lane & 7;
        const uint32_t TB = sb + OFF_TAB + warp * TAB_W;
        const uint32_t UB = sb + OFF_U + warp * U_CH;
        if (mi < 2) sts128(UB + mi * U_PL + r * 16, 0, 0, 0, 0);
        if (lane < 4) sts128(TB + lane * T_PL, 0, 0, 0, 0);
        sts128(sb + OFF_SCR + warp * 8192 + lane * 16, 0x3C00u, 0x3C00u, 0x3C00u, 0x3C00u);
        asm volatile("barrier.cluster.wait.acquire.aligned;" ::: "memory");
        __syncwarp();

        uint32_t cfix;
        {
            KSTAMP(4, v_la.x ^ v_ai.x ^ v_cr.x ^ v_ci.x ^ ldt16);
            const float dt = bf_round(exp_acc(__uint_as_float(ldt16 << 16)));
            float l2[4], li[4];
            {
                const uint32_t la[2] = {v_la.x, v_la.y}, ai[2] = {v_ai.x, v_ai.y};
                const float dt2 = -1.4426950408889634f * dt;
#pragma unroll
                for (int i = 0; i < 4; i++) {
                    l2[i] = bf_round(ex2f(((i & 1) ? bf_hi(la[i >> 1]) : bf_lo(la[i >> 1])) * 1.4426950408889634f)) * dt2;
                    li[i] = ((i & 1) ? bf_hi(ai[i >> 1]) : bf_lo(ai[i >> 1])) * dt;
                }
            }
            const uint32_t SX = sb + OFF_SCR + warp * 8192;
            const uint32_t sw = SX + (lane << 4);
#define PUT(buf, row, v) sts128((buf) == 2 ? TB + (row) * T_PL + 16 + 16 * lane : ((sw + (row) * 512) ^ ((row) << 4)) + (buf) * 4096, v[0], v[1], v[2], v[3])
#define EMIT(bufa, rowa, bufb, rowb, xr, xi, k, kp) do { uint32_t pk[4], pd[4]; sched_fence(); \
                _Pragma("unroll") for (int i = 0; i < 4; i++) { pk[i] = pack_h(xr[i], xi[i]); pd[i] = hcmul(pk[i], k[i], kp[i]); } \
                PUT(bufa, rowa, pk); PUT(bufb, rowb, pd); } while (0)
#define CMUL4(orr, oi, ar, ai, br, bi) _Pragma("unroll") for (int i = 0; i < 4; i++) CMUL(orr[i], oi[i], ar[i], ai[i], br[i], bi[i])
#define CSQ4(orr, oi, ar, ai) _Pragma("unroll") for (int i = 0; i < 4; i++) CSQ(orr[i], oi[i], ar[i], ai[i])
            float z1r[4], z1i[4], z2r[4], z2i[4], z8r[4], z8i[4], z256r[4], z256i[4];
            uint32_t k4[4], k4p[4];
            float z4r[4], z4i[4];
#pragma unroll
            for (int i = 0; i < 4; i++) cexp_pow(l2[i], li[i], 1.f, z1r[i], z1i[i]);
            CSQ4(z2r, z2i, z1r, z1i);
            CSQ4(z4r, z4i, z2r, z2i);
            CSQ4(z8r, z8i, z4r, z4i);
            KSTAMP(5, __float_as_uint(z8r[3]));
            uint32_t Ya[16][4];
            float cr[4], ci[4], inv;
            {
                float w1r[4], w1i[4], ar[4], ai[4], br[4], bi[4];
                uint32_t k8[4], k8p[4];
#pragma unroll
                for (int i = 0; i < 4; i++) {
                    k8[i] = pack_h(z8r[i], -z8i[i]); k8p[i] = pack_h(z8i[i], z8r[i]);
                    CSQ(w1r[i], w1i[i], z8r[i], z8i[i]); w1i[i] = -w1i[i];
                }
                PUT(1, 0, k8);
                EMIT(0, 1, 1, 1, w1r, w1i, k8, k8p);
                CSQ4(ar, ai, w1r, w1i);            EMIT(0, 2, 1, 2, ar, ai, k8, k8p);
                CMUL4(br, bi, ar, ai, w1r, w1i);   EMIT(0, 3, 1, 3, br, bi, k8, k8p);
                CSQ4(ar, ai, ar, ai);              EMIT(0, 4, 1, 4, ar, ai, k8, k8p);
                CMUL4(ar, ai, ar, ai, w1r, w1i);   EMIT(0, 5, 1, 5, ar, ai, k8, k8p);
                CSQ4(br, bi, br, bi);              EMIT(0, 6, 1, 6, br, bi, k8, k8p);
                CMUL4(br, bi, br, bi, w1r, w1i);   EMIT(0, 7, 1, 7, br, bi, k8, k8p);
                __syncwarp();
                KSTAMP(6, 0);
                sched_fence();
                const uint32_t ab = SX + (mi & 1) * 4096 + r * 512, ax = ((mi >> 1) ^ r) << 4;
                const uint32_t vr[2] = {v_cr.x, v_cr.y}, vi[2] = {v_ci.x, v_ci.y};
                const uint32_t m2 = __vmaxu2(__vmaxu2(vr[0] & 0x7fff7fffu, vr[1] & 0x7fff7fffu), __vmaxu2(vi[0] & 0x7fff7fffu, vi[1] & 0x7fff7fffu));
                const uint32_t mx = __reduce_max_sync(0xffffffffu, max(m2, m2 << 16));
                const uint32_t e = min(max(mx >> 23, 11u), 254u);
                const float sc = __uint_as_float((264u - e) << 23);
                inv = __uint_as_float((e - 10u) << 23) * (2.f * dt);
#pragma unroll
                for (int i = 0; i < 4; i++) {
#pragma unroll
                    for (int k = 0; k < 4; k++) ldsm4(ab + (ax ^ (i << 5)) + k * 128, Ya[4 * k + i][0], Ya[4 * k + i][1], Ya[4 * k + i][2], Ya[4 * k + i][3]);
                    float tr, ti;
                    cexp_pow(l2[i], li[i], 128.f, tr, ti);
                    sts32(TB + 2176 + 256 * i + 4 * (lane ^ (8 * i)), pack_h(tr, ti));
                    sts32(TB + 2176 + 256 * i + 128 + 4 * (lane ^ (8 * i + 4)), pack_h(-ti, tr));
                    k4[i] = pack_h(z4r[i], z4i[i]); k4p[i] = pack_h(-z4i[i], z4r[i]);
                    CSQ(z256r[i], z256i[i], tr, ti);
                    cr[i] = ((i & 1) ? bf_hi(vr[i >> 1]) : bf_lo(vr[i >> 1])) * sc;
                    ci[i] = ((i & 1) ? bf_hi(vi[i >> 1]) : bf_lo(vi[i >> 1])) * sc;
                    if (i < 3) sched_fence();
                }
                __syncwarp();
            }
            KSTAMP(7, Ya[15][0]);
            const uint32_t ld0 = SX + r * 512 + ((mi ^ r) << 4), ld1 = ld0 ^ 64;
            float R[6][4], s1024;
            {
                float xr[4], xi[4], yr[4], yi[4];
                EMIT(0, 0, 0, 1, cr, ci, k4, k4p);
                CMUL4(yr, yi, cr, ci, z1r, z1i);        EMIT(0, 2, 0, 3, yr, yi, k4, k4p);
                CMUL4(xr, xi, cr, ci, z256r, z256i);    EMIT(2, 0, 2, 1, xr, xi, k4, k4p);
                CMUL4(yr, yi, yr, yi, z1r, z1i);        EMIT(0, 4, 0, 5, yr, yi, k4, k4p);
                CMUL4(cr, ci, yr, yi, z256r, z256i);    EMIT(2, 2, 2, 3, cr, ci, k4, k4p);
                CMUL4(yr, yi, yr, yi, z1r, z1i);        EMIT(0, 6, 0, 7, yr, yi, k4, k4p);
                CMUL4(xr, xi, xr, xi, z256r, z256i);    EMIT(1, 0, 1, 1, xr, xi, k4, k4p);
                CMUL4(xr, xi, xr, xi, z256r, z256i);    EMIT(1, 2, 1, 3, xr, xi, k4, k4p);
                CMUL4(xr, xi, xr, xi, z256r, z256i);
                s1024 = (xr[0] + xr[1]) + (xr[2] + xr[3]);
#pragma unroll
                for (int m = 4; m < 8; m++) {
                    if (m == 4) { CMUL4(xr, xi, xr, xi, z8r, z8i); } else { CMUL4(xr, xi, xr, xi, z256r, z256i); }
                    sched_fence();
                    const uint32_t pk[4] = {pack_h(xr[0], xi[0]), pack_h(xr[1], xi[1]), pack_h(xr[2], xi[2]), pack_h(xr[3], xi[3])};
                    PUT(1, m, pk);
                }
            }
            __syncwarp();
            {
                KSTAMP(8, 0);
                uint32_t bd[2][4] = {{0, 0, 0, 0}, {0, 0, 0, 0}};
                const bool on = (g >> 1) == t;
#pragma unroll
                for (int i = 0; i < 6; i++) { R[i][0] = R[i][1] = R[i][2] = R[i][3] = 0.f; }
                uint32_t x[2][4], y[2][4], z[2][4];
                auto fetch = [&](const int k2) {
                    const int b = k2 & 1;
                    lds128_if(on, TB + 2176 + g * 128 + 16 * (k2 ^ g), bd[b]);
                    ldsm4(((k2 & 1) ? ld1 : ld0) + (k2 >> 1) * 128, x[b][0], x[b][1], x[b][2], x[b][3]);
                    ldsm4(TB + ((r & 1) + ((r >> 1) == 2 ? 2 : 0)) * T_PL + 16 + 16 * mi + 64 * k2, y[b][0], y[b][1], y[b][2], y[b][3]);
                    ldsm4(((k2 & 1) ? ld1 : ld0) + (k2 >> 1) * 128 + 4096, z[b][0], z[b][1], z[b][2], z[b][3]);
                };
                fetch(0);
#pragma unroll
                for (int k2 = 0; k2 < 8; k2++) {
                    const int b = k2 & 1;
                    uint32_t a1[2][4];
                    if (k2 < 7) fetch(k2 + 1);
#pragma unroll
                    for (int u = 0; u < 2; u++) {
                        mma_hh_k8(a1[u][0], a1[u][1], Ya[2 * k2 + u][0], Ya[2 * k2 + u][1], bd[b][2 * u]);
                        mma_hh_k8(a1[u][2], a1[u][3], Ya[2 * k2 + u][2], Ya[2 * k2 + u][3], bd[b][2 * u + 1]);
                    }
#pragma unroll
                    for (int u = 0; u < 2; u++) {
                        const uint32_t(&a0)[4] = Ya[2 * k2 + u];
                        mma_h(R[0], a0[0], a0[1], a0[2], a0[3], x[b][2 * u], x[b][2 * u + 1]);
                        mma_h(R[2], a0[0], a0[1], a0[2], a0[3], y[b][2 * u], y[b][2 * u + 1]);
                        mma_h(R[4], a0[0], a0[1], a0[2], a0[3], z[b][2 * u], z[b][2 * u + 1]);
                        mma_h(R[1], a1[u][0], a1[u][1], a1[u][2], a1[u][3], x[b][2 * u], x[b][2 * u + 1]);
                        mma_h(R[3], a1[u][0], a1[u][1], a1[u][2], a1[u][3], y[b][2 * u], y[b][2 * u + 1]);
                        mma_h(R[5], a1[u][0], a1[u][1], a1[u][2], a1[u][3], z[b][2 * u], z[b][2 * u + 1]);
                    }
                }
            }
            __syncwarp();
            KSTAMP(9, __float_as_uint(R[3][0]));
            if (lane == 0) mbar_arrive(bars + 8 * B_KG + (__float_as_uint(R[0][0]) & __float_as_uint(R[4][0]) & p.zero));
            if (lane < 24) asm volatile("st.shared.v2.u32 [%0], {%1, %1};" :: "r"(TB + (lane < 9 ? 2176 : 2432) + 8 * lane), "r"(0) : "memory");
            __syncwarp();
#undef PUT
#undef EMIT
#pragma unroll
            for (int o = 16; o > 0; o >>= 1) s1024 += __shfl_xor_sync(0xffffffffu, s1024, o);
            uint32_t dsk = 0;
            cp_wait_all();
            asm volatile("{\n\t.reg .pred p;\n\tsetp.eq.u32 p, %2, 0;\n\t@p ld.shared.u16 %0, [%1];\n\t}" : "+r"(dsk) : "r"(sb + M_DSK + 4 * warp + 2 * (warp & 1)), "r"(lane) : "memory");
#pragma unroll
            for (int a = 0; a < 6; a++)
#pragma unroll
                for (int i = 0; i < 4; i++) R[a][i] = (a + i == 0) ? fmaf(R[0][0], inv, __uint_as_float(dsk << 16)) : R[a][i] * inv;
            const float k512 = __shfl_sync(0xffffffffu, R[4][0], 0), k516 = __shfl_sync(0xffffffffu, R[4][1], 0);
            const uint32_t w1 = TB + 16 + 16 * g + t * T_PL;
            float last;
#pragma unroll
            for (int a = 0; a < 4; a++) {
                const bool ahead = a >= 2 && t == 3;
                const float back = g == 7 ? (a ? R[a ? a - 1 : 0][3] : 0.f) : R[a][3], fwd = g == 0 ? (a == 2 ? R[3][0] : k512) : R[a][0];
                const float nb = __shfl_sync(0xffffffffu, ahead ? fwd : back, lane + (ahead ? 4 : 28));
                const float q0 = ahead ? R[a][0] : nb, q1 = ahead ? R[a][1] : R[a][0], q2 = ahead ? R[a][2] : R[a][1], q3 = ahead ? R[a][3] : R[a][2];
                last = ahead ? nb : R[a][3];
                sts128(w1 + 128 * a, pack_bf(q1, q0), pack_bf(q2, q1), pack_bf(q3, q2), pack_bf(last, q3));
            }
            {
                const float s0 = t == 3 ? k516 : k512, s1 = t < 2 ? k516 : 0.f;
                sts128_if(g == 7, w1 + 400, pack_bf(s0, last), pack_bf(s1, s0), pack_bf(0.f, s1), 0);
            }
            const uint32_t wq = TB + 8 * g + (t < 2 ? T_A + 8 * (32 + 16 * t) : T_B + 8 * (1 + 32 * t) + 12) + 64 * (t & 1), dq = 64 - 128 * (t & 1);
            uint32_t bw[2][2];
#pragma unroll
            for (int a = 0; a < 2; a++) {
                const uint32_t lo = pack_bf(R[4 + a][0], R[4 + a][1]), hi = pack_bf(R[4 + a][2], R[4 + a][3]);
                bw[a][0] = __byte_perm(lo, hi, t < 2 ? 0x1032 : 0x5410); bw[a][1] = __byte_perm(lo, hi, t < 2 ? 0x5476 : 0x7632);
            }
#pragma unroll
            for (int a = 0; a < 2; a++) {
                const uint32_t b0 = (t & 1) ? bw[a ^ 1][0] : bw[a][0], b1 = (t & 1) ? bw[a ^ 1][1] : bw[a][1], w = wq + a * dq;
                sts32_if(a == 1 || lane != 0, w, b0);
                sts32(w + (t < 2 ? 12 : 116), b1);
                sts32_if(t >= 2, w - 12, b0);
                sts32_if(t >= 2, w + 128, b1);
            }
            __syncwarp();
            if (lane == 31) sts16(w1 + 146, pack_bf(R[1][3], 0.f));
            cfix = pack_bf(s1024 * inv, s1024 * inv);
            if (lane == 0) sts32(TB + T_A + 8 * 64, cfix);
            __syncwarp();
        }
        WSTAMP(1);

        mbar_wait(bars + 8 * B_U);
        WSTAMP(2);

        float D[16][4];
        {
            const int x5 = g - t + 5;
            const uint32_t tabD = TB + (x5 & 3) * T_PL + (x5 & 12) + 16;
            {
                const uint32_t a1 = lds32(tabD - 8), a0 = p.zero;
#pragma unroll
                for (int jq = 0; jq < 4; jq++) {
                    uint32_t b[4];
                    ldsm4(UB + (9 + lane) * 16 + jq * 512, b[0], b[1], b[2], b[3]);
#pragma unroll
                    for (int i = 0; i < 4; i++) mma_bf_k8z(D[4 * jq + i], a0, a1, b[i]);
                }
            }
            const uint32_t ua = UB + (mi & 1) * U_PL + (8 + 8 * (mi >> 1) + r) * 16;
#pragma unroll 1
            for (int k0 = 0; k0 < 8; k0++) {
                uint32_t Uf[16][2];
#pragma unroll
                for (int jp = 0; jp < 8; jp++) ldsm4(ua + jp * 256 - k0 * 16, Uf[2 * jp][0], Uf[2 * jp][1], Uf[2 * jp + 1][0], Uf[2 * jp + 1][1]);
#pragma unroll
                for (int k1 = 0; k1 < 4; k1++) {
                    const uint32_t ta = tabD + 16 * (8 * k1 + k0);
                    const uint32_t a0 = lds32(ta), a1 = lds32(ta + 8), a2 = lds32(ta - 8), a3 = a0 ^ p.zero;
#pragma unroll
                    for (int J = k1; J < 16; J++) mma_bf(D[J], a0, a1, a2, a3, Uf[J - k1][0], Uf[J - k1][1]);
                }
                if (k0 == 0) {
                    const uint32_t ta = tabD + 16 * 32;
                    const uint32_t a0 = lds32(ta), a1 = lds32(ta + 8), a2 = lds32(ta - 8), a3 = a0 ^ p.zero;
#pragma unroll
                    for (int J = 4; J < 16; J++) mma_bf(D[J], a0, a1, a2, a3, Uf[J - 4][0], Uf[J - 4][1]);
                    const uint32_t f0 = (cfix ^ 0x80008000u) & (g == t ? 0xffffu : g == t + 4 ? 0xffff0000u : 0u);
                    const uint32_t f1 = p.zero, f2 = p.zero + p.zero, f3 = f0 ^ p.zero;
#pragma unroll
                    for (int J = 8; J < 16; J++) mma_bf(D[J], f0, f1, f2, f3, Uf[J - 8][0], Uf[J - 8][1]);
                }
            }
        }
        WSTAMP(3);
        {
            const int ch = 8 * h + warp;
            const uint32_t yo = sb + ch * 512 + ((lane ^ (((ch >> 2) << 1) | (ch & 1))) << 4);
            const uint32_t yr = mapa(yo, h ^ 1), ybr = mapa(bars + 8 * B_Y, h ^ 1);
            auto ship = [&](const int Q) {
                uint4 y[2];
#pragma unroll
                for (int hh = 0; hh < 2; hh++) {
                    const int J = 4 * Q + 2 * hh;
                    y[hh] = make_uint4(pack_bf(D[J][0], D[J][1]), pack_bf(D[J][2], D[J][3]), pack_bf(D[J + 1][0], D[J + 1][1]), pack_bf(D[J + 1][2], D[J + 1][3]));
                }
                if (!(Q & 1)) mbar_wait(bars + 8 * (B_F + (Q >> 1)));
                asm volatile("{\n\t.reg .pred p;\n\tsetp.eq.u32 p, %11, 0;\n\t"
                             "@p st.async.weak.shared::cluster.mbarrier::complete_tx::bytes.v4.b32 [%9], {%4,%5,%6,%7}, [%10];\n\t"
                             "@!p st.async.weak.shared::cluster.mbarrier::complete_tx::bytes.v4.b32 [%9], {%0,%1,%2,%3}, [%10];\n\t"
                             "@p st.shared.v4.b32 [%8], {%0,%1,%2,%3};\n\t@!p st.shared.v4.b32 [%8], {%4,%5,%6,%7};\n\t}"
                             :: "r"(y[0].x), "r"(y[0].y), "r"(y[0].z), "r"(y[0].w), "r"(y[1].x), "r"(y[1].y), "r"(y[1].z), "r"(y[1].w),
                                "r"(yo + y_off(Q)), "r"(yr + y_off(Q)), "r"(ybr + 8 * Q), "r"(h) : "memory");
                __syncwarp();
                if (lane == 0) mbar_arrive(bars + 8 * (B_Y + Q));
            };
            ship(0);
            const uint4 bA = lds128(sb + OFF_BAND + (g - t + 3) * 48), bB = lds128(sb + OFF_BAND + (g - t + 3) * 48 + 16);
            const uint2 bC = lds64(sb + OFF_BAND + (g - t + 3) * 48 + 32);
            uint2 QA[5][2], QB[8];
            const uint32_t tq = TB + 8 * (1 + g - 2 * t);
#pragma unroll
            for (int dd = 0; dd < 5; dd++) { QA[dd][0] = lds64(tq + T_A + 64 * (dd + 4)); QA[dd][1] = lds64(tq + T_A + 64 * (dd + 4) - 8); }
#pragma unroll
            for (int dd = 0; dd < 8; dd++) QB[dd] = lds64(tq + T_B + 64 * (dd + 8));
            const uint32_t u1 = UB + (mi & 1) * U_PL + (7 + r + (mi >> 1)) * 16;
            const uint32_t u2 = UB + ((mi & 1) ^ 1) * U_PL + (7 + r + (mi & 1) + 8 * (mi >> 1)) * 16;
            uint32_t n[4];
#pragma unroll
            for (int j = 0; j < 12; j++) {
                uint32_t m[4];
                ldsm4(u1 + j * 128, m[0], m[1], m[2], m[3]);
                if (!(j & 1)) ldsm4(u2 + j * 128, n[0], n[1], n[2], n[3]);
                const uint32_t n0 = n[2 * (j & 1)], n1 = n[2 * (j & 1) + 1];
                float wa[4], wb[4], wc[4], g1[4], g2[4];
                mma_bf_z(wa, bA.x, bA.y, bA.z, bA.w, m[0], m[1]);
                mma_bf_z(wb, bA.x, bA.y, bA.z, bA.w, n0, n1);
                mma_bf_z(wc, bA.x, bA.y, bA.z, bA.w, m[2], m[3]);
                if (j < 8) {
                    mma_bf_z(g1, bB.x, bB.y, bB.z, bB.w, m[0], m[1]);
                    mma_bf_z(g2, bB.x, bB.y, bB.z, bB.w, n0, n1);
                    mma_bf_k8(g1, bC.x, bC.y, m[2]);
                    mma_bf_k8(g2, bC.x, bC.y, m[3]);
                }
#pragma unroll
                for (int e = 0; e < 2; e++) {
                    const uint32_t q0 = pack_bf(wa[e], wa[e + 2]), q1 = pack_bf(wb[e], wb[e + 2]), q2 = q1 ^ p.zero, q3 = pack_bf(wc[e], wc[e + 2]);
#pragma unroll
                    for (int dd = 0; dd < 5; dd++)
                        if (j + 4 + dd < 16) mma_bf(D[j + 4 + dd], q0, q1, q2, q3, QA[dd][e].x, QA[dd][e].y);
                }
                if (j < 8) {
                    const uint32_t q0 = pack_bf(g1[0], g1[2]), q1 = pack_bf(g2[0], g2[2]), q2 = pack_bf(g1[1], g1[3]), q3 = pack_bf(g2[1], g2[3]);
#pragma unroll
                    for (int dd = 7 - j; dd >= 0; dd--) mma_bf(D[j + 8 + dd], q0, q1, q2, q3, QB[dd].x, QB[dd].y);
                }
                if ((j & 3) == 3) {
                    WSTAMP(4 + 2 * (j >> 2));
                    ship((j >> 2) + 1);
                }
            }
        }
        mix_rows<1>(p, &tm_out, sb, PQ, 4, warp, h, pr, lane);
        WSTAMP(10);
        WDUMP();
    } else if ((pw & 12) == AUX_W0) {
        const uint32_t t0 = clock();
        const int v = __reduce_max_sync(0xffffffffu, pw & 3);
        const int at = tid & 127;
        const int g = lane >> 2, t = lane & 3;
        unsigned tag;
        const bool gu = c < NGU_CTA;
        {
            const uint32_t xb = sb + (v < 2 ? OFF_XSEL : OFF_RING + 2 * 8192) + v * 8192;
            const uint32_t gws = sb + M_DPIN;
            const uint32_t row = 16 * c + 4 * v + (g >> 1);
#pragma unroll
            for (int i = 0; i < 8; i++)
                asm volatile("cp.async.ca.shared.global [%0], [%1], 4;" :: "r"((i < 4 ? sb + OFF_GP : gws) + 512 * (i & 3) + (tid & 124) * 4 + (tid & 1) * 8 + (tid & 2) * 2),
                             "l"((i < 4 ? p.wr : p.gatew) + 256 * (i & 3) + (tid & 127) * 2) : "memory");
            if ((tid & 127) < 33) cp16(sb + OFF_BAND + (tid & 127) * 16, p.band + (tid & 127));
            asm volatile("barrier.cluster.arrive.relaxed.aligned;" ::: "memory");
            tag = __reduce_max_sync(0xffffffffu, (*(volatile unsigned*)&p.sc->epoch + 1) & 0xffffu);
            if (gu) st_gpu32((uint32_t*)&p.sc->h[(tag + 1) & 1][32 * c] + at, 0);
            if (v == 2) sts32(sb + M_BMAP + lane * 4, 0);
            if (at == 0) sts32(sb + M_TAG, tag << 16);
            cp_wait_all();
            bar_sync(1, 128);
            uint2 w[16];
#pragma unroll
            for (int kb = 0; kb < 16; kb++) w[kb] = lds64((g < 4 ? sb + OFF_GP : gws) + 128 * kb + 32 * (g & 2) + 16 * t + 8 * (g & 1));
            asm volatile("barrier.cluster.wait.acquire.aligned;" ::: "memory");
            int early;
#pragma unroll 1
            while ((early = TR - (int)(clock() - t0)) > 0) __nanosleep(max(early >> 2, 32));
            mbar_wait(bars + 8 * (B_X + v));
            WSTAMP(10);
            float dr[4][4];
#pragma unroll
            for (int kb = 0; kb < 16; kb++) {
                const uint4 x = lds128(xb + (g >> 1) * 2048 + 128 * kb + 16 * (lane & 7));
                if (kb < 4) mma_bf_z(dr[kb], x.x, x.y, x.z, x.w, w[kb].x, w[kb].y);
                else mma_bf(dr[kb & 3], x.x, x.y, x.z, x.w, w[kb].x, w[kb].y);
            }
            float rs = ((dr[0][0] + dr[0][3]) + (dr[1][0] + dr[1][3])) + ((dr[2][0] + dr[2][3]) + (dr[3][0] + dr[3][3]));
            if (lane == 0) mbar_arrive(bars + 8 * (B_XE + v) + (__float_as_uint(rs) & p.zero));
            rs += __shfl_xor_sync(0xffffffffu, rs, 5);
            const uint32_t rb = pack_bf(0.f, rs);
            if (!(lane & 7)) st_gpu32((uint32_t*)p.sc->r + row, ((rb ^ (((int)rb >> 31) | 0x80000000u)) & 0xffff0000u) | tag);
            WSTAMP(1);
            {
                const int n = 3 + (lane >> 3) + 4 * (lane & 1);
                const uint32_t so = (n & 7) * S_PL + ((lane & 6) + (n >> 3)) * 32;
                const uint32_t src[2] = {sb + OFF_S + v * S_Q + s_addr(so, h), sb + OFF_S + v * S_Q + s_addr(so + 32, h)};
                const uint32_t dst = sb + OFF_U + g * U_CH + (8 + 32 * v + 16 * h + t) * 16;
                const uint32_t rdst = mapa(dst, h ^ 1), rbar = mapa(bars + 8 * B_U, h ^ 1);
                mbar_wait(bars + 8 * (B_S + v));
                WSTAMP(9);
                uint4 a[8];
#pragma unroll
                for (int b = 0; b < 2; b++) {
#pragma unroll
                    for (int j = 0; j < 8; j++) { const int u = 4 * b + (j >> 1) + 8 * (j & 1); ldsm4t((u < 8 ? src[u & 1] ^ 16 : src[u & 1]) + ((u >> 1) & 3) * 256, a[j].x, a[j].y, a[j].z, a[j].w); }
#pragma unroll
                    for (int j = 0; j < 8; j++) {
                        const int u = 4 * b + (j >> 1) + 8 * (j & 1);
                        if (u < 8) st_async16(rdst + ((u >> 1) & 3) * 64 + (u & 1) * U_PL, a[j], rbar);
                        else sts128(dst + ((u >> 1) & 3) * 64 + (u & 1) * U_PL, a[j].x, a[j].y, a[j].z, a[j].w);
                    }
                }
                if (h && v == 3) {
                    ldsm4t((src[0] ^ 16) + 1024, a[0].x, a[0].y, a[0].z, a[0].w);
                    ldsm4t(src[0] + 1024, a[1].x, a[1].y, a[1].z, a[1].w);
                    if (t == 0) {
                        st_async16(rdst + 256, make_uint4(a[0].x, a[0].y & 0xffffu, a[0].z & 0xffffu, a[0].w & 0xffffu), rbar);
                        sts128(dst + 256, a[1].x, a[1].y & 0xffffu, a[1].z & 0xffffu, a[1].w & 0xffffu);
                    }
                }
                __syncwarp();
                if (lane == 0) mbar_arrive(bars + 8 * B_U);
            }
            if ((lane & 7) == 2) st_gpu32((uint32_t*)p.sc->g + ((row & 256) << 2) + gate_pos(row), pack_bf(sigmoid_f(__uint_as_float(rb)), 0.f) | (tag << 16));
            WSTAMP(2);
        }
        {
            const bool lane0 = pin(lane, lane) == 0;
            const uint32_t own = pin(sb + OFF_XSEL + (at ^ ((at >> 1) & 4)) * 16, lane);
            float acc[8][4];
            const int krow = ((lane >> 1) & 8) + (lane & 7);
            const uint32_t tile0 = pin(sb + OFF_RING + v * 8192 + krow * 64 + ((((lane >> 3) & 1) ^ ((krow >> 1) & 3)) << 4), lane);
            const uint32_t xo = pin(sb + OFF_XSEL + (lane & 7) * XS_ROW + 512 * v + 2 * (lane & 24), lane);
            const uint32_t po = pin(sb + OFF_XSEL + t * XS_ROW + (g & 3) * 128 + (g & 1) * 64 + v * 16 + (lane >> 4) * 8, lane);
            const uint32_t po1 = pin(po + 64 - (g & 1) * 128, lane);
            uint32_t* hdst = pin((uint32_t*)&p.sc->h[tag & 1][32 * c] + at, lane);
            auto signal = [&](const int k, const uint32_t dep) {
                if (lane < 2 && v < 2)
                    asm volatile("st.async.weak.shared::cluster.mbarrier::complete_tx::bytes.b32 [%0], %1, [%2];"
                                 :: "r"(mapa(sb + M_SINK, lane)), "r"(dep), "r"(mapa(bars + 8 * (B_F + k), lane)) : "memory");
            };
            uint32_t a[16][4], b[2][4];
            auto load_a = [&](const uint32_t tile) {
#pragma unroll
                for (int q = 0; q < 16; q++) ldsm4t((tile ^ ((q & 1) << 5)) + ((q >> 1) & 1) * 4096 + (q >> 2) * 1024, a[q][0], a[q][1], a[q][2], a[q][3]);
            };
            auto load_b = [&](const uint32_t x) { ldsm4(x, b[0][0], b[0][1], b[0][2], b[0][3]); ldsm4(x + 64, b[1][0], b[1][1], b[1][2], b[1][3]); };
            auto burst = [&](const bool first) {
#pragma unroll
                for (int q = 0; q < 16; q++) {
                    if (first && q < 8) mma_bf_z(acc[q], a[q][0], a[q][1], a[q][2], a[q][3], b[0][(q >> 1) & 2], b[0][((q >> 1) & 2) + 1]);
                    else mma_bf(acc[q & 7], a[q][0], a[q][1], a[q][2], a[q][3], b[q >> 3][(q >> 1) & 2], b[q >> 3][((q >> 1) & 2) + 1]);
                }
            };
            if (gu) {
                mbar_wait(bars + 8 * (B_W + v));
                load_a(tile0);
                uint32_t dep = p.zero;
#pragma unroll
                for (int q = 0; q < 16; q += 2) dep &= a[q][0] & a[q + 1][0];
                if (lane == 0) mbar_arrive(bars + 8 * (B_E + v) + dep);
            }
            uint32_t top;
#pragma unroll 1
            for (int it = 0; it < (1 << 22); it++) {
                asm volatile("ld.relaxed.gpu.global.u32 %0, [%1];" : "=r"(top) : "l"(&p.sc->top[c % NTOP][g]) : "memory");
                if (__all_sync(0xffffffffu, ((top ^ (tag << 11)) & 0xf800u) == 0)) break;
                __nanosleep(40);
            }
            WSTAMP(3);
            if (gu) {
                const uint32_t k = 4 * h + v, row = __reduce_max_sync(0xffffffffu, lane == 4 * k ? ~top & 2047 : 0);
                asm volatile("{\n\t.reg .pred p;\n\telect.sync _|p, 0xffffffff;\n\t"
                             "@p cp.async.bulk.shared::cluster.global.mbarrier::complete_tx::bytes.multicast::cluster [%0], [%1], 2048, [%2], %3;\n\t}"
                    :: "r"(sb + OFF_XSEL + k * XS_ROW), "l"(p.u + (size_t)row * D_), "r"(bars + 8 * B_G), "h"((unsigned short)3) : "memory");
            }
            if (v == 2) {
                const uint32_t row = ~top & 2047;
                if (t == 0 && ((row >> 8) & 1) == h)
                    asm volatile("red.shared.or.b32 [%0], %1;" :: "r"(sb + M_BMAP + (row & 7) * 16 + (row >> 9) * 4), "r"(1u << (gate_pos(row) & 31)) : "memory");
                if (t == 0) sts32(sb + M_TOP + lane, top);
                if (c == 0 && lane == 0) *(volatile unsigned*)&p.sc->epoch = tag;
                __syncwarp();
                if (lane0) mbar_arrive(bars + 8 * B_Y);
            }
            if (gu) {
                mbar_wait(bars + 8 * B_G);
                WSTAMP(4);
                load_b(xo);
                burst(true);
#pragma unroll
                for (int i = 1; i < 4; i++) {
                    mbar_wait(bars + 8 * (B_W + 4 * i + v));
                    load_b(xo + 128 * i);
                    load_a(tile0 + (4 * i + v < 14 ? i : 0) * 32768);
                    if (lane0 && i > 1) mbar_arrive(bars + 8 * (B_E + 4 * i - 4 + v));
                    if (i == 2) signal(0, 0);
                    sched_fence();
                    burst(false);
                    sched_fence();
                }
                WSTAMP(5);
                __syncwarp();
#pragma unroll
                for (int q = 0; q < 4; q++) {
                    const int ct = q >> 1, e = 2 * (q & 1);
                    sts128(own + q * XS_ROW,
                           __float_as_uint(acc[ct][e] + acc[4 + ct][e]), __float_as_uint(acc[2 + ct][e] + acc[6 + ct][e]),
                           __float_as_uint(acc[ct][e + 1] + acc[4 + ct][e + 1]), __float_as_uint(acc[2 + ct][e + 1] + acc[6 + ct][e + 1]));
                }
                bar_sync(1, 128);
                float sl[2], uv[2];
#pragma unroll
                for (int e = 0; e < 2; e++) {
                    uint2 q[4];
#pragma unroll
                    for (int i = 0; i < 4; i++) q[i] = lds64((e ? po1 : po) + 512 * i);
                    const float s0 = (__uint_as_float(q[0].x) + __uint_as_float(q[1].x)) + (__uint_as_float(q[2].x) + __uint_as_float(q[3].x));
                    const float s1 = (__uint_as_float(q[0].y) + __uint_as_float(q[1].y)) + (__uint_as_float(q[2].y) + __uint_as_float(q[3].y));
                    const float gv = bf_round(p.gu_swap ? s1 : s0);
                    uv[e] = p.gu_swap ? s0 : s1;
                    sl[e] = gv * sigmoid_f(gv);
                }
                const uint32_t hw = hmul2_bf(pack_bf(sl[0], sl[1]), pack_bf(uv[0], uv[1]));
                st_gpu32(hdst, hw ? hw : 0x80000000u);
            }
            mbar_wait(bars + 8 * B_KG);
            signal(1, 0);
        }
        WSTAMP(6);
        {
            const uint32_t own = pin(sb + OFF_XSEL + at * 16, lane);
            const uint32_t hb = sb + (v < 2 ? OFF_XSEL + 7168 * v : OFF_RING + 8192 * v), hl = pin(hb + 16 * lane, lane);
            const int krow = ((lane >> 1) & 8) + (lane & 7);
            const uint32_t tile = pin(sb + OFF_RING + v * 8192 + krow * 32 + ((((lane >> 3) ^ (krow >> 2)) & 1) << 4), lane);
            float dd[4][4];
            bar_sync(1, 128);
            mbar_wait(bars + 8 * (B_W + HW));
            WSTAMP(12);
            const uint4* hs = &p.sc->h[tag & 1][32 * (56 * h + 14 * v)];
            bulk_load(hb, hs, 3584, bars + 8 * (B_X + v));
            bulk_load(hb + 3584, hs + 224, 3584, bars + 8 * (B_XE + v));
            mbar_wait(bars + 8 * B_Y);
            const uint32_t top = lds32(sb + M_TOP + 8 * v + 4 * (lane >> 4));
            const uint32_t row = ~top & 2047, ch = lane & 15;
            uint32_t gx, x16;
            asm volatile("ld.shared.u16 %0, [%1];" : "=r"(gx) : "r"(sb + OFF_GP + gate_pos(row) * 2) : "memory");
            asm volatile("ld.shared.u16 %0, [%1];" : "=r"(x16) : "r"(sb + OFF_S + (row >> 9) * S_Q + s_addr((row & 7) * S_PL + 32 + (row & 248) * 4, ch >> 3) + 2 * (ch & 7)) : "memory");
            gx = pin(gx | (x16 << 16), lane);
            const uint32_t rq = pin(pack_bf(0.f, sigmoid_f(__uint_as_float((top ^ (((int)~top >> 31) | 0x80000000u)) & 0xffff0000u))) | (row >> 8), lane);
            const uint32_t po = pin(sb + (4 * (ch & 7) + v) * 16 + (ch >> 3) * 8 + (lane >> 4) * 4, lane);
            const uint32_t ya = pin(sb + y_off(row >> 9) + ch * 512 + (((4 * (row & 7) + ((row >> 5) & 3)) ^ (((ch >> 2) << 1) | (ch & 1))) << 4) + 2 * row_elem(row), lane);
            const uint32_t oo = pin(row * D_ + 16 * pr + ch, lane);
            uint4 hq[7];
            {
                uint32_t a[14][4];
                mbar_wait(bars + 8 * (B_W + 16 + v));
#pragma unroll
                for (int j = 0; j < 14; j++) ldsm4t(tile + (v & 2) * 16384 + j * 512, a[j][0], a[j][1], a[j][2], a[j][3]);
#pragma unroll
                for (int k = 0; k < 2; k++) {
                    mbar_wait(bars + 8 * ((k ? B_XE : B_X) + v), 1);
                    if (!k) WSTAMP(7);
                    uint32_t mn = 0xffffffffu;
#pragma unroll
                    for (int j = 0; j < 7; j++) { hq[j] = lds128(hl + 3584 * k + 512 * j); mn = min(mn, hq[j].x); }
#pragma unroll 1
                    for (int it = 0; it < (1 << 20) && !__all_sync(0xffffffffu, mn != 0); it++) {
                        mn = 0xffffffffu;
#pragma unroll
                        for (int j = 0; j < 7; j++)
                            asm volatile("{\n\t.reg .pred p;\n\tsetp.eq.u32 p, %0, 0;\n\t@p ld.relaxed.gpu.global.v4.u32 {%0,%1,%2,%3}, [%4];\n\t}"
                                         : "+r"(hq[j].x), "+r"(hq[j].y), "+r"(hq[j].z), "+r"(hq[j].w) : "l"(hs + 224 * k + 32 * j + lane) : "memory");
#pragma unroll
                        for (int j = 0; j < 7; j++) mn = min(mn, hq[j].x);
                    }
                    if (!k) {
#pragma unroll
                        for (int j = 0; j < 14; j++) {
                            const uint4& q = hq[j >> 1];
                            if (j < 4) mma_bf_z(dd[j], a[j][0], a[j][1], a[j][2], a[j][3], (j & 1) ? q.z : q.x, (j & 1) ? q.w : q.y);
                            else mma_bf(dd[j & 3], a[j][0], a[j][1], a[j][2], a[j][3], (j & 1) ? q.z : q.x, (j & 1) ? q.w : q.y);
                        }
                    }
                }
            }
            mbar_wait(bars + 8 * (B_W + 20 + v));
#pragma unroll
            for (int j = 0; j < 14; j++) {
                uint32_t f[4];
                ldsm4t(tile + 65536 + j * 512, f[0], f[1], f[2], f[3]);
                mma_bf(dd[(j + 2) & 3], f[0], f[1], f[2], f[3], (j & 1) ? hq[j >> 1].z : hq[j >> 1].x, (j & 1) ? hq[j >> 1].w : hq[j >> 1].y);
            }
            WSTAMP(8);
            uint4 part;
            part.x = __float_as_uint((dd[0][0] + dd[1][0]) + (dd[2][0] + dd[3][0])); part.y = __float_as_uint((dd[0][1] + dd[1][1]) + (dd[2][1] + dd[3][1]));
            part.z = __float_as_uint((dd[0][2] + dd[1][2]) + (dd[2][2] + dd[3][2])); part.w = __float_as_uint((dd[0][3] + dd[1][3]) + (dd[2][3] + dd[3][3]));
            st_async16(mapa(own + (M_DPIN - OFF_XSEL), h ^ 1), part, mapa(bars + 8 * B_DP, h ^ 1));
            sts128(own + 14336, part.x, part.y, part.z, part.w);
            __syncwarp();
            if (lane == 0) mbar_arrive(bars + 8 * B_DP);
            const bool mine = (rq & 1) == h;
            uint32_t y16 = 0;
            if (mine) {
                mbar_wait(bars + 8 * B_Y + 4 * (rq & 6));
                asm volatile("ld.shared.u16 %0, [%1];" : "=r"(y16) : "r"(ya) : "memory");
            }
            mbar_wait(bars + 8 * B_DP);
            float q[8];
#pragma unroll
            for (int i = 0; i < 4; i++) { q[i] = ldsf(po + M_DPIN + 512 * i); q[4 + i] = ldsf(po + OFF_XSEL + 14336 + 512 * i); }
            const float tot = ((q[0] + q[1]) + (q[2] + q[3])) + ((q[4] + q[5]) + (q[6] + q[7]));
            const float b = bf_round(bf_hi(gx) + bf_round(bf_round(tot) * bf_hi(rq)));
            if (mine) p.out[oo] = __float2bfloat16_rn(fmaf(bf_lo(gx), __uint_as_float(y16 << 16), bf_round(bf_round(1.f - bf_lo(gx)) * b)));
            WSTAMP(11);
        }
        WDUMP();
    } else {
        asm volatile("setmaxnreg.dec.sync.aligned.u32 64;");
        const int v = __reduce_max_sync(0xffffffffu, pw - PREP_W0);
        const bool gu = c < NGU_CTA;
        const uint32_t t0 = clock();
        const uint32_t bu = bars + 8 * v;
        if (lane == 0) { mbar_init(bu + 8 * B_X, 1); mbar_init(bu + 8 * B_S, 1); }
        __syncwarp();
        while ((uint32_t)clock() - t0 < TX) {}
        bulk_load(sb + (v < 2 ? OFF_XSEL : OFF_RING + 2 * 8192) + v * 8192, p.u + (size_t)(16 * c + 4 * v) * D_, 8192, bu + 8 * B_X);
        tma3d(sb + OFF_S + v * S_Q, &tm_x, 16 * pr, 64 * v + 32 * h - 1, bars + 8 * (B_S + v), S_Q);
        if (lane == 0) {
#pragma unroll
            for (int i = 0; i < 9; i++) mbar_init(bu + 32 * i, 1);
            mbar_init(bu + 8 * B_XE, 1);
            mbar_init(bu + 8 * B_Y, v == 0 ? 11 : 9);
            mbar_init(bu + 8 * B_DP, (0x1855 >> (4 * v)) & 15);
            mbar_init(bu + 8 * B_F, 1);
            mbar_init(bu + 8 * B_H, 1);
            asm volatile("fence.mbarrier_init.release.cluster;" ::: "memory");
            mbar_expect(bu + 8 * B_Y, 4096);
            if (v != 2) mbar_expect(bu + 8 * B_DP, v == 0 ? 2048 : (h || v == 3) ? 16384 : 16384 + 128);
            mbar_expect(bu + 8 * B_F, (gu || v) ? 16 : 0);
        }
        __syncwarp();
        asm volatile("barrier.cluster.arrive.relaxed.aligned;" ::: "memory");
        WSTAMP(9);
        if (v < 3 && lane == 0) asm volatile("prefetch.tensormap [%0];" :: "l"(v == 0 ? &tm_gu : v == 1 ? &tm_down : &tm_out) : "memory");
        asm volatile("barrier.cluster.wait.acquire.aligned;" ::: "memory");
        uint32_t desc;
        {
            const int s = 6 * v + lane, i = s >> 2, w = s & 3, slot = s < 14 ? s : (s | 1) == 17 ? s - 16 : s - 12;
            const int fb = s < 4 ? B_H : (gu && s >= 14) ? B_E + slot : s < 6 ? B_XE + s - 2 : B_KG;
            desc = slot | (fb << 4) | ((i < 4 ? 256 * w + 64 * i : 1792 * h + 448 * w + 224 * (i - 4)) << 10);
            if (lane < 6) mbar_expect(bars + 8 * (B_W + s), i < 4 ? 8192 : 7168);
            if (tid == 32 * PREP_W0) mbar_arrive(bars + 8 * B_H);
        }
        if (v == 3) {
            mbar_wait(bars + 8 * B_U);
            mbar_wait(bars + 8 * (gu ? B_G : B_H + 2));
            const uint32_t tag16 = lds32(sb + M_TAG);
            uint4 q[8];
#pragma unroll 1
            for (int it = 0; it < (1 << 22); it++) {
                uint32_t bad = 0;
#pragma unroll
                for (int i = 0; i < 8; i++) q[i] = ld_gpu128(&p.sc->g[256 * h + 32 * i + lane]);
#pragma unroll
                for (int i = 0; i < 8; i++) bad |= ((q[i].x ^ tag16) | (q[i].y ^ tag16)) | ((q[i].z ^ tag16) | (q[i].w ^ tag16));
                if ((bad >> 16) == 0) break;
                __nanosleep(200);
            }
#pragma unroll
            for (int i = 0; i < 8; i++)
                asm volatile("st.shared.v2.u32 [%0], {%1, %2};" :: "r"(sb + OFF_GP + 256 * i + lane * 8),
                             "r"(__byte_perm(q[i].x, q[i].y, 0x5410)), "r"(__byte_perm(q[i].z, q[i].w, 0x5410)) : "memory");
            __syncwarp();
            if (lane == 0) mbar_arrive(bars + 8 * B_Y);
        }
        mbar_wait(bars + 8 * (B_H + v));
        {
            const int gap = v == 0 ? GAP : v == 1 ? GAP1 : v == 2 ? GAP2 : GAP3;
            uint32_t last = v ? clock() - SLACK : t0 + T0 - GAP + GAP * ((pr * 5) & 15) / 16;
#pragma unroll 1
            for (int k = 0; k < 6; k++) {
                const uint32_t dk = __reduce_max_sync(0xffffffffu, lane == k ? desc : 0);
                const bool dn = 6 * v + k >= 16;
                const uint32_t dst = sb + OFF_RING + (dk & 15) * 8192, bar = bars + 8 * (B_W + 6 * v + k), c0 = dn ? 16 * pr : 32 * c, c1 = dk >> 10;
                const CUtensorMap* tm = dn ? &tm_down : &tm_gu;
                mbar_wait(bars + ((dk >> 1) & 0x1f8));
                int late;
#pragma unroll 1
                while ((late = (int)(clock() - last) - gap) < 0) __nanosleep(max(-late >> 2, 32));
                WSTAMP(3 + k);
                if (gu || dn)
                    asm volatile("{\n\t.reg .pred p;\n\telect.sync _|p, 0xffffffff;\n\t"
                                 "@p cp.async.bulk.tensor.3d.shared::cluster.global.mbarrier::complete_tx::bytes [%0], [%1, {%3, %4, 0}], [%2];\n\t}"
                        :: "r"(dst), "l"(tm), "r"(bar), "r"(c0), "r"(c1) : "memory");
                last += gap + max(late - SLACK, 0);
            }
            if (lane == 0 && v < 3) mbar_arrive(bars + 8 * (B_H + v + 1));
        }
        {
            WSTAMP(1);
            mix_rows<2>(p, &tm_out, sb, 0, PQ, v, h, pr, lane);
            WSTAMP(2);
            asm volatile("cp.async.bulk.commit_group;" ::: "memory");
        }
        asm volatile("cp.async.bulk.wait_group.read 0;" ::: "memory");
        WSTAMP(10);
        WDUMP();
    }
}

typedef CUresult (*EncodeFn)(CUtensorMap*, CUtensorMapDataType, cuuint32_t, void*, const cuuint64_t*, const cuuint64_t*,
                             const cuuint32_t*, const cuuint32_t*, CUtensorMapInterleave, CUtensorMapSwizzle,
                             CUtensorMapL2promotion, CUtensorMapFloatOOBfill);

void make_map(EncodeFn f, CUtensorMap* m, const void* ptr, uint64_t cols, uint64_t rows, uint64_t pitch, uint32_t bc, uint32_t br, CUtensorMapSwizzle sw, CUtensorMapL2promotion prom,
              uint32_t planes = 1, uint64_t plane_stride = 0, uint32_t box_planes = 0) {
    cuuint64_t dims[3] = {cols, rows, planes};
    cuuint64_t str[2] = {pitch, planes > 1 ? plane_stride : pitch * rows};
    cuuint32_t box[3] = {bc, br, box_planes ? box_planes : planes};
    cuuint32_t es[3] = {1, 1, 1};
    f(m, CU_TENSOR_MAP_DATA_TYPE_BFLOAT16, 3, (void*)ptr, dims, str, box, es, CU_TENSOR_MAP_INTERLEAVE_NONE, sw,
      prom, CU_TENSOR_MAP_FLOAT_OOB_FILL_NONE);
}

}

extern "C" void kernel_launch(void* const* d_in, const int* in_sizes, int n_in, void* d_out, int out_size) {
    static EncodeFn enc = nullptr;
    static void *sc = nullptr, *band = nullptr;
    static int sms = 0;
    if (!enc) {
        void* fn = nullptr;
        cudaDriverEntryPointQueryResult qr;
        cudaGetDriverEntryPoint("cuTensorMapEncodeTiled", &fn, cudaEnableDefault, &qr);
        enc = (EncodeFn)fn;
        cudaGetSymbolAddress(&sc, g_scratch);
        cudaGetSymbolAddress(&band, g_band);
        int dev = 0;
        cudaGetDevice(&dev);
        cudaDeviceGetAttribute(&sms, cudaDevAttrMultiProcessorCount, dev);
        cudaFuncSetAttribute(fused_kernel, cudaFuncAttributeMaxDynamicSharedMemorySize, SMEM_BYTES);
    }
    CUtensorMap tg, td, tx, to;
    const char *wg = (const char*)d_in[9], *wu = (const char*)d_in[10];
    const bool swap = wu < wg;
    make_map(enc, &tg, swap ? wu : wg, F_, D_, F_ * 2, 32, 64, CU_TENSOR_MAP_SWIZZLE_64B, CU_TENSOR_MAP_L2_PROMOTION_L2_128B, 2, swap ? wg - wu : wu - wg);
    make_map(enc, &td, d_in[11], D_, F_, D_ * 2, 16, 224, CU_TENSOR_MAP_SWIZZLE_32B,
             sms == 132 ? CU_TENSOR_MAP_L2_PROMOTION_L2_128B : CU_TENSOR_MAP_L2_PROMOTION_L2_64B);
    make_map(enc, &tx, d_in[0], D_, L_ / 8, D_ * 16, 16, 33, CU_TENSOR_MAP_SWIZZLE_32B, CU_TENSOR_MAP_L2_PROMOTION_NONE, 8, D_ * 2);
    make_map(enc, &to, d_out, D_, L_ / 8, D_ * 16, 16, 32, CU_TENSOR_MAP_SWIZZLE_NONE, CU_TENSOR_MAP_L2_PROMOTION_NONE, 8, D_ * 2, 1);
    Params p;
    p.u = (const bf16*)d_in[0]; p.logA = (const bf16*)d_in[1]; p.Aim = (const bf16*)d_in[2];
    p.Cre = (const bf16*)d_in[3]; p.Cim = (const bf16*)d_in[4]; p.logdt = (const bf16*)d_in[5];
    p.Dskip = (const bf16*)d_in[6]; p.wr = (const bf16*)d_in[8]; p.gatew = (const bf16*)d_in[12];
    p.out = (bf16*)d_out;
    p.sc = (Scratch*)sc; p.band = (const uint4*)band;
    p.gu_swap = swap;
    p.zero = 0;
    fused_kernel<<<NCTA, NTHREADS, SMEM_BYTES>>>(p, tg, td, tx, to);
}
```
